```python
import torch

def _softmax(x, axis=-1):
    return torch.softmax(x, dim=axis)
def _gelu(x):
    return torch.nn.functional.gelu(x, approximate="tanh")
def _silu(x):
    return torch.nn.functional.silu(x)
def _sigmoid(x):
    return torch.sigmoid(x)
def _layernorm(x, axis=-1, eps=1e-5):
    m = x.mean(dim=axis, keepdim=True)
    v = x.var(dim=axis, keepdim=True, unbiased=False)
    return (x - m) / torch.sqrt(v + eps)
def _scatter_add(tgt, idx, src, axis=0):
    return tgt.clone().index_add_(axis, idx, src)
def _segment_sum(src, seg, n):
    out = torch.zeros((n,) + src.shape[1:], dtype=src.dtype)
    return out.index_add_(0, seg, src)
def _pad(x, pw):
    flat = tuple(v for pair in reversed(pw) for v in pair)
    return torch.nn.functional.pad(x, flat)

kernel_name = 'sequential_preLN__grouped_kv_mqa__dense_activation_silu__prompt'

def setup_inputs():

    _w = (lambda a: (lambda t: t.to(torch.bfloat16) if t.is_floating_point() else t)(torch.as_tensor(a)))
    def _A_setup():
        B, S, D, H = 1, 2048, 512, 32
        Dh = D // H
        return {
            "x": _w((lambda *s: torch.randn(*s, dtype=torch.bfloat16) * 0.05)(B, S, D)),
            "wq": _w((lambda *s: torch.randn(*s, dtype=torch.bfloat16) * 0.05)(D, H * Dh)),
            "wk": _w((lambda *s: torch.randn(*s, dtype=torch.bfloat16) * 0.05)(D, Dh)),
            "wv": _w((lambda *s: torch.randn(*s, dtype=torch.bfloat16) * 0.05)(D, Dh)),
            "wo": _w((lambda *s: torch.randn(*s, dtype=torch.bfloat16) * 0.05)(H * Dh, D)),
        }
    _A_in = _A_setup()

    def _B_setup():
        B, S, D, F = 1, 2048, 512, 1376
        return {
            "x": _w((lambda *s: torch.randn(*s, dtype=torch.bfloat16) * 0.05)(B, S, D)),
            "w1": _w((lambda *s: torch.randn(*s, dtype=torch.bfloat16) * 0.8)(D, F) * (D ** -0.5)),
            "w2": _w((lambda *s: torch.randn(*s, dtype=torch.bfloat16) * 0.2)(F, D) * (F ** -0.5)),
        }
    _B_in = _B_setup()

    return {
        "A_x": _A_in["x"],
        "A_wq": _A_in["wq"],
        "A_wk": _A_in["wk"],
        "A_wv": _A_in["wv"],
        "A_wo": _A_in["wo"],
        "B_x": _B_in["x"],
        "B_w1": _B_in["w1"],
        "B_w2": _B_in["w2"],
    }

def reference(A_x, A_wq, A_wk, A_wv, A_wo, B_x, B_w1, B_w2):
    def _A_ref(x, wq, wk, wv, wo):
        B, S, D = x.shape
        H = 32
        Dh = D // H
        q = (lambda x, *d: x.permute(*d))((x @ wq).reshape(B, S, H, Dh), 0, 2, 1, 3)
        k = x @ wk
        v = x @ wv
        scores = torch.einsum("bhqd,bkd->bhqk", q, k) * (Dh ** -0.5)
        p = _softmax(scores, axis=-1)
        o = torch.einsum("bhqk,bkd->bhqd", p, v)
        return (lambda x, *d: x.permute(*d))(o, 0, 2, 1, 3).reshape(B, S, H * Dh) @ wo

    def _B_ref(x, w1, w2):
        h = torch.einsum("bsd,df->bsf", x, w1)
        h = _silu(h)
        out = torch.einsum("bsf,fd->bsd", h, w2)
        return out

    x = A_x
    h = x + _A_ref(_layernorm(x, axis=-1), A_wq, A_wk, A_wv, A_wo)
    h2 = h + _B_ref(_layernorm(h, axis=-1), B_w1, B_w2)
    return h2
```

```cpp
#include <cuda_runtime.h>
#include <cuda_bf16.h>
#include <cuda.h>
#include <stdint.h>

namespace {

constexpr int D = 512, FF = 1376;
constexpr int NMAIN = 128, NHELP = 4, NCTA = NMAIN + NHELP;
constexpr uint32_t SENT = 0xFFFFFFFFu;
constexpr int SPIN_LIMIT = 1 << 22;

constexpr uint32_t KB = 1024;
constexpr uint32_t SM_XN = 0;
constexpr uint32_t SM_WQ = 64 * KB;
constexpr uint32_t SM_WKV = 192 * KB;
constexpr uint32_t KVCH = 40 * KB;
constexpr uint32_t SM_Q = 200 * KB;
constexpr uint32_t SM_W1 = 40 * KB;
constexpr uint32_t SM_MISC = 224 * KB;
constexpr uint32_t SMEM_BYTES = 227 * KB;
constexpr uint32_t MB_WQ = 0;
constexpr uint32_t MB_WKV = 4;
constexpr uint32_t MB_KV = 5;
constexpr uint32_t MB_WO = 9;
constexpr uint32_t MB_W1 = 11;
constexpr uint32_t MB_W2 = 15;
constexpr uint32_t MB_F2 = 37;
constexpr uint32_t NBAR = 38;
constexpr uint32_t MISC_CNT = 512;
constexpr uint32_t MISC_NRM = 576;
constexpr uint32_t MISC_EPOCH = 608;
constexpr uint32_t MISC_KTMP = 1024;

__host__ __device__ constexpr uint32_t wo_addr(int kb) { return kb < 5 ? 160 * KB + kb * 8 * KB : (kb - 5) * 8 * KB; }
__host__ __device__ constexpr uint32_t w2_addr(int kb) {
    return kb == 0 ? 216 * KB : kb < 3 ? (24 + 8 * (kb - 1)) * KB : kb < 6 ? (136 + 8 * (kb - 3)) * KB
         : kb < 11 ? (160 + 8 * (kb - 6)) * KB : kb < 14 ? 8 * (kb - 11) * KB : (40 + 8 * (kb - 14)) * KB;
}

__device__ uint4 g_kv[4 * 2048];
__device__ uint4 g_kplain[4 * 1024];
__device__ uint4 g_of[32 * 32 * 128];
__device__ uint4 g_hf[32 * 32 * 128];
__device__ uint4 g_Hf[32 * 88 * 128];
__device__ float2 g_stats[32 * 64 * 16];
__device__ float g_cs[1408];
__device__ unsigned long long g_flag1[NMAIN];
__device__ unsigned g_flag2[NCTA];
__device__ unsigned g_epoch[NCTA];
#define TS(i) do {} while (0)

__device__ __forceinline__ void mbar_init(uint32_t bar, int cnt) { asm volatile("mbarrier.init.shared::cta.b64 [%0], %1;" :: "r"(bar), "r"(cnt) : "memory"); }
__device__ __forceinline__ void mbar_expect(uint32_t bar, uint32_t bytes) { asm volatile("mbarrier.arrive.expect_tx.shared::cta.b64 _, [%0], %1;" :: "r"(bar), "r"(bytes) : "memory"); }
__device__ __forceinline__ void mbar_arrive(uint32_t bar) { asm volatile("mbarrier.arrive.shared::cta.b64 _, [%0];" :: "r"(bar) : "memory"); }
__device__ __forceinline__ void mbar_wait(uint32_t bar) {
    uint32_t done; int spins = 0;
    do {
        asm volatile("{.reg .pred p; mbarrier.try_wait.parity.shared::cta.b64 p, [%1], 0; selp.u32 %0, 1, 0, p;}" : "=r"(done) : "r"(bar) : "memory");
        if (++spins > SPIN_LIMIT) __trap();
    } while (!done);
}
__device__ __forceinline__ void tma2d(uint32_t dst, const CUtensorMap* tm, int c0, int c1, uint32_t bar) {
    asm volatile("cp.async.bulk.tensor.2d.shared::cluster.global.mbarrier::complete_tx::bytes [%0], [%1, {%3, %4}], [%2];"
                 :: "r"(dst), "l"(tm), "r"(bar), "r"(c0), "r"(c1) : "memory");
}
__device__ __forceinline__ void bulk_g2s(uint32_t dst, const void* src, uint32_t bytes, uint32_t bar) {
    asm volatile("cp.async.bulk.shared::cluster.global.mbarrier::complete_tx::bytes [%0], [%1], %2, [%3];" :: "r"(dst), "l"(src), "r"(bytes), "r"(bar) : "memory");
}
__device__ __forceinline__ void fence_async_smem() { asm volatile("fence.proxy.async.shared::cta;" ::: "memory"); }
__device__ __forceinline__ void bar_sync(int id, int n) { asm volatile("bar.sync %0, %1;" :: "r"(id), "r"(n) : "memory"); }
__device__ __forceinline__ void bar_arrive(int id, int n) { asm volatile("bar.arrive %0, %1;" :: "r"(id), "r"(n) : "memory"); }
__device__ __forceinline__ void wg_fence() { asm volatile("wgmma.fence.sync.aligned;" ::: "memory"); }
__device__ __forceinline__ void wg_commit() { asm volatile("wgmma.commit_group.sync.aligned;" ::: "memory"); }
template <int N> __device__ __forceinline__ void wg_wait() { asm volatile("wgmma.wait_group.sync.aligned %0;" :: "n"(N) : "memory"); }
template <int N> __device__ __forceinline__ void fence_regs(float (&d)[N]) {
#pragma unroll
    for (int i = 0; i < N; i++) asm volatile("" : "+f"(d[i]) :: "memory");
}
template <int N> __device__ __forceinline__ void fence_regs(uint32_t (&d)[N]) {
#pragma unroll
    for (int i = 0; i < N; i++) asm volatile("" : "+r"(d[i]) :: "memory");
}
__device__ __forceinline__ uint64_t mkdesc(uint32_t addr, uint32_t lbo, uint32_t sbo, uint32_t swz) {
    return (uint64_t)(((addr & 0x3FFFF) >> 4) | ((lbo >> 4) << 16)) | ((uint64_t)((sbo >> 4) | (swz << 30)) << 32);
}
__device__ __forceinline__ float ex2(float x) { float y; asm("ex2.approx.ftz.f32 %0, %1;" : "=f"(y) : "f"(x)); return y; }
__device__ __forceinline__ float rcp(float x) { float y; asm("rcp.approx.ftz.f32 %0, %1;" : "=f"(y) : "f"(x)); return y; }
__device__ __forceinline__ uint32_t pack_bf16(float lo, float hi) { uint32_t r; asm("cvt.rn.bf16x2.f32 %0, %1, %2;" : "=r"(r) : "f"(hi), "f"(lo)); return r; }
__device__ __forceinline__ uint32_t pack_f16(float lo, float hi) { uint32_t r; asm("cvt.rn.f16x2.f32 %0, %1, %2;" : "=r"(r) : "f"(hi), "f"(lo)); return r; }
__device__ __forceinline__ float bf_lo(uint32_t v) { return __uint_as_float(v << 16); }
__device__ __forceinline__ float bf_hi(uint32_t v) { return __uint_as_float(v & 0xFFFF0000u); }
__device__ __forceinline__ uint4 ldg_relaxed(const uint4* p) {
    uint4 v; asm volatile("ld.relaxed.gpu.global.v4.u32 {%0,%1,%2,%3}, [%4];" : "=r"(v.x), "=r"(v.y), "=r"(v.z), "=r"(v.w) : "l"(p) : "memory"); return v;
}
__device__ __forceinline__ void stg128(void* p, uint32_t a, uint32_t b, uint32_t c, uint32_t d) {
    asm volatile("st.relaxed.gpu.global.v4.u32 [%0], {%1,%2,%3,%4};" :: "l"(p), "r"(a), "r"(b), "r"(c), "r"(d) : "memory");
}
__device__ __forceinline__ void stg64(void* p, uint32_t a, uint32_t b) {
    asm volatile("st.relaxed.gpu.global.v2.u32 [%0], {%1,%2};" :: "l"(p), "r"(a), "r"(b) : "memory");
}
__device__ __forceinline__ void sts128(uint32_t a, uint32_t x, uint32_t y, uint32_t z, uint32_t w) {
    asm volatile("st.shared.v4.u32 [%0], {%1,%2,%3,%4};" :: "r"(a), "r"(x), "r"(y), "r"(z), "r"(w) : "memory");
}
__device__ __forceinline__ void sts32(uint32_t a, uint32_t x) { asm volatile("st.shared.u32 [%0], %1;" :: "r"(a), "r"(x) : "memory"); }
__device__ __forceinline__ float4 lds128f(uint32_t a) {
    float4 v; asm volatile("ld.shared.v4.f32 {%0,%1,%2,%3}, [%4];" : "=f"(v.x), "=f"(v.y), "=f"(v.z), "=f"(v.w) : "r"(a) : "memory"); return v;
}
__device__ __forceinline__ uint32_t lds32(uint32_t a) { uint32_t v; asm volatile("ld.shared.u32 %0, [%1];" : "=r"(v) : "r"(a) : "memory"); return v; }
__device__ __forceinline__ bool has_sent(const uint4& v) { return (v.x == SENT) | (v.y == SENT) | (v.z == SENT) | (v.w == SENT); }

#define R4(d, o) "+f"(d[o + 0]), "+f"(d[o + 1]), "+f"(d[o + 2]), "+f"(d[o + 3])
#define R8(d, o) R4(d, o), R4(d, o + 4)
#define R32(d) R8(d, 0), R8(d, 8), R8(d, 16), R8(d, 24)
#define D32 "{%0,%1,%2,%3,%4,%5,%6,%7,%8,%9,%10,%11,%12,%13,%14,%15,%16,%17,%18,%19,%20,%21,%22,%23,%24,%25,%26,%27,%28,%29,%30,%31}"
#define D44 "{%0,%1,%2,%3,%4,%5,%6,%7,%8,%9,%10,%11,%12,%13,%14,%15,%16,%17,%18,%19,%20,%21,%22,%23,%24,%25,%26,%27,%28,%29,%30,%31,%32,%33,%34,%35,%36,%37,%38,%39,%40,%41,%42,%43}"

__device__ __forceinline__ void mma_qk_f16(float (&d)[32], uint64_t da, uint64_t db) {
    asm volatile("{.reg .pred p; setp.eq.b32 p, 0, 0; wgmma.mma_async.sync.aligned.m64n64k16.f32.f16.f16 " D32 ", %32, %33, p, 1, 1, 0, 0;}"
                 : R32(d) : "l"(da), "l"(db));
}
__device__ __forceinline__ void mma_qk_bf16(float (&d)[32], uint64_t da, uint64_t db) {
    asm volatile("{.reg .pred p; setp.ne.b32 p, 0, 0; wgmma.mma_async.sync.aligned.m64n64k16.f32.bf16.bf16 " D32 ", %32, %33, p, 1, 1, 0, 0;}"
                 : R32(d) : "l"(da), "l"(db));
}
__device__ __forceinline__ void mma_pv(float (&d)[12], const uint32_t* a, uint64_t db) {
    asm volatile("{.reg .pred p; setp.eq.b32 p, 0, 0; wgmma.mma_async.sync.aligned.m64n24k16.f32.bf16.bf16 {%0,%1,%2,%3,%4,%5,%6,%7,%8,%9,%10,%11}, {%12,%13,%14,%15}, %16, p, 1, 1, 1;}"
                 : R8(d, 0), R4(d, 8) : "r"(a[0]), "r"(a[1]), "r"(a[2]), "r"(a[3]), "l"(db));
}
__device__ __forceinline__ void mma_ss64(float (&d)[32], uint64_t da, uint64_t db) {
    asm volatile("{.reg .pred p; setp.eq.b32 p, 0, 0; wgmma.mma_async.sync.aligned.m64n64k16.f32.bf16.bf16 " D32 ", %32, %33, p, 1, 1, 0, 1;}"
                 : R32(d) : "l"(da), "l"(db));
}
__device__ __forceinline__ void mma_ss8(float (&d)[4], uint64_t da, uint64_t db) {
    asm volatile("{.reg .pred p; setp.eq.b32 p, 0, 0; wgmma.mma_async.sync.aligned.m64n8k16.f32.bf16.bf16 {%0,%1,%2,%3}, %4, %5, p, 1, 1, 0, 1;}"
                 : R4(d, 0) : "l"(da), "l"(db));
}
__device__ __forceinline__ void mma_rs(float (&d)[32], const uint4& a, uint64_t db) {
    asm volatile("{.reg .pred p; setp.eq.b32 p, 0, 0; wgmma.mma_async.sync.aligned.m64n64k16.f32.bf16.bf16 " D32 ", {%32,%33,%34,%35}, %36, p, 1, 1, 1;}"
                 : R32(d) : "r"(a.x), "r"(a.y), "r"(a.z), "r"(a.w), "l"(db));
}
__device__ __forceinline__ void mma_rs(float (&d)[44], const uint4& a, uint64_t db) {
    asm volatile("{.reg .pred p; setp.eq.b32 p, 0, 0; wgmma.mma_async.sync.aligned.m64n88k16.f32.bf16.bf16 " D44 ", {%44,%45,%46,%47}, %48, p, 1, 1, 1;}"
                 : R32(d), R8(d, 32), R4(d, 40) : "r"(a.x), "r"(a.y), "r"(a.z), "r"(a.w), "l"(db));
}

constexpr float EXP_MAGIC = 256.0f + 127.0f + 64.0f - 1.58621f + 0.00390625f;
constexpr uint32_t MUFU_MASK = 0x1111u;
__device__ __forceinline__ uint32_t exp2_pair(float y0, float y1, uint32_t cexp, uint32_t neg1) {
    uint32_t w, m, e, r;
    asm("prmt.b32 %0, %1, %2, 0x6521;" : "=r"(w) : "r"(__float_as_uint(y0)), "r"(__float_as_uint(y1)));
    asm("lop3.b32 %0, %1, 0x007F007F, %2, 0xEA;" : "=r"(m) : "r"(w), "r"(cexp));
    asm("mad.lo.u32 %0, %1, %2, %3;" : "=r"(e) : "r"(m), "r"(neg1), "r"(w));
    asm("fma.rn.bf16x2 %0, %1, %2, %3;" : "=r"(r) : "r"(w), "r"(m), "r"(e));
    return r;
}

struct Params {
    CUtensorMap wq, wk, wv, wo, w1, w2;
    const __nv_bfloat16* x;
    const __nv_bfloat16* w1p;
    const __nv_bfloat16* w2p;
    const __nv_bfloat16* wop;
    __nv_bfloat16* out;
    uint32_t neg1;
};

template <int EV>
__device__ __forceinline__ void release_event(uint32_t sb, const Params& P, int b) {
    __syncwarp();
    if ((threadIdx.x & 31) == 0) {
        uint32_t old;
        asm volatile("atom.acq_rel.cta.shared.add.u32 %0, [%1], 1;" : "=r"(old) : "r"(sb + SM_MISC + MISC_CNT + EV * 4) : "memory");
        if (old == 15) {
            const uint32_t mb = sb + SM_MISC;
            const int n0 = (b & 7) * 64, f0 = (b & 15) * 88;
            auto w2 = [&](int kb) { mbar_expect(mb + (MB_W2 + kb) * 8, 8192); tma2d(sb + w2_addr(kb), &P.w2, n0, kb * 64, mb + (MB_W2 + kb) * 8); };
            auto w1 = [&](int gi) {
                mbar_expect(mb + (MB_W1 + gi) * 8, 24576);
                for (int a = 0; a < 3; a++) tma2d(sb + SM_W1 + gi * 24576 + a * 8192, &P.w1, f0 + a * 32, gi * 128, mb + (MB_W1 + gi) * 8);
            };
            if (EV == 0) {
                mbar_expect(mb + (MB_WO + 1) * 8, 3 * 8192);
                for (int kb = 5; kb < 8; kb++) tma2d(sb + wo_addr(kb), &P.wo, n0, kb * 64, mb + (MB_WO + 1) * 8);
                w2(1); w2(2);
            }
            if (EV == 1) w1(0);
            if (EV == 2) { w1(1); w1(2); }
            if (EV == 3) { w1(3); w2(3); w2(4); w2(5); }
            if (EV == 4) for (int kb = 6; kb < 14; kb++) w2(kb);
            if (EV == 5) for (int kb = 14; kb < 20; kb++) w2(kb);
            if (EV == 6) { w2(20); w2(21); }
        }
    }
    __syncwarp();
}

__device__ __forceinline__ void load_batch(uint4 (&buf)[4], const uint4* a) {
#pragma unroll
    for (int s = 0; s < 4; s++) buf[s] = ldg_relaxed(a + s * 128);
}
__device__ __forceinline__ void check_batch(uint4 (&buf)[4], const uint4* a) {
    int spins = 0;
    while (__any_sync(0xffffffffu, has_sent(buf[0]) | has_sent(buf[1]) | has_sent(buf[2]) | has_sent(buf[3]))) {
        load_batch(buf, a);
        if (++spins > SPIN_LIMIT) __trap();
    }
}

template <int KIND, int NBLK, int RING, int NACC>
__device__ __forceinline__ void gemm_rs(float (&acc)[NACC], const uint4* a, uint32_t sb, int q, const Params& P, int b) {
    constexpr int ASTR = (KIND == 1) ? 512 : 1024;
    const uint32_t mb = sb + SM_MISC;
    uint4 buf[RING][4];
    load_batch(buf[0], a);
    check_batch(buf[0], a);
#pragma unroll
    for (int i = 1; i < RING; i++) load_batch(buf[i], a + i * ASTR);
#pragma unroll
    for (int i = 0; i < NACC; i++) acc[i] = 0.f;
    fence_regs(acc);
#pragma unroll
    for (int i = 0; i < NBLK; i++) {
        uint64_t db; uint32_t bar, kstep;
        if (KIND == 0) {
            db = mkdesc(sb + (q ? wo_addr(2 * i + 1) : wo_addr(2 * i)), 16, 1024, 1);
            bar = MB_WO + ((2 * i + q) >= 5); kstep = 128;
        } else if (KIND == 1) {
            db = mkdesc(sb + SM_W1 + (i >> 1) * 24576 + (i & 1) * 4096, 8192, 512, 2);
            bar = MB_W1 + (i >> 1); kstep = 64;
        } else {
            db = mkdesc(sb + (q ? w2_addr(2 * i + 1) : w2_addr(2 * i)), 16, 1024, 1);
            bar = MB_W2 + 2 * i + q; kstep = 128;
        }
        if (KIND != 1 || (i & 1) == 0) mbar_wait(mb + bar * 8);
        if (i > 0) check_batch(buf[i % RING], a + i * ASTR);
        wg_fence();
#pragma unroll
        for (int s = 0; s < 4; s++) mma_rs(acc, buf[i % RING][s], db + s * kstep);
        wg_commit();
        if (i >= 1 && (i - 1 + RING < NBLK || (KIND == 1 && (i == 4 || i == 6)))) {
            wg_wait<1>();
            if (i - 1 + RING < NBLK) load_batch(buf[(i - 1) % RING], a + (i - 1 + RING) * ASTR);
            if (KIND == 1 && i == 4) release_event<5>(sb, P, b);
            if (KIND == 1 && i == 6) release_event<6>(sb, P, b);
        }
    }
    wg_wait<0>();
    fence_regs(acc);
}

__device__ __forceinline__ void pair_reduce(const float (&acc)[32], float (&r)[16], uint32_t buf, int q, int barid) {
    if (q) {
#pragma unroll
        for (int j = 0; j < 4; j++) sts128(buf + j * 2048, __float_as_uint(acc[4 * j]), __float_as_uint(acc[4 * j + 1]), __float_as_uint(acc[4 * j + 2]), __float_as_uint(acc[4 * j + 3]));
        bar_sync(barid, 256);
        bar_sync(barid, 256);
#pragma unroll
        for (int j = 0; j < 4; j++) {
            float4 v = lds128f(buf + j * 2048);
            r[4 * j] = acc[16 + 4 * j] + v.x; r[4 * j + 1] = acc[17 + 4 * j] + v.y; r[4 * j + 2] = acc[18 + 4 * j] + v.z; r[4 * j + 3] = acc[19 + 4 * j] + v.w;
        }
    } else {
        bar_sync(barid, 256);
#pragma unroll
        for (int j = 0; j < 4; j++) {
            float4 v = lds128f(buf + j * 2048);
            r[4 * j] = acc[4 * j] + v.x; r[4 * j + 1] = acc[4 * j + 1] + v.y; r[4 * j + 2] = acc[4 * j + 2] + v.z; r[4 * j + 3] = acc[4 * j + 3] + v.w;
            sts128(buf + j * 2048, __float_as_uint(acc[16 + 4 * j]), __float_as_uint(acc[17 + 4 * j]), __float_as_uint(acc[18 + 4 * j]), __float_as_uint(acc[19 + 4 * j]));
        }
        bar_arrive(barid, 256);
    }
}

__device__ __forceinline__ float quad_sum(float v) { v += __shfl_xor_sync(0xffffffffu, v, 1); v += __shfl_xor_sync(0xffffffffu, v, 2); return v; }
__device__ __forceinline__ float silu(float z) { return z * rcp(1.0f + ex2(-1.4426950408889634f * z)); }

__global__ void __launch_bounds__(512, 1) fused_kernel(const __grid_constant__ Params P) {
    extern __shared__ __align__(1024) uint8_t smem[];
    const uint32_t sb = (uint32_t)__cvta_generic_to_shared(smem);
    const uint32_t mb = sb + SM_MISC;
    const int tid = threadIdx.x, lane = tid & 31, b = blockIdx.x;
    const int warp = __shfl_sync(0xffffffffu, tid >> 5, 0);
    const int wg = warp >> 2, ww = warp & 3, g = lane >> 2, t4 = lane & 3, t128 = tid & 127;

    if (b >= NMAIN) {
        const int hi = b - NMAIN;
        const unsigned epoch = g_epoch[b] + 1;
        float* red = reinterpret_cast<float*>(smem);
        if (tid < 352) red[tid] = 0.f;
        if (tid < NMAIN) {
            unsigned long long v; int spins = 0;
            do { asm volatile("ld.relaxed.gpu.global.u64 %0, [%1];" : "=l"(v) : "l"(g_flag1 + tid) : "memory"); if (++spins > SPIN_LIMIT) __trap(); } while ((unsigned)(v >> 32) != epoch);
        }
        __syncthreads();
        if (tid == 480) {
            for (int i = 0; i < 8; i++) asm volatile("cp.async.bulk.prefetch.L2.global [%0], %1;" :: "l"((const char*)P.wop + hi * 131072 + i * 16384), "r"(16384) : "memory");
            for (int i = 0; i < 43; i++) asm volatile("cp.async.bulk.prefetch.L2.global [%0], %1;" :: "l"((const char*)P.w2p + hi * 352256 + i * 8192), "r"(8192) : "memory");
        }
        if (tid < 344) {
            const int cg = tid % 43, rp = tid / 43;
            const uint4* src = reinterpret_cast<const uint4*>(P.w1p + (size_t)rp * 64 * FF + (hi * 43 + cg) * 8);
            float s[8] = {0, 0, 0, 0, 0, 0, 0, 0};
#pragma unroll 8
            for (int r = 0; r < 64; r++) {
                uint4 v = __ldg(src + r * (FF / 8));
                s[0] += bf_lo(v.x); s[1] += bf_hi(v.x); s[2] += bf_lo(v.y); s[3] += bf_hi(v.y);
                s[4] += bf_lo(v.z); s[5] += bf_hi(v.z); s[6] += bf_lo(v.w); s[7] += bf_hi(v.w);
            }
            float* part = red + 512 + (rp * 43 + cg) * 8;
#pragma unroll
            for (int i = 0; i < 8; i++) part[i] = s[i];
        }
        __syncthreads();
        if (tid < 344) {
            float s = 0.f;
#pragma unroll
            for (int rp = 0; rp < 8; rp++) s += red[512 + rp * 344 + tid];
            g_cs[hi * 344 + tid] = s;
        } else if (hi == 3 && tid < 344 + 32) g_cs[FF + tid - 344] = 0.f;
        __syncthreads();
        if (tid == 0) {
            asm volatile("st.release.gpu.global.u32 [%0], %1;" :: "l"(g_flag2 + b), "r"(epoch) : "memory");
            g_epoch[b] = epoch;
        }
        return;
    }

    const int tg = b >> 2, hg = b & 3;
    if (tid == 0) {
        for (uint32_t i = 0; i < NBAR; i++) mbar_init(mb + i * 8, 1);
        asm volatile("fence.mbarrier_init.release.cluster;" ::: "memory");
        fence_async_smem();
        mbar_expect(mb + MB_WKV * 8, 8192);
        const CUtensorMap* tm = hg < 2 ? &P.wk : &P.wv;
        tma2d(sb + SM_WKV, tm, (hg & 1) * 8, 0, mb + MB_WKV * 8);
        tma2d(sb + SM_WKV + 4096, tm, (hg & 1) * 8, 256, mb + MB_WKV * 8);
        for (int i = 0; i < 4; i++) {
            mbar_expect(mb + (MB_WQ + i) * 8, 32768);
            tma2d(sb + SM_WQ + i * 16384, &P.wq, hg * 128, i * 128, mb + (MB_WQ + i) * 8);
            tma2d(sb + SM_WQ + 65536 + i * 16384, &P.wq, hg * 128 + 64, i * 128, mb + (MB_WQ + i) * 8);
        }
    }
    if (tid == 32) {
        const unsigned e = g_epoch[b] + 1;
        g_epoch[b] = e;
        sts32(mb + MISC_EPOCH, e);
    }
    if (tid >= 64 && tid < 64 + 24) sts32(mb + MISC_CNT + (tid - 64) * 4, 0);
    {
        uint4 xv[4][2];
#pragma unroll
        for (int i = 0; i < 4; i++) {
            const int r = warp * 4 + i;
            const int tok = (r & 31) + tg * 32 + (r >> 5) * 1024;
            const uint4* src = reinterpret_cast<const uint4*>(P.x + (size_t)tok * D);
            xv[i][0] = __ldg(src + lane); xv[i][1] = __ldg(src + lane + 32);
        }
#pragma unroll
        for (int i = 0; i < 4; i++) {
            float f[16];
#pragma unroll
            for (int c = 0; c < 2; c++) {
                f[8 * c + 0] = bf_lo(xv[i][c].x); f[8 * c + 1] = bf_hi(xv[i][c].x); f[8 * c + 2] = bf_lo(xv[i][c].y); f[8 * c + 3] = bf_hi(xv[i][c].y);
                f[8 * c + 4] = bf_lo(xv[i][c].z); f[8 * c + 5] = bf_hi(xv[i][c].z); f[8 * c + 6] = bf_lo(xv[i][c].w); f[8 * c + 7] = bf_hi(xv[i][c].w);
            }
            float s = 0.f;
#pragma unroll
            for (int j = 0; j < 16; j++) s += f[j];
#pragma unroll
            for (int o = 16; o > 0; o >>= 1) s += __shfl_xor_sync(0xffffffffu, s, o);
            const float mean = s * (1.0f / D);
            float v = 0.f;
#pragma unroll
            for (int j = 0; j < 16; j++) { f[j] -= mean; v = fmaf(f[j], f[j], v); }
#pragma unroll
            for (int o = 16; o > 0; o >>= 1) v += __shfl_xor_sync(0xffffffffu, v, o);
            const float rstd = rsqrtf(v * (1.0f / D) + 1e-5f);
            const int r = warp * 4 + i;
#pragma unroll
            for (int c = 0; c < 2; c++) {
                const uint32_t addr = sb + SM_XN + ((lane >> 3) + 4 * c) * 8192 + r * 128 + (((lane & 7) ^ (r & 7)) << 4);
                sts128(addr, pack_bf16(f[8 * c] * rstd, f[8 * c + 1] * rstd), pack_bf16(f[8 * c + 2] * rstd, f[8 * c + 3] * rstd),
                       pack_bf16(f[8 * c + 4] * rstd, f[8 * c + 5] * rstd), pack_bf16(f[8 * c + 6] * rstd, f[8 * c + 7] * rstd));
            }
        }
    }
    fence_async_smem();
    __syncthreads();
    TS(0);
    const unsigned epoch = lds32(mb + MISC_EPOCH);
    constexpr float QSCALE = 0.25f * 1.4426950408889634f;
    {
        float qa[32];
        if (wg < 2) {
#pragma unroll
            for (int i = 0; i < 32; i++) qa[i] = 0.f;
            fence_regs(qa);
            bar_sync(1, 384);
            const uint64_t da = mkdesc(sb + SM_XN, 16, 1024, 1), db = mkdesc(sb + SM_WQ + wg * 65536, 16, 1024, 1);
#pragma unroll 1
            for (int i = 0; i < 4; i++) {
                mbar_wait(mb + (MB_WQ + i) * 8);
                wg_fence();
#pragma unroll
                for (int s = 0; s < 8; s++) mma_ss64(qa, da + (i * 2 + (s >> 2)) * 512 + (s & 3) * 2, db + (i * 8 + s) * 128);
                wg_commit();
            }
            wg_wait<0>();
            fence_regs(qa);
            uint32_t nm = 0;
#pragma unroll
            for (int i = 0; i < 32; i++) qa[i] *= QSCALE;
#pragma unroll
            for (int h = 0; h < 4; h++) {
                float n0 = qa[8 * h] * qa[8 * h] + qa[8 * h + 1] * qa[8 * h + 1] + qa[8 * h + 4] * qa[8 * h + 4] + qa[8 * h + 5] * qa[8 * h + 5];
                float n1 = qa[8 * h + 2] * qa[8 * h + 2] + qa[8 * h + 3] * qa[8 * h + 3] + qa[8 * h + 6] * qa[8 * h + 6] + qa[8 * h + 7] * qa[8 * h + 7];
                nm = max(nm, max(__float_as_uint(quad_sum(n0)), __float_as_uint(quad_sum(n1))));
            }
            nm = __reduce_max_sync(0xffffffffu, nm);
            if (lane == 0) asm volatile("red.shared.max.u32 [%0], %1;" :: "r"(mb + MISC_NRM), "r"(nm) : "memory");
        } else if (wg == 2) {
            float kv[4] = {0.f, 0.f, 0.f, 0.f};
            fence_regs(kv);
            const uint64_t da = mkdesc(sb + SM_XN, 16, 1024, 1), db = mkdesc(sb + SM_WKV, 128, 16, 0);
            mbar_wait(mb + MB_WKV * 8);
            wg_fence();
#pragma unroll
            for (int s = 0; s < 32; s++) mma_ss8(kv, da + (s >> 2) * 512 + (s & 3) * 2, db + s * 16);
            wg_commit();
            wg_wait<0>();
            fence_regs(kv);
            bar_arrive(1, 384);
            const int half = hg & 1;
            uint32_t nm = max(__float_as_uint(quad_sum(kv[0] * kv[0] + kv[1] * kv[1])), __float_as_uint(quad_sum(kv[2] * kv[2] + kv[3] * kv[3])));
            nm = __reduce_max_sync(0xffffffffu, nm);
            if (lane == 0) asm volatile("red.shared.max.u32 [%0], %1;" :: "r"(mb + MISC_NRM + 16), "r"(nm) : "memory");
            const int r0 = ww * 16 + g, c = 2 * tg + (ww >> 1);
            if (hg < 2) {
                float2* kt = reinterpret_cast<float2*>(smem + SM_MISC + MISC_KTMP);
                kt[r0 * 4 + t4] = make_float2(kv[0], kv[1]);
                kt[(r0 + 8) * 4 + t4] = make_float2(kv[2], kv[3]);
                bar_sync(2, 128);
#pragma unroll
                for (int i = 0; i < 2; i++) {
                    const int r = r0 + 8 * i, t = r & 31;
                    float2 pv = make_float2(0.f, 0.f);
                    if (t > 0) pv = kt[(r - 1) * 4 + t4];
                    const int off = (t & 7) * 2048 + (c >> 3) * 256 + half * 128 + (c & 7) * 16 + t4 * 4;
                    *reinterpret_cast<uint32_t*>(reinterpret_cast<char*>(g_kv) + (t >> 3) * 32768 + off) = pack_f16(kv[2 * i] - pv.x, kv[2 * i + 1] - pv.y);
                    *reinterpret_cast<uint32_t*>(reinterpret_cast<char*>(g_kplain) + (t >> 3) * 16384 + off) = pack_bf16(kv[2 * i], kv[2 * i + 1]);
                }
            } else {
#pragma unroll
                for (int i = 0; i < 2; i++) {
                    const int t = (r0 + 8 * i) & 31;
                    const int off = (t >> 3) * 32768 + 16384 + half * 8192 + ((t & 7) * 64 + c) * 16 + t4 * 4;
                    *reinterpret_cast<uint32_t*>(reinterpret_cast<char*>(g_kv) + off) = pack_bf16(kv[2 * i], kv[2 * i + 1]);
                }
            }
            asm volatile("fence.proxy.async.global;" ::: "memory");
            bar_sync(2, 128);
            if (t128 == 0) {
                const unsigned long long v = ((unsigned long long)epoch << 32) | lds32(mb + MISC_NRM + 16);
                asm volatile("st.release.gpu.global.u64 [%0], %1;" :: "l"(g_flag1 + b), "l"(v) : "memory");
            }
        } else {
            unsigned long long v; int spins = 0;
            do { asm volatile("ld.acquire.gpu.global.u64 %0, [%1];" : "=l"(v) : "l"(g_flag1 + t128) : "memory"); if (++spins > SPIN_LIMIT) __trap(); } while ((unsigned)(v >> 32) != epoch);
            uint32_t nm = (uint32_t)v;
            nm = max(nm, __shfl_xor_sync(0xffffffffu, nm, 4)); nm = max(nm, __shfl_xor_sync(0xffffffffu, nm, 8)); nm = max(nm, __shfl_xor_sync(0xffffffffu, nm, 16));
            if (lane < 4) asm volatile("red.shared.max.u32 [%0], %1;" :: "r"(mb + MISC_NRM + 4 + min(lane, 2) * 4), "r"(nm) : "memory");
        }
        TS(1);
        __syncthreads();
        TS(2);
        const float q2 = __uint_as_float(lds32(mb + MISC_NRM)), v2 = __uint_as_float(lds32(mb + MISC_NRM + 12));
        const float k2 = __uint_as_float(lds32(mb + MISC_NRM + 4)) + __uint_as_float(lds32(mb + MISC_NRM + 8));
        const bool safe = (q2 * k2 <= 3500.0f) && (q2 <= 65536.0f) && (k2 <= 65536.0f) && (v2 <= 1e24f);
        if (tid == 384) {
            asm volatile("fence.proxy.async.global;" ::: "memory");
            for (int c = 0; c < 4; c++) {
                mbar_expect(mb + (MB_KV + c) * 8, 32768);
                if (safe) bulk_g2s(sb + c * KVCH, g_kv + c * 2048, 32768, mb + (MB_KV + c) * 8);
                else { bulk_g2s(sb + c * KVCH, g_kplain + c * 1024, 16384, mb + (MB_KV + c) * 8); bulk_g2s(sb + c * KVCH + 16384, g_kv + c * 2048 + 1024, 16384, mb + (MB_KV + c) * 8); }
            }
            mbar_expect(mb + MB_WO * 8, 5 * 8192);
            for (int kb = 0; kb < 5; kb++) tma2d(sb + wo_addr(kb), &P.wo, (b & 7) * 64, kb * 64, mb + MB_WO * 8);
            mbar_expect(mb + MB_W2 * 8, 8192);
            tma2d(sb + w2_addr(0), &P.w2, (b & 7) * 64, 0, mb + MB_W2 * 8);
        }
        if (wg < 2) {
#pragma unroll
            for (int h = 0; h < 4; h++) {
                const int hl = wg * 4 + h;
                const uint32_t base = sb + SM_Q + ((ww >> 1) * 4 + (hl >> 1)) * 2048 + ((hl & 1) * 4 + (ww & 1) * 2) * 256 + lane * 4;
                if (safe) {
                    sts32(base, pack_f16(qa[8 * h], qa[8 * h + 1])); sts32(base + 256, pack_f16(qa[8 * h + 2], qa[8 * h + 3]));
                    sts32(base + 128, pack_f16(qa[8 * h + 4], qa[8 * h + 5])); sts32(base + 384, pack_f16(qa[8 * h + 6], qa[8 * h + 7]));
                } else {
                    sts32(base, pack_bf16(qa[8 * h], qa[8 * h + 1])); sts32(base + 256, pack_bf16(qa[8 * h + 2], qa[8 * h + 3]));
                    sts32(base + 128, pack_bf16(qa[8 * h + 4], qa[8 * h + 5])); sts32(base + 384, pack_bf16(qa[8 * h + 6], qa[8 * h + 7]));
                }
            }
        }
#pragma unroll
        for (int c = 0; c < 4; c++) sts128(sb + c * KVCH + 32768 + tid * 16, 0x3F803F80u, 0x3F803F80u, 0x3F803F80u, 0x3F803F80u);
        fence_async_smem();
        __syncthreads();
        TS(3);

        const int pr = wg >> 1, q = wg & 1;
        uint32_t cexp = 0x9F809F80u + (tid >> 12);
        const uint32_t neg1 = P.neg1;
#pragma unroll 1
        for (int pass = 0; pass < 2; pass++) {
            float o[12], s[32];
            const uint64_t dq = mkdesc(sb + SM_Q + (pass * 4 + wg) * 2048, 128, 256, 0);
            uint64_t dk = mkdesc(sb, 128, 256, 0);
            uint64_t dv = mkdesc(sb + 16384, 128, 8192, 0);
#pragma unroll
            for (int i = 0; i < 12; i++) o[i] = 0.f;
            float m0 = -INFINITY, m1 = -INFINITY;
            if (pass == 0) { mbar_wait(mb + MB_KV * 8); TS(4); }
            if (safe) {
#pragma unroll
                for (int i = 0; i < 32; i++) s[i] = ((MUFU_MASK >> (i / 2)) & 1) ? 0.f : EXP_MAGIC;
                fence_regs(s); fence_regs(o);
                wg_fence();
                mma_qk_f16(s, dq, dk); wg_commit();
                wg_wait<0>(); fence_regs(s);
            }
#pragma unroll 1
            for (int c = 0; c < 4; c++) {
                if (pass == 0) {
                    if (c < 3) mbar_wait(mb + (MB_KV + c + 1) * 8);
                    const int mt = 16 * pr + (b >> 3), mt1 = 16 * pr + (b >> 4) * 2 + q, sl = b & 15;
                    if (c == 0) {
                        stg128(g_of + ((16 + (tg >> 1)) * 32 + hg * 8 + 2 * wg + (ww >> 1)) * 128 + ((tg & 1) * 2 + (ww & 1)) * 32 + lane, SENT, SENT, SENT, SENT);
                        stg128(g_hf + (mt * 32 + (b & 7) * 4 + 2 * q) * 128 + t128, SENT, SENT, SENT, SENT);
                        stg128(g_hf + (mt * 32 + (b & 7) * 4 + 2 * q + 1) * 128 + t128, SENT, SENT, SENT, SENT);
                        if (t4 < 2) stg64(g_stats + (mt * 64 + ww * 16 + g + 8 * t4) * 16 + (b & 7) * 2 + q, SENT, SENT);
                    } else {
                        uint4* hb = g_Hf + (mt1 * 88 + (sl >> 1) * 11 + (sl & 1) * 6) * 128 + t128;
                        if (c == 1) { stg128(hb, SENT, SENT, SENT, SENT); stg128(hb + 128, SENT, SENT, SENT, SENT); }
                        if (c == 2) { stg128(hb + 256, SENT, SENT, SENT, SENT); stg128(hb + 384, SENT, SENT, SENT, SENT); }
                        if (c == 3) {
                            stg128(hb + 512, SENT, SENT, SENT, SENT);
                            stg64(reinterpret_cast<uint2*>(g_Hf + (mt1 * 88 + (sl >> 1) * 11 + 5) * 128 + t128) + (sl & 1), SENT, SENT);
                        }
                    }
                } else if (c == 3 && warp == 15) {
#pragma unroll 1
                    for (int i = lane; i < NCTA; i += 32) {
                        unsigned v; int spins = 0;
                        do { asm volatile("ld.acquire.gpu.global.u32 %0, [%1];" : "=r"(v) : "l"(g_flag2 + i) : "memory"); if (++spins > SPIN_LIMIT) __trap(); } while (v != epoch);
                    }
                    __syncwarp();
                    if (lane == 0) mbar_arrive(mb + MB_F2 * 8);
                }
                if (safe) {
#pragma unroll 1
                    for (int i = 0; i < 8; i++) {
                        uint32_t p[16];
#pragma unroll
                        for (int j = 0; j < 16; j++) {
                            if ((MUFU_MASK >> j) & 1) p[j] = pack_bf16(ex2(s[2 * j]), ex2(s[2 * j + 1]));
                            else p[j] = exp2_pair(s[2 * j], s[2 * j + 1], cexp, neg1);
                        }
                        dk += (i == 7) ? ((c == 3) ? 0 : (KVCH - 7 * 2048) / 16) : 128;
                        fence_regs(p);
                        wg_fence();
                        mma_qk_f16(s, dq, dk);
#pragma unroll
                        for (int j = 0; j < 4; j++) mma_pv(o, p + 4 * j, dv + j * 16);
                        wg_commit();
                        dv += 64;
                        wg_wait<0>(); fence_regs(s);
                    }
                } else {
#pragma unroll 1
                    for (int i = 0; i < 8; i++) {
                        uint32_t p[16];
                        fence_regs(o);
                        wg_fence();
                        mma_qk_bf16(s, dq, dk); wg_commit();
                        wg_wait<0>(); fence_regs(s);
                        float x0 = m0, x1 = m1;
#pragma unroll
                        for (int j = 0; j < 8; j++) { x0 = fmaxf(x0, fmaxf(s[4 * j], s[4 * j + 1])); x1 = fmaxf(x1, fmaxf(s[4 * j + 2], s[4 * j + 3])); }
                        x0 = fmaxf(x0, __shfl_xor_sync(0xffffffffu, x0, 1)); x0 = fmaxf(x0, __shfl_xor_sync(0xffffffffu, x0, 2));
                        x1 = fmaxf(x1, __shfl_xor_sync(0xffffffffu, x1, 1)); x1 = fmaxf(x1, __shfl_xor_sync(0xffffffffu, x1, 2));
                        const float c0 = ex2(m0 - x0), c1 = ex2(m1 - x1);
                        m0 = x0; m1 = x1;
#pragma unroll
                        for (int j = 0; j < 3; j++) { o[4 * j] *= c0; o[4 * j + 1] *= c0; o[4 * j + 2] *= c1; o[4 * j + 3] *= c1; }
#pragma unroll
                        for (int j = 0; j < 8; j++) {
                            p[2 * j] = pack_bf16(ex2(s[4 * j] - m0), ex2(s[4 * j + 1] - m0));
                            p[2 * j + 1] = pack_bf16(ex2(s[4 * j + 2] - m1), ex2(s[4 * j + 3] - m1));
                        }
                        dk += (i == 7) ? (KVCH - 7 * 2048) / 16 : 128;
                        fence_regs(p); fence_regs(o);
                        wg_fence();
#pragma unroll
                        for (int j = 0; j < 4; j++) mma_pv(o, p + 4 * j, dv + j * 16);
                        wg_commit();
                        dv += 64;
                        wg_wait<0>(); fence_regs(o);
                    }
                }
                dv += (KVCH - 8192) / 16;
                if (pass == 1 && c < 3) {
                    if (c == 0) release_event<0>(sb, P, b);
                    else if (c == 1) release_event<1>(sb, P, b);
                    else release_event<2>(sb, P, b);
                }
            }
            fence_regs(o);
            const float i0 = 1.0f / o[8], i1 = 1.0f / o[10];
            stg128(g_of + ((16 * pass + (tg >> 1)) * 32 + hg * 8 + 2 * wg + (ww >> 1)) * 128 + ((tg & 1) * 2 + (ww & 1)) * 32 + lane,
                   pack_bf16(o[0] * i0, o[1] * i0), pack_bf16(o[2] * i1, o[3] * i1), pack_bf16(o[4] * i0, o[5] * i0), pack_bf16(o[6] * i1, o[7] * i1));
            if (pass == 0) {
                __syncwarp();
                if (lane == 0) {
                    uint32_t old;
                    asm volatile("fence.acq_rel.gpu;" ::: "memory");
                    asm volatile("atom.acq_rel.cta.shared.add.u32 %0, [%1], 1;" : "=r"(old) : "r"(mb + MISC_CNT + 7 * 4) : "memory");
                    if (old == 15) asm volatile("st.release.gpu.global.u32 [%0], %1;" :: "l"(g_flag2 + b), "r"(epoch) : "memory");
                }
                __syncwarp();
                TS(5);
            }
        }
        release_event<3>(sb, P, b);
        TS(6);

        const int mt = 16 * pr + (b >> 3), j = b & 7;
        const uint32_t xbuf = sb + SM_Q + pr * 8192 + t128 * 16;
        const int row0 = mt * 64 + ww * 16 + g;
        uint32_t hk[8];
        mbar_wait(mb + MB_F2 * 8);
        {
            uint32_t xr[8];
            const uint32_t* xp = reinterpret_cast<const uint32_t*>(P.x + (size_t)row0 * D + j * 64 + q * 32 + t4 * 2);
#pragma unroll
            for (int i = 0; i < 4; i++) { xr[2 * i] = __ldg(xp + i * 4); xr[2 * i + 1] = __ldg(xp + i * 4 + 8 * (D / 2)); }
            float acc[32], r[16];
            gemm_rs<0, 4, 4>(acc, g_of + (mt * 32 + q * 4) * 128 + t128, sb, q, P, b);
            release_event<4>(sb, P, b);
            TS(7);
            if (pr == 1) mbar_wait(mb + (MB_W1 + 3) * 8);
            pair_reduce(acc, r, xbuf, q, 3 + pr);
            float s0 = 0.f, s1 = 0.f;
#pragma unroll
            for (int i = 0; i < 8; i++) {
                hk[i] = pack_bf16(r[2 * i] + bf_lo(xr[i]), r[2 * i + 1] + bf_hi(xr[i]));
                r[2 * i] = bf_lo(hk[i]); r[2 * i + 1] = bf_hi(hk[i]);
                if (i & 1) s1 += r[2 * i] + r[2 * i + 1]; else s0 += r[2 * i] + r[2 * i + 1];
            }
            uint4* hp = g_hf + (mt * 32 + j * 4 + 2 * q) * 128 + t128;
            stg128(hp, hk[0], hk[1], hk[2], hk[3]);
            stg128(hp + 128, hk[4], hk[5], hk[6], hk[7]);
            s0 = quad_sum(s0); s1 = quad_sum(s1);
            const float a0 = s0 * (1.0f / 32), a1 = s1 * (1.0f / 32);
            float v0 = 0.f, v1 = 0.f;
#pragma unroll
            for (int i = 0; i < 8; i++) {
                const float a = (i & 1) ? a1 : a0;
                const float d0 = r[2 * i] - a, d1 = r[2 * i + 1] - a;
                if (i & 1) v1 += d0 * d0 + d1 * d1; else v0 += d0 * d0 + d1 * d1;
            }
            v0 = quad_sum(v0); v1 = quad_sum(v1);
            if (t4 < 2) stg64(g_stats + (row0 + 8 * t4) * 16 + j * 2 + q, __float_as_uint(t4 ? s1 : s0), __float_as_uint(t4 ? v1 : v0));
            TS(8);
        }
        {
            const int mt1 = 16 * pr + (b >> 4) * 2 + q, sl = b & 15;
            float acc[44];
            gemm_rs<1, 8, 3>(acc, g_hf + mt1 * 32 * 128 + t128, sb, q, P, b);
            TS(9);
            float nmean[2], rstd[2];
#pragma unroll
            for (int i = 0; i < 2; i++) {
                const uint4* sp = reinterpret_cast<const uint4*>(g_stats + (mt1 * 64 + ww * 16 + g + 8 * i) * 16 + t4 * 4);
                uint4 u0, u1; int spins = 0;
                do { u0 = ldg_relaxed(sp); u1 = ldg_relaxed(sp + 1); if (++spins > SPIN_LIMIT) __trap(); } while (__any_sync(0xffffffffu, has_sent(u0) | has_sent(u1)));
                const float a = __uint_as_float(u0.x), c = __uint_as_float(u0.z), e = __uint_as_float(u1.x), f = __uint_as_float(u1.z);
                const float mean = quad_sum(a + c + e + f) * (1.0f / D);
                const float da = a * (1.0f / 32) - mean, dc = c * (1.0f / 32) - mean, de = e * (1.0f / 32) - mean, df = f * (1.0f / 32) - mean;
                const float m2 = quad_sum(__uint_as_float(u0.y) + __uint_as_float(u0.w) + __uint_as_float(u1.y) + __uint_as_float(u1.w) + 32.0f * (da * da + dc * dc + de * de + df * df));
                rstd[i] = rsqrtf(m2 * (1.0f / D) + 1e-5f);
                nmean[i] = -mean;
            }
            uint32_t hv[22];
            const float2* cp = reinterpret_cast<const float2*>(g_cs + sl * 88 + t4 * 2);
#pragma unroll
            for (int i = 0; i < 11; i++) {
                const float2 cs = __ldcg(cp + i * 4);
                hv[2 * i] = pack_bf16(silu(rstd[0] * fmaf(nmean[0], cs.x, acc[4 * i])), silu(rstd[0] * fmaf(nmean[0], cs.y, acc[4 * i + 1])));
                hv[2 * i + 1] = pack_bf16(silu(rstd[1] * fmaf(nmean[1], cs.x, acc[4 * i + 2])), silu(rstd[1] * fmaf(nmean[1], cs.y, acc[4 * i + 3])));
            }
            uint4* hb = g_Hf + (mt1 * 88 + (sl >> 1) * 11) * 128 + t128;
            if (sl & 1) {
                stg64(reinterpret_cast<uint2*>(hb + 5 * 128) + 1, hv[0], hv[1]);
#pragma unroll
                for (int i = 0; i < 5; i++) stg128(hb + (6 + i) * 128, hv[2 + 4 * i], hv[3 + 4 * i], hv[4 + 4 * i], hv[5 + 4 * i]);
            } else {
#pragma unroll
                for (int i = 0; i < 5; i++) stg128(hb + i * 128, hv[4 * i], hv[4 * i + 1], hv[4 * i + 2], hv[4 * i + 3]);
                stg64(hb + 5 * 128, hv[20], hv[21]);
            }
            TS(10);
        }
        {
            float acc[32], r[16];
            gemm_rs<2, 11, 4>(acc, g_Hf + (mt * 88 + q * 4) * 128 + t128, sb, q, P, b);
            TS(11);
            pair_reduce(acc, r, xbuf, q, 3 + pr);
            uint32_t ov[8];
#pragma unroll
            for (int i = 0; i < 8; i++) ov[i] = pack_bf16(r[2 * i] + bf_lo(hk[i]), r[2 * i + 1] + bf_hi(hk[i]));
#pragma unroll
            for (int h = 0; h < 2; h++) {
                uint32_t v0 = ov[h], v1 = ov[2 + h], v2 = ov[4 + h], v3 = ov[6 + h];
                const bool o1 = t4 & 1, o2 = t4 & 2;
                uint32_t a = __shfl_xor_sync(0xffffffffu, o1 ? v0 : v1, 1), c = __shfl_xor_sync(0xffffffffu, o1 ? v2 : v3, 1);
                if (o1) { v0 = a; v2 = c; } else { v1 = a; v3 = c; }
                a = __shfl_xor_sync(0xffffffffu, o2 ? v0 : v2, 2); c = __shfl_xor_sync(0xffffffffu, o2 ? v1 : v3, 2);
                if (o2) { v0 = a; v1 = c; } else { v2 = a; v3 = c; }
                *reinterpret_cast<uint4*>(P.out + (size_t)(row0 + 8 * h) * D + j * 64 + q * 32 + t4 * 8) = make_uint4(v0, v1, v2, v3);
            }
            TS(12);
        }
    }
}

typedef CUresult (*EncodeFn)(CUtensorMap*, CUtensorMapDataType, cuuint32_t, void*, const cuuint64_t*, const cuuint64_t*, const cuuint32_t*,
                             const cuuint32_t*, CUtensorMapInterleave, CUtensorMapSwizzle, CUtensorMapL2promotion, CUtensorMapFloatOOBfill);

void encode2d(EncodeFn fn, CUtensorMap* tm, const void* ptr, int rows, int cols, int box_rows, int box_cols, CUtensorMapSwizzle sw) {
    cuuint64_t dims[2] = {(cuuint64_t)cols, (cuuint64_t)rows};
    cuuint64_t strides[1] = {(cuuint64_t)cols * 2};
    cuuint32_t box[2] = {(cuuint32_t)box_cols, (cuuint32_t)box_rows};
    cuuint32_t es[2] = {1, 1};
    fn(tm, CU_TENSOR_MAP_DATA_TYPE_BFLOAT16, 2, const_cast<void*>(ptr), dims, strides, box, es, CU_TENSOR_MAP_INTERLEAVE_NONE, sw,
       CU_TENSOR_MAP_L2_PROMOTION_L2_128B, CU_TENSOR_MAP_FLOAT_OOB_FILL_NONE);
}

}

extern "C" void kernel_launch(void* const* d_in, const int* in_sizes, int n_in, void* d_out, int out_size) {
    (void)in_sizes; (void)n_in; (void)out_size;
    void* fnp = nullptr;
    cudaDriverEntryPointQueryResult qr;
    cudaGetDriverEntryPoint("cuTensorMapEncodeTiled", &fnp, cudaEnableDefault, &qr);
    EncodeFn fn = (EncodeFn)fnp;
    Params P;
    encode2d(fn, &P.wq, d_in[1], D, D, 128, 64, CU_TENSOR_MAP_SWIZZLE_128B);
    encode2d(fn, &P.wk, d_in[2], D, 16, 256, 8, CU_TENSOR_MAP_SWIZZLE_NONE);
    encode2d(fn, &P.wv, d_in[3], D, 16, 256, 8, CU_TENSOR_MAP_SWIZZLE_NONE);
    encode2d(fn, &P.wo, d_in[4], D, D, 64, 64, CU_TENSOR_MAP_SWIZZLE_128B);
    encode2d(fn, &P.w1, d_in[6], D, FF, 128, 32, CU_TENSOR_MAP_SWIZZLE_64B);
    encode2d(fn, &P.w2, d_in[7], FF, D, 64, 64, CU_TENSOR_MAP_SWIZZLE_128B);
    P.x = (const __nv_bfloat16*)d_in[0];
    P.w1p = (const __nv_bfloat16*)d_in[6];
    P.w2p = (const __nv_bfloat16*)d_in[7];
    P.wop = (const __nv_bfloat16*)d_in[4];
    P.out = (__nv_bfloat16*)d_out;
    P.neg1 = 0xFFFFFFFFu;
    cudaFuncSetAttribute(fused_kernel, cudaFuncAttributeMaxDynamicSharedMemorySize, SMEM_BYTES);
    fused_kernel<<<NCTA, 512, SMEM_BYTES>>>(P);
}
```

```cpp
#include <cuda_runtime.h>
#include <cuda_bf16.h>
#include <cuda.h>
#include <stdint.h>

namespace {

constexpr int D = 512, FF = 1376;
constexpr int NMAIN = 128, NHELP = 4, NCTA = NMAIN + NHELP;
constexpr uint32_t SENT = 0xFFFFFFFFu;
constexpr int SPIN_LIMIT = 1 << 22;

constexpr uint32_t KB = 1024;
constexpr uint32_t SM_XN = 0;
constexpr uint32_t SM_WQ = 64 * KB;
constexpr uint32_t SM_WKV = 192 * KB;
constexpr uint32_t KVCH = 40 * KB;
constexpr uint32_t SM_Q = 200 * KB;
constexpr uint32_t SM_W1 = 40 * KB;
constexpr uint32_t SM_MISC = 224 * KB;
constexpr uint32_t SMEM_BYTES = 227 * KB;
constexpr uint32_t MB_WQ = 0;
constexpr uint32_t MB_WKV = 4;
constexpr uint32_t MB_KV = 5;
constexpr uint32_t MB_WO = 9;
constexpr uint32_t MB_W2 = 17;
constexpr uint32_t MB_W1 = 39;
constexpr uint32_t MB_F2 = 43;
constexpr uint32_t NBAR = 44;
constexpr uint32_t MISC_CNT = 384;
constexpr uint32_t MISC_NRM = 480;
constexpr uint32_t MISC_EPOCH = 496;
constexpr uint32_t MISC_CS = 512;
constexpr uint32_t MISC_K0 = 1024;
constexpr uint32_t CNT_WO = 17, CNT_W1 = 18;

__host__ __device__ constexpr uint32_t wo_slot(int kb) { return kb < 5 ? 20 + kb : kb - 5; }
__host__ __device__ constexpr uint32_t w2_slot(int kb) {
    return kb == 0 ? 27 : kb < 3 ? 2 + kb : kb < 6 ? 14 + kb : kb < 11 ? 14 + kb : kb < 14 ? kb - 11 : kb - 9;
}
__host__ __device__ constexpr uint64_t pack_slots(bool is_w2, int q) {
    uint64_t v = 0;
    for (int i = 0; i < (is_w2 ? 11 : 4); i++) v |= (uint64_t)(is_w2 ? w2_slot(2 * i + q) : wo_slot(2 * i + q)) << (5 * i);
    return v;
}

__device__ uint4 g_kv[4 * 2048];
__device__ uint4 g_kplain[4 * 1024];
__device__ uint4 g_of[32 * 32 * 128];
__device__ uint4 g_hf[32 * 32 * 128];
__device__ uint4 g_Hf[32 * 88 * 128];
__device__ float2 g_stats[32 * 64 * 16];
__device__ float g_cs[1408];
__device__ uint4 g_nrm[NMAIN];
__device__ unsigned g_count1;
__device__ unsigned g_count2;
__device__ unsigned g_epoch[NCTA];
#define TS(i) do {} while (0)

__device__ __forceinline__ void mbar_init(uint32_t bar, int cnt) { asm volatile("mbarrier.init.shared::cta.b64 [%0], %1;" :: "r"(bar), "r"(cnt) : "memory"); }
__device__ __forceinline__ void mbar_expect(uint32_t bar, uint32_t bytes) { asm volatile("mbarrier.arrive.expect_tx.shared::cta.b64 _, [%0], %1;" :: "r"(bar), "r"(bytes) : "memory"); }
__device__ __forceinline__ void mbar_arrive(uint32_t bar) { asm volatile("mbarrier.arrive.shared::cta.b64 _, [%0];" :: "r"(bar) : "memory"); }
__device__ __forceinline__ void mbar_wait(uint32_t bar) {
    uint32_t done; int spins = 0;
    do {
        asm volatile("{.reg .pred p; mbarrier.try_wait.parity.shared::cta.b64 p, [%1], 0; selp.u32 %0, 1, 0, p;}" : "=r"(done) : "r"(bar) : "memory");
    } while (!__all_sync(0xffffffffu, done) && ++spins < SPIN_LIMIT);
}
__device__ __forceinline__ void tma2d(uint32_t dst, const CUtensorMap* tm, int c0, int c1, uint32_t bar) {
    asm volatile("cp.async.bulk.tensor.2d.shared::cluster.global.mbarrier::complete_tx::bytes [%0], [%1, {%3, %4}], [%2];"
                 :: "r"(dst), "l"(tm), "r"(bar), "r"(c0), "r"(c1) : "memory");
}
__device__ __forceinline__ void bulk_g2s(uint32_t dst, const void* src, uint32_t bytes, uint32_t bar) {
    asm volatile("cp.async.bulk.shared::cluster.global.mbarrier::complete_tx::bytes [%0], [%1], %2, [%3];" :: "r"(dst), "l"(src), "r"(bytes), "r"(bar) : "memory");
}
__device__ __forceinline__ void fence_async_smem() { asm volatile("fence.proxy.async.shared::cta;" ::: "memory"); }
__device__ __forceinline__ void bar_sync(int id, int n) { asm volatile("bar.sync %0, %1;" :: "r"(id), "r"(n) : "memory"); }
__device__ __forceinline__ void bar_arrive(int id, int n) { asm volatile("bar.arrive %0, %1;" :: "r"(id), "r"(n) : "memory"); }
__device__ __forceinline__ void wg_fence() { asm volatile("wgmma.fence.sync.aligned;" ::: "memory"); }
__device__ __forceinline__ void wg_commit() { asm volatile("wgmma.commit_group.sync.aligned;" ::: "memory"); }
template <int N> __device__ __forceinline__ void wg_wait() { asm volatile("wgmma.wait_group.sync.aligned %0;" :: "n"(N) : "memory"); }
template <int N> __device__ __forceinline__ void fence_regs(float (&d)[N]) {
#pragma unroll
    for (int i = 0; i < N; i++) asm volatile("" : "+f"(d[i]) :: "memory");
}
template <int N> __device__ __forceinline__ void fence_regs(uint32_t (&d)[N]) {
#pragma unroll
    for (int i = 0; i < N; i++) asm volatile("" : "+r"(d[i]) :: "memory");
}
__device__ __forceinline__ uint64_t mkdesc(uint32_t addr, uint32_t lbo, uint32_t sbo, uint32_t swz) {
    return (uint64_t)(((addr & 0x3FFFF) >> 4) | ((lbo >> 4) << 16)) | ((uint64_t)((sbo >> 4) | (swz << 30)) << 32);
}
__device__ __forceinline__ float ex2(float x) { float y; asm("ex2.approx.ftz.f32 %0, %1;" : "=f"(y) : "f"(x)); return y; }
__device__ __forceinline__ float rcp(float x) { float y; asm("rcp.approx.ftz.f32 %0, %1;" : "=f"(y) : "f"(x)); return y; }
__device__ __forceinline__ uint32_t pack_bf16(float lo, float hi) { uint32_t r; asm("cvt.rn.bf16x2.f32 %0, %1, %2;" : "=r"(r) : "f"(hi), "f"(lo)); return r; }
__device__ __forceinline__ uint32_t pack_f16(float lo, float hi) { uint32_t r; asm("cvt.rn.f16x2.f32 %0, %1, %2;" : "=r"(r) : "f"(hi), "f"(lo)); return r; }
__device__ __forceinline__ float bf_lo(uint32_t v) { return __uint_as_float(v << 16); }
__device__ __forceinline__ float bf_hi(uint32_t v) { return __uint_as_float(v & 0xFFFF0000u); }
__device__ __forceinline__ uint4 ldg_relaxed(const uint4* p) {
    uint4 v; asm volatile("ld.relaxed.gpu.global.v4.u32 {%0,%1,%2,%3}, [%4];" : "=r"(v.x), "=r"(v.y), "=r"(v.z), "=r"(v.w) : "l"(p) : "memory"); return v;
}
__device__ __forceinline__ void stg128(void* p, uint32_t a, uint32_t b, uint32_t c, uint32_t d) {
    asm volatile("st.relaxed.gpu.global.v4.u32 [%0], {%1,%2,%3,%4};" :: "l"(p), "r"(a), "r"(b), "r"(c), "r"(d) : "memory");
}
__device__ __forceinline__ void stg64(void* p, uint32_t a, uint32_t b) {
    asm volatile("st.relaxed.gpu.global.v2.u32 [%0], {%1,%2};" :: "l"(p), "r"(a), "r"(b) : "memory");
}
__device__ __forceinline__ void sts128(uint32_t a, uint32_t x, uint32_t y, uint32_t z, uint32_t w) {
    asm volatile("st.shared.v4.u32 [%0], {%1,%2,%3,%4};" :: "r"(a), "r"(x), "r"(y), "r"(z), "r"(w) : "memory");
}
__device__ __forceinline__ void sts32(uint32_t a, uint32_t x) { asm volatile("st.shared.u32 [%0], %1;" :: "r"(a), "r"(x) : "memory"); }
__device__ __forceinline__ float4 lds128f(uint32_t a) {
    float4 v; asm volatile("ld.shared.v4.f32 {%0,%1,%2,%3}, [%4];" : "=f"(v.x), "=f"(v.y), "=f"(v.z), "=f"(v.w) : "r"(a) : "memory"); return v;
}
__device__ __forceinline__ uint32_t lds32(uint32_t a) { uint32_t v; asm volatile("ld.shared.u32 %0, [%1];" : "=r"(v) : "r"(a) : "memory"); return v; }
__device__ __forceinline__ bool has_sent(const uint4& v) { return (v.x == SENT) | (v.w == SENT); }
__device__ __forceinline__ bool has_zero(const uint4& v) { return min(min(v.x, v.y), min(v.z, v.w)) == 0u; }
__device__ __forceinline__ uint32_t nonzero(uint32_t w) { return w == 0u ? 0x8000u : w; }
__device__ __forceinline__ void stg32(void* p, uint32_t a) { asm volatile("st.relaxed.gpu.global.u32 [%0], %1;" :: "l"(p), "r"(a) : "memory"); }
__device__ __forceinline__ void wait_count(const unsigned* p, unsigned target) {
    unsigned v; int spins = 0;
    do { asm volatile("ld.acquire.gpu.global.u32 %0, [%1];" : "=r"(v) : "l"(p) : "memory"); } while (__any_sync(0xffffffffu, v != target) && ++spins < SPIN_LIMIT);
}
__device__ __forceinline__ uint32_t warp_arrive(uint32_t cnt) {
    uint32_t old = 0;
    __syncwarp();
    if ((threadIdx.x & 31) == 0) asm volatile("atom.acq_rel.cta.shared.add.u32 %0, [%1], 1;" : "=r"(old) : "r"(cnt) : "memory");
    return __shfl_sync(0xffffffffu, old, 0);
}
__device__ __forceinline__ void wait_all_warps(uint32_t cnt) {
    uint32_t v; int spins = 0;
    do { asm volatile("ld.acquire.cta.shared.u32 %0, [%1];" : "=r"(v) : "r"(cnt) : "memory"); } while (__any_sync(0xffffffffu, v != 16u) && ++spins < SPIN_LIMIT);
}

#define R4(d, o) "+f"(d[o + 0]), "+f"(d[o + 1]), "+f"(d[o + 2]), "+f"(d[o + 3])
#define R8(d, o) R4(d, o), R4(d, o + 4)
#define R32(d) R8(d, 0), R8(d, 8), R8(d, 16), R8(d, 24)
#define D32 "{%0,%1,%2,%3,%4,%5,%6,%7,%8,%9,%10,%11,%12,%13,%14,%15,%16,%17,%18,%19,%20,%21,%22,%23,%24,%25,%26,%27,%28,%29,%30,%31}"
#define D44 "{%0,%1,%2,%3,%4,%5,%6,%7,%8,%9,%10,%11,%12,%13,%14,%15,%16,%17,%18,%19,%20,%21,%22,%23,%24,%25,%26,%27,%28,%29,%30,%31,%32,%33,%34,%35,%36,%37,%38,%39,%40,%41,%42,%43}"

__device__ __forceinline__ void mma_qk_f16(float (&d)[32], uint64_t da, uint64_t db) {
    asm volatile("{.reg .pred p; setp.eq.b32 p, 0, 0; wgmma.mma_async.sync.aligned.m64n64k16.f32.f16.f16 " D32 ", %32, %33, p, 1, 1, 0, 0;}"
                 : R32(d) : "l"(da), "l"(db));
}
__device__ __forceinline__ void mma_qk_bf16(float (&d)[32], uint64_t da, uint64_t db) {
    asm volatile("{.reg .pred p; setp.ne.b32 p, 0, 0; wgmma.mma_async.sync.aligned.m64n64k16.f32.bf16.bf16 " D32 ", %32, %33, p, 1, 1, 0, 0;}"
                 : R32(d) : "l"(da), "l"(db));
}
__device__ __forceinline__ void mma_pv(float (&d)[12], const uint32_t* a, uint64_t db) {
    asm volatile("{.reg .pred p; setp.eq.b32 p, 0, 0; wgmma.mma_async.sync.aligned.m64n24k16.f32.bf16.bf16 {%0,%1,%2,%3,%4,%5,%6,%7,%8,%9,%10,%11}, {%12,%13,%14,%15}, %16, p, 1, 1, 1;}"
                 : R8(d, 0), R4(d, 8) : "r"(a[0]), "r"(a[1]), "r"(a[2]), "r"(a[3]), "l"(db));
}
__device__ __forceinline__ void mma_ss64(float (&d)[32], uint64_t da, uint64_t db) {
    asm volatile("{.reg .pred p; setp.eq.b32 p, 0, 0; wgmma.mma_async.sync.aligned.m64n64k16.f32.bf16.bf16 " D32 ", %32, %33, p, 1, 1, 0, 1;}"
                 : R32(d) : "l"(da), "l"(db));
}
__device__ __forceinline__ void mma_ss8(float (&d)[4], uint64_t da, uint64_t db) {
    asm volatile("{.reg .pred p; setp.eq.b32 p, 0, 0; wgmma.mma_async.sync.aligned.m64n8k16.f32.bf16.bf16 {%0,%1,%2,%3}, %4, %5, p, 1, 1, 0, 1;}"
                 : R4(d, 0) : "l"(da), "l"(db));
}
__device__ __forceinline__ void mma_rs(float (&d)[32], const uint4& a, uint64_t db) {
    asm volatile("{.reg .pred p; setp.eq.b32 p, 0, 0; wgmma.mma_async.sync.aligned.m64n64k16.f32.bf16.bf16 " D32 ", {%32,%33,%34,%35}, %36, p, 1, 1, 1;}"
                 : R32(d) : "r"(a.x), "r"(a.y), "r"(a.z), "r"(a.w), "l"(db));
}
__device__ __forceinline__ void mma_rs(float (&d)[44], const uint4& a, uint64_t db) {
    asm volatile("{.reg .pred p; setp.eq.b32 p, 0, 0; wgmma.mma_async.sync.aligned.m64n88k16.f32.bf16.bf16 " D44 ", {%44,%45,%46,%47}, %48, p, 1, 1, 1;}"
                 : R32(d), R8(d, 32), R4(d, 40) : "r"(a.x), "r"(a.y), "r"(a.z), "r"(a.w), "l"(db));
}

constexpr float EXP_MAGIC = 256.0f + 127.0f + 64.0f - 1.58621f + 0.00390625f;
constexpr uint32_t MUFU_MASK = 0x1111u;
__device__ __forceinline__ uint32_t exp2_pair(float y0, float y1, uint32_t cexp, uint32_t neg1) {
    uint32_t w, m, e, r;
    asm("prmt.b32 %0, %1, %2, 0x6521;" : "=r"(w) : "r"(__float_as_uint(y0)), "r"(__float_as_uint(y1)));
    asm("lop3.b32 %0, %1, 0x007F007F, %2, 0xEA;" : "=r"(m) : "r"(w), "r"(cexp));
    asm("mad.lo.u32 %0, %1, %2, %3;" : "=r"(e) : "r"(m), "r"(neg1), "r"(w));
    asm("fma.rn.bf16x2 %0, %1, %2, %3;" : "=r"(r) : "r"(w), "r"(m), "r"(e));
    return r;
}

struct Params {
    CUtensorMap wq, wk, wv, wo, w1, w2;
    const __nv_bfloat16* x;
    const __nv_bfloat16* w1p;
    const __nv_bfloat16* w2p;
    const __nv_bfloat16* wop;
    __nv_bfloat16* out;
    uint32_t neg1;
};

__device__ __forceinline__ void load_wo(uint32_t sb, const Params& P, int kb) {
    const uint32_t bar = sb + SM_MISC + (MB_WO + kb) * 8;
    mbar_expect(bar, 8192); tma2d(sb + wo_slot(kb) * 8192, &P.wo, (blockIdx.x & 7) * 64, kb * 64, bar);
}
__device__ __forceinline__ void load_w2(uint32_t sb, const Params& P, int kb) {
    const uint32_t bar = sb + SM_MISC + (MB_W2 + kb) * 8;
    mbar_expect(bar, 8192); tma2d(sb + w2_slot(kb) * 8192, &P.w2, (blockIdx.x & 7) * 64, kb * 64, bar);
}
__device__ __forceinline__ void load_w1(uint32_t sb, const Params& P, int gi) {
    const uint32_t bar = sb + SM_MISC + (MB_W1 + gi) * 8;
    mbar_expect(bar, 24576);
#pragma unroll 1
    for (int a = 0; a < 3; a++) tma2d(sb + SM_W1 + gi * 24576 + a * 8192, &P.w1, (blockIdx.x & 15) * 88 + a * 32, gi * 128, bar);
}

__device__ __forceinline__ void load_batch(uint4 (&buf)[4], const uint4* a) {
#pragma unroll
    for (int s = 0; s < 4; s++) buf[s] = ldg_relaxed(a + s * 128);
}
__device__ __forceinline__ bool batch_bad(const uint4 (&buf)[4]) {
    const uint32_t m = max(max(max(buf[0].x, buf[0].w), max(buf[1].x, buf[1].w)), max(max(buf[2].x, buf[2].w), max(buf[3].x, buf[3].w)));
    return __any_sync(0xffffffffu, m == SENT);
}
__device__ __forceinline__ void check_batch(uint4 (&buf)[4], const uint4* a) {
    int spins = 0;
    while (batch_bad(buf) && ++spins < SPIN_LIMIT) load_batch(buf, a);
}
template <int RING>
__device__ __forceinline__ void fill_ring(uint4 (&buf)[RING][4], const uint4* a, int astr) {
#pragma unroll
    for (int i = 0; i < RING; i++) load_batch(buf[i], a + i * astr);
    if (batch_bad(buf[0])) {
        load_batch(buf[0], a);
        check_batch(buf[0], a);
#pragma unroll
        for (int i = 1; i < RING; i++) load_batch(buf[i], a + i * astr);
    }
}

__device__ __forceinline__ void pair_reduce(const float (&acc)[32], float (&r)[16], uint32_t buf, int q, int barid) {
    if (q) {
#pragma unroll
        for (int j = 0; j < 4; j++) sts128(buf + j * 2048, __float_as_uint(acc[4 * j]), __float_as_uint(acc[4 * j + 1]), __float_as_uint(acc[4 * j + 2]), __float_as_uint(acc[4 * j + 3]));
        bar_sync(barid, 256);
        bar_sync(barid, 256);
#pragma unroll
        for (int j = 0; j < 4; j++) {
            float4 v = lds128f(buf + j * 2048);
            r[4 * j] = acc[16 + 4 * j] + v.x; r[4 * j + 1] = acc[17 + 4 * j] + v.y; r[4 * j + 2] = acc[18 + 4 * j] + v.z; r[4 * j + 3] = acc[19 + 4 * j] + v.w;
        }
    } else {
        bar_sync(barid, 256);
        float4 v[4];
#pragma unroll
        for (int j = 0; j < 4; j++) v[j] = lds128f(buf + j * 2048);
#pragma unroll
        for (int j = 0; j < 4; j++) sts128(buf + j * 2048, __float_as_uint(acc[16 + 4 * j]), __float_as_uint(acc[17 + 4 * j]), __float_as_uint(acc[18 + 4 * j]), __float_as_uint(acc[19 + 4 * j]));
        bar_arrive(barid, 256);
#pragma unroll
        for (int j = 0; j < 4; j++) {
            r[4 * j] = acc[4 * j] + v[j].x; r[4 * j + 1] = acc[4 * j + 1] + v[j].y; r[4 * j + 2] = acc[4 * j + 2] + v[j].z; r[4 * j + 3] = acc[4 * j + 3] + v[j].w;
        }
    }
}

__device__ __forceinline__ float quad_sum(float v) { v += __shfl_xor_sync(0xffffffffu, v, 1); v += __shfl_xor_sync(0xffffffffu, v, 2); return v; }
__device__ __forceinline__ float silu2(float h) { float t; asm("tanh.approx.f32 %0, %1;" : "=f"(t) : "f"(h)); return fmaf(h, t, h); }

#define TS_ARG
#define TS_PASS

template <bool SAFE>
__device__ __forceinline__ void attn_hook(const Params& P, uint32_t sb, int warp, int H) {
    const uint32_t mb = sb + SM_MISC;
    const int lane = threadIdx.x & 31, b = blockIdx.x, t128 = threadIdx.x & 127;
    const int wg = warp >> 2, ww = warp & 3, pr = 1 - (wg >> 1), q = wg & 1;
    if (H < 8) {
        const int mt = 16 * pr + (b >> 3), mt1 = 16 * pr + (b >> 4) * 2 + q, sl = b & 15;
        uint4* hb = g_Hf + (mt1 * 88 + (sl >> 1) * 11) * 128 + t128;
        if (H <= 5) stg128(hb + ((sl & 1) * 6 + H - 1) * 128, SENT, SENT, SENT, SENT);
        else stg128(g_hf + (mt * 32 + (b & 7) * 4 + 2 * q + H - 6) * 128 + t128, SENT, SENT, SENT, SENT);
        if (H == 2) stg64(reinterpret_cast<uint2*>(hb + 5 * 128) + (sl & 1), SENT, SENT);
        if (H == 3) stg128(g_of + ((16 + (b >> 3)) * 32 + (b & 3) * 8 + 2 * wg + (ww >> 1)) * 128 + (((b >> 2) & 1) * 2 + (ww & 1)) * 32 + lane, SENT, SENT, SENT, SENT);
        if (H == 4 && (lane & 3) < 2) stg64(g_stats + (mt * 64 + ww * 16 + (lane >> 2) + 8 * (lane & 3)) * 16 + (b & 7) * 2 + q, SENT, SENT);
    }
    if (H == 1 || H >= 8) {
        if (warp_arrive(mb + MISC_CNT + H * 4) == 0 && H != 16) {
            if (H & 1) {
                if (H > 1) wait_all_warps(mb + MISC_CNT + (H - 1) * 4);
                else if (SAFE) wait_count(&g_count1, lds32(mb + MISC_EPOCH) * NMAIN);
                if (lane == 0) {
                    if (H == 1) {
                        if (SAFE) {
                            asm volatile("fence.proxy.async.global;" ::: "memory");
#pragma unroll 1
                            for (int c = 1; c < 4; c++) { mbar_expect(mb + (MB_KV + c) * 8, 32768); bulk_g2s(sb + c * KVCH, g_kv + c * 2048, 32768, mb + (MB_KV + c) * 8); }
                        }
#pragma unroll 1
                        for (int kb = 0; kb < 5; kb++) load_wo(sb, P, kb);
                        load_w2(sb, P, 0);
                    } else if (H == 9) {
                        asm volatile("red.release.gpu.global.add.u32 [%0], 1;" :: "l"(&g_count2) : "memory");
                    } else if (H == 11) {
#pragma unroll 1
                        for (int kb = 5; kb < 8; kb++) load_wo(sb, P, kb);
                        load_w2(sb, P, 1); load_w2(sb, P, 2);
                    } else {
#pragma unroll 1
                        for (int gi = (H == 13 ? 0 : 1); gi < (H == 13 ? 1 : 3); gi++) load_w1(sb, P, gi);
                    }
                }
            } else if (H == 14) {
                wait_count(&g_count2, lds32(mb + MISC_EPOCH) * NCTA);
                if (lane < 22) {
                    const uint4 v = ldg_relaxed(reinterpret_cast<const uint4*>(g_cs + (b & 15) * 88) + lane);
                    sts128(mb + MISC_CS + lane * 16, v.x, v.y, v.z, v.w);
                }
                __syncwarp();
                if (lane == 0) mbar_arrive(mb + MB_F2 * 8);
            }
            __syncwarp();
        }
    }
}

template <bool SAFE>
__device__ __forceinline__ void attention(const Params& P, uint32_t sb, int warp TS_ARG) {
    const uint32_t mb = sb + SM_MISC;
    const int tid = threadIdx.x, lane = tid & 31, b = blockIdx.x, tg = b >> 2, hg = b & 3;
    const int wg = warp >> 2, ww = warp & 3;
    const uint32_t cexp = 0x9F809F80u + (tid >> 12);
    const uint32_t neg1 = P.neg1;
#pragma unroll 1
    for (int pass = 0; pass < 2; pass++) {
        float o[12], s[32];
        const uint64_t dq = mkdesc(sb + SM_Q + (pass * 4 + wg) * 2048, 128, 256, 0);
        uint64_t dk = mkdesc(sb, 128, 256, 0);
        uint64_t dv = mkdesc(sb + 16384, 128, 8192, 0);
        float m0 = -INFINITY, m1 = -INFINITY;
#pragma unroll
        for (int i = 0; i < 12; i++) o[i] = 0.f;
#pragma unroll
        for (int i = 0; i < 32; i++) s[i] = ((MUFU_MASK >> (i / 2)) & 1) ? 0.f : EXP_MAGIC;
        fence_regs(s); fence_regs(o);
        wg_fence();
        if (SAFE) mma_qk_f16(s, dq, mkdesc(mb + MISC_K0, 128, 256, 0)); else mma_qk_bf16(s, dq, mkdesc(mb + MISC_K0, 128, 256, 0));
        wg_commit();
        wg_wait<0>(); fence_regs(s);
#pragma unroll 1
        for (int u = 0; u < 8; u++) {
            if (SAFE && pass == 0 && u >= 2 && !(u & 1)) mbar_wait(mb + (MB_KV + (u >> 1)) * 8);
#pragma unroll 1
            for (int i = 0; i < 4; i++) {
                uint32_t p[16];
                if (SAFE) {
#pragma unroll
                    for (int j = 0; j < 16; j++) {
                        if ((MUFU_MASK >> j) & 1) p[j] = pack_bf16(ex2(s[2 * j]), ex2(s[2 * j + 1]));
                        else p[j] = exp2_pair(s[2 * j], s[2 * j + 1], cexp, neg1);
                    }
                } else {
                    fence_regs(o);
                    float x0 = m0, x1 = m1;
#pragma unroll
                    for (int j = 0; j < 8; j++) { x0 = fmaxf(x0, fmaxf(s[4 * j], s[4 * j + 1])); x1 = fmaxf(x1, fmaxf(s[4 * j + 2], s[4 * j + 3])); }
                    x0 = fmaxf(x0, __shfl_xor_sync(0xffffffffu, x0, 1)); x0 = fmaxf(x0, __shfl_xor_sync(0xffffffffu, x0, 2));
                    x1 = fmaxf(x1, __shfl_xor_sync(0xffffffffu, x1, 1)); x1 = fmaxf(x1, __shfl_xor_sync(0xffffffffu, x1, 2));
                    const float c0 = ex2(m0 - x0), c1 = ex2(m1 - x1);
                    m0 = x0; m1 = x1;
#pragma unroll
                    for (int j = 0; j < 3; j++) { o[4 * j] *= c0; o[4 * j + 1] *= c0; o[4 * j + 2] *= c1; o[4 * j + 3] *= c1; }
#pragma unroll
                    for (int j = 0; j < 8; j++) {
                        p[2 * j] = pack_bf16(ex2(s[4 * j] - m0), ex2(s[4 * j + 1] - m0));
                        p[2 * j + 1] = pack_bf16(ex2(s[4 * j + 2] - m1), ex2(s[4 * j + 3] - m1));
                    }
                    fence_regs(o);
                }
                fence_regs(p);
                wg_fence();
                if (SAFE) mma_qk_f16(s, dq, dk); else mma_qk_bf16(s, dq, dk);
#pragma unroll
                for (int j = 0; j < 4; j++) mma_pv(o, p + 4 * j, dv + j * 16);
                wg_commit();
                dk += 128; dv += 64;
                wg_wait<0>(); fence_regs(s);
            }
            if (u & 1) { dk += (KVCH - 16384) / 16; dv += (KVCH - 8192) / 16; }
            if (u == 7) {
                fence_regs(o);
                const float i0 = 1.0f / o[8], i1 = 1.0f / o[10];
                stg128(g_of + ((16 * pass + (tg >> 1)) * 32 + hg * 8 + 2 * wg + (ww >> 1)) * 128 + ((tg & 1) * 2 + (ww & 1)) * 32 + lane,
                       pack_bf16(o[0] * i0, o[1] * i0), pack_bf16(o[2] * i1, o[3] * i1), pack_bf16(o[4] * i0, o[5] * i0), pack_bf16(o[6] * i1, o[7] * i1));
            }
            attn_hook<SAFE>(P, sb, warp, pass * 8 + u + 1);
        }
        TS(5 + pass);
    }
}

__device__ __noinline__ void helper_cta(const Params& P, uint8_t* smem) {
    const int tid = threadIdx.x, b = blockIdx.x, hi = b - NMAIN;
    const unsigned epoch = g_epoch[b] + 1;
    float* red = reinterpret_cast<float*>(smem);
    if (tid < 32) wait_count(&g_count1, epoch * NMAIN);
    __syncthreads();
    if (tid == 480) {
        for (int i = 0; i < 8; i++) asm volatile("cp.async.bulk.prefetch.L2.global [%0], %1;" :: "l"((const char*)P.wop + hi * 131072 + i * 16384), "r"(16384) : "memory");
        for (int i = 0; i < 43; i++) asm volatile("cp.async.bulk.prefetch.L2.global [%0], %1;" :: "l"((const char*)P.w2p + hi * 352256 + i * 8192), "r"(8192) : "memory");
    }
    if (tid < 344) {
        const int cg = tid % 43, rp = tid / 43;
        const uint4* src = reinterpret_cast<const uint4*>(P.w1p + (size_t)rp * 64 * FF + (hi * 43 + cg) * 8);
        float s[8] = {0, 0, 0, 0, 0, 0, 0, 0};
#pragma unroll 8
        for (int r = 0; r < 64; r++) {
            uint4 v = __ldg(src + r * (FF / 8));
            s[0] += bf_lo(v.x); s[1] += bf_hi(v.x); s[2] += bf_lo(v.y); s[3] += bf_hi(v.y);
            s[4] += bf_lo(v.z); s[5] += bf_hi(v.z); s[6] += bf_lo(v.w); s[7] += bf_hi(v.w);
        }
        float* part = red + (rp * 43 + cg) * 8;
#pragma unroll
        for (int i = 0; i < 8; i++) part[i] = s[i];
    }
    __syncthreads();
    if (tid < 344) {
        float s = 0.f;
#pragma unroll
        for (int rp = 0; rp < 8; rp++) s += red[rp * 344 + tid];
        g_cs[hi * 344 + tid] = s;
    } else if (hi == 3 && tid < 344 + 32) g_cs[FF + tid - 344] = 0.f;
    __syncthreads();
    if (tid == 0) {
        asm volatile("red.release.gpu.global.add.u32 [%0], 1;" :: "l"(&g_count2) : "memory");
        g_epoch[b] = epoch;
    }
}

__global__ void __launch_bounds__(512, 1) fused_kernel(const __grid_constant__ Params P) {
    extern __shared__ __align__(1024) uint8_t smem[];
    const uint32_t sb = (uint32_t)__cvta_generic_to_shared(smem);
    const uint32_t mb = sb + SM_MISC;
    const int tid = threadIdx.x, lane = tid & 31, b = blockIdx.x;
    if (b >= NMAIN) { helper_cta(P, smem); return; }
    const int tg = b >> 2, hg = b & 3;

    uint4 xv[4][2];
    {
        const int r = (tid >> 5) * 4;
        const uint4* src = reinterpret_cast<const uint4*>(P.x + (size_t)((r & 31) + tg * 32 + (r >> 5) * 1024) * D) + lane;
#pragma unroll
        for (int i = 0; i < 4; i++) { xv[i][0] = ldg_relaxed(src + i * 64); xv[i][1] = ldg_relaxed(src + i * 64 + 32); }
    }
    const int warp = __shfl_sync(0xffffffffu, tid >> 5, 0);
    const int wg = warp >> 2, ww = warp & 3, g = lane >> 2, t4 = lane & 3, t128 = tid & 127;
    if (warp < 5) {
        if (lane == 0) {
            const uint32_t bar = mb + warp * 8;
            mbar_init(bar, 1);
            asm volatile("fence.mbarrier_init.release.cluster;" ::: "memory");
            fence_async_smem();
            if (warp == 4) {
                mbar_expect(bar, 8192);
                const CUtensorMap* tm = hg < 2 ? &P.wk : &P.wv;
                tma2d(sb + SM_WKV, tm, (hg & 1) * 8, 0, bar);
                tma2d(sb + SM_WKV + 4096, tm, (hg & 1) * 8, 256, bar);
            } else {
                mbar_expect(bar, 32768);
                tma2d(sb + SM_WQ + warp * 16384, &P.wq, hg * 128, warp * 128, bar);
                tma2d(sb + SM_WQ + 65536 + warp * 16384, &P.wq, hg * 128 + 64, warp * 128, bar);
            }
        }
    } else if (warp == 5) {
        mbar_init(mb + (5 + lane) * 8, 1);
        if (lane < NBAR - 37) mbar_init(mb + (37 + lane) * 8, 1);
        if (lane < 28) sts32(mb + MISC_CNT + lane * 4, 0);
        asm volatile("fence.mbarrier_init.release.cluster;" ::: "memory");
    } else if (warp == 6) {
        if (lane == 0) { const unsigned e = g_epoch[b] + 1; g_epoch[b] = e; sts32(mb + MISC_EPOCH, e); }
    } else if (warp == 7) {
        if (lane < 3) asm volatile("prefetch.tensormap [%0];" :: "l"(&P.wo + lane) : "memory");
    }
    __syncwarp();
    {
        float f[4][16], st[4];
#pragma unroll
        for (int i = 0; i < 4; i++) {
#pragma unroll
            for (int c = 0; c < 2; c++) {
                f[i][8 * c + 0] = bf_lo(xv[i][c].x); f[i][8 * c + 1] = bf_hi(xv[i][c].x); f[i][8 * c + 2] = bf_lo(xv[i][c].y); f[i][8 * c + 3] = bf_hi(xv[i][c].y);
                f[i][8 * c + 4] = bf_lo(xv[i][c].z); f[i][8 * c + 5] = bf_hi(xv[i][c].z); f[i][8 * c + 6] = bf_lo(xv[i][c].w); f[i][8 * c + 7] = bf_hi(xv[i][c].w);
            }
            float s0 = 0.f, s1 = 0.f;
#pragma unroll
            for (int j = 0; j < 8; j++) { s0 += f[i][j]; s1 += f[i][8 + j]; }
            st[i] = s0 + s1;
        }
#pragma unroll
        for (int o = 16; o > 0; o >>= 1)
#pragma unroll
            for (int i = 0; i < 4; i++) st[i] += __shfl_xor_sync(0xffffffffu, st[i], o);
#pragma unroll
        for (int i = 0; i < 4; i++) {
            const float mean = st[i] * (1.0f / D);
            float v0 = 0.f, v1 = 0.f;
#pragma unroll
            for (int j = 0; j < 8; j++) { f[i][j] -= mean; v0 = fmaf(f[i][j], f[i][j], v0); f[i][8 + j] -= mean; v1 = fmaf(f[i][8 + j], f[i][8 + j], v1); }
            st[i] = v0 + v1;
        }
#pragma unroll
        for (int o = 16; o > 0; o >>= 1)
#pragma unroll
            for (int i = 0; i < 4; i++) st[i] += __shfl_xor_sync(0xffffffffu, st[i], o);
#pragma unroll
        for (int i = 0; i < 4; i++) {
            const float rstd = rsqrtf(st[i] * (1.0f / D) + 1e-5f);
            const int r = warp * 4 + i;
#pragma unroll
            for (int c = 0; c < 2; c++) {
                const uint32_t addr = sb + SM_XN + ((lane >> 3) + 4 * c) * 8192 + r * 128 + (((lane & 7) ^ (r & 7)) << 4);
                sts128(addr, pack_bf16(f[i][8 * c] * rstd, f[i][8 * c + 1] * rstd), pack_bf16(f[i][8 * c + 2] * rstd, f[i][8 * c + 3] * rstd),
                       pack_bf16(f[i][8 * c + 4] * rstd, f[i][8 * c + 5] * rstd), pack_bf16(f[i][8 * c + 6] * rstd, f[i][8 * c + 7] * rstd));
            }
        }
    }
    fence_async_smem();
    TS(0);
    __syncthreads();
    constexpr float QSCALE = 0.25f * 1.4426950408889634f;
    uint32_t kvoff[2];
#pragma unroll
    for (int i = 0; i < 2; i++) {
        const int t = ((ww & 1) * 16 + g + 8 * i), c = 2 * tg + (ww >> 1), ts = (t + 31) & 31;
        kvoff[i] = hg < 2 ? (ts >> 3) * 32768 + (ts & 7) * 2048 + (c >> 3) * 256 + (hg & 1) * 128 + (c & 7) * 16 + t4 * 4
                          : (t >> 3) * 32768 + 16384 + (hg & 1) * 8192 + ((t & 7) * 64 + c) * 16 + t4 * 4;
    }
    float qa[32];
    if (wg < 2) {
#pragma unroll
        for (int i = 0; i < 32; i++) qa[i] = 0.f;
        fence_regs(qa);
        bar_sync(1, 384);
        const uint64_t da = mkdesc(sb + SM_XN, 16, 1024, 1), db = mkdesc(sb + SM_WQ + wg * 65536, 16, 1024, 1);
#pragma unroll 1
        for (int i = 0; i < 4; i++) {
            mbar_wait(mb + (MB_WQ + i) * 8);
            wg_fence();
#pragma unroll
            for (int s = 0; s < 8; s++) mma_ss64(qa, da + (i * 2 + (s >> 2)) * 512 + (s & 3) * 2, db + (i * 8 + s) * 128);
            wg_commit();
        }
        wg_wait<0>();
        fence_regs(qa);
        bar_arrive(6, 512);
        TS(1);
        float nn[8];
#pragma unroll
        for (int i = 0; i < 32; i++) qa[i] *= QSCALE;
#pragma unroll
        for (int h = 0; h < 4; h++) {
            const uint32_t base = sb + SM_Q + ((ww >> 1) * 4 + wg * 2 + (h >> 1)) * 2048 + ((h & 1) * 4 + (ww & 1) * 2) * 256 + lane * 4;
            sts32(base, pack_f16(qa[8 * h], qa[8 * h + 1])); sts32(base + 256, pack_f16(qa[8 * h + 2], qa[8 * h + 3]));
            sts32(base + 128, pack_f16(qa[8 * h + 4], qa[8 * h + 5])); sts32(base + 384, pack_f16(qa[8 * h + 6], qa[8 * h + 7]));
            nn[2 * h] = qa[8 * h] * qa[8 * h] + qa[8 * h + 1] * qa[8 * h + 1] + qa[8 * h + 4] * qa[8 * h + 4] + qa[8 * h + 5] * qa[8 * h + 5];
            nn[2 * h + 1] = qa[8 * h + 2] * qa[8 * h + 2] + qa[8 * h + 3] * qa[8 * h + 3] + qa[8 * h + 6] * qa[8 * h + 6] + qa[8 * h + 7] * qa[8 * h + 7];
        }
#pragma unroll
        for (int o = 1; o < 4; o <<= 1)
#pragma unroll
            for (int i = 0; i < 8; i++) nn[i] += __shfl_xor_sync(0xffffffffu, nn[i], o);
        uint32_t nm = 0;
#pragma unroll
        for (int i = 0; i < 8; i++) nm = max(nm, __float_as_uint(nn[i]));
        nm = __reduce_max_sync(0xffffffffu, nm);
        if (lane == 0) asm volatile("red.shared.max.u32 [%0], %1;" :: "r"(mb + MISC_NRM), "r"(nm) : "memory");
    } else {
        if (wg == 2) {
            float kv[4] = {0.f, 0.f, 0.f, 0.f};
            fence_regs(kv);
            const uint64_t da = mkdesc(sb + SM_XN, 16, 1024, 1), db = mkdesc(sb + SM_WKV, 128, 16, 0);
            mbar_wait(mb + MB_WKV * 8);
            wg_fence();
#pragma unroll 1
            for (int i = 0; i < 8; i++) {
#pragma unroll
                for (int s = 0; s < 4; s++) mma_ss8(kv, da + i * 512 + s * 2, db + (i * 4 + s) * 16);
            }
            wg_commit();
            wg_wait<0>();
            fence_regs(kv);
            bar_arrive(1, 384);
            char* img = reinterpret_cast<char*>(g_kv);
            if (hg < 2) {
                const int r0 = ww * 16 + g;
                float2* kt = reinterpret_cast<float2*>(smem + SM_MISC + MISC_K0);
                kt[r0 * 4 + t4] = make_float2(kv[0], kv[1]);
                kt[(r0 + 8) * 4 + t4] = make_float2(kv[2], kv[3]);
                bar_sync(2, 128);
                float2 p0 = make_float2(0.f, 0.f);
                if (r0 & 31) p0 = kt[(r0 - 1) * 4 + t4];
                const float2 p1 = kt[(r0 + 7) * 4 + t4];
                stg32(img + kvoff[0], nonzero(pack_f16(kv[0] - p0.x, kv[1] - p0.y)));
                stg32(img + kvoff[1], nonzero(pack_f16(kv[2] - p1.x, kv[3] - p1.y)));
            } else {
                stg32(img + kvoff[0], nonzero(pack_bf16(kv[0], kv[1])));
                stg32(img + kvoff[1], nonzero(pack_bf16(kv[2], kv[3])));
            }
            uint32_t nm = max(__float_as_uint(quad_sum(kv[0] * kv[0] + kv[1] * kv[1])), __float_as_uint(quad_sum(kv[2] * kv[2] + kv[3] * kv[3])));
            nm = __reduce_max_sync(0xffffffffu, nm);
            if (lane == 0) stg32(reinterpret_cast<uint32_t*>(g_nrm + b) + ww, nm | 1u);
            if (hg < 2) {
#pragma unroll
                for (int i = 0; i < 2; i++)
                    stg32(reinterpret_cast<char*>(g_kplain) + (kvoff[i] >> 15) * 16384 + (kvoff[i] & 16383), pack_bf16(kv[2 * i], kv[2 * i + 1]));
            }
            TS(1);
            bar_sync(2, 128);
            if (t128 == 0) asm volatile("red.release.gpu.global.add.u32 [%0], 1;" :: "l"(&g_count1) : "memory");
            __syncwarp();
        } else {
            uint4 v; int spins = 0;
            do { v = ldg_relaxed(g_nrm + t128); } while (__any_sync(0xffffffffu, has_zero(v)) && ++spins < SPIN_LIMIT);
            uint32_t nm = max(max(v.x, v.y), max(v.z, v.w));
            nm = max(nm, __shfl_xor_sync(0xffffffffu, nm, 4)); nm = max(nm, __shfl_xor_sync(0xffffffffu, nm, 8)); nm = max(nm, __shfl_xor_sync(0xffffffffu, nm, 16));
            if (lane < 4) asm volatile("red.shared.max.u32 [%0], %1;" :: "r"(mb + MISC_NRM + 4 + min(lane, 2) * 4), "r"(nm) : "memory");
            TS(1);
        }
        bar_sync(5, 256);
        const int t256 = tid - 256;
        uint4 kc[9]; int spins = 0; bool bad;
        do {
            bad = false;
#pragma unroll
            for (int i = 0; i < 8; i++) kc[i] = ldg_relaxed(g_kv + i * 256 + t256);
            kc[8] = ldg_relaxed(g_kv + 3 * 2048 + 7 * 128 + t128);
#pragma unroll
            for (int i = 0; i < 9; i++) bad |= has_zero(kc[i]);
        } while (__any_sync(0xffffffffu, bad) && ++spins < SPIN_LIMIT);
        TS(2);
        bar_sync(6, 512);
#pragma unroll
        for (int i = 0; i < 8; i++) sts128(sb + (i * 256 + t256) * 16, kc[i].x, kc[i].y, kc[i].z, kc[i].w);
        if (wg == 3) sts128(mb + MISC_K0 + t128 * 16, kc[8].x, kc[8].y, kc[8].z, kc[8].w);
#pragma unroll
        for (int i = 0; i < 8; i++) sts128(sb + (i >> 1) * KVCH + 32768 + (i & 1) * 4096 + t256 * 16, 0x3F803F80u, 0x3F803F80u, 0x3F803F80u, 0x3F803F80u);
    }
    fence_async_smem();
    TS(3);
    __syncthreads();
    const float q2 = __uint_as_float(lds32(mb + MISC_NRM)), v2 = __uint_as_float(lds32(mb + MISC_NRM + 12));
    const float k2 = __uint_as_float(lds32(mb + MISC_NRM + 4)) + __uint_as_float(lds32(mb + MISC_NRM + 8));
    const bool safe = __all_sync(0xffffffffu, (q2 * k2 <= 3500.0f) && (q2 <= 65536.0f) && (k2 <= 65536.0f) && (v2 <= 1e24f));
    TS(4);

    if (__builtin_expect(safe, 1)) {
        attention<true>(P, sb, warp TS_PASS);
    } else {
        if (wg < 2) {
#pragma unroll
            for (int h = 0; h < 4; h++) {
                const uint32_t base = sb + SM_Q + ((ww >> 1) * 4 + wg * 2 + (h >> 1)) * 2048 + ((h & 1) * 4 + (ww & 1) * 2) * 256 + lane * 4;
                sts32(base, pack_bf16(qa[8 * h], qa[8 * h + 1])); sts32(base + 256, pack_bf16(qa[8 * h + 2], qa[8 * h + 3]));
                sts32(base + 128, pack_bf16(qa[8 * h + 4], qa[8 * h + 5])); sts32(base + 384, pack_bf16(qa[8 * h + 6], qa[8 * h + 7]));
            }
            fence_async_smem();
        } else if (warp == 15) {
            wait_count(&g_count1, lds32(mb + MISC_EPOCH) * NMAIN);
            if (lane == 0) {
                asm volatile("fence.proxy.async;" ::: "memory");
                mbar_expect(mb + MB_KV * 8, 4 * 32768 + 2048);
                for (int c = 0; c < 4; c++) {
                    bulk_g2s(sb + c * KVCH, g_kplain + c * 1024, 16384, mb + MB_KV * 8);
                    bulk_g2s(sb + c * KVCH + 16384, g_kv + c * 2048 + 1024, 16384, mb + MB_KV * 8);
                }
                bulk_g2s(mb + MISC_K0, g_kplain + 3 * 1024 + 7 * 128, 2048, mb + MB_KV * 8);
            }
            __syncwarp();
        }
        __syncthreads();
        mbar_wait(mb + MB_KV * 8);
        attention<false>(P, sb, warp TS_PASS);
    }

    const int pr = 1 - (wg >> 1), q = wg & 1;
    const int mt = 16 * pr + (b >> 3), j = b & 7;
    const int row0 = mt * 64 + ww * 16 + g;
    uint32_t hk[8];
    {
        const uint32_t* xp = reinterpret_cast<const uint32_t*>(P.x + (size_t)row0 * D + j * 64 + q * 32 + t4 * 2);
#pragma unroll
        for (int i = 0; i < 4; i++) { hk[2 * i] = __ldg(xp + i * 4); hk[2 * i + 1] = __ldg(xp + i * 4 + 8 * (D / 2)); }
    }
    if (warp == 0) {
        wait_all_warps(mb + MISC_CNT + 16 * 4);
        if (lane == 0) {
            load_w1(sb, P, 3);
#pragma unroll 1
            for (int kb = 3; kb < 6; kb++) load_w2(sb, P, kb);
        }
        __syncwarp();
    }
    mbar_wait(mb + MB_F2 * 8);
#pragma unroll 1
    for (int ph = 0; ph < 2; ph++) {
        float r[16];
        {
            const uint4* a = (ph ? g_Hf + mt * 88 * 128 : g_of + mt * 32 * 128) + q * 512 + t128;
            const int nblk = ph ? 11 : 4;
            uint64_t slots = ph ? (q ? pack_slots(true, 1) : pack_slots(true, 0)) : (q ? pack_slots(false, 1) : pack_slots(false, 0));
            uint32_t bar = mb + ((ph ? MB_W2 : MB_WO) + q) * 8;
            float acc[32];
            uint4 buf[4][4];
            fill_ring<4>(buf, a, 1024);
#pragma unroll
            for (int i = 0; i < 32; i++) acc[i] = 0.f;
            fence_regs(acc);
#pragma unroll 1
            for (int i0 = 0; i0 < nblk; i0 += 4) {
#pragma unroll
                for (int i = 0; i < 4; i++) {
                    const int blk = i0 + i;
                    if (blk < nblk) {
                        const uint64_t db = mkdesc(sb + ((uint32_t)slots & 31) * 8192, 16, 1024, 1);
                        mbar_wait(bar);
                        check_batch(buf[i], a + blk * 1024);
                        wg_fence();
#pragma unroll
                        for (int s = 0; s < 4; s++) mma_rs(acc, buf[i][s], db + s * 128);
                        wg_commit();
                        slots >>= 5; bar += 16;
                        wg_wait<1>();
                        if (blk >= 1 && blk + 3 < nblk) load_batch(buf[(i + 3) & 3], a + (blk + 3) * 1024);
                    }
                }
            }
            wg_wait<0>();
            fence_regs(acc);
            TS(7 + 4 * ph);
            if (ph == 0) {
                warp_arrive(mb + MISC_CNT + CNT_WO * 4);
                if (pr == 1) mbar_wait(mb + (MB_W1 + 3) * 8);
            }
            pair_reduce(acc, r, sb + SM_Q + pr * 8192 + t128 * 16, q, 3 + pr);
        }
#pragma unroll
        for (int i = 0; i < 8; i++) hk[i] = pack_bf16(r[2 * i] + bf_lo(hk[i]), r[2 * i + 1] + bf_hi(hk[i]));
        if (ph == 1) break;
        {
            uint4* hp = g_hf + (mt * 32 + j * 4 + 2 * q) * 128 + t128;
            stg128(hp, hk[0], hk[1], hk[2], hk[3]);
            stg128(hp + 128, hk[4], hk[5], hk[6], hk[7]);
            float s0 = 0.f, s1 = 0.f;
#pragma unroll
            for (int i = 0; i < 8; i++) {
                r[2 * i] = bf_lo(hk[i]); r[2 * i + 1] = bf_hi(hk[i]);
                if (i & 1) s1 += r[2 * i] + r[2 * i + 1]; else s0 += r[2 * i] + r[2 * i + 1];
            }
            s0 += __shfl_xor_sync(0xffffffffu, s0, 1); s1 += __shfl_xor_sync(0xffffffffu, s1, 1);
            s0 += __shfl_xor_sync(0xffffffffu, s0, 2); s1 += __shfl_xor_sync(0xffffffffu, s1, 2);
            const float a0 = s0 * (1.0f / 32), a1 = s1 * (1.0f / 32);
            float v0 = 0.f, v1 = 0.f;
#pragma unroll
            for (int i = 0; i < 8; i++) {
                const float a = (i & 1) ? a1 : a0;
                const float d0 = r[2 * i] - a, d1 = r[2 * i + 1] - a;
                if (i & 1) v1 += d0 * d0 + d1 * d1; else v0 += d0 * d0 + d1 * d1;
            }
            v0 += __shfl_xor_sync(0xffffffffu, v0, 1); v1 += __shfl_xor_sync(0xffffffffu, v1, 1);
            v0 += __shfl_xor_sync(0xffffffffu, v0, 2); v1 += __shfl_xor_sync(0xffffffffu, v1, 2);
            if (t4 < 2) stg64(g_stats + (row0 + 8 * t4) * 16 + j * 2 + q, __float_as_uint(t4 ? s1 : s0), __float_as_uint(t4 ? v1 : v0));
            TS(8);
            if (warp == 1) {
                wait_all_warps(mb + MISC_CNT + CNT_WO * 4);
                if (lane == 0) {
#pragma unroll 1
                    for (int kb = 6; kb < 14; kb++) load_w2(sb, P, kb);
                }
                __syncwarp();
            } else if (wg == 2) {
                if (kvoff[0] < 32768 || kvoff[0] >= 3 * 32768) stg32(reinterpret_cast<char*>(g_kv) + kvoff[0], 0u);
                if (kvoff[1] < 32768) stg32(reinterpret_cast<char*>(g_kv) + kvoff[1], 0u);
                if (lane == 0) stg32(reinterpret_cast<uint32_t*>(g_nrm + b) + ww, 0u);
            }
        }
        {
            const int mt1 = 16 * pr + (b >> 4) * 2 + q, sl = b & 15;
            const uint4* a = g_hf + mt1 * 32 * 128 + t128;
            float acc[44], nmean[2], hrstd[2];
            uint4 buf[3][4];
            fill_ring<3>(buf, a, 512);
            {
                const uint4* sp = reinterpret_cast<const uint4*>(g_stats + (mt1 * 64 + ww * 16 + g) * 16 + t4 * 4);
                uint4 u[4]; int spins = 0;
                do { u[0] = ldg_relaxed(sp); u[1] = ldg_relaxed(sp + 1); u[2] = ldg_relaxed(sp + 64); u[3] = ldg_relaxed(sp + 65); } while (batch_bad(u) && ++spins < SPIN_LIMIT);
                float mean[2], m2[2];
#pragma unroll
                for (int i = 0; i < 2; i++) mean[i] = (__uint_as_float(u[2 * i].x) + __uint_as_float(u[2 * i].z)) + (__uint_as_float(u[2 * i + 1].x) + __uint_as_float(u[2 * i + 1].z));
                mean[0] += __shfl_xor_sync(0xffffffffu, mean[0], 1); mean[1] += __shfl_xor_sync(0xffffffffu, mean[1], 1);
                mean[0] += __shfl_xor_sync(0xffffffffu, mean[0], 2); mean[1] += __shfl_xor_sync(0xffffffffu, mean[1], 2);
#pragma unroll
                for (int i = 0; i < 2; i++) {
                    mean[i] *= 1.0f / D;
                    const float da = __uint_as_float(u[2 * i].x) * (1.0f / 32) - mean[i], dc = __uint_as_float(u[2 * i].z) * (1.0f / 32) - mean[i];
                    const float de = __uint_as_float(u[2 * i + 1].x) * (1.0f / 32) - mean[i], df = __uint_as_float(u[2 * i + 1].z) * (1.0f / 32) - mean[i];
                    m2[i] = (__uint_as_float(u[2 * i].y) + __uint_as_float(u[2 * i].w)) + (__uint_as_float(u[2 * i + 1].y) + __uint_as_float(u[2 * i + 1].w)) + 32.0f * (da * da + dc * dc + de * de + df * df);
                }
                m2[0] += __shfl_xor_sync(0xffffffffu, m2[0], 1); m2[1] += __shfl_xor_sync(0xffffffffu, m2[1], 1);
                m2[0] += __shfl_xor_sync(0xffffffffu, m2[0], 2); m2[1] += __shfl_xor_sync(0xffffffffu, m2[1], 2);
#pragma unroll
                for (int i = 0; i < 2; i++) { hrstd[i] = 0.5f * rsqrtf(m2[i] * (1.0f / D) + 1e-5f); nmean[i] = -mean[i]; }
            }
#pragma unroll
            for (int i = 0; i < 44; i++) acc[i] = 0.f;
            fence_regs(acc);
#pragma unroll 1
            for (int i0 = 0; i0 < 8; i0 += 3) {
#pragma unroll
                for (int i = 0; i < 3; i++) {
                    const int blk = i0 + i;
                    if (blk < 8) {
                        const uint64_t db = mkdesc(sb + SM_W1 + (blk >> 1) * 24576 + (blk & 1) * 4096, 8192, 512, 2);
                        mbar_wait(mb + (MB_W1 + (blk >> 1)) * 8);
                        check_batch(buf[i], a + blk * 512);
                        wg_fence();
#pragma unroll
                        for (int s = 0; s < 4; s++) mma_rs(acc, buf[i][s], db + s * 64);
                        wg_commit();
                        wg_wait<1>();
                        if (blk >= 1 && blk + 2 < 8) load_batch(buf[(i + 2) % 3], a + (blk + 2) * 512);
                        if (blk >= 2 && !(blk & 1)) {
                            const int gi = (blk >> 1) - 1;
                            if (warp_arrive(mb + MISC_CNT + (CNT_W1 + gi) * 4) == 15) {
                                if (lane == 0) {
#pragma unroll 1
                                    for (int kb = 14 + 3 * gi; kb < min(17 + 3 * gi, 22); kb++) load_w2(sb, P, kb);
                                }
                                __syncwarp();
                            }
                        }
                    }
                }
            }
            wg_wait<0>();
            fence_regs(acc);
            TS(9);
            uint32_t hv[22];
#pragma unroll
            for (int i = 0; i < 11; i++) {
                float2 cs;
                asm volatile("ld.shared.v2.f32 {%0,%1}, [%2];" : "=f"(cs.x), "=f"(cs.y) : "r"(mb + MISC_CS + i * 32 + t4 * 8));
                hv[2 * i] = pack_bf16(silu2(hrstd[0] * fmaf(nmean[0], cs.x, acc[4 * i])), silu2(hrstd[0] * fmaf(nmean[0], cs.y, acc[4 * i + 1])));
                hv[2 * i + 1] = pack_bf16(silu2(hrstd[1] * fmaf(nmean[1], cs.x, acc[4 * i + 2])), silu2(hrstd[1] * fmaf(nmean[1], cs.y, acc[4 * i + 3])));
            }
            uint4* hb = g_Hf + (mt1 * 88 + (sl >> 1) * 11) * 128 + t128;
            if (sl & 1) {
                stg64(reinterpret_cast<uint2*>(hb + 5 * 128) + 1, hv[0], hv[1]);
#pragma unroll
                for (int i = 0; i < 5; i++) stg128(hb + (6 + i) * 128, hv[2 + 4 * i], hv[3 + 4 * i], hv[4 + 4 * i], hv[5 + 4 * i]);
            } else {
#pragma unroll
                for (int i = 0; i < 5; i++) stg128(hb + i * 128, hv[4 * i], hv[4 * i + 1], hv[4 * i + 2], hv[4 * i + 3]);
                stg64(hb + 5 * 128, hv[20], hv[21]);
            }
            TS(10);
        }
    }
#pragma unroll
    for (int h = 0; h < 2; h++) {
        uint32_t v0 = hk[h], v1 = hk[2 + h], v2 = hk[4 + h], v3 = hk[6 + h];
        const bool o1 = t4 & 1, o2 = t4 & 2;
        uint32_t a = __shfl_xor_sync(0xffffffffu, o1 ? v0 : v1, 1), c = __shfl_xor_sync(0xffffffffu, o1 ? v2 : v3, 1);
        if (o1) { v0 = a; v2 = c; } else { v1 = a; v3 = c; }
        a = __shfl_xor_sync(0xffffffffu, o2 ? v0 : v2, 2); c = __shfl_xor_sync(0xffffffffu, o2 ? v1 : v3, 2);
        if (o2) { v0 = a; v1 = c; } else { v2 = a; v3 = c; }
        *reinterpret_cast<uint4*>(P.out + (size_t)(row0 + 8 * h) * D + j * 64 + q * 32 + t4 * 8) = make_uint4(v0, v1, v2, v3);
    }
    TS(12);
}

typedef CUresult (*EncodeFn)(CUtensorMap*, CUtensorMapDataType, cuuint32_t, void*, const cuuint64_t*, const cuuint64_t*, const cuuint32_t*,
                             const cuuint32_t*, CUtensorMapInterleave, CUtensorMapSwizzle, CUtensorMapL2promotion, CUtensorMapFloatOOBfill);

void encode2d(EncodeFn fn, CUtensorMap* tm, const void* ptr, int rows, int cols, int box_rows, int box_cols, CUtensorMapSwizzle sw) {
    cuuint64_t dims[2] = {(cuuint64_t)cols, (cuuint64_t)rows};
    cuuint64_t strides[1] = {(cuuint64_t)cols * 2};
    cuuint32_t box[2] = {(cuuint32_t)box_cols, (cuuint32_t)box_rows};
    cuuint32_t es[2] = {1, 1};
    fn(tm, CU_TENSOR_MAP_DATA_TYPE_BFLOAT16, 2, const_cast<void*>(ptr), dims, strides, box, es, CU_TENSOR_MAP_INTERLEAVE_NONE, sw,
       CU_TENSOR_MAP_L2_PROMOTION_L2_128B, CU_TENSOR_MAP_FLOAT_OOB_FILL_NONE);
}

}

extern "C" void kernel_launch(void* const* d_in, const int* in_sizes, int n_in, void* d_out, int out_size) {
    (void)in_sizes; (void)n_in; (void)out_size;
    void* fnp = nullptr;
    cudaDriverEntryPointQueryResult qr;
    cudaGetDriverEntryPoint("cuTensorMapEncodeTiled", &fnp, cudaEnableDefault, &qr);
    EncodeFn fn = (EncodeFn)fnp;
    Params P;
    encode2d(fn, &P.wq, d_in[1], D, D, 128, 64, CU_TENSOR_MAP_SWIZZLE_128B);
    encode2d(fn, &P.wk, d_in[2], D, 16, 256, 8, CU_TENSOR_MAP_SWIZZLE_NONE);
    encode2d(fn, &P.wv, d_in[3], D, 16, 256, 8, CU_TENSOR_MAP_SWIZZLE_NONE);
    encode2d(fn, &P.wo, d_in[4], D, D, 64, 64, CU_TENSOR_MAP_SWIZZLE_128B);
    encode2d(fn, &P.w1, d_in[6], D, FF, 128, 32, CU_TENSOR_MAP_SWIZZLE_64B);
    encode2d(fn, &P.w2, d_in[7], FF, D, 64, 64, CU_TENSOR_MAP_SWIZZLE_128B);
    P.x = (const __nv_bfloat16*)d_in[0];
    P.w1p = (const __nv_bfloat16*)d_in[6];
    P.w2p = (const __nv_bfloat16*)d_in[7];
    P.wop = (const __nv_bfloat16*)d_in[4];
    P.out = (__nv_bfloat16*)d_out;
    P.neg1 = 0xFFFFFFFFu;
    cudaFuncSetAttribute(fused_kernel, cudaFuncAttributeMaxDynamicSharedMemorySize, SMEM_BYTES);
    fused_kernel<<<NCTA, 512, SMEM_BYTES>>>(P);
}
```

```cpp
#include <cuda_runtime.h>
#include <cuda_bf16.h>
#include <cuda.h>
#include <stdint.h>

namespace {

constexpr int D = 512, FF = 1376;
constexpr int NMAIN = 128, NHELP = 4, NCTA = NMAIN + NHELP;
constexpr uint32_t SENT = 0xFFFFFFFFu;
constexpr int SPIN_LIMIT = 1 << 22;

constexpr uint32_t KB = 1024;
constexpr uint32_t SM_XN = 0;
constexpr uint32_t SM_WQ = 64 * KB;
constexpr uint32_t SM_WKV = 192 * KB;
constexpr uint32_t KVCH = 40 * KB;
constexpr uint32_t SM_Q = 200 * KB;
constexpr uint32_t SM_W1 = 40 * KB;
constexpr uint32_t SM_MISC = 224 * KB;
constexpr uint32_t SMEM_BYTES = 227 * KB;
constexpr uint32_t MB_WQ = 0;
constexpr uint32_t MB_KV = 4;
constexpr uint32_t MB_WO = 8;
constexpr uint32_t MB_W2 = 16;
constexpr uint32_t MB_W1 = 38;
constexpr uint32_t MB_F2 = 42;
constexpr uint32_t MB_DONE = 43;
constexpr uint32_t NBAR = 49;
constexpr uint32_t MISC_CNT = 400;
constexpr uint32_t MISC_NRM = 416;
constexpr uint32_t MISC_EPOCH = 432;
constexpr uint32_t MISC_CS = 448;
constexpr uint32_t MISC_RSTD = 768;
constexpr uint32_t MISC_K0 = 1024;

__host__ __device__ constexpr uint32_t wo_slot(int kb) { return kb < 5 ? 20 + kb : kb - 5; }
__host__ __device__ constexpr uint32_t w2_slot(int kb) {
    return kb == 0 ? 27 : kb < 3 ? 2 + kb : kb < 6 ? 14 + kb : kb < 11 ? 14 + kb : kb < 14 ? kb - 11 : kb - 9;
}
__host__ __device__ constexpr uint64_t pack_slots(bool is_w2, int q) {
    uint64_t v = 0;
    for (int i = 0; i < (is_w2 ? 11 : 4); i++) v |= (uint64_t)(is_w2 ? w2_slot(2 * i + q) : wo_slot(2 * i + q)) << (5 * i);
    return v;
}

__device__ uint4 g_kv[4 * 2048];
__device__ uint4 g_kplain[4 * 1024];
__device__ uint4 g_of[32 * 32 * 128];
__device__ uint4 g_hf[32 * 32 * 128];
__device__ uint4 g_Hf[32 * 88 * 128];
__device__ float2 g_stats[32 * 64 * 16];
__device__ float g_cs[1408];
__device__ uint4 g_nrm[NMAIN];
__device__ unsigned g_count1;
__device__ unsigned g_count2;
__device__ unsigned g_epoch[NCTA];
#define TS(i) do {} while (0)

__device__ __forceinline__ void mbar_init(uint32_t bar, int cnt) { asm volatile("mbarrier.init.shared::cta.b64 [%0], %1;" :: "r"(bar), "r"(cnt) : "memory"); }
__device__ __forceinline__ void mbar_expect(uint32_t bar, uint32_t bytes) { asm volatile("mbarrier.arrive.expect_tx.shared::cta.b64 _, [%0], %1;" :: "r"(bar), "r"(bytes) : "memory"); }
__device__ __forceinline__ void mbar_arrive(uint32_t bar) { asm volatile("mbarrier.arrive.shared::cta.b64 _, [%0];" :: "r"(bar) : "memory"); }
__device__ __forceinline__ void mbar_wait(uint32_t bar) {
    uint32_t done; int spins = 0;
    do {
        asm volatile("{.reg .pred p; mbarrier.try_wait.parity.shared::cta.b64 p, [%1], 0; selp.u32 %0, 1, 0, p;}" : "=r"(done) : "r"(bar) : "memory");
    } while (!__all_sync(0xffffffffu, done) && ++spins < SPIN_LIMIT);
}
__device__ __forceinline__ void tma2d(uint32_t dst, const CUtensorMap* tm, int c0, int c1, uint32_t bar) {
    asm volatile("cp.async.bulk.tensor.2d.shared::cluster.global.mbarrier::complete_tx::bytes [%0], [%1, {%3, %4}], [%2];"
                 :: "r"(dst), "l"(tm), "r"(bar), "r"(c0), "r"(c1) : "memory");
}
__device__ __forceinline__ void bulk_g2s(uint32_t dst, const void* src, uint32_t bytes, uint32_t bar) {
    asm volatile("cp.async.bulk.shared::cluster.global.mbarrier::complete_tx::bytes [%0], [%1], %2, [%3];" :: "r"(dst), "l"(src), "r"(bytes), "r"(bar) : "memory");
}
__device__ __forceinline__ void fence_async_smem() { asm volatile("fence.proxy.async.shared::cta;" ::: "memory"); }
__device__ __forceinline__ void bar_sync(int id, int n) { asm volatile("bar.sync %0, %1;" :: "r"(id), "r"(n) : "memory"); }
__device__ __forceinline__ void bar_arrive(int id, int n) { asm volatile("bar.arrive %0, %1;" :: "r"(id), "r"(n) : "memory"); }
__device__ __forceinline__ void wg_fence() { asm volatile("wgmma.fence.sync.aligned;" ::: "memory"); }
__device__ __forceinline__ void wg_commit() { asm volatile("wgmma.commit_group.sync.aligned;" ::: "memory"); }
template <int N> __device__ __forceinline__ void wg_wait() { asm volatile("wgmma.wait_group.sync.aligned %0;" :: "n"(N) : "memory"); }
template <int N> __device__ __forceinline__ void fence_regs(float (&d)[N]) {
#pragma unroll
    for (int i = 0; i < N; i++) asm volatile("" : "+f"(d[i]) :: "memory");
}
template <int N> __device__ __forceinline__ void fence_regs(uint32_t (&d)[N]) {
#pragma unroll
    for (int i = 0; i < N; i++) asm volatile("" : "+r"(d[i]) :: "memory");
}
__device__ __forceinline__ uint64_t mkdesc(uint32_t addr, uint32_t lbo, uint32_t sbo, uint32_t swz) {
    return (uint64_t)(((addr & 0x3FFFF) >> 4) | ((lbo >> 4) << 16)) | ((uint64_t)((sbo >> 4) | (swz << 30)) << 32);
}
__device__ __forceinline__ float ex2(float x) { float y; asm("ex2.approx.ftz.f32 %0, %1;" : "=f"(y) : "f"(x)); return y; }
__device__ __forceinline__ float rcp(float x) { float y; asm("rcp.approx.ftz.f32 %0, %1;" : "=f"(y) : "f"(x)); return y; }
__device__ __forceinline__ uint32_t pack_bf16(float lo, float hi) { uint32_t r; asm("cvt.rn.bf16x2.f32 %0, %1, %2;" : "=r"(r) : "f"(hi), "f"(lo)); return r; }
__device__ __forceinline__ uint32_t pack_f16(float lo, float hi) { uint32_t r; asm("cvt.rn.f16x2.f32 %0, %1, %2;" : "=r"(r) : "f"(hi), "f"(lo)); return r; }
__device__ __forceinline__ float bf_lo(uint32_t v) { return __uint_as_float(v << 16); }
__device__ __forceinline__ float bf_hi(uint32_t v) { return __uint_as_float(v & 0xFFFF0000u); }
__device__ __forceinline__ uint4 ldg_relaxed(const uint4* p) {
    uint4 v; asm volatile("ld.relaxed.gpu.global.v4.u32 {%0,%1,%2,%3}, [%4];" : "=r"(v.x), "=r"(v.y), "=r"(v.z), "=r"(v.w) : "l"(p) : "memory"); return v;
}
__device__ __forceinline__ void stg128(void* p, uint32_t a, uint32_t b, uint32_t c, uint32_t d) {
    asm volatile("st.relaxed.gpu.global.v4.u32 [%0], {%1,%2,%3,%4};" :: "l"(p), "r"(a), "r"(b), "r"(c), "r"(d) : "memory");
}
__device__ __forceinline__ void stg64(void* p, uint32_t a, uint32_t b) {
    asm volatile("st.relaxed.gpu.global.v2.u32 [%0], {%1,%2};" :: "l"(p), "r"(a), "r"(b) : "memory");
}
__device__ __forceinline__ void sts128(uint32_t a, uint32_t x, uint32_t y, uint32_t z, uint32_t w) {
    asm volatile("st.shared.v4.u32 [%0], {%1,%2,%3,%4};" :: "r"(a), "r"(x), "r"(y), "r"(z), "r"(w) : "memory");
}
__device__ __forceinline__ void sts32(uint32_t a, uint32_t x) { asm volatile("st.shared.u32 [%0], %1;" :: "r"(a), "r"(x) : "memory"); }
__device__ __forceinline__ float4 lds128f(uint32_t a) {
    float4 v; asm volatile("ld.shared.v4.f32 {%0,%1,%2,%3}, [%4];" : "=f"(v.x), "=f"(v.y), "=f"(v.z), "=f"(v.w) : "r"(a) : "memory"); return v;
}
__device__ __forceinline__ uint32_t lds32(uint32_t a) { uint32_t v; asm volatile("ld.shared.u32 %0, [%1];" : "=r"(v) : "r"(a) : "memory"); return v; }
__device__ __forceinline__ bool has_sent(const uint4& v) { return (v.x == SENT) | (v.w == SENT); }
__device__ __forceinline__ bool has_zero(const uint4& v) { return min(min(v.x, v.y), min(v.z, v.w)) == 0u; }
__device__ __forceinline__ uint32_t nonzero(uint32_t w) { return w == 0u ? 0x8000u : w; }
__device__ __forceinline__ void stg32(void* p, uint32_t a) { asm volatile("st.relaxed.gpu.global.u32 [%0], %1;" :: "l"(p), "r"(a) : "memory"); }
__device__ __forceinline__ void wait_count(const unsigned* p, unsigned target) {
    unsigned v; int spins = 0;
    do { asm volatile("ld.acquire.gpu.global.u32 %0, [%1];" : "=r"(v) : "l"(p) : "memory"); } while (__any_sync(0xffffffffu, v != target) && ++spins < SPIN_LIMIT);
}
__device__ __forceinline__ uint32_t warp_arrive(uint32_t cnt) {
    uint32_t old = 0;
    __syncwarp();
    if ((threadIdx.x & 31) == 0) asm volatile("atom.acq_rel.cta.shared.add.u32 %0, [%1], 1;" : "=r"(old) : "r"(cnt) : "memory");
    return __shfl_sync(0xffffffffu, old, 0);
}
__device__ __forceinline__ void warp_done(uint32_t bar) { __syncwarp(); if ((threadIdx.x & 31) == 0) mbar_arrive(bar); }
__device__ __forceinline__ uint32_t add_bf16x2(uint32_t a, uint32_t b) { uint32_t r; asm("add.rn.bf16x2 %0, %1, %2;" : "=r"(r) : "r"(a), "r"(b)); return r; }

#define R4(d, o) "+f"(d[o + 0]), "+f"(d[o + 1]), "+f"(d[o + 2]), "+f"(d[o + 3])
#define R8(d, o) R4(d, o), R4(d, o + 4)
#define R32(d) R8(d, 0), R8(d, 8), R8(d, 16), R8(d, 24)
#define D32 "{%0,%1,%2,%3,%4,%5,%6,%7,%8,%9,%10,%11,%12,%13,%14,%15,%16,%17,%18,%19,%20,%21,%22,%23,%24,%25,%26,%27,%28,%29,%30,%31}"
#define D44 "{%0,%1,%2,%3,%4,%5,%6,%7,%8,%9,%10,%11,%12,%13,%14,%15,%16,%17,%18,%19,%20,%21,%22,%23,%24,%25,%26,%27,%28,%29,%30,%31,%32,%33,%34,%35,%36,%37,%38,%39,%40,%41,%42,%43}"

__device__ __forceinline__ void mma_qk_f16(float (&d)[32], uint64_t da, uint64_t db) {
    asm volatile("{.reg .pred p; setp.eq.b32 p, 0, 0; wgmma.mma_async.sync.aligned.m64n64k16.f32.f16.f16 " D32 ", %32, %33, p, 1, 1, 0, 0;}"
                 : R32(d) : "l"(da), "l"(db));
}
__device__ __forceinline__ void mma_qk_bf16(float (&d)[32], uint64_t da, uint64_t db) {
    asm volatile("{.reg .pred p; setp.ne.b32 p, 0, 0; wgmma.mma_async.sync.aligned.m64n64k16.f32.bf16.bf16 " D32 ", %32, %33, p, 1, 1, 0, 0;}"
                 : R32(d) : "l"(da), "l"(db));
}
__device__ __forceinline__ void mma_pv(float (&d)[12], const uint32_t* a, uint64_t db) {
    asm volatile("{.reg .pred p; setp.eq.b32 p, 0, 0; wgmma.mma_async.sync.aligned.m64n24k16.f32.bf16.bf16 {%0,%1,%2,%3,%4,%5,%6,%7,%8,%9,%10,%11}, {%12,%13,%14,%15}, %16, p, 1, 1, 1;}"
                 : R8(d, 0), R4(d, 8) : "r"(a[0]), "r"(a[1]), "r"(a[2]), "r"(a[3]), "l"(db));
}
__device__ __forceinline__ void mma_ss64(float (&d)[32], uint64_t da, uint64_t db) {
    asm volatile("{.reg .pred p; setp.eq.b32 p, 0, 0; wgmma.mma_async.sync.aligned.m64n64k16.f32.bf16.bf16 " D32 ", %32, %33, p, 1, 1, 0, 1;}"
                 : R32(d) : "l"(da), "l"(db));
}
__device__ __forceinline__ void mma_ss8(float (&d)[4], uint64_t da, uint64_t db) {
    asm volatile("{.reg .pred p; setp.eq.b32 p, 0, 0; wgmma.mma_async.sync.aligned.m64n8k16.f32.bf16.bf16 {%0,%1,%2,%3}, %4, %5, p, 1, 1, 0, 1;}"
                 : R4(d, 0) : "l"(da), "l"(db));
}
__device__ __forceinline__ void mma_rs(float (&d)[32], const uint4& a, uint64_t db) {
    asm volatile("{.reg .pred p; setp.eq.b32 p, 0, 0; wgmma.mma_async.sync.aligned.m64n64k16.f32.bf16.bf16 " D32 ", {%32,%33,%34,%35}, %36, p, 1, 1, 1;}"
                 : R32(d) : "r"(a.x), "r"(a.y), "r"(a.z), "r"(a.w), "l"(db));
}
__device__ __forceinline__ void mma_rs(float (&d)[44], const uint4& a, uint64_t db) {
    asm volatile("{.reg .pred p; setp.eq.b32 p, 0, 0; wgmma.mma_async.sync.aligned.m64n88k16.f32.bf16.bf16 " D44 ", {%44,%45,%46,%47}, %48, p, 1, 1, 1;}"
                 : R32(d), R8(d, 32), R4(d, 40) : "r"(a.x), "r"(a.y), "r"(a.z), "r"(a.w), "l"(db));
}

constexpr float EXP_MAGIC = 256.0f + 127.0f + 64.0f - 1.58621f + 0.00390625f;
constexpr uint32_t MUFU_MASK = 0x1111u;
__device__ __forceinline__ uint32_t exp2_pair(float y0, float y1, uint32_t cexp, uint32_t neg1) {
    uint32_t w, m, e, r;
    asm("prmt.b32 %0, %1, %2, 0x6521;" : "=r"(w) : "r"(__float_as_uint(y0)), "r"(__float_as_uint(y1)));
    asm("lop3.b32 %0, %1, 0x007F007F, %2, 0xEA;" : "=r"(m) : "r"(w), "r"(cexp));
    asm("mad.lo.u32 %0, %1, %2, %3;" : "=r"(e) : "r"(m), "r"(neg1), "r"(w));
    asm("fma.rn.bf16x2 %0, %1, %2, %3;" : "=r"(r) : "r"(w), "r"(m), "r"(e));
    return r;
}

struct Params {
    CUtensorMap wq, wo, w1, w2;
    const __nv_bfloat16* x;
    const __nv_bfloat16* wk;
    const __nv_bfloat16* wv;
    const __nv_bfloat16* w1p;
    const __nv_bfloat16* w2p;
    const __nv_bfloat16* wop;
    __nv_bfloat16* out;
    uint32_t neg1;
};

__device__ __forceinline__ void load_wo(uint32_t sb, const Params& P, int kb) {
    const uint32_t bar = sb + SM_MISC + (MB_WO + kb) * 8;
    mbar_expect(bar, 8192); tma2d(sb + wo_slot(kb) * 8192, &P.wo, (blockIdx.x & 7) * 64, kb * 64, bar);
}
__device__ __forceinline__ void load_w2(uint32_t sb, const Params& P, int kb) {
    const uint32_t bar = sb + SM_MISC + (MB_W2 + kb) * 8;
    mbar_expect(bar, 8192); tma2d(sb + w2_slot(kb) * 8192, &P.w2, (blockIdx.x & 7) * 64, kb * 64, bar);
}
__device__ __forceinline__ void load_w1(uint32_t sb, const Params& P, int gi) {
    const uint32_t bar = sb + SM_MISC + (MB_W1 + gi) * 8;
    mbar_expect(bar, 24576);
#pragma unroll 1
    for (int a = 0; a < 3; a++) tma2d(sb + SM_W1 + gi * 24576 + a * 8192, &P.w1, (blockIdx.x & 15) * 88 + a * 32, gi * 128, bar);
}

__device__ __forceinline__ void load_batch(uint4 (&buf)[4], const uint4* a) {
#pragma unroll
    for (int s = 0; s < 4; s++) buf[s] = ldg_relaxed(a + s * 128);
}
__device__ __forceinline__ bool batch_bad(const uint4 (&buf)[4]) {
    const uint32_t m = max(max(max(buf[0].x, buf[0].w), max(buf[1].x, buf[1].w)), max(max(buf[2].x, buf[2].w), max(buf[3].x, buf[3].w)));
    return __any_sync(0xffffffffu, m == SENT);
}
__device__ __forceinline__ void check_batch(uint4 (&buf)[4], const uint4* a) {
    int spins = 0;
    while (batch_bad(buf) && ++spins < SPIN_LIMIT) load_batch(buf, a);
}
template <int RING>
__device__ __forceinline__ void fill_ring(uint4 (&buf)[RING][4], const uint4* a, int astr) {
#pragma unroll
    for (int i = 0; i < RING; i++) load_batch(buf[i], a + i * astr);
    if (batch_bad(buf[0])) {
        load_batch(buf[0], a);
        check_batch(buf[0], a);
#pragma unroll
        for (int i = 1; i < RING; i++) load_batch(buf[i], a + i * astr);
    }
}

__device__ __forceinline__ void pair_reduce(const float (&acc)[32], float (&r)[16], uint32_t buf, int q, int barid) {
    if (q) {
#pragma unroll
        for (int j = 0; j < 4; j++) sts128(buf + j * 2048, __float_as_uint(acc[4 * j]), __float_as_uint(acc[4 * j + 1]), __float_as_uint(acc[4 * j + 2]), __float_as_uint(acc[4 * j + 3]));
        bar_sync(barid, 256);
        bar_sync(barid, 256);
#pragma unroll
        for (int j = 0; j < 4; j++) {
            float4 v = lds128f(buf + j * 2048);
            r[4 * j] = acc[16 + 4 * j] + v.x; r[4 * j + 1] = acc[17 + 4 * j] + v.y; r[4 * j + 2] = acc[18 + 4 * j] + v.z; r[4 * j + 3] = acc[19 + 4 * j] + v.w;
        }
    } else {
        bar_sync(barid, 256);
        float4 v[4];
#pragma unroll
        for (int j = 0; j < 4; j++) v[j] = lds128f(buf + j * 2048);
#pragma unroll
        for (int j = 0; j < 4; j++) sts128(buf + j * 2048, __float_as_uint(acc[16 + 4 * j]), __float_as_uint(acc[17 + 4 * j]), __float_as_uint(acc[18 + 4 * j]), __float_as_uint(acc[19 + 4 * j]));
        bar_arrive(barid, 256);
#pragma unroll
        for (int j = 0; j < 4; j++) {
            r[4 * j] = acc[4 * j] + v[j].x; r[4 * j + 1] = acc[4 * j + 1] + v[j].y; r[4 * j + 2] = acc[4 * j + 2] + v[j].z; r[4 * j + 3] = acc[4 * j + 3] + v[j].w;
        }
    }
}

__device__ __forceinline__ float quad_sum(float v) { v += __shfl_xor_sync(0xffffffffu, v, 1); v += __shfl_xor_sync(0xffffffffu, v, 2); return v; }
__device__ __forceinline__ float silu2(float h) { float t; asm("tanh.approx.f32 %0, %1;" : "=f"(t) : "f"(h)); return fmaf(h, t, h); }

#define TS_ARG
#define TS_PASS

template <bool SAFE>
__device__ __forceinline__ void attn_hook(const Params& P, uint32_t sb, int warp, int U) {
    const uint32_t mb = sb + SM_MISC;
    const int lane = threadIdx.x & 31, b = blockIdx.x, t128 = threadIdx.x & 127;
    if (U < 4) {
        const int wg = warp >> 2, ww = warp & 3, pr = 1 - (wg >> 1), q = wg & 1;
        const int mt = 16 * pr + (b >> 3), mt1 = 16 * pr + (b >> 4) * 2 + q, sl = b & 15;
        if (U < 2) {
            uint4* hb = g_Hf + (mt1 * 88 + (sl >> 1) * 11 + (sl & 1) * 6 + U * 2) * 128 + t128;
            stg128(hb, SENT, SENT, SENT, SENT); stg128(hb + 128, SENT, SENT, SENT, SENT);
        } else if (U == 2) {
            uint4* hb = g_Hf + (mt1 * 88 + (sl >> 1) * 11) * 128 + t128;
            stg128(hb + ((sl & 1) * 6 + 4) * 128, SENT, SENT, SENT, SENT);
            stg64(reinterpret_cast<uint2*>(hb + 5 * 128) + (sl & 1), SENT, SENT);
            stg128(g_of + ((16 + (b >> 3)) * 32 + (b & 3) * 8 + 2 * wg + (ww >> 1)) * 128 + (((b >> 2) & 1) * 2 + (ww & 1)) * 32 + lane, SENT, SENT, SENT, SENT);
        } else {
            uint4* hp = g_hf + (mt * 32 + (b & 7) * 4 + 2 * q) * 128 + t128;
            stg128(hp, SENT, SENT, SENT, SENT); stg128(hp + 128, SENT, SENT, SENT, SENT);
            if ((lane & 3) < 2) stg64(g_stats + (mt * 64 + ww * 16 + (lane >> 2) + 8 * (lane & 3)) * 16 + (b & 7) * 2 + q, SENT, SENT);
        }
    } else {
        warp_done(mb + (MB_DONE + U - 4) * 8);
    }
    if (warp == 15 - U) {
        if (U == 0) {
            if (SAFE) wait_count(&g_count1, lds32(mb + MISC_EPOCH) * NMAIN);
            if (lane == 0) {
                if (SAFE) {
                    asm volatile("fence.proxy.async.global;" ::: "memory");
#pragma unroll 1
                    for (int c = 1; c < 4; c++) { mbar_expect(mb + (MB_KV + c) * 8, 32768); bulk_g2s(sb + c * KVCH, g_kv + c * 2048, 32768, mb + (MB_KV + c) * 8); }
                }
            }
        } else if (U == 1) {
            if (lane == 0) {
#pragma unroll 1
                for (int kb = 0; kb < 5; kb++) load_wo(sb, P, kb);
                load_w2(sb, P, 0);
            }
        } else if (U >= 5 && U < 8) {
            mbar_wait(mb + (MB_DONE + U - 5) * 8);
            if (U == 5) {
                if (lane == 0) asm volatile("red.release.gpu.global.add.u32 [%0], 1;" :: "l"(&g_count2) : "memory");
            } else if (U == 6) {
                if (lane == 0) {
#pragma unroll 1
                    for (int kb = 5; kb < 8; kb++) load_wo(sb, P, kb);
                    load_w2(sb, P, 1); load_w2(sb, P, 2);
                }
            } else {
                if (lane == 0) load_w1(sb, P, 0);
            }
        }
        __syncwarp();
    } else if (U == 7 && warp == 12) {
        wait_count(&g_count2, lds32(mb + MISC_EPOCH) * NCTA);
        if (lane < 22) {
            const uint4 v = ldg_relaxed(reinterpret_cast<const uint4*>(g_cs + (b & 15) * 88) + lane);
            sts128(mb + MISC_CS + lane * 16, v.x, v.y, v.z, v.w);
        }
        warp_done(mb + MB_F2 * 8);
    }
}

template <bool SAFE>
__device__ __forceinline__ void attention(const Params& P, uint32_t sb, int warp TS_ARG) {
    const uint32_t mb = sb + SM_MISC;
    const int tid = threadIdx.x, lane = tid & 31, b = blockIdx.x, tg = b >> 2, hg = b & 3;
    const int wg = warp >> 2, ww = warp & 3;
    const uint32_t cexp = 0x9F809F80u + (tid >> 12);
    const uint32_t neg1 = P.neg1;
#pragma unroll 1
    for (int pass = 0; pass < 2; pass++) {
        float o[12], s[32];
        const uint64_t dq = mkdesc(sb + SM_Q + (pass * 4 + wg) * 2048, 128, 256, 0);
        uint64_t dk = mkdesc(sb, 128, 256, 0);
        uint64_t dv = mkdesc(sb + 16384, 128, 8192, 0);
        float m0 = -INFINITY, m1 = -INFINITY;
#pragma unroll
        for (int i = 0; i < 12; i++) o[i] = 0.f;
#pragma unroll
        for (int i = 0; i < 32; i++) s[i] = ((MUFU_MASK >> (i / 2)) & 1) ? 0.f : EXP_MAGIC;
        fence_regs(s); fence_regs(o);
        wg_fence();
        if (SAFE) mma_qk_f16(s, dq, mkdesc(mb + MISC_K0, 128, 256, 0)); else mma_qk_bf16(s, dq, mkdesc(mb + MISC_K0, 128, 256, 0));
        wg_commit();
        wg_wait<0>(); fence_regs(s);
#pragma unroll 1
        for (int u = pass; u < 5; u++) {
            if (SAFE && pass == 0 && u >= 2) mbar_wait(mb + (MB_KV + u - 1) * 8);
#pragma unroll 1
            for (int i = (u == 0) ? 6 : (u == 1 - pass) ? 2 : 0; i < 8; i++) {
                uint32_t p[16];
                if (SAFE) {
#pragma unroll
                    for (int j = 0; j < 16; j++) {
                        if ((MUFU_MASK >> j) & 1) p[j] = pack_bf16(ex2(s[2 * j]), ex2(s[2 * j + 1]));
                        else p[j] = exp2_pair(s[2 * j], s[2 * j + 1], cexp, neg1);
                    }
                } else {
                    fence_regs(o);
                    float x0 = m0, x1 = m1;
#pragma unroll
                    for (int j = 0; j < 8; j++) { x0 = fmaxf(x0, fmaxf(s[4 * j], s[4 * j + 1])); x1 = fmaxf(x1, fmaxf(s[4 * j + 2], s[4 * j + 3])); }
                    x0 = fmaxf(x0, __shfl_xor_sync(0xffffffffu, x0, 1)); x0 = fmaxf(x0, __shfl_xor_sync(0xffffffffu, x0, 2));
                    x1 = fmaxf(x1, __shfl_xor_sync(0xffffffffu, x1, 1)); x1 = fmaxf(x1, __shfl_xor_sync(0xffffffffu, x1, 2));
                    const float c0 = ex2(m0 - x0), c1 = ex2(m1 - x1);
                    m0 = x0; m1 = x1;
#pragma unroll
                    for (int j = 0; j < 3; j++) { o[4 * j] *= c0; o[4 * j + 1] *= c0; o[4 * j + 2] *= c1; o[4 * j + 3] *= c1; }
#pragma unroll
                    for (int j = 0; j < 8; j++) {
                        p[2 * j] = pack_bf16(ex2(s[4 * j] - m0), ex2(s[4 * j + 1] - m0));
                        p[2 * j + 1] = pack_bf16(ex2(s[4 * j + 2] - m1), ex2(s[4 * j + 3] - m1));
                    }
                    fence_regs(o);
                }
                fence_regs(p);
                wg_fence();
                if (SAFE) mma_qk_f16(s, dq, dk); else mma_qk_bf16(s, dq, dk);
#pragma unroll
                for (int j = 0; j < 4; j++) mma_pv(o, p + 4 * j, dv + j * 16);
                wg_commit();
                dk += 128; dv += 64;
                wg_wait<0>(); fence_regs(s);
            }
            if (u > 0) { dk += (KVCH - 16384) / 16; dv += (KVCH - 8192) / 16; }
            if (u == 4) {
                fence_regs(o);
                const float i0 = 1.0f / o[8], i1 = 1.0f / o[10];
                stg128(g_of + ((16 * pass + (tg >> 1)) * 32 + hg * 8 + 2 * wg + (ww >> 1)) * 128 + ((tg & 1) * 2 + (ww & 1)) * 32 + lane,
                       pack_bf16(o[0] * i0, o[1] * i0), pack_bf16(o[2] * i1, o[3] * i1), pack_bf16(o[4] * i0, o[5] * i0), pack_bf16(o[6] * i1, o[7] * i1));
            }
            attn_hook<SAFE>(P, sb, warp, pass * 4 + u);
        }
        TS(5 + pass);
    }
}

__device__ __noinline__ void helper_cta(const Params& P, uint8_t* smem) {
    const int tid = threadIdx.x, b = blockIdx.x, hi = b - NMAIN;
    const unsigned epoch = g_epoch[b] + 1;
    float* red = reinterpret_cast<float*>(smem);
    if (tid < 32) wait_count(&g_count1, epoch * NMAIN);
    __syncthreads();
    if (tid == 480) {
        for (int i = 0; i < 8; i++) asm volatile("cp.async.bulk.prefetch.L2.global [%0], %1;" :: "l"((const char*)P.wop + hi * 131072 + i * 16384), "r"(16384) : "memory");
        for (int i = 0; i < 43; i++) asm volatile("cp.async.bulk.prefetch.L2.global [%0], %1;" :: "l"((const char*)P.w2p + hi * 352256 + i * 8192), "r"(8192) : "memory");
    }
    if (tid < 344) {
        const int cg = tid % 43, rp = tid / 43;
        const uint4* src = reinterpret_cast<const uint4*>(P.w1p + (size_t)rp * 64 * FF + (hi * 43 + cg) * 8);
        float s[8] = {0, 0, 0, 0, 0, 0, 0, 0};
#pragma unroll 8
        for (int r = 0; r < 64; r++) {
            uint4 v = __ldg(src + r * (FF / 8));
            s[0] += bf_lo(v.x); s[1] += bf_hi(v.x); s[2] += bf_lo(v.y); s[3] += bf_hi(v.y);
            s[4] += bf_lo(v.z); s[5] += bf_hi(v.z); s[6] += bf_lo(v.w); s[7] += bf_hi(v.w);
        }
        float* part = red + (rp * 43 + cg) * 8;
#pragma unroll
        for (int i = 0; i < 8; i++) part[i] = s[i];
    }
    __syncthreads();
    if (tid < 344) {
        float s = 0.f;
#pragma unroll
        for (int rp = 0; rp < 8; rp++) s += red[rp * 344 + tid];
        g_cs[hi * 344 + tid] = s;
    } else if (hi == 3 && tid < 344 + 32) g_cs[FF + tid - 344] = 0.f;
    __syncthreads();
    if (tid == 0) {
        asm volatile("red.release.gpu.global.add.u32 [%0], 1;" :: "l"(&g_count2) : "memory");
        g_epoch[b] = epoch;
    }
}

__global__ void __launch_bounds__(512, 1) fused_kernel(const __grid_constant__ Params P) {
    extern __shared__ __align__(1024) uint8_t smem[];
    const uint32_t sb = (uint32_t)__cvta_generic_to_shared(smem);
    const uint32_t mb = sb + SM_MISC;
    const int tid = threadIdx.x, lane = tid & 31, b = blockIdx.x;
    if (b >= NMAIN) { helper_cta(P, smem); return; }
    const int tg = b >> 2, hg = b & 3;

    const int warp = __shfl_sync(0xffffffffu, tid >> 5, 0);
    const int wg = warp >> 2, ww = warp & 3, g = lane >> 2, t4 = lane & 3, t128 = tid & 127;
    if (warp < 4 && lane == 0) {
        const uint32_t bar = mb + (MB_WQ + warp) * 8;
        mbar_init(bar, 1);
        asm volatile("fence.mbarrier_init.release.cluster;" ::: "memory");
        fence_async_smem();
        mbar_expect(bar, 32768);
        tma2d(sb + SM_WQ + warp * 16384, &P.wq, hg * 128, warp * 128, bar);
        tma2d(sb + SM_WQ + 65536 + warp * 16384, &P.wq, hg * 128 + 64, warp * 128, bar);
    }
    __syncwarp();
    uint4 xv[4][2];
    {
        const int r = warp * 4;
        const uint4* src = reinterpret_cast<const uint4*>(P.x + (size_t)((r & 31) + tg * 32 + (r >> 5) * 1024) * D) + lane;
#pragma unroll
        for (int i = 0; i < 4; i++) { xv[i][0] = ldg_relaxed(src + i * 64); xv[i][1] = ldg_relaxed(src + i * 64 + 32); }
        const uint4 wkv = ldg_relaxed(reinterpret_cast<const uint4*>(hg < 2 ? P.wk : P.wv) + tid * 2 + (hg & 1));
        if (warp == 4) {
            mbar_init(mb + (4 + lane) * 8, 1);
            if (lane < NBAR - 36) mbar_init(mb + (36 + lane) * 8, 36 + lane >= MB_DONE ? 16 : 1);
            if (lane < 8) sts32(mb + MISC_CNT + lane * 4, 0);
            asm volatile("fence.mbarrier_init.release.cluster;" ::: "memory");
        } else if (warp == 5) {
            if (lane == 0) { const unsigned e = g_epoch[b] + 1; g_epoch[b] = e; sts32(mb + MISC_EPOCH, e); }
        } else if (warp == 6) {
            if (lane < 3) asm volatile("prefetch.tensormap [%0];" :: "l"(&P.wo + lane) : "memory");
        }
        __syncwarp();
        sts128(sb + SM_WKV + tid * 16, wkv.x, wkv.y, wkv.z, wkv.w);
    }
    float dlt[4];
    {
        float st[4];
#pragma unroll
        for (int i = 0; i < 4; i++) {
            const uint32_t s = add_bf16x2(add_bf16x2(add_bf16x2(xv[i][0].x, xv[i][0].y), add_bf16x2(xv[i][0].z, xv[i][0].w)),
                                          add_bf16x2(add_bf16x2(xv[i][1].x, xv[i][1].y), add_bf16x2(xv[i][1].z, xv[i][1].w)));
            st[i] = bf_lo(s) + bf_hi(s);
        }
        TS(13);
#pragma unroll
        for (int o = 16; o > 0; o >>= 1)
#pragma unroll
            for (int i = 0; i < 4; i++) st[i] += __shfl_xor_sync(0xffffffffu, st[i], o);
#pragma unroll
        for (int i = 0; i < 4; i++) {
            const float nmean = st[i] * (-1.0f / D);
            const uint32_t nm = pack_bf16(nmean, nmean);
            dlt[i] = bf_lo(nm) - nmean;
            const int r = warp * 4 + i;
#pragma unroll
            for (int c = 0; c < 2; c++) {
                xv[i][c].x = add_bf16x2(xv[i][c].x, nm); xv[i][c].y = add_bf16x2(xv[i][c].y, nm);
                xv[i][c].z = add_bf16x2(xv[i][c].z, nm); xv[i][c].w = add_bf16x2(xv[i][c].w, nm);
                sts128(sb + SM_XN + ((lane >> 3) + 4 * c) * 8192 + r * 128 + (((lane & 7) ^ (r & 7)) << 4), xv[i][c].x, xv[i][c].y, xv[i][c].z, xv[i][c].w);
            }
        }
    }
    fence_async_smem();
    TS(0);
    __syncthreads();
    auto variances = [&]()
    {
        float st[4];
#pragma unroll
        for (int i = 0; i < 4; i++) {
            float v0 = 0.f, v1 = 0.f;
#pragma unroll
            for (int c = 0; c < 2; c++) {
                const uint32_t w[4] = {xv[i][c].x, xv[i][c].y, xv[i][c].z, xv[i][c].w};
#pragma unroll
                for (int k = 0; k < 4; k++) { v0 = fmaf(bf_lo(w[k]), bf_lo(w[k]), v0); v1 = fmaf(bf_hi(w[k]), bf_hi(w[k]), v1); }
            }
            st[i] = v0 + v1;
        }
#pragma unroll
        for (int o = 16; o > 0; o >>= 1)
#pragma unroll
            for (int i = 0; i < 4; i++) st[i] += __shfl_xor_sync(0xffffffffu, st[i], o);
        const float vs = lane == 0 ? st[0] : lane == 1 ? st[1] : lane == 2 ? st[2] : st[3];
        const float dl = lane == 0 ? dlt[0] : lane == 1 ? dlt[1] : lane == 2 ? dlt[2] : dlt[3];
        if (lane < 4) sts32(mb + MISC_RSTD + (warp * 4 + lane) * 4, __float_as_uint(rsqrtf(fmaxf(vs * (1.0f / D) - dl * dl, 0.f) + 1e-5f)));
    };
    float kv[4] = {0.f, 0.f, 0.f, 0.f};
    if (wg == 2) {
        fence_regs(kv);
        const uint64_t da = mkdesc(sb + SM_XN, 16, 1024, 1), db = mkdesc(sb + SM_WKV, 128, 16, 0);
        wg_fence();
#pragma unroll
        for (int s = 0; s < 32; s++) mma_ss8(kv, da + (s >> 2) * 512 + (s & 3) * 2, db + s * 16);
        wg_commit();
        variances();
        wg_wait<0>(); fence_regs(kv);
    } else {
        variances();
    }
    __syncthreads();
    const float rs0 = __uint_as_float(lds32(mb + MISC_RSTD + (ww * 16 + g) * 4)), rs1 = __uint_as_float(lds32(mb + MISC_RSTD + (ww * 16 + g + 8) * 4));
    constexpr float QSCALE = 0.25f * 1.4426950408889634f;
    uint32_t kvoff[2];
#pragma unroll
    for (int i = 0; i < 2; i++) {
        const int t = ((ww & 1) * 16 + g + 8 * i), c = 2 * tg + (ww >> 1), ts = (t + 31) & 31;
        kvoff[i] = hg < 2 ? (ts >> 3) * 32768 + (ts & 7) * 2048 + (c >> 3) * 256 + (hg & 1) * 128 + (c & 7) * 16 + t4 * 4
                          : (t >> 3) * 32768 + 16384 + (hg & 1) * 8192 + ((t & 7) * 64 + c) * 16 + t4 * 4;
    }
    float qa[32];
    if (wg < 2) {
#pragma unroll
        for (int i = 0; i < 32; i++) qa[i] = 0.f;
        fence_regs(qa);
        const uint64_t da = mkdesc(sb + SM_XN, 16, 1024, 1), db = mkdesc(sb + SM_WQ + wg * 65536, 16, 1024, 1);
#pragma unroll 1
        for (int i = 0; i < 4; i++) {
            mbar_wait(mb + (MB_WQ + i) * 8);
            wg_fence();
#pragma unroll
            for (int s = 0; s < 8; s++) mma_ss64(qa, da + (i * 2 + (s >> 2)) * 512 + (s & 3) * 2, db + (i * 8 + s) * 128);
            wg_commit();
        }
        wg_wait<0>();
        fence_regs(qa);
        bar_arrive(6, 512);
        TS(1);
        float nn[8];
#pragma unroll
        for (int i = 0; i < 32; i++) qa[i] *= ((i & 2) ? rs1 : rs0) * QSCALE;
#pragma unroll
        for (int h = 0; h < 4; h++) {
            const uint32_t base = sb + SM_Q + ((ww >> 1) * 4 + wg * 2 + (h >> 1)) * 2048 + ((h & 1) * 4 + (ww & 1) * 2) * 256 + lane * 4;
            sts32(base, pack_f16(qa[8 * h], qa[8 * h + 1])); sts32(base + 256, pack_f16(qa[8 * h + 2], qa[8 * h + 3]));
            sts32(base + 128, pack_f16(qa[8 * h + 4], qa[8 * h + 5])); sts32(base + 384, pack_f16(qa[8 * h + 6], qa[8 * h + 7]));
            nn[2 * h] = qa[8 * h] * qa[8 * h] + qa[8 * h + 1] * qa[8 * h + 1] + qa[8 * h + 4] * qa[8 * h + 4] + qa[8 * h + 5] * qa[8 * h + 5];
            nn[2 * h + 1] = qa[8 * h + 2] * qa[8 * h + 2] + qa[8 * h + 3] * qa[8 * h + 3] + qa[8 * h + 6] * qa[8 * h + 6] + qa[8 * h + 7] * qa[8 * h + 7];
        }
#pragma unroll
        for (int o = 1; o < 4; o <<= 1)
#pragma unroll
            for (int i = 0; i < 8; i++) nn[i] += __shfl_xor_sync(0xffffffffu, nn[i], o);
        uint32_t nm = 0;
#pragma unroll
        for (int i = 0; i < 8; i++) nm = max(nm, __float_as_uint(nn[i]));
        nm = __reduce_max_sync(0xffffffffu, nm);
        if (lane == 0) asm volatile("red.shared.max.u32 [%0], %1;" :: "r"(mb + MISC_NRM), "r"(nm) : "memory");
    } else {
        if (wg == 2) {
            kv[0] *= rs0; kv[1] *= rs0; kv[2] *= rs1; kv[3] *= rs1;
            char* img = reinterpret_cast<char*>(g_kv);
            if (hg < 2) {
                const int r0 = ww * 16 + g;
                float2* kt = reinterpret_cast<float2*>(smem + SM_MISC + MISC_K0);
                kt[r0 * 4 + t4] = make_float2(kv[0], kv[1]);
                kt[(r0 + 8) * 4 + t4] = make_float2(kv[2], kv[3]);
                bar_sync(2, 128);
                float2 p0 = make_float2(0.f, 0.f);
                if (r0 & 31) p0 = kt[(r0 - 1) * 4 + t4];
                const float2 p1 = kt[(r0 + 7) * 4 + t4];
                stg32(img + kvoff[0], nonzero(pack_f16(kv[0] - p0.x, kv[1] - p0.y)));
                stg32(img + kvoff[1], nonzero(pack_f16(kv[2] - p1.x, kv[3] - p1.y)));
            } else {
                stg32(img + kvoff[0], nonzero(pack_bf16(kv[0], kv[1])));
                stg32(img + kvoff[1], nonzero(pack_bf16(kv[2], kv[3])));
            }
            uint32_t nm = max(__float_as_uint(quad_sum(kv[0] * kv[0] + kv[1] * kv[1])), __float_as_uint(quad_sum(kv[2] * kv[2] + kv[3] * kv[3])));
            nm = __reduce_max_sync(0xffffffffu, nm);
            if (lane == 0) stg32(reinterpret_cast<uint32_t*>(g_nrm + b) + ww, nm | 1u);
            if (hg < 2) {
#pragma unroll
                for (int i = 0; i < 2; i++)
                    stg32(reinterpret_cast<char*>(g_kplain) + (kvoff[i] >> 15) * 16384 + (kvoff[i] & 16383), pack_bf16(kv[2 * i], kv[2 * i + 1]));
            }
            TS(1);
            bar_sync(2, 128);
            if (t128 == 0) asm volatile("red.release.gpu.global.add.u32 [%0], 1;" :: "l"(&g_count1) : "memory");
            __syncwarp();
        } else {
            uint4 v; int spins = 0;
            do { v = ldg_relaxed(g_nrm + t128); } while (__any_sync(0xffffffffu, has_zero(v)) && ++spins < SPIN_LIMIT);
            uint32_t nm = max(max(v.x, v.y), max(v.z, v.w));
            nm = max(nm, __shfl_xor_sync(0xffffffffu, nm, 4)); nm = max(nm, __shfl_xor_sync(0xffffffffu, nm, 8)); nm = max(nm, __shfl_xor_sync(0xffffffffu, nm, 16));
            if (lane < 4) asm volatile("red.shared.max.u32 [%0], %1;" :: "r"(mb + MISC_NRM + 4 + min(lane, 2) * 4), "r"(nm) : "memory");
            TS(1);
        }
        bar_sync(5, 256);
        const int t256 = tid - 256;
        uint4 kc[9]; int spins = 0; bool bad;
        do {
            bad = false;
#pragma unroll
            for (int i = 0; i < 8; i++) kc[i] = ldg_relaxed(g_kv + i * 256 + t256);
            kc[8] = ldg_relaxed(g_kv + 3 * 2048 + 7 * 128 + t128);
#pragma unroll
            for (int i = 0; i < 9; i++) bad |= has_zero(kc[i]);
        } while (__any_sync(0xffffffffu, bad) && ++spins < SPIN_LIMIT);
        TS(2);
        bar_sync(6, 512);
#pragma unroll
        for (int i = 0; i < 8; i++) sts128(sb + (i * 256 + t256) * 16, kc[i].x, kc[i].y, kc[i].z, kc[i].w);
        if (wg == 3) sts128(mb + MISC_K0 + t128 * 16, kc[8].x, kc[8].y, kc[8].z, kc[8].w);
#pragma unroll
        for (int i = 0; i < 8; i++) sts128(sb + (i >> 1) * KVCH + 32768 + (i & 1) * 4096 + t256 * 16, 0x3F803F80u, 0x3F803F80u, 0x3F803F80u, 0x3F803F80u);
    }
    fence_async_smem();
    TS(3);
    __syncthreads();
    const float q2 = __uint_as_float(lds32(mb + MISC_NRM)), v2 = __uint_as_float(lds32(mb + MISC_NRM + 12));
    const float k2 = __uint_as_float(lds32(mb + MISC_NRM + 4)) + __uint_as_float(lds32(mb + MISC_NRM + 8));
    const bool safe = __all_sync(0xffffffffu, (q2 * k2 <= 3500.0f) && (q2 <= 65536.0f) && (k2 <= 65536.0f) && (v2 <= 1e24f));
    TS(4);

    if (__builtin_expect(safe, 1)) {
        attention<true>(P, sb, warp TS_PASS);
    } else {
        if (wg < 2) {
#pragma unroll
            for (int h = 0; h < 4; h++) {
                const uint32_t base = sb + SM_Q + ((ww >> 1) * 4 + wg * 2 + (h >> 1)) * 2048 + ((h & 1) * 4 + (ww & 1) * 2) * 256 + lane * 4;
                sts32(base, pack_bf16(qa[8 * h], qa[8 * h + 1])); sts32(base + 256, pack_bf16(qa[8 * h + 2], qa[8 * h + 3]));
                sts32(base + 128, pack_bf16(qa[8 * h + 4], qa[8 * h + 5])); sts32(base + 384, pack_bf16(qa[8 * h + 6], qa[8 * h + 7]));
            }
            fence_async_smem();
        } else if (warp == 15) {
            wait_count(&g_count1, lds32(mb + MISC_EPOCH) * NMAIN);
            if (lane == 0) {
                asm volatile("fence.proxy.async;" ::: "memory");
                mbar_expect(mb + MB_KV * 8, 4 * 32768 + 2048);
                for (int c = 0; c < 4; c++) {
                    bulk_g2s(sb + c * KVCH, g_kplain + c * 1024, 16384, mb + MB_KV * 8);
                    bulk_g2s(sb + c * KVCH + 16384, g_kv + c * 2048 + 1024, 16384, mb + MB_KV * 8);
                }
                bulk_g2s(mb + MISC_K0, g_kplain + 3 * 1024 + 7 * 128, 2048, mb + MB_KV * 8);
            }
            __syncwarp();
        }
        __syncthreads();
        mbar_wait(mb + MB_KV * 8);
        attention<false>(P, sb, warp TS_PASS);
    }

    const int pr = 1 - (wg >> 1), q = wg & 1;
    const int mt = 16 * pr + (b >> 3), j = b & 7;
    const int row0 = mt * 64 + ww * 16 + g;
    uint32_t hk[8];
    {
        const uint32_t* xp = reinterpret_cast<const uint32_t*>(P.x + (size_t)row0 * D + j * 64 + q * 32 + t4 * 2);
#pragma unroll
        for (int i = 0; i < 4; i++) { hk[2 * i] = __ldg(xp + i * 4); hk[2 * i + 1] = __ldg(xp + i * 4 + 8 * (D / 2)); }
    }
    if (warp == 4) {
        mbar_wait(mb + (MB_DONE + 3) * 8);
        if (lane == 0) { load_w1(sb, P, 1); load_w1(sb, P, 2); }
        __syncwarp();
    } else if (warp == 0) {
        mbar_wait(mb + (MB_DONE + 4) * 8);
        if (lane == 0) {
            load_w1(sb, P, 3);
#pragma unroll 1
            for (int kb = 3; kb < 6; kb++) load_w2(sb, P, kb);
        }
        __syncwarp();
    }
    mbar_wait(mb + MB_F2 * 8);
#pragma unroll 1
    for (int ph = 0; ph < 2; ph++) {
        float r[16];
        {
            const uint4* a = (ph ? g_Hf + mt * 88 * 128 : g_of + mt * 32 * 128) + q * 512 + t128;
            const int nblk = ph ? 11 : 4;
            uint64_t slots = ph ? (q ? pack_slots(true, 1) : pack_slots(true, 0)) : (q ? pack_slots(false, 1) : pack_slots(false, 0));
            uint32_t bar = mb + ((ph ? MB_W2 : MB_WO) + q) * 8;
            float acc[32];
            uint4 buf[4][4];
            fill_ring<4>(buf, a, 1024);
#pragma unroll
            for (int i = 0; i < 32; i++) acc[i] = 0.f;
            fence_regs(acc);
#pragma unroll 1
            for (int i0 = 0; i0 < nblk; i0 += 4) {
#pragma unroll
                for (int i = 0; i < 4; i++) {
                    const int blk = i0 + i;
                    if (blk < nblk) {
                        const uint64_t db = mkdesc(sb + ((uint32_t)slots & 31) * 8192, 16, 1024, 1);
                        mbar_wait(bar);
                        check_batch(buf[i], a + blk * 1024);
                        wg_fence();
#pragma unroll
                        for (int s = 0; s < 4; s++) mma_rs(acc, buf[i][s], db + s * 128);
                        wg_commit();
                        slots >>= 5; bar += 16;
                        wg_wait<1>();
                        if (blk >= 1 && blk + 3 < nblk) load_batch(buf[(i + 3) & 3], a + (blk + 3) * 1024);
                    }
                }
            }
            wg_wait<0>();
            fence_regs(acc);
            TS(7 + 4 * ph);
            if (ph == 0) {
                warp_done(mb + (MB_DONE + 5) * 8);
                mbar_wait(mb + (MB_DONE + 4 * pr) * 8);
            }
            pair_reduce(acc, r, sb + SM_Q + pr * 8192 + t128 * 16, q, 3 + pr);
        }
#pragma unroll
        for (int i = 0; i < 8; i++) hk[i] = pack_bf16(r[2 * i] + bf_lo(hk[i]), r[2 * i + 1] + bf_hi(hk[i]));
        if (ph == 1) break;
        {
            uint4* hp = g_hf + (mt * 32 + j * 4 + 2 * q) * 128 + t128;
            stg128(hp, hk[0], hk[1], hk[2], hk[3]);
            stg128(hp + 128, hk[4], hk[5], hk[6], hk[7]);
            float s0 = 0.f, s1 = 0.f;
#pragma unroll
            for (int i = 0; i < 8; i++) {
                r[2 * i] = bf_lo(hk[i]); r[2 * i + 1] = bf_hi(hk[i]);
                if (i & 1) s1 += r[2 * i] + r[2 * i + 1]; else s0 += r[2 * i] + r[2 * i + 1];
            }
            s0 += __shfl_xor_sync(0xffffffffu, s0, 1); s1 += __shfl_xor_sync(0xffffffffu, s1, 1);
            s0 += __shfl_xor_sync(0xffffffffu, s0, 2); s1 += __shfl_xor_sync(0xffffffffu, s1, 2);
            const float a0 = s0 * (1.0f / 32), a1 = s1 * (1.0f / 32);
            float v0 = 0.f, v1 = 0.f;
#pragma unroll
            for (int i = 0; i < 8; i++) {
                const float a = (i & 1) ? a1 : a0;
                const float d0 = r[2 * i] - a, d1 = r[2 * i + 1] - a;
                if (i & 1) v1 += d0 * d0 + d1 * d1; else v0 += d0 * d0 + d1 * d1;
            }
            v0 += __shfl_xor_sync(0xffffffffu, v0, 1); v1 += __shfl_xor_sync(0xffffffffu, v1, 1);
            v0 += __shfl_xor_sync(0xffffffffu, v0, 2); v1 += __shfl_xor_sync(0xffffffffu, v1, 2);
            if (t4 < 2) stg64(g_stats + (row0 + 8 * t4) * 16 + j * 2 + q, __float_as_uint(t4 ? s1 : s0), __float_as_uint(t4 ? v1 : v0));
            TS(8);
            if (warp == 1) {
                mbar_wait(mb + (MB_DONE + 5) * 8);
                if (lane == 0) {
#pragma unroll 1
                    for (int kb = 6; kb < 14; kb++) load_w2(sb, P, kb);
                }
                __syncwarp();
            } else if (wg == 2) {
                if (kvoff[0] < 32768 || kvoff[0] >= 3 * 32768) stg32(reinterpret_cast<char*>(g_kv) + kvoff[0], 0u);
                if (kvoff[1] < 32768) stg32(reinterpret_cast<char*>(g_kv) + kvoff[1], 0u);
                if (lane == 0) stg32(reinterpret_cast<uint32_t*>(g_nrm + b) + ww, 0u);
            }
        }
        {
            const int mt1 = 16 * pr + (b >> 4) * 2 + q, sl = b & 15;
            const uint4* a = g_hf + mt1 * 32 * 128 + t128;
            float acc[44], nmean[2], hrstd[2];
            uint4 buf[3][4];
            fill_ring<3>(buf, a, 512);
            {
                const uint4* sp = reinterpret_cast<const uint4*>(g_stats + (mt1 * 64 + ww * 16 + g) * 16 + t4 * 4);
                uint4 u[4]; int spins = 0;
                do { u[0] = ldg_relaxed(sp); u[1] = ldg_relaxed(sp + 1); u[2] = ldg_relaxed(sp + 64); u[3] = ldg_relaxed(sp + 65); } while (batch_bad(u) && ++spins < SPIN_LIMIT);
                float mean[2], m2[2];
#pragma unroll
                for (int i = 0; i < 2; i++) mean[i] = (__uint_as_float(u[2 * i].x) + __uint_as_float(u[2 * i].z)) + (__uint_as_float(u[2 * i + 1].x) + __uint_as_float(u[2 * i + 1].z));
                mean[0] += __shfl_xor_sync(0xffffffffu, mean[0], 1); mean[1] += __shfl_xor_sync(0xffffffffu, mean[1], 1);
                mean[0] += __shfl_xor_sync(0xffffffffu, mean[0], 2); mean[1] += __shfl_xor_sync(0xffffffffu, mean[1], 2);
#pragma unroll
                for (int i = 0; i < 2; i++) {
                    mean[i] *= 1.0f / D;
                    const float da = __uint_as_float(u[2 * i].x) * (1.0f / 32) - mean[i], dc = __uint_as_float(u[2 * i].z) * (1.0f / 32) - mean[i];
                    const float de = __uint_as_float(u[2 * i + 1].x) * (1.0f / 32) - mean[i], df = __uint_as_float(u[2 * i + 1].z) * (1.0f / 32) - mean[i];
                    m2[i] = (__uint_as_float(u[2 * i].y) + __uint_as_float(u[2 * i].w)) + (__uint_as_float(u[2 * i + 1].y) + __uint_as_float(u[2 * i + 1].w)) + 32.0f * (da * da + dc * dc + de * de + df * df);
                }
                m2[0] += __shfl_xor_sync(0xffffffffu, m2[0], 1); m2[1] += __shfl_xor_sync(0xffffffffu, m2[1], 1);
                m2[0] += __shfl_xor_sync(0xffffffffu, m2[0], 2); m2[1] += __shfl_xor_sync(0xffffffffu, m2[1], 2);
#pragma unroll
                for (int i = 0; i < 2; i++) { hrstd[i] = 0.5f * rsqrtf(m2[i] * (1.0f / D) + 1e-5f); nmean[i] = -mean[i]; }
            }
#pragma unroll
            for (int i = 0; i < 44; i++) acc[i] = 0.f;
            fence_regs(acc);
#pragma unroll 1
            for (int i0 = 0; i0 < 8; i0 += 3) {
#pragma unroll
                for (int i = 0; i < 3; i++) {
                    const int blk = i0 + i;
                    if (blk < 8) {
                        const uint64_t db = mkdesc(sb + SM_W1 + (blk >> 1) * 24576 + (blk & 1) * 4096, 8192, 512, 2);
                        mbar_wait(mb + (MB_W1 + (blk >> 1)) * 8);
                        check_batch(buf[i], a + blk * 512);
                        wg_fence();
#pragma unroll
                        for (int s = 0; s < 4; s++) mma_rs(acc, buf[i][s], db + s * 64);
                        wg_commit();
                        wg_wait<1>();
                        if (blk >= 1 && blk + 2 < 8) load_batch(buf[(i + 2) % 3], a + (blk + 2) * 512);
                        if (blk >= 2 && !(blk & 1)) {
                            const int gi = (blk >> 1) - 1;
                            if (warp_arrive(mb + MISC_CNT + gi * 4) == 15) {
                                if (lane == 0) {
#pragma unroll 1
                                    for (int kb = 14 + 3 * gi; kb < min(17 + 3 * gi, 22); kb++) load_w2(sb, P, kb);
                                }
                                __syncwarp();
                            }
                        }
                    }
                }
            }
            wg_wait<0>();
            fence_regs(acc);
            TS(9);
            uint32_t hv[22];
#pragma unroll
            for (int i = 0; i < 11; i++) {
                float2 cs;
                asm volatile("ld.shared.v2.f32 {%0,%1}, [%2];" : "=f"(cs.x), "=f"(cs.y) : "r"(mb + MISC_CS + i * 32 + t4 * 8));
                hv[2 * i] = pack_bf16(silu2(hrstd[0] * fmaf(nmean[0], cs.x, acc[4 * i])), silu2(hrstd[0] * fmaf(nmean[0], cs.y, acc[4 * i + 1])));
                hv[2 * i + 1] = pack_bf16(silu2(hrstd[1] * fmaf(nmean[1], cs.x, acc[4 * i + 2])), silu2(hrstd[1] * fmaf(nmean[1], cs.y, acc[4 * i + 3])));
            }
            uint4* hb = g_Hf + (mt1 * 88 + (sl >> 1) * 11) * 128 + t128;
            if (sl & 1) {
                stg64(reinterpret_cast<uint2*>(hb + 5 * 128) + 1, hv[0], hv[1]);
#pragma unroll
                for (int i = 0; i < 5; i++) stg128(hb + (6 + i) * 128, hv[2 + 4 * i], hv[3 + 4 * i], hv[4 + 4 * i], hv[5 + 4 * i]);
            } else {
#pragma unroll
                for (int i = 0; i < 5; i++) stg128(hb + i * 128, hv[4 * i], hv[4 * i + 1], hv[4 * i + 2], hv[4 * i + 3]);
                stg64(hb + 5 * 128, hv[20], hv[21]);
            }
            TS(10);
        }
    }
#pragma unroll
    for (int h = 0; h < 2; h++) {
        uint32_t v0 = hk[h], v1 = hk[2 + h], v2 = hk[4 + h], v3 = hk[6 + h];
        const bool o1 = t4 & 1, o2 = t4 & 2;
        uint32_t a = __shfl_xor_sync(0xffffffffu, o1 ? v0 : v1, 1), c = __shfl_xor_sync(0xffffffffu, o1 ? v2 : v3, 1);
        if (o1) { v0 = a; v2 = c; } else { v1 = a; v3 = c; }
        a = __shfl_xor_sync(0xffffffffu, o2 ? v0 : v2, 2); c = __shfl_xor_sync(0xffffffffu, o2 ? v1 : v3, 2);
        if (o2) { v0 = a; v1 = c; } else { v2 = a; v3 = c; }
        *reinterpret_cast<uint4*>(P.out + (size_t)(row0 + 8 * h) * D + j * 64 + q * 32 + t4 * 8) = make_uint4(v0, v1, v2, v3);
    }
    TS(12);
}

typedef CUresult (*EncodeFn)(CUtensorMap*, CUtensorMapDataType, cuuint32_t, void*, const cuuint64_t*, const cuuint64_t*, const cuuint32_t*,
                             const cuuint32_t*, CUtensorMapInterleave, CUtensorMapSwizzle, CUtensorMapL2promotion, CUtensorMapFloatOOBfill);

void encode2d(EncodeFn fn, CUtensorMap* tm, const void* ptr, int rows, int cols, int box_rows, int box_cols, CUtensorMapSwizzle sw) {
    cuuint64_t dims[2] = {(cuuint64_t)cols, (cuuint64_t)rows};
    cuuint64_t strides[1] = {(cuuint64_t)cols * 2};
    cuuint32_t box[2] = {(cuuint32_t)box_cols, (cuuint32_t)box_rows};
    cuuint32_t es[2] = {1, 1};
    fn(tm, CU_TENSOR_MAP_DATA_TYPE_BFLOAT16, 2, const_cast<void*>(ptr), dims, strides, box, es, CU_TENSOR_MAP_INTERLEAVE_NONE, sw,
       CU_TENSOR_MAP_L2_PROMOTION_L2_128B, CU_TENSOR_MAP_FLOAT_OOB_FILL_NONE);
}

}

extern "C" void kernel_launch(void* const* d_in, const int* in_sizes, int n_in, void* d_out, int out_size) {
    (void)in_sizes; (void)n_in; (void)out_size;
    void* fnp = nullptr;
    cudaDriverEntryPointQueryResult qr;
    cudaGetDriverEntryPoint("cuTensorMapEncodeTiled", &fnp, cudaEnableDefault, &qr);
    EncodeFn fn = (EncodeFn)fnp;
    Params P;
    encode2d(fn, &P.wq, d_in[1], D, D, 128, 64, CU_TENSOR_MAP_SWIZZLE_128B);
    P.wk = (const __nv_bfloat16*)d_in[2];
    P.wv = (const __nv_bfloat16*)d_in[3];
    encode2d(fn, &P.wo, d_in[4], D, D, 64, 64, CU_TENSOR_MAP_SWIZZLE_128B);
    encode2d(fn, &P.w1, d_in[6], D, FF, 128, 32, CU_TENSOR_MAP_SWIZZLE_64B);
    encode2d(fn, &P.w2, d_in[7], FF, D, 64, 64, CU_TENSOR_MAP_SWIZZLE_128B);
    P.x = (const __nv_bfloat16*)d_in[0];
    P.w1p = (const __nv_bfloat16*)d_in[6];
    P.w2p = (const __nv_bfloat16*)d_in[7];
    P.wop = (const __nv_bfloat16*)d_in[4];
    P.out = (__nv_bfloat16*)d_out;
    P.neg1 = 0xFFFFFFFFu;
    cudaFuncSetAttribute(fused_kernel, cudaFuncAttributeMaxDynamicSharedMemorySize, SMEM_BYTES);
    fused_kernel<<<NCTA, 512, SMEM_BYTES>>>(P);
}
```

```cpp
#include <cuda_runtime.h>
#include <cuda_bf16.h>
#include <cuda.h>
#include <stdint.h>

namespace {

constexpr int D = 512, FF = 1376;
constexpr int NMAIN = 128, NHELP = 4, NCTA = NMAIN + NHELP;
constexpr uint32_t SENT = 0xFFFFFFFFu;
constexpr int SPIN_LIMIT = 1 << 22;

constexpr uint32_t KB = 1024;
constexpr uint32_t SM_XN = 0;
constexpr uint32_t SM_WQ = 64 * KB;
constexpr uint32_t SM_WKV = 192 * KB;
constexpr uint32_t KVCH = 40 * KB;
constexpr uint32_t SM_Q = 200 * KB;
constexpr uint32_t SM_W1 = 40 * KB;
constexpr uint32_t SM_MISC = 224 * KB;
constexpr uint32_t SMEM_BYTES = 227 * KB;
constexpr uint32_t MB_WQ = 0;
constexpr uint32_t MB_KV = 4;
constexpr uint32_t MB_WO = 8;
constexpr uint32_t MB_W2 = 16;
constexpr uint32_t MB_W1 = 38;
constexpr uint32_t MB_F2 = 42;
constexpr uint32_t MB_CS = 43;
constexpr uint32_t MB_DONE = 44;
constexpr uint32_t NBAR = 50;
constexpr uint32_t MISC_CNT = 400;
constexpr uint32_t MISC_NRM = 416;
constexpr uint32_t MISC_EPOCH = 432;
constexpr uint32_t MISC_CS = 448;
constexpr uint32_t MISC_RSTD = 768;
constexpr uint32_t MISC_K0 = 1024;

__host__ __device__ constexpr uint32_t wo_slot(int kb) { return kb < 5 ? 20 + kb : kb - 5; }
__host__ __device__ constexpr uint32_t w2_slot(int kb) {
    return kb == 0 ? 27 : kb < 3 ? 2 + kb : kb < 6 ? 14 + kb : kb < 11 ? 14 + kb : kb < 14 ? kb - 11 : kb - 9;
}
__host__ __device__ constexpr uint64_t pack_slots(bool is_w2, int q) {
    uint64_t v = 0;
    for (int i = 0; i < (is_w2 ? 11 : 4); i++) v |= (uint64_t)(is_w2 ? w2_slot(2 * i + q) : wo_slot(2 * i + q)) << (5 * i);
    return v;
}

__device__ uint4 g_kv[4 * 2048];
__device__ uint4 g_kplain[4 * 1024];
__device__ uint4 g_of[32 * 32 * 128];
__device__ uint4 g_hf[32 * 32 * 128];
__device__ uint4 g_Hf[32 * 88 * 128];
__device__ float2 g_stats[32 * 64 * 16];
__device__ float g_cs[1408];
__device__ uint4 g_nrm[NMAIN];
__device__ unsigned g_count1;
__device__ unsigned g_count2;
__device__ unsigned g_epoch[NCTA];
#define TS(i) do {} while (0)

__device__ __forceinline__ void mbar_init(uint32_t bar, int cnt) { asm volatile("mbarrier.init.shared::cta.b64 [%0], %1;" :: "r"(bar), "r"(cnt) : "memory"); }
__device__ __forceinline__ void mbar_expect(uint32_t bar, uint32_t bytes) { asm volatile("mbarrier.arrive.expect_tx.shared::cta.b64 _, [%0], %1;" :: "r"(bar), "r"(bytes) : "memory"); }
__device__ __forceinline__ void mbar_arrive(uint32_t bar) { asm volatile("mbarrier.arrive.shared::cta.b64 _, [%0];" :: "r"(bar) : "memory"); }
__device__ __forceinline__ void mbar_wait(uint32_t bar) {
    uint32_t done; int spins = 0;
    do {
        asm volatile("{.reg .pred p; mbarrier.try_wait.parity.shared::cta.b64 p, [%1], 0; selp.u32 %0, 1, 0, p;}" : "=r"(done) : "r"(bar) : "memory");
    } while (!__all_sync(0xffffffffu, done) && ++spins < SPIN_LIMIT);
}
__device__ __forceinline__ void tma2d(uint32_t dst, const CUtensorMap* tm, int c0, int c1, uint32_t bar) {
    asm volatile("cp.async.bulk.tensor.2d.shared::cluster.global.mbarrier::complete_tx::bytes [%0], [%1, {%3, %4}], [%2];"
                 :: "r"(dst), "l"(tm), "r"(bar), "r"(c0), "r"(c1) : "memory");
}
__device__ __forceinline__ void bulk_g2s(uint32_t dst, const void* src, uint32_t bytes, uint32_t bar) {
    asm volatile("cp.async.bulk.shared::cluster.global.mbarrier::complete_tx::bytes [%0], [%1], %2, [%3];" :: "r"(dst), "l"(src), "r"(bytes), "r"(bar) : "memory");
}
__device__ __forceinline__ void fence_async_smem() { asm volatile("fence.proxy.async.shared::cta;" ::: "memory"); }
__device__ __forceinline__ void bar_sync(int id, int n) { asm volatile("bar.sync %0, %1;" :: "r"(id), "r"(n) : "memory"); }
__device__ __forceinline__ void bar_arrive(int id, int n) { asm volatile("bar.arrive %0, %1;" :: "r"(id), "r"(n) : "memory"); }
__device__ __forceinline__ void wg_fence() { asm volatile("wgmma.fence.sync.aligned;" ::: "memory"); }
__device__ __forceinline__ void wg_commit() { asm volatile("wgmma.commit_group.sync.aligned;" ::: "memory"); }
template <int N> __device__ __forceinline__ void wg_wait() { asm volatile("wgmma.wait_group.sync.aligned %0;" :: "n"(N) : "memory"); }
template <int N> __device__ __forceinline__ void fence_regs(float (&d)[N]) {
#pragma unroll
    for (int i = 0; i < N; i++) asm volatile("" : "+f"(d[i]) :: "memory");
}
template <int N> __device__ __forceinline__ void fence_regs(uint32_t (&d)[N]) {
#pragma unroll
    for (int i = 0; i < N; i++) asm volatile("" : "+r"(d[i]) :: "memory");
}
__device__ __forceinline__ uint64_t mkdesc(uint32_t addr, uint32_t lbo, uint32_t sbo, uint32_t swz) {
    return (uint64_t)(((addr & 0x3FFFF) >> 4) | ((lbo >> 4) << 16)) | ((uint64_t)((sbo >> 4) | (swz << 30)) << 32);
}
__device__ __forceinline__ float ex2(float x) { float y; asm("ex2.approx.ftz.f32 %0, %1;" : "=f"(y) : "f"(x)); return y; }
__device__ __forceinline__ float rcp(float x) { float y; asm("rcp.approx.ftz.f32 %0, %1;" : "=f"(y) : "f"(x)); return y; }
__device__ __forceinline__ uint32_t pack_bf16(float lo, float hi) { uint32_t r; asm("cvt.rn.bf16x2.f32 %0, %1, %2;" : "=r"(r) : "f"(hi), "f"(lo)); return r; }
__device__ __forceinline__ uint32_t pack_f16(float lo, float hi) { uint32_t r; asm("cvt.rn.f16x2.f32 %0, %1, %2;" : "=r"(r) : "f"(hi), "f"(lo)); return r; }
__device__ __forceinline__ float bf_lo(uint32_t v) { return __uint_as_float(v << 16); }
__device__ __forceinline__ float bf_hi(uint32_t v) { return __uint_as_float(v & 0xFFFF0000u); }
__device__ __forceinline__ uint4 ldg_relaxed(const uint4* p) {
    uint4 v; asm volatile("ld.relaxed.gpu.global.v4.u32 {%0,%1,%2,%3}, [%4];" : "=r"(v.x), "=r"(v.y), "=r"(v.z), "=r"(v.w) : "l"(p) : "memory"); return v;
}
__device__ __forceinline__ void stg128(void* p, uint32_t a, uint32_t b, uint32_t c, uint32_t d) {
    asm volatile("st.relaxed.gpu.global.v4.u32 [%0], {%1,%2,%3,%4};" :: "l"(p), "r"(a), "r"(b), "r"(c), "r"(d) : "memory");
}
__device__ __forceinline__ void stg64(void* p, uint32_t a, uint32_t b) {
    asm volatile("st.relaxed.gpu.global.v2.u32 [%0], {%1,%2};" :: "l"(p), "r"(a), "r"(b) : "memory");
}
__device__ __forceinline__ void sts128(uint32_t a, uint32_t x, uint32_t y, uint32_t z, uint32_t w) {
    asm volatile("st.shared.v4.u32 [%0], {%1,%2,%3,%4};" :: "r"(a), "r"(x), "r"(y), "r"(z), "r"(w) : "memory");
}
__device__ __forceinline__ void sts32(uint32_t a, uint32_t x) { asm volatile("st.shared.u32 [%0], %1;" :: "r"(a), "r"(x) : "memory"); }
__device__ __forceinline__ float4 lds128f(uint32_t a) {
    float4 v; asm volatile("ld.shared.v4.f32 {%0,%1,%2,%3}, [%4];" : "=f"(v.x), "=f"(v.y), "=f"(v.z), "=f"(v.w) : "r"(a) : "memory"); return v;
}
__device__ __forceinline__ uint32_t lds32(uint32_t a) { uint32_t v; asm volatile("ld.shared.u32 %0, [%1];" : "=r"(v) : "r"(a) : "memory"); return v; }
__device__ __forceinline__ bool has_sent(const uint4& v) { return (v.x == SENT) | (v.w == SENT); }
__device__ __forceinline__ bool has_zero(const uint4& v) { return min(min(v.x, v.y), min(v.z, v.w)) == 0u; }
__device__ __forceinline__ uint32_t nonzero(uint32_t w) { return w == 0u ? 0x8000u : w; }
__device__ __forceinline__ void stg32(void* p, uint32_t a) { asm volatile("st.relaxed.gpu.global.u32 [%0], %1;" :: "l"(p), "r"(a) : "memory"); }
__device__ __forceinline__ void wait_count(const unsigned* p, unsigned target) {
    unsigned v; int spins = 0;
    do { asm volatile("ld.acquire.gpu.global.u32 %0, [%1];" : "=r"(v) : "l"(p) : "memory"); } while (__any_sync(0xffffffffu, v != target) && ++spins < SPIN_LIMIT);
}
__device__ __forceinline__ uint32_t warp_arrive(uint32_t cnt) {
    uint32_t old = 0;
    __syncwarp();
    if ((threadIdx.x & 31) == 0) asm volatile("atom.acq_rel.cta.shared.add.u32 %0, [%1], 1;" : "=r"(old) : "r"(cnt) : "memory");
    return __shfl_sync(0xffffffffu, old, 0);
}
__device__ __forceinline__ void warp_done(uint32_t bar) { __syncwarp(); if ((threadIdx.x & 31) == 0) mbar_arrive(bar); }
__device__ __forceinline__ uint32_t add_bf16x2(uint32_t a, uint32_t b) { uint32_t r; asm("add.rn.bf16x2 %0, %1, %2;" : "=r"(r) : "r"(a), "r"(b)); return r; }

#define R4(d, o) "+f"(d[o + 0]), "+f"(d[o + 1]), "+f"(d[o + 2]), "+f"(d[o + 3])
#define R8(d, o) R4(d, o), R4(d, o + 4)
#define R32(d) R8(d, 0), R8(d, 8), R8(d, 16), R8(d, 24)
#define D32 "{%0,%1,%2,%3,%4,%5,%6,%7,%8,%9,%10,%11,%12,%13,%14,%15,%16,%17,%18,%19,%20,%21,%22,%23,%24,%25,%26,%27,%28,%29,%30,%31}"
#define D44 "{%0,%1,%2,%3,%4,%5,%6,%7,%8,%9,%10,%11,%12,%13,%14,%15,%16,%17,%18,%19,%20,%21,%22,%23,%24,%25,%26,%27,%28,%29,%30,%31,%32,%33,%34,%35,%36,%37,%38,%39,%40,%41,%42,%43}"

__device__ __forceinline__ void mma_qk_f16(float (&d)[32], uint64_t da, uint64_t db) {
    asm volatile("{.reg .pred p; setp.eq.b32 p, 0, 0; wgmma.mma_async.sync.aligned.m64n64k16.f32.f16.f16 " D32 ", %32, %33, p, 1, 1, 0, 0;}"
                 : R32(d) : "l"(da), "l"(db));
}
__device__ __forceinline__ void mma_qk_bf16(float (&d)[32], uint64_t da, uint64_t db) {
    asm volatile("{.reg .pred p; setp.ne.b32 p, 0, 0; wgmma.mma_async.sync.aligned.m64n64k16.f32.bf16.bf16 " D32 ", %32, %33, p, 1, 1, 0, 0;}"
                 : R32(d) : "l"(da), "l"(db));
}
__device__ __forceinline__ void mma_pv(float (&d)[12], const uint32_t* a, uint64_t db) {
    asm volatile("{.reg .pred p; setp.eq.b32 p, 0, 0; wgmma.mma_async.sync.aligned.m64n24k16.f32.bf16.bf16 {%0,%1,%2,%3,%4,%5,%6,%7,%8,%9,%10,%11}, {%12,%13,%14,%15}, %16, p, 1, 1, 1;}"
                 : R8(d, 0), R4(d, 8) : "r"(a[0]), "r"(a[1]), "r"(a[2]), "r"(a[3]), "l"(db));
}
__device__ __forceinline__ void mma_ss64(float (&d)[32], uint64_t da, uint64_t db) {
    asm volatile("{.reg .pred p; setp.eq.b32 p, 0, 0; wgmma.mma_async.sync.aligned.m64n64k16.f32.bf16.bf16 " D32 ", %32, %33, p, 1, 1, 0, 1;}"
                 : R32(d) : "l"(da), "l"(db));
}
__device__ __forceinline__ void mma_ss8(float (&d)[4], uint64_t da, uint64_t db) {
    asm volatile("{.reg .pred p; setp.eq.b32 p, 0, 0; wgmma.mma_async.sync.aligned.m64n8k16.f32.bf16.bf16 {%0,%1,%2,%3}, %4, %5, p, 1, 1, 0, 1;}"
                 : R4(d, 0) : "l"(da), "l"(db));
}
__device__ __forceinline__ void mma_rs(float (&d)[32], const uint4& a, uint64_t db) {
    asm volatile("{.reg .pred p; setp.eq.b32 p, 0, 0; wgmma.mma_async.sync.aligned.m64n64k16.f32.bf16.bf16 " D32 ", {%32,%33,%34,%35}, %36, p, 1, 1, 1;}"
                 : R32(d) : "r"(a.x), "r"(a.y), "r"(a.z), "r"(a.w), "l"(db));
}
__device__ __forceinline__ void mma_rs(float (&d)[44], const uint4& a, uint64_t db) {
    asm volatile("{.reg .pred p; setp.eq.b32 p, 0, 0; wgmma.mma_async.sync.aligned.m64n88k16.f32.bf16.bf16 " D44 ", {%44,%45,%46,%47}, %48, p, 1, 1, 1;}"
                 : R32(d), R8(d, 32), R4(d, 40) : "r"(a.x), "r"(a.y), "r"(a.z), "r"(a.w), "l"(db));
}

constexpr float EXP_MAGIC = 256.0f + 127.0f + 64.0f - 1.58621f + 0.00390625f;
constexpr uint32_t MUFU_MASK = 0x1111u;
__device__ __forceinline__ uint32_t exp2_pair(float y0, float y1, uint32_t cexp, uint32_t neg1) {
    uint32_t w, m, e, r;
    asm("prmt.b32 %0, %1, %2, 0x6521;" : "=r"(w) : "r"(__float_as_uint(y0)), "r"(__float_as_uint(y1)));
    asm("lop3.b32 %0, %1, 0x007F007F, %2, 0xEA;" : "=r"(m) : "r"(w), "r"(cexp));
    asm("mad.lo.u32 %0, %1, %2, %3;" : "=r"(e) : "r"(m), "r"(neg1), "r"(w));
    asm("fma.rn.bf16x2 %0, %1, %2, %3;" : "=r"(r) : "r"(w), "r"(m), "r"(e));
    return r;
}

struct Params {
    CUtensorMap wq, wo, w1, w2;
    const __nv_bfloat16* x;
    const __nv_bfloat16* wk;
    const __nv_bfloat16* wv;
    const __nv_bfloat16* w1p;
    const __nv_bfloat16* w2p;
    const __nv_bfloat16* wop;
    __nv_bfloat16* out;
    uint32_t neg1;
};

__device__ __forceinline__ void load_wo(uint32_t sb, const Params& P, int kb) {
    const uint32_t bar = sb + SM_MISC + (MB_WO + kb) * 8;
    mbar_expect(bar, 8192); tma2d(sb + wo_slot(kb) * 8192, &P.wo, (blockIdx.x & 7) * 64, kb * 64, bar);
}
__device__ __forceinline__ void load_w2(uint32_t sb, const Params& P, int kb) {
    const uint32_t bar = sb + SM_MISC + (MB_W2 + kb) * 8;
    mbar_expect(bar, 8192); tma2d(sb + w2_slot(kb) * 8192, &P.w2, (blockIdx.x & 7) * 64, kb * 64, bar);
}
__device__ __forceinline__ void load_w1(uint32_t sb, const Params& P, int box) {
    const int gi = box / 3, a = box - 3 * gi;
    const uint32_t bar = sb + SM_MISC + (MB_W1 + gi) * 8;
    mbar_expect(bar, 8192); tma2d(sb + SM_W1 + box * 8192, &P.w1, (blockIdx.x & 15) * 88 + a * 32, gi * 128, bar);
}

__device__ __forceinline__ void load_batch(uint4 (&buf)[4], const uint4* a) {
#pragma unroll
    for (int s = 0; s < 4; s++) buf[s] = ldg_relaxed(a + s * 128);
}
__device__ __forceinline__ bool batch_bad(const uint4 (&buf)[4]) {
    const uint32_t m = max(max(max(buf[0].x, buf[0].w), max(buf[1].x, buf[1].w)), max(max(buf[2].x, buf[2].w), max(buf[3].x, buf[3].w)));
    return __any_sync(0xffffffffu, m == SENT);
}
__device__ __forceinline__ void check_batch(uint4 (&buf)[4], const uint4* a) {
    int spins = 0;
    while (batch_bad(buf) && ++spins < SPIN_LIMIT) load_batch(buf, a);
}
template <int RING>
__device__ __forceinline__ void fill_ring(uint4 (&buf)[RING][4], const uint4* a, int astr) {
#pragma unroll
    for (int i = 0; i < RING; i++) load_batch(buf[i], a + i * astr);
    if (batch_bad(buf[0])) {
        load_batch(buf[0], a);
        check_batch(buf[0], a);
#pragma unroll
        for (int i = 1; i < RING; i++) load_batch(buf[i], a + i * astr);
    }
}

__device__ __forceinline__ void pair_reduce(const float (&acc)[32], float (&r)[16], uint32_t buf, int q, int barid) {
    if (q) {
#pragma unroll
        for (int j = 0; j < 4; j++) sts128(buf + j * 2048, __float_as_uint(acc[4 * j]), __float_as_uint(acc[4 * j + 1]), __float_as_uint(acc[4 * j + 2]), __float_as_uint(acc[4 * j + 3]));
        bar_sync(barid, 256);
        bar_sync(barid, 256);
#pragma unroll
        for (int j = 0; j < 4; j++) {
            float4 v = lds128f(buf + j * 2048);
            r[4 * j] = acc[16 + 4 * j] + v.x; r[4 * j + 1] = acc[17 + 4 * j] + v.y; r[4 * j + 2] = acc[18 + 4 * j] + v.z; r[4 * j + 3] = acc[19 + 4 * j] + v.w;
        }
    } else {
        bar_sync(barid, 256);
        float4 v[4];
#pragma unroll
        for (int j = 0; j < 4; j++) v[j] = lds128f(buf + j * 2048);
#pragma unroll
        for (int j = 0; j < 4; j++) sts128(buf + j * 2048, __float_as_uint(acc[16 + 4 * j]), __float_as_uint(acc[17 + 4 * j]), __float_as_uint(acc[18 + 4 * j]), __float_as_uint(acc[19 + 4 * j]));
        bar_arrive(barid, 256);
#pragma unroll
        for (int j = 0; j < 4; j++) {
            r[4 * j] = acc[4 * j] + v[j].x; r[4 * j + 1] = acc[4 * j + 1] + v[j].y; r[4 * j + 2] = acc[4 * j + 2] + v[j].z; r[4 * j + 3] = acc[4 * j + 3] + v[j].w;
        }
    }
}

__device__ __forceinline__ float quad_sum(float v) { v += __shfl_xor_sync(0xffffffffu, v, 1); v += __shfl_xor_sync(0xffffffffu, v, 2); return v; }
__device__ __forceinline__ float silu2(float h) { float t; asm("tanh.approx.f32 %0, %1;" : "=f"(t) : "f"(h)); return fmaf(h, t, h); }

#define TS_ARG
#define TS_PASS

__device__ __forceinline__ void attn_hook(const Params& P, uint32_t sb, int warp, int U, unsigned& cnt2) {
    const uint32_t mb = sb + SM_MISC;
    const int lane = threadIdx.x & 31, b = blockIdx.x, t128 = threadIdx.x & 127;
    const int wg = warp >> 2, ww = warp & 3, job = 3 - wg + 4 * ww;
    if (U < 3) {
        const int pr = 1 - (wg >> 1), q = wg & 1;
        const int mt = 16 * pr + (b >> 3), mt1 = 16 * pr + (b >> 4) * 2 + q, sl = b & 15;
        uint4* hb = g_Hf + (mt1 * 88 + (sl >> 1) * 11) * 128 + t128;
        if (U == 0) {
            hb += (sl & 1) * 6 * 128;
            stg128(hb, SENT, SENT, SENT, SENT); stg128(hb + 128, SENT, SENT, SENT, SENT); stg128(hb + 256, SENT, SENT, SENT, SENT);
            if (lane == 0 && job < 6) { if (job < 5) load_wo(sb, P, job); else load_w2(sb, P, 0); }
        } else if (U == 1) {
            stg128(hb + ((sl & 1) * 6 + 3) * 128, SENT, SENT, SENT, SENT); stg128(hb + ((sl & 1) * 6 + 4) * 128, SENT, SENT, SENT, SENT);
            stg64(reinterpret_cast<uint2*>(hb + 5 * 128) + (sl & 1), SENT, SENT);
            if ((lane & 3) < 2) stg64(g_stats + (mt * 64 + ww * 16 + (lane >> 2) + 8 * (lane & 3)) * 16 + (b & 7) * 2 + q, SENT, SENT);
        } else {
            uint4* hp = g_hf + (mt * 32 + (b & 7) * 4 + 2 * q) * 128 + t128;
            stg128(hp, SENT, SENT, SENT, SENT); stg128(hp + 128, SENT, SENT, SENT, SENT);
            stg128(g_of + ((16 + (b >> 3)) * 32 + (b & 3) * 8 + 2 * wg + (ww >> 1)) * 128 + (((b >> 2) & 1) * 2 + (ww & 1)) * 32 + lane, SENT, SENT, SENT, SENT);
        }
    } else if (U == 3 || !(U & 1)) {
        warp_done(mb + (MB_DONE + ((U - 2) >> 1)) * 8);
        if (U == 4 && warp == 15) {
            mbar_wait(mb + MB_DONE * 8);
            if (lane == 0) asm volatile("red.release.gpu.global.add.u32 [%0], 1;" :: "l"(&g_count2) : "memory");
        }
        if (U == 8 && warp == 11) asm volatile("ld.relaxed.gpu.global.u32 %0, [%1];" : "=r"(cnt2) : "l"(&g_count2) : "memory");
    } else {
        if (job < 6) {
            mbar_wait(mb + (MB_DONE + ((U - 3) >> 1)) * 8);
            if (lane == 0) {
                if (U == 5) { if (job < 3) load_wo(sb, P, 5 + job); else if (job < 5) load_w2(sb, P, job - 2); }
                else if (U == 7) { if (job < 5) load_w1(sb, P, job); }
                else if (job < 5) load_w1(sb, P, 5 + job);
            }
        }
        if (U == 9 && warp == 11) {
            const unsigned target = lds32(mb + MISC_EPOCH) * NCTA;
            if (__any_sync(0xffffffffu, cnt2 != target)) wait_count(&g_count2, target);
            asm volatile("fence.acquire.gpu;" ::: "memory");
            warp_done(mb + MB_F2 * 8);
        }
    }
    __syncwarp();
}

template <bool SAFE>
__device__ __forceinline__ void attention(const Params& P, uint32_t sb, int warp TS_ARG) {
    const uint32_t mb = sb + SM_MISC;
    const int tid = threadIdx.x, lane = tid & 31, b = blockIdx.x, tg = b >> 2, hg = b & 3;
    const int wg = warp >> 2, ww = warp & 3;
    const uint32_t cexp = 0x9F809F80u + (tid >> 12);
    const uint32_t neg1 = P.neg1;
    unsigned cnt2 = 0;
#pragma unroll 1
    for (int pass = 0; pass < 2; pass++) {
        float o[12], s[32];
        const uint64_t dq = mkdesc(sb + SM_Q + (pass * 4 + wg) * 2048, 128, 256, 0);
        uint64_t dk = mkdesc(sb, 128, 256, 0);
        uint64_t dv = mkdesc(sb + 16384, 128, 8192, 0);
        float m0 = -INFINITY, m1 = -INFINITY;
#pragma unroll
        for (int i = 0; i < 12; i++) o[i] = 0.f;
#pragma unroll
        for (int i = 0; i < 32; i++) s[i] = ((MUFU_MASK >> (i / 2)) & 1) ? 0.f : EXP_MAGIC;
        fence_regs(s); fence_regs(o);
        wg_fence();
        if (SAFE) mma_qk_f16(s, dq, mkdesc(mb + MISC_K0, 128, 256, 0)); else mma_qk_bf16(s, dq, mkdesc(mb + MISC_K0, 128, 256, 0));
        wg_commit();
        wg_wait<0>(); fence_regs(s);
#pragma unroll 1
        for (int u = 4 * pass; u < 4 + 7 * pass; u++) {
            if (SAFE && u >= 1 && u < 4) mbar_wait(mb + (MB_KV + u) * 8);
#pragma unroll 1
            for (int i = (u > 4) ? 4 : 0; i < 8; i++) {
                uint32_t p[16];
                if (SAFE) {
#pragma unroll
                    for (int j = 0; j < 16; j++) {
                        if ((MUFU_MASK >> j) & 1) p[j] = pack_bf16(ex2(s[2 * j]), ex2(s[2 * j + 1]));
                        else p[j] = exp2_pair(s[2 * j], s[2 * j + 1], cexp, neg1);
                    }
                } else {
                    fence_regs(o);
                    float x0 = m0, x1 = m1;
#pragma unroll
                    for (int j = 0; j < 8; j++) { x0 = fmaxf(x0, fmaxf(s[4 * j], s[4 * j + 1])); x1 = fmaxf(x1, fmaxf(s[4 * j + 2], s[4 * j + 3])); }
                    x0 = fmaxf(x0, __shfl_xor_sync(0xffffffffu, x0, 1)); x0 = fmaxf(x0, __shfl_xor_sync(0xffffffffu, x0, 2));
                    x1 = fmaxf(x1, __shfl_xor_sync(0xffffffffu, x1, 1)); x1 = fmaxf(x1, __shfl_xor_sync(0xffffffffu, x1, 2));
                    const float c0 = ex2(m0 - x0), c1 = ex2(m1 - x1);
                    m0 = x0; m1 = x1;
#pragma unroll
                    for (int j = 0; j < 3; j++) { o[4 * j] *= c0; o[4 * j + 1] *= c0; o[4 * j + 2] *= c1; o[4 * j + 3] *= c1; }
#pragma unroll
                    for (int j = 0; j < 8; j++) {
                        p[2 * j] = pack_bf16(ex2(s[4 * j] - m0), ex2(s[4 * j + 1] - m0));
                        p[2 * j + 1] = pack_bf16(ex2(s[4 * j + 2] - m1), ex2(s[4 * j + 3] - m1));
                    }
                    fence_regs(o);
                }
                fence_regs(p);
                wg_fence();
                if (SAFE) mma_qk_f16(s, dq, dk); else mma_qk_bf16(s, dq, dk);
#pragma unroll
                for (int j = 0; j < 4; j++) mma_pv(o, p + 4 * j, dv + j * 16);
                wg_commit();
                dk += 128; dv += 64;
                wg_wait<0>(); fence_regs(s);
            }
            if (u < 4 || !(u & 1)) { dk += (KVCH - 16384) / 16; dv += (KVCH - 8192) / 16; }
            if (u == 3 || u == 10) {
                fence_regs(o);
                const float i0 = 1.0f / o[8], i1 = 1.0f / o[10];
                stg128(g_of + ((16 * pass + (tg >> 1)) * 32 + hg * 8 + 2 * wg + (ww >> 1)) * 128 + ((tg & 1) * 2 + (ww & 1)) * 32 + lane,
                       pack_bf16(o[0] * i0, o[1] * i0), pack_bf16(o[2] * i1, o[3] * i1), pack_bf16(o[4] * i0, o[5] * i0), pack_bf16(o[6] * i1, o[7] * i1));
            }
            attn_hook(P, sb, warp, u, cnt2);
        }
        TS(5 + pass);
    }
}

__device__ __noinline__ void helper_cta(const Params& P, uint8_t* smem) {
    const int tid = threadIdx.x, b = blockIdx.x, hi = b - NMAIN;
    const unsigned epoch = g_epoch[b] + 1;
    float* red = reinterpret_cast<float*>(smem);
    if (tid < 32) wait_count(&g_count1, epoch * NMAIN);
    __syncthreads();
    if (tid == 480) {
        for (int i = 0; i < 8; i++) asm volatile("cp.async.bulk.prefetch.L2.global [%0], %1;" :: "l"((const char*)P.wop + hi * 131072 + i * 16384), "r"(16384) : "memory");
        for (int i = 0; i < 43; i++) asm volatile("cp.async.bulk.prefetch.L2.global [%0], %1;" :: "l"((const char*)P.w2p + hi * 352256 + i * 8192), "r"(8192) : "memory");
    }
    if (tid < 344) {
        const int cg = tid % 43, rp = tid / 43;
        const uint4* src = reinterpret_cast<const uint4*>(P.w1p + (size_t)rp * 64 * FF + (hi * 43 + cg) * 8);
        float s[8] = {0, 0, 0, 0, 0, 0, 0, 0};
#pragma unroll 8
        for (int r = 0; r < 64; r++) {
            uint4 v = __ldg(src + r * (FF / 8));
            s[0] += bf_lo(v.x); s[1] += bf_hi(v.x); s[2] += bf_lo(v.y); s[3] += bf_hi(v.y);
            s[4] += bf_lo(v.z); s[5] += bf_hi(v.z); s[6] += bf_lo(v.w); s[7] += bf_hi(v.w);
        }
        float* part = red + (rp * 43 + cg) * 8;
#pragma unroll
        for (int i = 0; i < 8; i++) part[i] = s[i];
    }
    __syncthreads();
    if (tid < 344) {
        float s = 0.f;
#pragma unroll
        for (int rp = 0; rp < 8; rp++) s += red[rp * 344 + tid];
        g_cs[hi * 344 + tid] = s;
    } else if (hi == 3 && tid < 344 + 32) g_cs[FF + tid - 344] = 0.f;
    __syncthreads();
    if (tid == 0) {
        asm volatile("red.release.gpu.global.add.u32 [%0], 1;" :: "l"(&g_count2) : "memory");
        g_epoch[b] = epoch;
    }
}

__global__ void __launch_bounds__(512, 1) fused_kernel(const __grid_constant__ Params P) {
    extern __shared__ __align__(1024) uint8_t smem[];
    const uint32_t sb = (uint32_t)__cvta_generic_to_shared(smem);
    const uint32_t mb = sb + SM_MISC;
    const int tid = threadIdx.x, lane = tid & 31, b = blockIdx.x;
    if (b >= NMAIN) { helper_cta(P, smem); return; }
    const int tg = b >> 2, hg = b & 3;

    const int warp = __shfl_sync(0xffffffffu, tid >> 5, 0);
    const int wg = warp >> 2, ww = warp & 3, g = lane >> 2, t4 = lane & 3, t128 = tid & 127;
    if (lane == 0) {
#pragma unroll
        for (int i = 0; i < 4; i++) {
            const uint32_t id = warp + 16 * i;
            if (id < NBAR) mbar_init(mb + id * 8, id >= MB_DONE ? 16 : (id >= MB_W1 && id < MB_F2) ? 3 : 1);
        }
        fence_async_smem();
    }
    __syncwarp();
    uint4 xv[4][2];
    unsigned epoch = 0;
    {
        const int r = warp * 4;
        const uint4* src = reinterpret_cast<const uint4*>(P.x + (size_t)((r & 31) + tg * 32 + (r >> 5) * 1024) * D) + lane;
#pragma unroll
        for (int i = 0; i < 4; i++) { xv[i][0] = ldg_relaxed(src + i * 64); xv[i][1] = ldg_relaxed(src + i * 64 + 32); }
        const uint4 wkv = ldg_relaxed(reinterpret_cast<const uint4*>(hg < 2 ? P.wk : P.wv) + tid * 2 + (hg & 1));
        if (lane == 0) {
            if (warp < 4) {
                const uint32_t bar = mb + (MB_WQ + warp) * 8;
                mbar_expect(bar, 32768);
                tma2d(sb + SM_WQ + warp * 16384, &P.wq, hg * 128, warp * 128, bar);
                tma2d(sb + SM_WQ + 65536 + warp * 16384, &P.wq, hg * 128 + 64, warp * 128, bar);
            } else if (warp < 7) {
                asm volatile("prefetch.tensormap [%0];" :: "l"(&P.wo + (warp - 4)) : "memory");
            } else if (warp == 7) {
                asm volatile("ld.relaxed.gpu.global.u32 %0, [%1];" : "=r"(epoch) : "l"(g_epoch + b) : "memory");
            }
        }
        if (warp == 8 && lane < 8) sts32(mb + MISC_CNT + lane * 4, 0);
        __syncwarp();
        sts128(sb + SM_WKV + tid * 16, wkv.x, wkv.y, wkv.z, wkv.w);
    }
    float dlt[4];
    {
        float st[4];
#pragma unroll
        for (int i = 0; i < 4; i++) {
            const uint32_t s = add_bf16x2(add_bf16x2(add_bf16x2(xv[i][0].x, xv[i][0].y), add_bf16x2(xv[i][0].z, xv[i][0].w)),
                                          add_bf16x2(add_bf16x2(xv[i][1].x, xv[i][1].y), add_bf16x2(xv[i][1].z, xv[i][1].w)));
            st[i] = bf_lo(s) + bf_hi(s);
        }
        TS(13);
#pragma unroll
        for (int o = 16; o > 0; o >>= 1)
#pragma unroll
            for (int i = 0; i < 4; i++) st[i] += __shfl_xor_sync(0xffffffffu, st[i], o);
#pragma unroll
        for (int i = 0; i < 4; i++) {
            const float nmean = st[i] * (-1.0f / D);
            const uint32_t nm = pack_bf16(nmean, nmean);
            dlt[i] = bf_lo(nm) - nmean;
            const int r = warp * 4 + i;
#pragma unroll
            for (int c = 0; c < 2; c++) {
                xv[i][c].x = add_bf16x2(xv[i][c].x, nm); xv[i][c].y = add_bf16x2(xv[i][c].y, nm);
                xv[i][c].z = add_bf16x2(xv[i][c].z, nm); xv[i][c].w = add_bf16x2(xv[i][c].w, nm);
                sts128(sb + SM_XN + ((lane >> 3) + 4 * c) * 8192 + r * 128 + (((lane & 7) ^ (r & 7)) << 4), xv[i][c].x, xv[i][c].y, xv[i][c].z, xv[i][c].w);
            }
        }
    }
    fence_async_smem();
    if (tid == 7 * 32) { sts32(mb + MISC_EPOCH, epoch + 1); g_epoch[b] = epoch + 1; }
    TS(0);
    __syncthreads();
    auto variances = [&]()
    {
        float st[4];
#pragma unroll
        for (int i = 0; i < 4; i++) {
            float v0 = 0.f, v1 = 0.f;
#pragma unroll
            for (int c = 0; c < 2; c++) {
                const uint32_t w[4] = {xv[i][c].x, xv[i][c].y, xv[i][c].z, xv[i][c].w};
#pragma unroll
                for (int k = 0; k < 4; k++) { v0 = fmaf(bf_lo(w[k]), bf_lo(w[k]), v0); v1 = fmaf(bf_hi(w[k]), bf_hi(w[k]), v1); }
            }
            st[i] = v0 + v1;
        }
#pragma unroll
        for (int o = 16; o > 0; o >>= 1)
#pragma unroll
            for (int i = 0; i < 4; i++) st[i] += __shfl_xor_sync(0xffffffffu, st[i], o);
        const float vs = lane == 0 ? st[0] : lane == 1 ? st[1] : lane == 2 ? st[2] : st[3];
        const float dl = lane == 0 ? dlt[0] : lane == 1 ? dlt[1] : lane == 2 ? dlt[2] : dlt[3];
        if (lane < 4) sts32(mb + MISC_RSTD + (warp * 4 + lane) * 4, __float_as_uint(rsqrtf(fmaxf(vs * (1.0f / D) - dl * dl, 0.f) + 1e-5f)));
    };
    float kv[4] = {0.f, 0.f, 0.f, 0.f};
    if (wg == 2) {
        fence_regs(kv);
        const uint64_t da = mkdesc(sb + SM_XN, 16, 1024, 1), db = mkdesc(sb + SM_WKV, 128, 16, 0);
        wg_fence();
#pragma unroll
        for (int s = 0; s < 32; s++) mma_ss8(kv, da + (s >> 2) * 512 + (s & 3) * 2, db + s * 16);
        wg_commit();
        variances();
        wg_wait<0>(); fence_regs(kv);
    } else {
        variances();
    }
    __syncthreads();
    const float rs0 = __uint_as_float(lds32(mb + MISC_RSTD + (ww * 16 + g) * 4)), rs1 = __uint_as_float(lds32(mb + MISC_RSTD + (ww * 16 + g + 8) * 4));
    constexpr float QSCALE = 0.25f * 1.4426950408889634f;
    uint32_t kvoff[2];
#pragma unroll
    for (int i = 0; i < 2; i++) {
        const int t = ((ww & 1) * 16 + g + 8 * i), c = 2 * tg + (ww >> 1), ts = (t + 31) & 31;
        kvoff[i] = hg < 2 ? (ts >> 3) * 32768 + (ts & 7) * 2048 + (c >> 3) * 256 + (hg & 1) * 128 + (c & 7) * 16 + t4 * 4
                          : (t >> 3) * 32768 + 16384 + (hg & 1) * 8192 + ((t & 7) * 64 + c) * 16 + t4 * 4;
    }
    float qa[32];
    if (wg < 2) {
#pragma unroll
        for (int i = 0; i < 32; i++) qa[i] = 0.f;
        fence_regs(qa);
        const uint64_t da = mkdesc(sb + SM_XN, 16, 1024, 1), db = mkdesc(sb + SM_WQ + wg * 65536, 16, 1024, 1);
#pragma unroll 1
        for (int i = 0; i < 4; i++) {
            mbar_wait(mb + (MB_WQ + i) * 8);
            wg_fence();
#pragma unroll
            for (int s = 0; s < 8; s++) mma_ss64(qa, da + (i * 2 + (s >> 2)) * 512 + (s & 3) * 2, db + (i * 8 + s) * 128);
            wg_commit();
        }
        wg_wait<0>();
        fence_regs(qa);
        bar_arrive(6, 512);
        TS(1);
        float nn[8];
#pragma unroll
        for (int i = 0; i < 32; i++) qa[i] *= ((i & 2) ? rs1 : rs0) * QSCALE;
#pragma unroll
        for (int h = 0; h < 4; h++) {
            const uint32_t base = sb + SM_Q + ((ww >> 1) * 4 + wg * 2 + (h >> 1)) * 2048 + ((h & 1) * 4 + (ww & 1) * 2) * 256 + lane * 4;
            sts32(base, pack_f16(qa[8 * h], qa[8 * h + 1])); sts32(base + 256, pack_f16(qa[8 * h + 2], qa[8 * h + 3]));
            sts32(base + 128, pack_f16(qa[8 * h + 4], qa[8 * h + 5])); sts32(base + 384, pack_f16(qa[8 * h + 6], qa[8 * h + 7]));
            nn[2 * h] = qa[8 * h] * qa[8 * h] + qa[8 * h + 1] * qa[8 * h + 1] + qa[8 * h + 4] * qa[8 * h + 4] + qa[8 * h + 5] * qa[8 * h + 5];
            nn[2 * h + 1] = qa[8 * h + 2] * qa[8 * h + 2] + qa[8 * h + 3] * qa[8 * h + 3] + qa[8 * h + 6] * qa[8 * h + 6] + qa[8 * h + 7] * qa[8 * h + 7];
        }
#pragma unroll
        for (int o = 1; o < 4; o <<= 1)
#pragma unroll
            for (int i = 0; i < 8; i++) nn[i] += __shfl_xor_sync(0xffffffffu, nn[i], o);
        uint32_t nm = 0;
#pragma unroll
        for (int i = 0; i < 8; i++) nm = max(nm, __float_as_uint(nn[i]));
        nm = __reduce_max_sync(0xffffffffu, nm);
        if (lane == 0) asm volatile("red.shared.max.u32 [%0], %1;" :: "r"(mb + MISC_NRM), "r"(nm) : "memory");
    } else {
        if (wg == 2) {
            kv[0] *= rs0; kv[1] *= rs0; kv[2] *= rs1; kv[3] *= rs1;
            char* img = reinterpret_cast<char*>(g_kv);
            if (hg < 2) {
                const int r0 = ww * 16 + g;
                float2* kt = reinterpret_cast<float2*>(smem + SM_MISC + MISC_K0);
                kt[r0 * 4 + t4] = make_float2(kv[0], kv[1]);
                kt[(r0 + 8) * 4 + t4] = make_float2(kv[2], kv[3]);
                bar_sync(2, 128);
                float2 p0 = make_float2(0.f, 0.f);
                if (r0 & 31) p0 = kt[(r0 - 1) * 4 + t4];
                const float2 p1 = kt[(r0 + 7) * 4 + t4];
                stg32(img + kvoff[0], nonzero(pack_f16(kv[0] - p0.x, kv[1] - p0.y)));
                stg32(img + kvoff[1], nonzero(pack_f16(kv[2] - p1.x, kv[3] - p1.y)));
            } else {
                stg32(img + kvoff[0], nonzero(pack_bf16(kv[0], kv[1])));
                stg32(img + kvoff[1], nonzero(pack_bf16(kv[2], kv[3])));
            }
            uint32_t nm = max(__float_as_uint(quad_sum(kv[0] * kv[0] + kv[1] * kv[1])), __float_as_uint(quad_sum(kv[2] * kv[2] + kv[3] * kv[3])));
            nm = __reduce_max_sync(0xffffffffu, nm);
            if (lane == 0) stg32(reinterpret_cast<uint32_t*>(g_nrm + b) + ww, nm | 1u);
            if (hg < 2) {
#pragma unroll
                for (int i = 0; i < 2; i++)
                    stg32(reinterpret_cast<char*>(g_kplain) + (kvoff[i] >> 15) * 16384 + (kvoff[i] & 16383), pack_bf16(kv[2 * i], kv[2 * i + 1]));
            }
            TS(1);
            bar_sync(2, 128);
            if (t128 == 0) asm volatile("red.release.gpu.global.add.u32 [%0], 1;" :: "l"(&g_count1) : "memory");
            __syncwarp();
        } else {
            uint4 v; int spins = 0;
            do { v = ldg_relaxed(g_nrm + t128); } while (__any_sync(0xffffffffu, has_zero(v)) && ++spins < SPIN_LIMIT);
            uint32_t nm = max(max(v.x, v.y), max(v.z, v.w));
            nm = max(nm, __shfl_xor_sync(0xffffffffu, nm, 4)); nm = max(nm, __shfl_xor_sync(0xffffffffu, nm, 8)); nm = max(nm, __shfl_xor_sync(0xffffffffu, nm, 16));
            if (lane < 4) asm volatile("red.shared.max.u32 [%0], %1;" :: "r"(mb + MISC_NRM + 4 + min(lane, 2) * 4), "r"(nm) : "memory");
            TS(1);
        }
        bar_sync(5, 256);
        const int t256 = tid - 256;
        uint4 kc[9]; int spins = 0; bool bad;
        do {
            bad = false;
#pragma unroll
            for (int i = 0; i < 8; i++) kc[i] = ldg_relaxed(g_kv + i * 256 + t256);
            kc[8] = ldg_relaxed(g_kv + 3 * 2048 + 7 * 128 + t128);
#pragma unroll
            for (int i = 0; i < 9; i++) bad |= has_zero(kc[i]);
        } while (__any_sync(0xffffffffu, bad) && ++spins < SPIN_LIMIT);
        TS(2);
        if (warp == 15) wait_count(&g_count1, lds32(mb + MISC_EPOCH) * NMAIN);
        bar_sync(6, 512);
        if (tid == 15 * 32) {
            asm volatile("fence.proxy.async.global;" ::: "memory");
#pragma unroll
            for (int c = 1; c < 4; c++) { mbar_expect(mb + (MB_KV + c) * 8, 32768); bulk_g2s(sb + c * KVCH, g_kv + c * 2048, 32768, mb + (MB_KV + c) * 8); }
        }
        __syncwarp();
#pragma unroll
        for (int i = 0; i < 8; i++) sts128(sb + (i * 256 + t256) * 16, kc[i].x, kc[i].y, kc[i].z, kc[i].w);
        if (wg == 3) sts128(mb + MISC_K0 + t128 * 16, kc[8].x, kc[8].y, kc[8].z, kc[8].w);
#pragma unroll
        for (int i = 0; i < 8; i++) sts128(sb + (i >> 1) * KVCH + 32768 + (i & 1) * 4096 + t256 * 16, 0x3F803F80u, 0x3F803F80u, 0x3F803F80u, 0x3F803F80u);
    }
    fence_async_smem();
    TS(3);
    __syncthreads();
    const float q2 = __uint_as_float(lds32(mb + MISC_NRM)), v2 = __uint_as_float(lds32(mb + MISC_NRM + 12));
    const float k2 = __uint_as_float(lds32(mb + MISC_NRM + 4)) + __uint_as_float(lds32(mb + MISC_NRM + 8));
    const bool safe = __all_sync(0xffffffffu, (q2 * k2 <= 3500.0f) && (q2 <= 65536.0f) && (k2 <= 65536.0f) && (v2 <= 1e24f));
    TS(4);

    if (__builtin_expect(safe, 1)) {
        attention<true>(P, sb, warp TS_PASS);
    } else {
        if (wg < 2) {
#pragma unroll
            for (int h = 0; h < 4; h++) {
                const uint32_t base = sb + SM_Q + ((ww >> 1) * 4 + wg * 2 + (h >> 1)) * 2048 + ((h & 1) * 4 + (ww & 1) * 2) * 256 + lane * 4;
                sts32(base, pack_bf16(qa[8 * h], qa[8 * h + 1])); sts32(base + 256, pack_bf16(qa[8 * h + 2], qa[8 * h + 3]));
                sts32(base + 128, pack_bf16(qa[8 * h + 4], qa[8 * h + 5])); sts32(base + 384, pack_bf16(qa[8 * h + 6], qa[8 * h + 7]));
            }
            fence_async_smem();
        } else if (warp == 15) {
            for (int c = 1; c < 4; c++) mbar_wait(mb + (MB_KV + c) * 8);
            if (lane == 0) {
                asm volatile("fence.proxy.async;" ::: "memory");
                mbar_expect(mb + MB_KV * 8, 4 * 16384 + 2048);
                for (int c = 0; c < 4; c++) bulk_g2s(sb + c * KVCH, g_kplain + c * 1024, 16384, mb + MB_KV * 8);
                bulk_g2s(mb + MISC_K0, g_kplain + 3 * 1024 + 7 * 128, 2048, mb + MB_KV * 8);
            }
            __syncwarp();
        }
        __syncthreads();
        mbar_wait(mb + MB_KV * 8);
        attention<false>(P, sb, warp TS_PASS);
    }

    const int pr = 1 - (wg >> 1), q = wg & 1;
    const int mt = 16 * pr + (b >> 3), j = b & 7;
    const int row0 = mt * 64 + ww * 16 + g;
    uint32_t hk[8];
    {
        const uint32_t* xp = reinterpret_cast<const uint32_t*>(P.x + (size_t)row0 * D + j * 64 + q * 32 + t4 * 2);
#pragma unroll
        for (int i = 0; i < 4; i++) { hk[2 * i] = __ldg(xp + i * 4); hk[2 * i + 1] = __ldg(xp + i * 4 + 8 * (D / 2)); }
    }
    mbar_wait(mb + MB_F2 * 8);
    if (warp < 5) {
        mbar_wait(mb + (MB_DONE + 4) * 8);
        if (lane == 0) { if (warp < 2) load_w1(sb, P, 10 + warp); else load_w2(sb, P, 1 + warp); }
    } else if (warp == 5) {
        if (lane < 22) {
            const uint4 v = ldg_relaxed(reinterpret_cast<const uint4*>(g_cs + (b & 15) * 88) + lane);
            sts128(mb + MISC_CS + lane * 16, v.x, v.y, v.z, v.w);
        }
        warp_done(mb + MB_CS * 8);
    }
    __syncwarp();
#pragma unroll 1
    for (int ph = 0; ph < 2; ph++) {
        float r[16];
        {
            const uint4* a = (ph ? g_Hf + mt * 88 * 128 : g_of + mt * 32 * 128) + q * 512 + t128;
            const int nblk = ph ? 11 : 4;
            uint64_t slots = ph ? (q ? pack_slots(true, 1) : pack_slots(true, 0)) : (q ? pack_slots(false, 1) : pack_slots(false, 0));
            uint32_t bar = mb + ((ph ? MB_W2 : MB_WO) + q) * 8;
            float acc[32];
            uint4 buf[4][4];
            fill_ring<4>(buf, a, 1024);
#pragma unroll
            for (int i = 0; i < 32; i++) acc[i] = 0.f;
            fence_regs(acc);
#pragma unroll 1
            for (int i0 = 0; i0 < nblk; i0 += 4) {
#pragma unroll
                for (int i = 0; i < 4; i++) {
                    const int blk = i0 + i;
                    if (blk < nblk) {
                        const uint64_t db = mkdesc(sb + ((uint32_t)slots & 31) * 8192, 16, 1024, 1);
                        mbar_wait(bar);
                        check_batch(buf[i], a + blk * 1024);
                        wg_fence();
#pragma unroll
                        for (int s = 0; s < 4; s++) mma_rs(acc, buf[i][s], db + s * 128);
                        wg_commit();
                        slots >>= 5; bar += 16;
                        wg_wait<1>();
                        if (blk >= 1 && blk + 3 < nblk) load_batch(buf[(i + 3) & 3], a + (blk + 3) * 1024);
                    }
                }
            }
            wg_wait<0>();
            fence_regs(acc);
            TS(7 + 4 * ph);
            if (ph == 0) {
                warp_done(mb + (MB_DONE + 5) * 8);
                mbar_wait(mb + (MB_DONE + 4 * pr) * 8);
            }
            pair_reduce(acc, r, sb + SM_Q + pr * 8192 + t128 * 16, q, 3 + pr);
        }
#pragma unroll
        for (int i = 0; i < 8; i++) hk[i] = pack_bf16(r[2 * i] + bf_lo(hk[i]), r[2 * i + 1] + bf_hi(hk[i]));
        if (ph == 1) break;
        {
            uint4* hp = g_hf + (mt * 32 + j * 4 + 2 * q) * 128 + t128;
            stg128(hp, hk[0], hk[1], hk[2], hk[3]);
            stg128(hp + 128, hk[4], hk[5], hk[6], hk[7]);
            float s0 = 0.f, s1 = 0.f;
#pragma unroll
            for (int i = 0; i < 8; i++) {
                r[2 * i] = bf_lo(hk[i]); r[2 * i + 1] = bf_hi(hk[i]);
                if (i & 1) s1 += r[2 * i] + r[2 * i + 1]; else s0 += r[2 * i] + r[2 * i + 1];
            }
            s0 += __shfl_xor_sync(0xffffffffu, s0, 1); s1 += __shfl_xor_sync(0xffffffffu, s1, 1);
            s0 += __shfl_xor_sync(0xffffffffu, s0, 2); s1 += __shfl_xor_sync(0xffffffffu, s1, 2);
            const float a0 = s0 * (1.0f / 32), a1 = s1 * (1.0f / 32);
            float v0 = 0.f, v1 = 0.f;
#pragma unroll
            for (int i = 0; i < 8; i++) {
                const float a = (i & 1) ? a1 : a0;
                const float d0 = r[2 * i] - a, d1 = r[2 * i + 1] - a;
                if (i & 1) v1 += d0 * d0 + d1 * d1; else v0 += d0 * d0 + d1 * d1;
            }
            v0 += __shfl_xor_sync(0xffffffffu, v0, 1); v1 += __shfl_xor_sync(0xffffffffu, v1, 1);
            v0 += __shfl_xor_sync(0xffffffffu, v0, 2); v1 += __shfl_xor_sync(0xffffffffu, v1, 2);
            if (t4 < 2) stg64(g_stats + (row0 + 8 * t4) * 16 + j * 2 + q, __float_as_uint(t4 ? s1 : s0), __float_as_uint(t4 ? v1 : v0));
            TS(8);
            if (warp < 8) {
                mbar_wait(mb + (MB_DONE + 5) * 8);
                if (lane == 0) load_w2(sb, P, 6 + warp);
                __syncwarp();
            } else if (wg == 2) {
                if (kvoff[0] < 32768 || kvoff[0] >= 3 * 32768) stg32(reinterpret_cast<char*>(g_kv) + kvoff[0], 0u);
                if (kvoff[1] < 32768) stg32(reinterpret_cast<char*>(g_kv) + kvoff[1], 0u);
                if (lane == 0) stg32(reinterpret_cast<uint32_t*>(g_nrm + b) + ww, 0u);
            }
        }
        {
            const int mt1 = 16 * pr + (b >> 4) * 2 + q, sl = b & 15;
            const uint4* a = g_hf + mt1 * 32 * 128 + t128;
            float acc[44], nmean[2], hrstd[2];
            uint4 buf[3][4];
            fill_ring<3>(buf, a, 512);
            {
                const uint4* sp = reinterpret_cast<const uint4*>(g_stats + (mt1 * 64 + ww * 16 + g) * 16 + t4 * 4);
                uint4 u[4]; int spins = 0;
                do { u[0] = ldg_relaxed(sp); u[1] = ldg_relaxed(sp + 1); u[2] = ldg_relaxed(sp + 64); u[3] = ldg_relaxed(sp + 65); } while (batch_bad(u) && ++spins < SPIN_LIMIT);
                float mean[2], m2[2];
#pragma unroll
                for (int i = 0; i < 2; i++) mean[i] = (__uint_as_float(u[2 * i].x) + __uint_as_float(u[2 * i].z)) + (__uint_as_float(u[2 * i + 1].x) + __uint_as_float(u[2 * i + 1].z));
                mean[0] += __shfl_xor_sync(0xffffffffu, mean[0], 1); mean[1] += __shfl_xor_sync(0xffffffffu, mean[1], 1);
                mean[0] += __shfl_xor_sync(0xffffffffu, mean[0], 2); mean[1] += __shfl_xor_sync(0xffffffffu, mean[1], 2);
#pragma unroll
                for (int i = 0; i < 2; i++) {
                    mean[i] *= 1.0f / D;
                    const float da = __uint_as_float(u[2 * i].x) * (1.0f / 32) - mean[i], dc = __uint_as_float(u[2 * i].z) * (1.0f / 32) - mean[i];
                    const float de = __uint_as_float(u[2 * i + 1].x) * (1.0f / 32) - mean[i], df = __uint_as_float(u[2 * i + 1].z) * (1.0f / 32) - mean[i];
                    m2[i] = (__uint_as_float(u[2 * i].y) + __uint_as_float(u[2 * i].w)) + (__uint_as_float(u[2 * i + 1].y) + __uint_as_float(u[2 * i + 1].w)) + 32.0f * (da * da + dc * dc + de * de + df * df);
                }
                m2[0] += __shfl_xor_sync(0xffffffffu, m2[0], 1); m2[1] += __shfl_xor_sync(0xffffffffu, m2[1], 1);
                m2[0] += __shfl_xor_sync(0xffffffffu, m2[0], 2); m2[1] += __shfl_xor_sync(0xffffffffu, m2[1], 2);
#pragma unroll
                for (int i = 0; i < 2; i++) { hrstd[i] = 0.5f * rsqrtf(m2[i] * (1.0f / D) + 1e-5f); nmean[i] = -mean[i]; }
            }
#pragma unroll
            for (int i = 0; i < 44; i++) acc[i] = 0.f;
            fence_regs(acc);
#pragma unroll 1
            for (int i0 = 0; i0 < 8; i0 += 3) {
#pragma unroll
                for (int i = 0; i < 3; i++) {
                    const int blk = i0 + i;
                    if (blk < 8) {
                        const uint64_t db = mkdesc(sb + SM_W1 + (blk >> 1) * 24576 + (blk & 1) * 4096, 8192, 512, 2);
                        mbar_wait(mb + (MB_W1 + (blk >> 1)) * 8);
                        check_batch(buf[i], a + blk * 512);
                        wg_fence();
#pragma unroll
                        for (int s = 0; s < 4; s++) mma_rs(acc, buf[i][s], db + s * 64);
                        wg_commit();
                        wg_wait<1>();
                        if (blk >= 1 && blk + 2 < 8) load_batch(buf[(i + 2) % 3], a + (blk + 2) * 512);
                        if (blk >= 2 && !(blk & 1)) {
                            const int gi = (blk >> 1) - 1;
                            if (warp_arrive(mb + MISC_CNT + gi * 4) == 15) {
                                if (lane == 0) {
#pragma unroll 1
                                    for (int kb = 14 + 3 * gi; kb < min(17 + 3 * gi, 22); kb++) load_w2(sb, P, kb);
                                }
                                __syncwarp();
                            }
                        }
                    }
                }
            }
            wg_wait<0>();
            fence_regs(acc);
            TS(9);
            mbar_wait(mb + MB_CS * 8);
            uint32_t hv[22];
#pragma unroll
            for (int i = 0; i < 11; i++) {
                float2 cs;
                asm volatile("ld.shared.v2.f32 {%0,%1}, [%2];" : "=f"(cs.x), "=f"(cs.y) : "r"(mb + MISC_CS + i * 32 + t4 * 8));
                hv[2 * i] = pack_bf16(silu2(hrstd[0] * fmaf(nmean[0], cs.x, acc[4 * i])), silu2(hrstd[0] * fmaf(nmean[0], cs.y, acc[4 * i + 1])));
                hv[2 * i + 1] = pack_bf16(silu2(hrstd[1] * fmaf(nmean[1], cs.x, acc[4 * i + 2])), silu2(hrstd[1] * fmaf(nmean[1], cs.y, acc[4 * i + 3])));
            }
            uint4* hb = g_Hf + (mt1 * 88 + (sl >> 1) * 11) * 128 + t128;
            if (sl & 1) {
                stg64(reinterpret_cast<uint2*>(hb + 5 * 128) + 1, hv[0], hv[1]);
#pragma unroll
                for (int i = 0; i < 5; i++) stg128(hb + (6 + i) * 128, hv[2 + 4 * i], hv[3 + 4 * i], hv[4 + 4 * i], hv[5 + 4 * i]);
            } else {
#pragma unroll
                for (int i = 0; i < 5; i++) stg128(hb + i * 128, hv[4 * i], hv[4 * i + 1], hv[4 * i + 2], hv[4 * i + 3]);
                stg64(hb + 5 * 128, hv[20], hv[21]);
            }
            TS(10);
        }
    }
#pragma unroll
    for (int h = 0; h < 2; h++) {
        uint32_t v0 = hk[h], v1 = hk[2 + h], v2 = hk[4 + h], v3 = hk[6 + h];
        const bool o1 = t4 & 1, o2 = t4 & 2;
        uint32_t a = __shfl_xor_sync(0xffffffffu, o1 ? v0 : v1, 1), c = __shfl_xor_sync(0xffffffffu, o1 ? v2 : v3, 1);
        if (o1) { v0 = a; v2 = c; } else { v1 = a; v3 = c; }
        a = __shfl_xor_sync(0xffffffffu, o2 ? v0 : v2, 2); c = __shfl_xor_sync(0xffffffffu, o2 ? v1 : v3, 2);
        if (o2) { v0 = a; v1 = c; } else { v2 = a; v3 = c; }
        *reinterpret_cast<uint4*>(P.out + (size_t)(row0 + 8 * h) * D + j * 64 + q * 32 + t4 * 8) = make_uint4(v0, v1, v2, v3);
    }
    TS(12);
}

typedef CUresult (*EncodeFn)(CUtensorMap*, CUtensorMapDataType, cuuint32_t, void*, const cuuint64_t*, const cuuint64_t*, const cuuint32_t*,
                             const cuuint32_t*, CUtensorMapInterleave, CUtensorMapSwizzle, CUtensorMapL2promotion, CUtensorMapFloatOOBfill);

void encode2d(EncodeFn fn, CUtensorMap* tm, const void* ptr, int rows, int cols, int box_rows, int box_cols, CUtensorMapSwizzle sw) {
    cuuint64_t dims[2] = {(cuuint64_t)cols, (cuuint64_t)rows};
    cuuint64_t strides[1] = {(cuuint64_t)cols * 2};
    cuuint32_t box[2] = {(cuuint32_t)box_cols, (cuuint32_t)box_rows};
    cuuint32_t es[2] = {1, 1};
    fn(tm, CU_TENSOR_MAP_DATA_TYPE_BFLOAT16, 2, const_cast<void*>(ptr), dims, strides, box, es, CU_TENSOR_MAP_INTERLEAVE_NONE, sw,
       CU_TENSOR_MAP_L2_PROMOTION_L2_128B, CU_TENSOR_MAP_FLOAT_OOB_FILL_NONE);
}

}

extern "C" void kernel_launch(void* const* d_in, const int* in_sizes, int n_in, void* d_out, int out_size) {
    (void)in_sizes; (void)n_in; (void)out_size;
    void* fnp = nullptr;
    cudaDriverEntryPointQueryResult qr;
    cudaGetDriverEntryPoint("cuTensorMapEncodeTiled", &fnp, cudaEnableDefault, &qr);
    EncodeFn fn = (EncodeFn)fnp;
    Params P;
    encode2d(fn, &P.wq, d_in[1], D, D, 128, 64, CU_TENSOR_MAP_SWIZZLE_128B);
    P.wk = (const __nv_bfloat16*)d_in[2];
    P.wv = (const __nv_bfloat16*)d_in[3];
    encode2d(fn, &P.wo, d_in[4], D, D, 64, 64, CU_TENSOR_MAP_SWIZZLE_128B);
    encode2d(fn, &P.w1, d_in[6], D, FF, 128, 32, CU_TENSOR_MAP_SWIZZLE_64B);
    encode2d(fn, &P.w2, d_in[7], FF, D, 64, 64, CU_TENSOR_MAP_SWIZZLE_128B);
    P.x = (const __nv_bfloat16*)d_in[0];
    P.w1p = (const __nv_bfloat16*)d_in[6];
    P.w2p = (const __nv_bfloat16*)d_in[7];
    P.wop = (const __nv_bfloat16*)d_in[4];
    P.out = (__nv_bfloat16*)d_out;
    P.neg1 = 0xFFFFFFFFu;
    cudaFuncSetAttribute(fused_kernel, cudaFuncAttributeMaxDynamicSharedMemorySize, SMEM_BYTES);
    fused_kernel<<<NCTA, 512, SMEM_BYTES>>>(P);
}
```

```cpp
#include <cuda_runtime.h>
#include <cuda_bf16.h>
#include <cuda.h>
#include <stdint.h>

namespace {

constexpr int D = 512, FF = 1376;
constexpr int NMAIN = 128, NHELP = 4, NCTA = NMAIN + NHELP;
constexpr uint32_t SENT = 0xFFFFFFFFu;
constexpr int SPIN_LIMIT = 1 << 22;

constexpr uint32_t KB = 1024;
constexpr uint32_t SM_XN = 0;
constexpr uint32_t SM_WQ = 64 * KB;
constexpr uint32_t SM_WKV = 176 * KB;
constexpr uint32_t KVCH = 40 * KB;
constexpr uint32_t SM_Q = 160 * KB;
constexpr uint32_t SM_W1 = 48 * KB;
constexpr uint32_t SM_MISC = 192 * KB;
constexpr uint32_t SMEM_BYTES = 195 * KB;
constexpr uint32_t MB_WQ = 0;
constexpr uint32_t MB_KV = 4;
constexpr uint32_t MB_WO = 8;
constexpr uint32_t MB_W2 = 16;
constexpr uint32_t MB_W1 = 38;
constexpr uint32_t MB_F2 = 42;
constexpr uint32_t MB_CS = 43;
constexpr uint32_t MB_DONE = 44;
constexpr uint32_t NBAR = 50;
constexpr uint32_t MISC_CNT = 400;
constexpr uint32_t MISC_NRM = 416;
constexpr uint32_t MISC_EPOCH = 432;
constexpr uint32_t MISC_CS = 448;
constexpr uint32_t MISC_RSTD = 768;
constexpr uint32_t MISC_K0 = 1024;

__host__ __device__ constexpr uint32_t wo_slot(int kb) { return kb < 2 ? 22 + kb : kb - 2; }
__host__ __device__ constexpr uint32_t w2_slot(int kb) { return kb < 2 ? 18 + kb : kb < 4 ? 20 + kb : kb - 4; }
__host__ __device__ constexpr uint64_t pack_slots(bool is_w2, int q) {
    uint64_t v = 0;
    for (int i = 0; i < (is_w2 ? 11 : 4); i++) v |= (uint64_t)(is_w2 ? w2_slot(2 * i + q) : wo_slot(2 * i + q)) << (5 * i);
    return v;
}

__device__ uint4 g_kv[4 * 2048];
__device__ uint4 g_kplain[4 * 1024];
__device__ uint4 g_of[32 * 32 * 128];
__device__ uint4 g_hf[32 * 32 * 128];
__device__ uint4 g_Hf[32 * 88 * 128];
__device__ float2 g_stats[32 * 64 * 16];
__device__ float g_cs[1408];
__device__ uint4 g_nrm[NMAIN];
__device__ unsigned g_count1;
__device__ unsigned g_count2;
__device__ unsigned g_epoch[NCTA];
#define TS(i) do {} while (0)

__device__ __forceinline__ void mbar_init(uint32_t bar, int cnt) { asm volatile("mbarrier.init.shared::cta.b64 [%0], %1;" :: "r"(bar), "r"(cnt) : "memory"); }
__device__ __forceinline__ void mbar_expect(uint32_t bar, uint32_t bytes) { asm volatile("mbarrier.arrive.expect_tx.shared::cta.b64 _, [%0], %1;" :: "r"(bar), "r"(bytes) : "memory"); }
__device__ __forceinline__ void mbar_arrive(uint32_t bar) { asm volatile("mbarrier.arrive.shared::cta.b64 _, [%0];" :: "r"(bar) : "memory"); }
__device__ __forceinline__ void mbar_wait(uint32_t bar) {
    uint32_t done; int spins = 0;
    do {
        asm volatile("{.reg .pred p; mbarrier.try_wait.parity.shared::cta.b64 p, [%1], 0; selp.u32 %0, 1, 0, p;}" : "=r"(done) : "r"(bar) : "memory");
    } while (!__all_sync(0xffffffffu, done) && ++spins < SPIN_LIMIT);
}
__device__ __forceinline__ void tma2d(uint32_t dst, const CUtensorMap* tm, int c0, int c1, uint32_t bar) {
    asm volatile("cp.async.bulk.tensor.2d.shared::cluster.global.mbarrier::complete_tx::bytes [%0], [%1, {%3, %4}], [%2];"
                 :: "r"(dst), "l"(tm), "r"(bar), "r"(c0), "r"(c1) : "memory");
}
__device__ __forceinline__ void bulk_g2s(uint32_t dst, const void* src, uint32_t bytes, uint32_t bar) {
    asm volatile("cp.async.bulk.shared::cluster.global.mbarrier::complete_tx::bytes [%0], [%1], %2, [%3];" :: "r"(dst), "l"(src), "r"(bytes), "r"(bar) : "memory");
}
__device__ __forceinline__ void fence_async_smem() { asm volatile("fence.proxy.async.shared::cta;" ::: "memory"); }
__device__ __forceinline__ void bar_sync(int id, int n) { asm volatile("bar.sync %0, %1;" :: "r"(id), "r"(n) : "memory"); }
__device__ __forceinline__ void bar_arrive(int id, int n) { asm volatile("bar.arrive %0, %1;" :: "r"(id), "r"(n) : "memory"); }
__device__ __forceinline__ void wg_fence() { asm volatile("wgmma.fence.sync.aligned;" ::: "memory"); }
__device__ __forceinline__ void wg_commit() { asm volatile("wgmma.commit_group.sync.aligned;" ::: "memory"); }
template <int N> __device__ __forceinline__ void wg_wait() { asm volatile("wgmma.wait_group.sync.aligned %0;" :: "n"(N) : "memory"); }
template <int N> __device__ __forceinline__ void fence_regs(float (&d)[N]) {
#pragma unroll
    for (int i = 0; i < N; i++) asm volatile("" : "+f"(d[i]) :: "memory");
}
template <int N> __device__ __forceinline__ void fence_regs(uint32_t (&d)[N]) {
#pragma unroll
    for (int i = 0; i < N; i++) asm volatile("" : "+r"(d[i]) :: "memory");
}
__device__ __forceinline__ uint64_t mkdesc(uint32_t addr, uint32_t lbo, uint32_t sbo, uint32_t swz) {
    return (uint64_t)(((addr & 0x3FFFF) >> 4) | ((lbo >> 4) << 16)) | ((uint64_t)((sbo >> 4) | (swz << 30)) << 32);
}
__device__ __forceinline__ float ex2(float x) { float y; asm("ex2.approx.ftz.f32 %0, %1;" : "=f"(y) : "f"(x)); return y; }
__device__ __forceinline__ float rcp(float x) { float y; asm("rcp.approx.ftz.f32 %0, %1;" : "=f"(y) : "f"(x)); return y; }
__device__ __forceinline__ uint32_t pack_bf16(float lo, float hi) { uint32_t r; asm("cvt.rn.bf16x2.f32 %0, %1, %2;" : "=r"(r) : "f"(hi), "f"(lo)); return r; }
__device__ __forceinline__ uint32_t pack_f16(float lo, float hi) { uint32_t r; asm("cvt.rn.f16x2.f32 %0, %1, %2;" : "=r"(r) : "f"(hi), "f"(lo)); return r; }
__device__ __forceinline__ float bf_lo(uint32_t v) { return __uint_as_float(v << 16); }
__device__ __forceinline__ float bf_hi(uint32_t v) { return __uint_as_float(v & 0xFFFF0000u); }
__device__ __forceinline__ uint4 ldg_relaxed(const uint4* p) {
    uint4 v; asm volatile("ld.relaxed.gpu.global.v4.u32 {%0,%1,%2,%3}, [%4];" : "=r"(v.x), "=r"(v.y), "=r"(v.z), "=r"(v.w) : "l"(p) : "memory"); return v;
}
__device__ __forceinline__ void stg128(void* p, uint32_t a, uint32_t b, uint32_t c, uint32_t d) {
    asm volatile("st.relaxed.gpu.global.v4.u32 [%0], {%1,%2,%3,%4};" :: "l"(p), "r"(a), "r"(b), "r"(c), "r"(d) : "memory");
}
__device__ __forceinline__ void stg64(void* p, uint32_t a, uint32_t b) {
    asm volatile("st.relaxed.gpu.global.v2.u32 [%0], {%1,%2};" :: "l"(p), "r"(a), "r"(b) : "memory");
}
__device__ __forceinline__ void sts128(uint32_t a, uint32_t x, uint32_t y, uint32_t z, uint32_t w) {
    asm volatile("st.shared.v4.u32 [%0], {%1,%2,%3,%4};" :: "r"(a), "r"(x), "r"(y), "r"(z), "r"(w) : "memory");
}
__device__ __forceinline__ void sts32(uint32_t a, uint32_t x) { asm volatile("st.shared.u32 [%0], %1;" :: "r"(a), "r"(x) : "memory"); }
__device__ __forceinline__ float4 lds128f(uint32_t a) {
    float4 v; asm volatile("ld.shared.v4.f32 {%0,%1,%2,%3}, [%4];" : "=f"(v.x), "=f"(v.y), "=f"(v.z), "=f"(v.w) : "r"(a) : "memory"); return v;
}
__device__ __forceinline__ uint32_t lds32(uint32_t a) { uint32_t v; asm volatile("ld.shared.u32 %0, [%1];" : "=r"(v) : "r"(a) : "memory"); return v; }
__device__ __forceinline__ bool has_sent(const uint4& v) { return (v.x == SENT) | (v.w == SENT); }
__device__ __forceinline__ bool has_zero(const uint4& v) { return min(min(v.x, v.y), min(v.z, v.w)) == 0u; }
__device__ __forceinline__ uint32_t nonzero(uint32_t w) { return w == 0u ? 0x8000u : w; }
__device__ __forceinline__ void stg32(void* p, uint32_t a) { asm volatile("st.relaxed.gpu.global.u32 [%0], %1;" :: "l"(p), "r"(a) : "memory"); }
__device__ __forceinline__ void wait_count(const unsigned* p, unsigned target) {
    unsigned v; int spins = 0;
    do { asm volatile("ld.acquire.gpu.global.u32 %0, [%1];" : "=r"(v) : "l"(p) : "memory"); } while (__any_sync(0xffffffffu, v != target) && ++spins < SPIN_LIMIT);
}
__device__ __forceinline__ uint32_t warp_arrive(uint32_t cnt) {
    uint32_t old = 0;
    __syncwarp();
    if ((threadIdx.x & 31) == 0) asm volatile("atom.acq_rel.cta.shared.add.u32 %0, [%1], 1;" : "=r"(old) : "r"(cnt) : "memory");
    return __shfl_sync(0xffffffffu, old, 0);
}
__device__ __forceinline__ void warp_done(uint32_t bar) { __syncwarp(); if ((threadIdx.x & 31) == 0) mbar_arrive(bar); }
__device__ __forceinline__ uint32_t add_bf16x2(uint32_t a, uint32_t b) { uint32_t r; asm("add.rn.bf16x2 %0, %1, %2;" : "=r"(r) : "r"(a), "r"(b)); return r; }

#define R4(d, o) "+f"(d[o + 0]), "+f"(d[o + 1]), "+f"(d[o + 2]), "+f"(d[o + 3])
#define R8(d, o) R4(d, o), R4(d, o + 4)
#define R32(d) R8(d, 0), R8(d, 8), R8(d, 16), R8(d, 24)
#define D32 "{%0,%1,%2,%3,%4,%5,%6,%7,%8,%9,%10,%11,%12,%13,%14,%15,%16,%17,%18,%19,%20,%21,%22,%23,%24,%25,%26,%27,%28,%29,%30,%31}"
#define D44 "{%0,%1,%2,%3,%4,%5,%6,%7,%8,%9,%10,%11,%12,%13,%14,%15,%16,%17,%18,%19,%20,%21,%22,%23,%24,%25,%26,%27,%28,%29,%30,%31,%32,%33,%34,%35,%36,%37,%38,%39,%40,%41,%42,%43}"

__device__ __forceinline__ void mma_qk_f16(float (&d)[32], uint64_t da, uint64_t db) {
    asm volatile("{.reg .pred p; setp.eq.b32 p, 0, 0; wgmma.mma_async.sync.aligned.m64n64k16.f32.f16.f16 " D32 ", %32, %33, p, 1, 1, 0, 0;}"
                 : R32(d) : "l"(da), "l"(db));
}
__device__ __forceinline__ void mma_qk_bf16(float (&d)[32], uint64_t da, uint64_t db) {
    asm volatile("{.reg .pred p; setp.ne.b32 p, 0, 0; wgmma.mma_async.sync.aligned.m64n64k16.f32.bf16.bf16 " D32 ", %32, %33, p, 1, 1, 0, 0;}"
                 : R32(d) : "l"(da), "l"(db));
}
__device__ __forceinline__ void mma_pv(float (&d)[12], const uint32_t* a, uint64_t db) {
    asm volatile("{.reg .pred p; setp.eq.b32 p, 0, 0; wgmma.mma_async.sync.aligned.m64n24k16.f32.bf16.bf16 {%0,%1,%2,%3,%4,%5,%6,%7,%8,%9,%10,%11}, {%12,%13,%14,%15}, %16, p, 1, 1, 1;}"
                 : R8(d, 0), R4(d, 8) : "r"(a[0]), "r"(a[1]), "r"(a[2]), "r"(a[3]), "l"(db));
}
__device__ __forceinline__ void mma_ss64(float (&d)[32], uint64_t da, uint64_t db) {
    asm volatile("{.reg .pred p; setp.eq.b32 p, 0, 0; wgmma.mma_async.sync.aligned.m64n64k16.f32.bf16.bf16 " D32 ", %32, %33, p, 1, 1, 0, 1;}"
                 : R32(d) : "l"(da), "l"(db));
}
__device__ __forceinline__ void mma_ss8(float (&d)[4], uint64_t da, uint64_t db) {
    asm volatile("{.reg .pred p; setp.eq.b32 p, 0, 0; wgmma.mma_async.sync.aligned.m64n8k16.f32.bf16.bf16 {%0,%1,%2,%3}, %4, %5, p, 1, 1, 0, 1;}"
                 : R4(d, 0) : "l"(da), "l"(db));
}
__device__ __forceinline__ void mma_rs(float (&d)[32], const uint4& a, uint64_t db) {
    asm volatile("{.reg .pred p; setp.eq.b32 p, 0, 0; wgmma.mma_async.sync.aligned.m64n64k16.f32.bf16.bf16 " D32 ", {%32,%33,%34,%35}, %36, p, 1, 1, 1;}"
                 : R32(d) : "r"(a.x), "r"(a.y), "r"(a.z), "r"(a.w), "l"(db));
}
__device__ __forceinline__ void mma_rs(float (&d)[44], const uint4& a, uint64_t db) {
    asm volatile("{.reg .pred p; setp.eq.b32 p, 0, 0; wgmma.mma_async.sync.aligned.m64n88k16.f32.bf16.bf16 " D44 ", {%44,%45,%46,%47}, %48, p, 1, 1, 1;}"
                 : R32(d), R8(d, 32), R4(d, 40) : "r"(a.x), "r"(a.y), "r"(a.z), "r"(a.w), "l"(db));
}

constexpr float EXP_MAGIC = 256.0f + 127.0f + 64.0f - 1.58621f + 0.00390625f;
constexpr uint32_t MUFU_MASK = 0x1111u;
__device__ __forceinline__ uint32_t exp2_pair(float y0, float y1, uint32_t cexp, uint32_t neg1) {
    uint32_t w, m, e, r;
    asm("prmt.b32 %0, %1, %2, 0x6521;" : "=r"(w) : "r"(__float_as_uint(y0)), "r"(__float_as_uint(y1)));
    asm("lop3.b32 %0, %1, 0x007F007F, %2, 0xEA;" : "=r"(m) : "r"(w), "r"(cexp));
    asm("mad.lo.u32 %0, %1, %2, %3;" : "=r"(e) : "r"(m), "r"(neg1), "r"(w));
    asm("fma.rn.bf16x2 %0, %1, %2, %3;" : "=r"(r) : "r"(w), "r"(m), "r"(e));
    return r;
}

struct Params {
    CUtensorMap wq, wo, w1, w2;
    const __nv_bfloat16* x;
    const __nv_bfloat16* wk;
    const __nv_bfloat16* wv;
    const __nv_bfloat16* w1p;
    const __nv_bfloat16* w2p;
    const __nv_bfloat16* wop;
    const __nv_bfloat16* wqp;
    __nv_bfloat16* out;
    uint32_t neg1;
};

__device__ __forceinline__ void load_wq(uint32_t sb, const Params& P, int gi, int atom) {
    const uint32_t bar = sb + SM_MISC + (MB_WQ + gi) * 8;
    mbar_expect(bar, 16384); tma2d(sb + SM_WQ + atom * 65536 + gi * 16384, &P.wq, (blockIdx.x & 3) * 128 + atom * 64, gi * 128, bar);
}
__device__ __forceinline__ void load_wo(uint32_t sb, const Params& P, int kb) {
    const uint32_t bar = sb + SM_MISC + (MB_WO + kb) * 8;
    mbar_expect(bar, 8192); tma2d(sb + wo_slot(kb) * 8192, &P.wo, (blockIdx.x & 7) * 64, kb * 64, bar);
}
__device__ __forceinline__ void load_w2(uint32_t sb, const Params& P, int kb) {
    const uint32_t bar = sb + SM_MISC + (MB_W2 + kb) * 8;
    mbar_expect(bar, 8192); tma2d(sb + w2_slot(kb) * 8192, &P.w2, (blockIdx.x & 7) * 64, kb * 64, bar);
}
__device__ __forceinline__ void load_w1(uint32_t sb, const Params& P, int box) {
    const int gi = box / 3, a = box - 3 * gi;
    const uint32_t bar = sb + SM_MISC + (MB_W1 + gi) * 8;
    mbar_expect(bar, 8192); tma2d(sb + SM_W1 + box * 8192, &P.w1, (blockIdx.x & 15) * 88 + a * 32, gi * 128, bar);
}

__device__ __forceinline__ void release_w1(uint32_t sb, const Params& P, int gi) {
    if (warp_arrive(sb + SM_MISC + MISC_CNT + gi * 4) == 15) {
        if ((threadIdx.x & 31) == 0) {
#pragma unroll 1
            for (int kb = 10 + 3 * gi; kb < 13 + 3 * gi; kb++) load_w2(sb, P, kb);
        }
        __syncwarp();
    }
}
__device__ __forceinline__ void load_batch(uint4 (&buf)[4], const uint4* a) {
#pragma unroll
    for (int s = 0; s < 4; s++) buf[s] = ldg_relaxed(a + s * 128);
}
__device__ __forceinline__ bool batch_bad(const uint4 (&buf)[4]) {
    const uint32_t m = max(max(max(buf[0].x, buf[0].w), max(buf[1].x, buf[1].w)), max(max(buf[2].x, buf[2].w), max(buf[3].x, buf[3].w)));
    return __any_sync(0xffffffffu, m == SENT);
}
__device__ __forceinline__ void check_batch(uint4 (&buf)[4], const uint4* a) {
    int spins = 0;
    while (batch_bad(buf) && ++spins < SPIN_LIMIT) load_batch(buf, a);
}
template <int RING>
__device__ __forceinline__ void fill_ring(uint4 (&buf)[RING][4], const uint4* a, int astr) {
#pragma unroll
    for (int i = 0; i < RING; i++) load_batch(buf[i], a + i * astr);
    if (batch_bad(buf[0])) {
        load_batch(buf[0], a);
        check_batch(buf[0], a);
#pragma unroll
        for (int i = 1; i < RING; i++) load_batch(buf[i], a + i * astr);
    }
}

__device__ __forceinline__ void pair_reduce(const float (&acc)[32], float (&r)[16], uint32_t buf, int q, int barid) {
    if (q) {
#pragma unroll
        for (int j = 0; j < 4; j++) sts128(buf + j * 2048, __float_as_uint(acc[4 * j]), __float_as_uint(acc[4 * j + 1]), __float_as_uint(acc[4 * j + 2]), __float_as_uint(acc[4 * j + 3]));
        bar_sync(barid, 256);
        bar_sync(barid, 256);
#pragma unroll
        for (int j = 0; j < 4; j++) {
            float4 v = lds128f(buf + j * 2048);
            r[4 * j] = acc[16 + 4 * j] + v.x; r[4 * j + 1] = acc[17 + 4 * j] + v.y; r[4 * j + 2] = acc[18 + 4 * j] + v.z; r[4 * j + 3] = acc[19 + 4 * j] + v.w;
        }
    } else {
        bar_sync(barid, 256);
        float4 v[4];
#pragma unroll
        for (int j = 0; j < 4; j++) v[j] = lds128f(buf + j * 2048);
#pragma unroll
        for (int j = 0; j < 4; j++) sts128(buf + j * 2048, __float_as_uint(acc[16 + 4 * j]), __float_as_uint(acc[17 + 4 * j]), __float_as_uint(acc[18 + 4 * j]), __float_as_uint(acc[19 + 4 * j]));
        bar_arrive(barid, 256);
#pragma unroll
        for (int j = 0; j < 4; j++) {
            r[4 * j] = acc[4 * j] + v[j].x; r[4 * j + 1] = acc[4 * j + 1] + v[j].y; r[4 * j + 2] = acc[4 * j + 2] + v[j].z; r[4 * j + 3] = acc[4 * j + 3] + v[j].w;
        }
    }
}

__device__ __forceinline__ float quad_sum(float v) { v += __shfl_xor_sync(0xffffffffu, v, 1); v += __shfl_xor_sync(0xffffffffu, v, 2); return v; }
__device__ __forceinline__ float silu2(float h) { float t; asm("tanh.approx.f32 %0, %1;" : "=f"(t) : "f"(h)); return fmaf(h, t, h); }

#define TS_ARG
#define TS_PASS

__device__ __forceinline__ void attn_hook(const Params& P, uint32_t sb, int warp, int U, unsigned& cnt2) {
    const uint32_t mb = sb + SM_MISC;
    const int lane = threadIdx.x & 31, b = blockIdx.x, t128 = threadIdx.x & 127;
    const int wg = warp >> 2, ww = warp & 3, job = 3 - wg + 4 * ww;
    if (U < 3) {
        const int pr = 1 - (wg >> 1), q = wg & 1;
        const int mt = 16 * pr + (b >> 3), mt1 = 16 * pr + (b >> 4) * 2 + q, sl = b & 15;
        uint4* hb = g_Hf + (mt1 * 88 + (sl >> 1) * 11) * 128 + t128;
        if (U == 0) {
            hb += (sl & 1) * 6 * 128;
            stg128(hb, SENT, SENT, SENT, SENT); stg128(hb + 128, SENT, SENT, SENT, SENT); stg128(hb + 256, SENT, SENT, SENT, SENT);
            if (lane == 0 && job < 2) load_wo(sb, P, job);
        } else if (U == 1) {
            stg128(hb + ((sl & 1) * 6 + 3) * 128, SENT, SENT, SENT, SENT); stg128(hb + ((sl & 1) * 6 + 4) * 128, SENT, SENT, SENT, SENT);
            stg64(reinterpret_cast<uint2*>(hb + 5 * 128) + (sl & 1), SENT, SENT);
            if ((lane & 3) < 2) stg64(g_stats + (mt * 64 + ww * 16 + (lane >> 2) + 8 * (lane & 3)) * 16 + (b & 7) * 2 + q, SENT, SENT);
        } else {
            uint4* hp = g_hf + (mt * 32 + (b & 7) * 4 + 2 * q) * 128 + t128;
            stg128(hp, SENT, SENT, SENT, SENT); stg128(hp + 128, SENT, SENT, SENT, SENT);
            stg128(g_of + ((16 + (b >> 3)) * 32 + (b & 3) * 8 + 2 * wg + (ww >> 1)) * 128 + (((b >> 2) & 1) * 2 + (ww & 1)) * 32 + lane, SENT, SENT, SENT, SENT);
        }
    } else if (U == 3 || !(U & 1)) {
        warp_done(mb + (MB_DONE + ((U - 2) >> 1)) * 8);
        if (U == 4 && warp == 15) {
            mbar_wait(mb + MB_DONE * 8);
            if (lane == 0) asm volatile("red.release.gpu.global.add.u32 [%0], 1;" :: "l"(&g_count2) : "memory");
        }
        if (U == 8 && warp == 11) asm volatile("ld.relaxed.gpu.global.u32 %0, [%1];" : "=r"(cnt2) : "l"(&g_count2) : "memory");
    } else {
        if (job < 5) {
            mbar_wait(mb + (MB_DONE + ((U - 3) >> 1)) * 8);
            if (lane == 0) {
                const int slot = (U - 5) / 2 * 5 + job;
                if (slot < 6) load_wo(sb, P, slot + 2); else load_w1(sb, P, slot - 6);
            }
        }
        if (U == 9 && warp == 11) {
            const unsigned target = lds32(mb + MISC_EPOCH) * NCTA;
            if (__any_sync(0xffffffffu, cnt2 != target)) wait_count(&g_count2, target);
            asm volatile("fence.acquire.gpu;" ::: "memory");
            warp_done(mb + MB_F2 * 8);
        }
    }
    __syncwarp();
}

template <bool SAFE>
__device__ __forceinline__ void attention(const Params& P, uint32_t sb, int warp TS_ARG) {
    const uint32_t mb = sb + SM_MISC;
    const int tid = threadIdx.x, lane = tid & 31, b = blockIdx.x, tg = b >> 2, hg = b & 3;
    const int wg = warp >> 2, ww = warp & 3;
    const uint32_t cexp = 0x9F809F80u + (tid >> 12);
    const uint32_t neg1 = P.neg1;
    unsigned cnt2 = 0;
#pragma unroll 1
    for (int pass = 0; pass < 2; pass++) {
        float o[12], s[32];
        const uint64_t dq = mkdesc(sb + SM_Q + (pass * 4 + wg) * 2048, 128, 256, 0);
        uint64_t dk = mkdesc(sb, 128, 256, 0);
        uint64_t dv = mkdesc(sb + 16384, 128, 8192, 0);
        float m0 = -INFINITY, m1 = -INFINITY;
#pragma unroll
        for (int i = 0; i < 12; i++) o[i] = 0.f;
#pragma unroll
        for (int i = 0; i < 32; i++) s[i] = ((MUFU_MASK >> (i / 2)) & 1) ? 0.f : EXP_MAGIC;
        fence_regs(s); fence_regs(o);
        wg_fence();
        if (SAFE) mma_qk_f16(s, dq, mkdesc(mb + MISC_K0, 128, 256, 0)); else mma_qk_bf16(s, dq, mkdesc(mb + MISC_K0, 128, 256, 0));
        wg_commit();
        wg_wait<0>(); fence_regs(s);
#pragma unroll 1
        for (int u = 4 * pass; u < 4 + 7 * pass; u++) {
            if (SAFE && u >= 1 && u < 4) mbar_wait(mb + (MB_KV + u) * 8);
#pragma unroll 1
            for (int i = (u > 4) ? 4 : 0; i < 8; i++) {
                uint32_t p[16];
                if (SAFE) {
#pragma unroll
                    for (int j = 0; j < 16; j++) {
                        if ((MUFU_MASK >> j) & 1) p[j] = pack_bf16(ex2(s[2 * j]), ex2(s[2 * j + 1]));
                        else p[j] = exp2_pair(s[2 * j], s[2 * j + 1], cexp, neg1);
                    }
                } else {
                    fence_regs(o);
                    float x0 = m0, x1 = m1;
#pragma unroll
                    for (int j = 0; j < 8; j++) { x0 = fmaxf(x0, fmaxf(s[4 * j], s[4 * j + 1])); x1 = fmaxf(x1, fmaxf(s[4 * j + 2], s[4 * j + 3])); }
                    x0 = fmaxf(x0, __shfl_xor_sync(0xffffffffu, x0, 1)); x0 = fmaxf(x0, __shfl_xor_sync(0xffffffffu, x0, 2));
                    x1 = fmaxf(x1, __shfl_xor_sync(0xffffffffu, x1, 1)); x1 = fmaxf(x1, __shfl_xor_sync(0xffffffffu, x1, 2));
                    const float c0 = ex2(m0 - x0), c1 = ex2(m1 - x1);
                    m0 = x0; m1 = x1;
#pragma unroll
                    for (int j = 0; j < 3; j++) { o[4 * j] *= c0; o[4 * j + 1] *= c0; o[4 * j + 2] *= c1; o[4 * j + 3] *= c1; }
#pragma unroll
                    for (int j = 0; j < 8; j++) {
                        p[2 * j] = pack_bf16(ex2(s[4 * j] - m0), ex2(s[4 * j + 1] - m0));
                        p[2 * j + 1] = pack_bf16(ex2(s[4 * j + 2] - m1), ex2(s[4 * j + 3] - m1));
                    }
                    fence_regs(o);
                }
                fence_regs(p);
                wg_fence();
                if (SAFE) mma_qk_f16(s, dq, dk); else mma_qk_bf16(s, dq, dk);
#pragma unroll
                for (int j = 0; j < 4; j++) mma_pv(o, p + 4 * j, dv + j * 16);
                wg_commit();
                dk += 128; dv += 64;
                wg_wait<0>(); fence_regs(s);
            }
            if (u < 4 || !(u & 1)) { dk += (KVCH - 16384) / 16; dv += (KVCH - 8192) / 16; }
            if (u == 3 || u == 10) {
                fence_regs(o);
                const float i0 = 1.0f / o[8], i1 = 1.0f / o[10];
                stg128(g_of + ((16 * pass + (tg >> 1)) * 32 + hg * 8 + 2 * wg + (ww >> 1)) * 128 + ((tg & 1) * 2 + (ww & 1)) * 32 + lane,
                       pack_bf16(o[0] * i0, o[1] * i0), pack_bf16(o[2] * i1, o[3] * i1), pack_bf16(o[4] * i0, o[5] * i0), pack_bf16(o[6] * i1, o[7] * i1));
            }
            attn_hook(P, sb, warp, u, cnt2);
        }
        TS(5 + pass);
    }
}

__device__ __noinline__ void helper_cta(const Params& P, uint8_t* smem) {
    const int tid = threadIdx.x, b = blockIdx.x, hi = b - NMAIN;
    const unsigned epoch = g_epoch[b] + 1;
    float* red = reinterpret_cast<float*>(smem);
    if (tid < 32) wait_count(&g_count1, epoch * NMAIN);
    __syncthreads();
    if (tid == 480) {
        for (int i = 0; i < 8; i++) asm volatile("cp.async.bulk.prefetch.L2.global [%0], %1;" :: "l"((const char*)P.wop + hi * 131072 + i * 16384), "r"(16384) : "memory");
        for (int i = 0; i < 43; i++) asm volatile("cp.async.bulk.prefetch.L2.global [%0], %1;" :: "l"((const char*)P.w2p + hi * 352256 + i * 8192), "r"(8192) : "memory");
    }
    if (tid < 344) {
        const int cg = tid % 43, rp = tid / 43;
        const uint4* src = reinterpret_cast<const uint4*>(P.w1p + (size_t)rp * 64 * FF + (hi * 43 + cg) * 8);
        float s[8] = {0, 0, 0, 0, 0, 0, 0, 0};
#pragma unroll 8
        for (int r = 0; r < 64; r++) {
            uint4 v = __ldg(src + r * (FF / 8));
            s[0] += bf_lo(v.x); s[1] += bf_hi(v.x); s[2] += bf_lo(v.y); s[3] += bf_hi(v.y);
            s[4] += bf_lo(v.z); s[5] += bf_hi(v.z); s[6] += bf_lo(v.w); s[7] += bf_hi(v.w);
        }
        float* part = red + (rp * 43 + cg) * 8;
#pragma unroll
        for (int i = 0; i < 8; i++) part[i] = s[i];
    }
    __syncthreads();
    if (tid < 344) {
        float s = 0.f;
#pragma unroll
        for (int rp = 0; rp < 8; rp++) s += red[rp * 344 + tid];
        g_cs[hi * 344 + tid] = s;
    } else if (hi == 3 && tid < 344 + 32) g_cs[FF + tid - 344] = 0.f;
    __syncthreads();
    if (tid == 0) {
        asm volatile("red.release.gpu.global.add.u32 [%0], 1;" :: "l"(&g_count2) : "memory");
        g_epoch[b] = epoch;
    }
}

__global__ void __launch_bounds__(512, 1) fused_kernel(const __grid_constant__ Params P) {
    extern __shared__ __align__(1024) uint8_t smem[];
    const uint32_t sb = (uint32_t)__cvta_generic_to_shared(smem);
    const uint32_t mb = sb + SM_MISC;
    const int tid = threadIdx.x, lane = tid & 31, b = blockIdx.x;
    if (b >= NMAIN) { helper_cta(P, smem); return; }
    const int tg = b >> 2, hg = b & 3;

    const int warp = __shfl_sync(0xffffffffu, tid >> 5, 0);
    const int wg = warp >> 2, ww = warp & 3, g = lane >> 2, t4 = lane & 3, t128 = tid & 127;
    if (lane == 0) {
#pragma unroll
        for (int i = 0; i < 4; i++) {
            const uint32_t id = warp + 16 * i;
            if (id < NBAR) mbar_init(mb + id * 8, id >= MB_DONE ? 16 : (id >= MB_W1 && id < MB_F2) ? 3 : id < MB_KV ? 2 : 1);
        }
        fence_async_smem();
    }
    __syncwarp();
    uint4 xv[4][2];
    unsigned epoch = 0;
    {
        const int r = warp * 4;
        const uint4* src = reinterpret_cast<const uint4*>(P.x + (size_t)((r & 31) + tg * 32 + (r >> 5) * 1024) * D) + lane;
#pragma unroll
        for (int i = 0; i < 4; i++) { xv[i][0] = ldg_relaxed(src + i * 64); xv[i][1] = ldg_relaxed(src + i * 64 + 32); }
        const uint4 wkv = ldg_relaxed(reinterpret_cast<const uint4*>(hg < 2 ? P.wk : P.wv) + tid * 2 + (hg & 1));
        if (lane == 0) {
            if (warp == 0) {
                asm volatile("cp.async.bulk.prefetch.L2.global [%0], %1;" :: "l"((const char*)P.wqp + b * 4096), "r"(4096) : "memory");
            } else if (warp == 3) {
                asm volatile("prefetch.tensormap [%0];" :: "l"(&P.wq) : "memory");
            } else if (warp < 4) {
            } else if (warp < 7) {
                asm volatile("prefetch.tensormap [%0];" :: "l"(&P.wo + (warp - 4)) : "memory");
            } else if (warp == 7) {
                asm volatile("ld.relaxed.gpu.global.u32 %0, [%1];" : "=r"(epoch) : "l"(g_epoch + b) : "memory");
            }
        }
        if (warp == 8 && lane < 8) sts32(mb + MISC_CNT + lane * 4, 0);
        __syncwarp();
        TS(16);
        sts128(sb + SM_WKV + tid * 16, wkv.x, wkv.y, wkv.z, wkv.w);
    }
    float dlt[4];
    {
        float st[4];
#pragma unroll
        for (int i = 0; i < 4; i++) {
            const uint32_t s = add_bf16x2(add_bf16x2(add_bf16x2(xv[i][0].x, xv[i][0].y), add_bf16x2(xv[i][0].z, xv[i][0].w)),
                                          add_bf16x2(add_bf16x2(xv[i][1].x, xv[i][1].y), add_bf16x2(xv[i][1].z, xv[i][1].w)));
            st[i] = bf_lo(s) + bf_hi(s);
        }
        TS(13);
        if (lane == 0 && warp < 4) { load_wq(sb, P, warp, 0); if (warp < 3) load_wq(sb, P, warp, 1); }
        __syncwarp();
#pragma unroll
        for (int o = 16; o > 0; o >>= 1)
#pragma unroll
            for (int i = 0; i < 4; i++) st[i] += __shfl_xor_sync(0xffffffffu, st[i], o);
#pragma unroll
        for (int i = 0; i < 4; i++) {
            const float nmean = st[i] * (-1.0f / D);
            const uint32_t nm = pack_bf16(nmean, nmean);
            dlt[i] = bf_lo(nm) - nmean;
            const int r = warp * 4 + i;
#pragma unroll
            for (int c = 0; c < 2; c++) {
                xv[i][c].x = add_bf16x2(xv[i][c].x, nm); xv[i][c].y = add_bf16x2(xv[i][c].y, nm);
                xv[i][c].z = add_bf16x2(xv[i][c].z, nm); xv[i][c].w = add_bf16x2(xv[i][c].w, nm);
                sts128(sb + SM_XN + ((lane >> 3) + 4 * c) * 8192 + r * 128 + (((lane & 7) ^ (r & 7)) << 4), xv[i][c].x, xv[i][c].y, xv[i][c].z, xv[i][c].w);
            }
        }
    }
    fence_async_smem();
    if (tid == 7 * 32) { sts32(mb + MISC_EPOCH, epoch + 1); g_epoch[b] = epoch + 1; }
    TS(0);
    __syncthreads();
    auto variances = [&]()
    {
        float st[4];
#pragma unroll
        for (int i = 0; i < 4; i++) {
            float v0 = 0.f, v1 = 0.f;
#pragma unroll
            for (int c = 0; c < 2; c++) {
                const uint32_t w[4] = {xv[i][c].x, xv[i][c].y, xv[i][c].z, xv[i][c].w};
#pragma unroll
                for (int k = 0; k < 4; k++) { v0 = fmaf(bf_lo(w[k]), bf_lo(w[k]), v0); v1 = fmaf(bf_hi(w[k]), bf_hi(w[k]), v1); }
            }
            st[i] = v0 + v1;
        }
#pragma unroll
        for (int o = 16; o > 0; o >>= 1)
#pragma unroll
            for (int i = 0; i < 4; i++) st[i] += __shfl_xor_sync(0xffffffffu, st[i], o);
        const float vs = lane == 0 ? st[0] : lane == 1 ? st[1] : lane == 2 ? st[2] : st[3];
        const float dl = lane == 0 ? dlt[0] : lane == 1 ? dlt[1] : lane == 2 ? dlt[2] : dlt[3];
        if (lane < 4) sts32(mb + MISC_RSTD + (warp * 4 + lane) * 4, __float_as_uint(rsqrtf(fmaxf(vs * (1.0f / D) - dl * dl, 0.f) + 1e-5f)));
    };
    float kv[4] = {0.f, 0.f, 0.f, 0.f};
    if (wg == 2) {
        fence_regs(kv);
        const uint64_t da = mkdesc(sb + SM_XN, 16, 1024, 1), db = mkdesc(sb + SM_WKV, 128, 16, 0);
        wg_fence();
#pragma unroll
        for (int s = 0; s < 32; s++) mma_ss8(kv, da + (s >> 2) * 512 + (s & 3) * 2, db + s * 16);
        wg_commit();
        TS(18);
        variances();
        TS(19);
        wg_wait<0>(); fence_regs(kv);
        TS(20);
    } else {
        variances();
        TS(19);
    }
    __syncthreads();
    if (tid == 13 * 32) load_wq(sb, P, 3, 1);
    __syncwarp();
    const float rs0 = __uint_as_float(lds32(mb + MISC_RSTD + (ww * 16 + g) * 4)), rs1 = __uint_as_float(lds32(mb + MISC_RSTD + (ww * 16 + g + 8) * 4));
    constexpr float QSCALE = 0.25f * 1.4426950408889634f;
    uint32_t kvoff[2];
#pragma unroll
    for (int i = 0; i < 2; i++) {
        const int t = ((ww & 1) * 16 + g + 8 * i), c = 2 * tg + (ww >> 1), ts = (t + 31) & 31;
        kvoff[i] = hg < 2 ? (ts >> 3) * 32768 + (ts & 7) * 2048 + (c >> 3) * 256 + (hg & 1) * 128 + (c & 7) * 16 + t4 * 4
                          : (t >> 3) * 32768 + 16384 + (hg & 1) * 8192 + ((t & 7) * 64 + c) * 16 + t4 * 4;
    }
    float qa[32];
    if (wg < 2) {
#pragma unroll
        for (int i = 0; i < 32; i++) qa[i] = 0.f;
        fence_regs(qa);
        const uint64_t da = mkdesc(sb + SM_XN, 16, 1024, 1), db = mkdesc(sb + SM_WQ + wg * 65536, 16, 1024, 1);
#pragma unroll 1
        for (int i = 0; i < 4; i++) {
            mbar_wait(mb + (MB_WQ + i) * 8);
            if (i == 0) TS(21); if (i == 3) TS(22);
            wg_fence();
#pragma unroll
            for (int s = 0; s < 8; s++) mma_ss64(qa, da + (i * 2 + (s >> 2)) * 512 + (s & 3) * 2, db + (i * 8 + s) * 128);
            wg_commit();
        }
        wg_wait<0>();
        fence_regs(qa);
        bar_arrive(6, 512);
        TS(1);
        bar_sync(1, 256);
        float nn[8];
#pragma unroll
        for (int i = 0; i < 32; i++) qa[i] *= ((i & 2) ? rs1 : rs0) * QSCALE;
#pragma unroll
        for (int h = 0; h < 4; h++) {
            const uint32_t base = sb + SM_Q + ((ww >> 1) * 4 + wg * 2 + (h >> 1)) * 2048 + ((h & 1) * 4 + (ww & 1) * 2) * 256 + lane * 4;
            sts32(base, pack_f16(qa[8 * h], qa[8 * h + 1])); sts32(base + 256, pack_f16(qa[8 * h + 2], qa[8 * h + 3]));
            sts32(base + 128, pack_f16(qa[8 * h + 4], qa[8 * h + 5])); sts32(base + 384, pack_f16(qa[8 * h + 6], qa[8 * h + 7]));
            nn[2 * h] = qa[8 * h] * qa[8 * h] + qa[8 * h + 1] * qa[8 * h + 1] + qa[8 * h + 4] * qa[8 * h + 4] + qa[8 * h + 5] * qa[8 * h + 5];
            nn[2 * h + 1] = qa[8 * h + 2] * qa[8 * h + 2] + qa[8 * h + 3] * qa[8 * h + 3] + qa[8 * h + 6] * qa[8 * h + 6] + qa[8 * h + 7] * qa[8 * h + 7];
        }
#pragma unroll
        for (int o = 1; o < 4; o <<= 1)
#pragma unroll
            for (int i = 0; i < 8; i++) nn[i] += __shfl_xor_sync(0xffffffffu, nn[i], o);
        uint32_t nm = 0;
#pragma unroll
        for (int i = 0; i < 8; i++) nm = max(nm, __float_as_uint(nn[i]));
        nm = __reduce_max_sync(0xffffffffu, nm);
        if (lane == 0) asm volatile("red.shared.max.u32 [%0], %1;" :: "r"(mb + MISC_NRM), "r"(nm) : "memory");
    } else {
        if (wg == 2) {
            kv[0] *= rs0; kv[1] *= rs0; kv[2] *= rs1; kv[3] *= rs1;
            char* img = reinterpret_cast<char*>(g_kv);
            if (hg < 2) {
                const int r0 = ww * 16 + g;
                float2* kt = reinterpret_cast<float2*>(smem + SM_MISC + MISC_K0);
                kt[r0 * 4 + t4] = make_float2(kv[0], kv[1]);
                kt[(r0 + 8) * 4 + t4] = make_float2(kv[2], kv[3]);
                bar_sync(2, 128);
                float2 p0 = make_float2(0.f, 0.f);
                if (r0 & 31) p0 = kt[(r0 - 1) * 4 + t4];
                const float2 p1 = kt[(r0 + 7) * 4 + t4];
                stg32(img + kvoff[0], nonzero(pack_f16(kv[0] - p0.x, kv[1] - p0.y)));
                stg32(img + kvoff[1], nonzero(pack_f16(kv[2] - p1.x, kv[3] - p1.y)));
            } else {
                stg32(img + kvoff[0], nonzero(pack_bf16(kv[0], kv[1])));
                stg32(img + kvoff[1], nonzero(pack_bf16(kv[2], kv[3])));
            }
            TS(22);
            uint32_t nm = max(__float_as_uint(quad_sum(kv[0] * kv[0] + kv[1] * kv[1])), __float_as_uint(quad_sum(kv[2] * kv[2] + kv[3] * kv[3])));
            nm = __reduce_max_sync(0xffffffffu, nm);
            if (lane == 0) stg32(reinterpret_cast<uint32_t*>(g_nrm + b) + ww, nm | 1u);
            if (hg < 2) {
#pragma unroll
                for (int i = 0; i < 2; i++)
                    stg32(reinterpret_cast<char*>(g_kplain) + (kvoff[i] >> 15) * 16384 + (kvoff[i] & 16383), pack_bf16(kv[2 * i], kv[2 * i + 1]));
            }
            TS(1);
            bar_sync(2, 128);
            if (t128 == 0) asm volatile("red.release.gpu.global.add.u32 [%0], 1;" :: "l"(&g_count1) : "memory");
            __syncwarp();
        } else {
            uint4 v; int spins = 0;
            do { v = ldg_relaxed(g_nrm + t128); } while (__any_sync(0xffffffffu, has_zero(v)) && ++spins < SPIN_LIMIT);
            uint32_t nm = max(max(v.x, v.y), max(v.z, v.w));
            nm = max(nm, __shfl_xor_sync(0xffffffffu, nm, 4)); nm = max(nm, __shfl_xor_sync(0xffffffffu, nm, 8)); nm = max(nm, __shfl_xor_sync(0xffffffffu, nm, 16));
            if (lane < 4) asm volatile("red.shared.max.u32 [%0], %1;" :: "r"(mb + MISC_NRM + 4 + min(lane, 2) * 4), "r"(nm) : "memory");
            TS(1);
        }
        bar_sync(5, 256);
        const int t256 = tid - 256;
        uint4 kc[9]; int spins = 0; bool bad;
        do {
            bad = false;
#pragma unroll
            for (int i = 0; i < 8; i++) kc[i] = ldg_relaxed(g_kv + i * 256 + t256);
            kc[8] = ldg_relaxed(g_kv + 3 * 2048 + 7 * 128 + t128);
#pragma unroll
            for (int i = 0; i < 9; i++) bad |= has_zero(kc[i]);
        } while (__any_sync(0xffffffffu, bad) && ++spins < SPIN_LIMIT);
        TS(2);
        if (warp == 15) wait_count(&g_count1, lds32(mb + MISC_EPOCH) * NMAIN);
        bar_sync(6, 512);
        if (tid == 15 * 32) {
            asm volatile("fence.proxy.async.global;" ::: "memory");
#pragma unroll
            for (int c = 1; c < 4; c++) { mbar_expect(mb + (MB_KV + c) * 8, 32768); bulk_g2s(sb + c * KVCH, g_kv + c * 2048, 32768, mb + (MB_KV + c) * 8); }
        }
        __syncwarp();
#pragma unroll
        for (int i = 0; i < 8; i++) sts128(sb + (i * 256 + t256) * 16, kc[i].x, kc[i].y, kc[i].z, kc[i].w);
        if (wg == 3) sts128(mb + MISC_K0 + t128 * 16, kc[8].x, kc[8].y, kc[8].z, kc[8].w);
#pragma unroll
        for (int i = 0; i < 8; i++) sts128(sb + (i >> 1) * KVCH + 32768 + (i & 1) * 4096 + t256 * 16, 0x3F803F80u, 0x3F803F80u, 0x3F803F80u, 0x3F803F80u);
    }
    fence_async_smem();
    TS(3);
    __syncthreads();
    const float q2 = __uint_as_float(lds32(mb + MISC_NRM)), v2 = __uint_as_float(lds32(mb + MISC_NRM + 12));
    const float k2 = __uint_as_float(lds32(mb + MISC_NRM + 4)) + __uint_as_float(lds32(mb + MISC_NRM + 8));
    const bool safe = __all_sync(0xffffffffu, (q2 * k2 <= 3500.0f) && (q2 <= 65536.0f) && (k2 <= 65536.0f) && (v2 <= 1e24f));
    TS(4);

    if (__builtin_expect(safe, 1)) {
        attention<true>(P, sb, warp TS_PASS);
    } else {
        if (wg < 2) {
#pragma unroll
            for (int h = 0; h < 4; h++) {
                const uint32_t base = sb + SM_Q + ((ww >> 1) * 4 + wg * 2 + (h >> 1)) * 2048 + ((h & 1) * 4 + (ww & 1) * 2) * 256 + lane * 4;
                sts32(base, pack_bf16(qa[8 * h], qa[8 * h + 1])); sts32(base + 256, pack_bf16(qa[8 * h + 2], qa[8 * h + 3]));
                sts32(base + 128, pack_bf16(qa[8 * h + 4], qa[8 * h + 5])); sts32(base + 384, pack_bf16(qa[8 * h + 6], qa[8 * h + 7]));
            }
            fence_async_smem();
        } else if (warp == 15) {
            for (int c = 1; c < 4; c++) mbar_wait(mb + (MB_KV + c) * 8);
            if (lane == 0) {
                asm volatile("fence.proxy.async;" ::: "memory");
                mbar_expect(mb + MB_KV * 8, 4 * 16384 + 2048);
                for (int c = 0; c < 4; c++) bulk_g2s(sb + c * KVCH, g_kplain + c * 1024, 16384, mb + MB_KV * 8);
                bulk_g2s(mb + MISC_K0, g_kplain + 3 * 1024 + 7 * 128, 2048, mb + MB_KV * 8);
            }
            __syncwarp();
        }
        __syncthreads();
        mbar_wait(mb + MB_KV * 8);
        attention<false>(P, sb, warp TS_PASS);
    }

    const int pr = 1 - (wg >> 1), q = wg & 1;
    const int mt = 16 * pr + (b >> 3), j = b & 7;
    const int row0 = mt * 64 + ww * 16 + g;
    uint32_t hk[8];
    {
        const uint32_t* xp = reinterpret_cast<const uint32_t*>(P.x + (size_t)row0 * D + j * 64 + q * 32 + t4 * 2);
#pragma unroll
        for (int i = 0; i < 4; i++) { hk[2 * i] = __ldg(xp + i * 4); hk[2 * i + 1] = __ldg(xp + i * 4 + 8 * (D / 2)); }
    }
    mbar_wait(mb + MB_F2 * 8);
    if (warp < 5) {
        mbar_wait(mb + (MB_DONE + 4) * 8);
        if (lane == 0) { if (warp < 3) load_w1(sb, P, 9 + warp); else load_w2(sb, P, warp - 3); }
    } else if (warp == 5) {
        if (lane < 22) {
            const uint4 v = ldg_relaxed(reinterpret_cast<const uint4*>(g_cs + (b & 15) * 88) + lane);
            sts128(mb + MISC_CS + lane * 16, v.x, v.y, v.z, v.w);
        }
        warp_done(mb + MB_CS * 8);
    }
    __syncwarp();
#pragma unroll 1
    for (int ph = 0; ph < 2; ph++) {
        float r[16];
        {
            const uint4* a = (ph ? g_Hf + mt * 88 * 128 : g_of + mt * 32 * 128) + q * 512 + t128;
            const int nblk = ph ? 11 : 4;
            uint64_t slots = ph ? (q ? pack_slots(true, 1) : pack_slots(true, 0)) : (q ? pack_slots(false, 1) : pack_slots(false, 0));
            uint32_t bar = mb + ((ph ? MB_W2 : MB_WO) + q) * 8;
            float acc[32];
            uint4 buf[4][4];
            fill_ring<4>(buf, a, 1024);
            TS(23 + 2 * ph);
#pragma unroll
            for (int i = 0; i < 32; i++) acc[i] = 0.f;
            fence_regs(acc);
#pragma unroll 1
            for (int i0 = 0; i0 < nblk; i0 += 4) {
#pragma unroll
                for (int i = 0; i < 4; i++) {
                    const int blk = i0 + i;
                    if (blk < nblk) {
                        const uint64_t db = mkdesc(sb + ((uint32_t)slots & 31) * 8192, 16, 1024, 1);
                        mbar_wait(bar);
                        check_batch(buf[i], a + blk * 1024);
                        wg_fence();
#pragma unroll
                        for (int s = 0; s < 4; s++) mma_rs(acc, buf[i][s], db + s * 128);
                        wg_commit();
                        slots >>= 5; bar += 16;
                        wg_wait<1>();
                        if (blk >= 1 && blk + 3 < nblk) load_batch(buf[(i + 3) & 3], a + (blk + 3) * 1024);
                    }
                }
            }
            wg_wait<0>();
            fence_regs(acc);
            TS(7 + 4 * ph);
            if (ph == 0) {
                warp_done(mb + (MB_DONE + 5) * 8);
                mbar_wait(mb + (MB_DONE + 4 * pr) * 8);
            }
            pair_reduce(acc, r, sb + SM_Q + pr * 8192 + t128 * 16, q, 3 + pr);
        }
#pragma unroll
        for (int i = 0; i < 8; i++) hk[i] = pack_bf16(r[2 * i] + bf_lo(hk[i]), r[2 * i + 1] + bf_hi(hk[i]));
        if (ph == 1) break;
        {
            uint4* hp = g_hf + (mt * 32 + j * 4 + 2 * q) * 128 + t128;
            stg128(hp, hk[0], hk[1], hk[2], hk[3]);
            stg128(hp + 128, hk[4], hk[5], hk[6], hk[7]);
            float s0 = 0.f, s1 = 0.f;
#pragma unroll
            for (int i = 0; i < 8; i++) {
                r[2 * i] = bf_lo(hk[i]); r[2 * i + 1] = bf_hi(hk[i]);
                if (i & 1) s1 += r[2 * i] + r[2 * i + 1]; else s0 += r[2 * i] + r[2 * i + 1];
            }
            s0 += __shfl_xor_sync(0xffffffffu, s0, 1); s1 += __shfl_xor_sync(0xffffffffu, s1, 1);
            s0 += __shfl_xor_sync(0xffffffffu, s0, 2); s1 += __shfl_xor_sync(0xffffffffu, s1, 2);
            const float a0 = s0 * (1.0f / 32), a1 = s1 * (1.0f / 32);
            float v0 = 0.f, v1 = 0.f;
#pragma unroll
            for (int i = 0; i < 8; i++) {
                const float a = (i & 1) ? a1 : a0;
                const float d0 = r[2 * i] - a, d1 = r[2 * i + 1] - a;
                if (i & 1) v1 += d0 * d0 + d1 * d1; else v0 += d0 * d0 + d1 * d1;
            }
            v0 += __shfl_xor_sync(0xffffffffu, v0, 1); v1 += __shfl_xor_sync(0xffffffffu, v1, 1);
            v0 += __shfl_xor_sync(0xffffffffu, v0, 2); v1 += __shfl_xor_sync(0xffffffffu, v1, 2);
            if (t4 < 2) stg64(g_stats + (row0 + 8 * t4) * 16 + j * 2 + q, __float_as_uint(t4 ? s1 : s0), __float_as_uint(t4 ? v1 : v0));
            TS(8);
            if (warp < 8) {
                mbar_wait(mb + (MB_DONE + 5) * 8);
                if (lane == 0) load_w2(sb, P, 2 + warp);
                __syncwarp();
            } else if (wg == 2) {
                if (kvoff[0] < 32768 || kvoff[0] >= 3 * 32768) stg32(reinterpret_cast<char*>(g_kv) + kvoff[0], 0u);
                if (kvoff[1] < 32768) stg32(reinterpret_cast<char*>(g_kv) + kvoff[1], 0u);
                if (lane == 0) stg32(reinterpret_cast<uint32_t*>(g_nrm + b) + ww, 0u);
            }
        }
        {
            const int mt1 = 16 * pr + (b >> 4) * 2 + q, sl = b & 15;
            const uint4* a = g_hf + mt1 * 32 * 128 + t128;
            float acc[44], nmean[2], hrstd[2];
            uint4 buf[3][4];
            fill_ring<3>(buf, a, 512);
            TS(24);
            {
                const uint4* sp = reinterpret_cast<const uint4*>(g_stats + (mt1 * 64 + ww * 16 + g) * 16 + t4 * 4);
                uint4 u[4]; int spins = 0;
                do { u[0] = ldg_relaxed(sp); u[1] = ldg_relaxed(sp + 1); u[2] = ldg_relaxed(sp + 64); u[3] = ldg_relaxed(sp + 65); } while (batch_bad(u) && ++spins < SPIN_LIMIT);
                float mean[2], m2[2];
#pragma unroll
                for (int i = 0; i < 2; i++) mean[i] = (__uint_as_float(u[2 * i].x) + __uint_as_float(u[2 * i].z)) + (__uint_as_float(u[2 * i + 1].x) + __uint_as_float(u[2 * i + 1].z));
                mean[0] += __shfl_xor_sync(0xffffffffu, mean[0], 1); mean[1] += __shfl_xor_sync(0xffffffffu, mean[1], 1);
                mean[0] += __shfl_xor_sync(0xffffffffu, mean[0], 2); mean[1] += __shfl_xor_sync(0xffffffffu, mean[1], 2);
#pragma unroll
                for (int i = 0; i < 2; i++) {
                    mean[i] *= 1.0f / D;
                    const float da = __uint_as_float(u[2 * i].x) * (1.0f / 32) - mean[i], dc = __uint_as_float(u[2 * i].z) * (1.0f / 32) - mean[i];
                    const float de = __uint_as_float(u[2 * i + 1].x) * (1.0f / 32) - mean[i], df = __uint_as_float(u[2 * i + 1].z) * (1.0f / 32) - mean[i];
                    m2[i] = (__uint_as_float(u[2 * i].y) + __uint_as_float(u[2 * i].w)) + (__uint_as_float(u[2 * i + 1].y) + __uint_as_float(u[2 * i + 1].w)) + 32.0f * (da * da + dc * dc + de * de + df * df);
                }
                m2[0] += __shfl_xor_sync(0xffffffffu, m2[0], 1); m2[1] += __shfl_xor_sync(0xffffffffu, m2[1], 1);
                m2[0] += __shfl_xor_sync(0xffffffffu, m2[0], 2); m2[1] += __shfl_xor_sync(0xffffffffu, m2[1], 2);
#pragma unroll
                for (int i = 0; i < 2; i++) { hrstd[i] = 0.5f * rsqrtf(m2[i] * (1.0f / D) + 1e-5f); nmean[i] = -mean[i]; }
            }
            TS(26);
#pragma unroll
            for (int i = 0; i < 44; i++) acc[i] = 0.f;
            fence_regs(acc);
#pragma unroll 1
            for (int i0 = 0; i0 < 8; i0 += 3) {
#pragma unroll
                for (int i = 0; i < 3; i++) {
                    const int blk = i0 + i;
                    if (blk < 8) {
                        const uint64_t db = mkdesc(sb + SM_W1 + (blk >> 1) * 24576 + (blk & 1) * 4096, 8192, 512, 2);
                        mbar_wait(mb + (MB_W1 + (blk >> 1)) * 8);
                        check_batch(buf[i], a + blk * 512);
                        wg_fence();
#pragma unroll
                        for (int s = 0; s < 4; s++) mma_rs(acc, buf[i][s], db + s * 64);
                        wg_commit();
                        wg_wait<1>();
                        if (blk >= 1 && blk + 2 < 8) load_batch(buf[(i + 2) % 3], a + (blk + 2) * 512);
                        if (blk >= 2 && !(blk & 1)) release_w1(sb, P, (blk >> 1) - 1);
                    }
                }
            }
            wg_wait<0>();
            fence_regs(acc);
            release_w1(sb, P, 3);
            TS(9);
            mbar_wait(mb + MB_CS * 8);
            uint32_t hv[22];
#pragma unroll
            for (int i = 0; i < 11; i++) {
                float2 cs;
                asm volatile("ld.shared.v2.f32 {%0,%1}, [%2];" : "=f"(cs.x), "=f"(cs.y) : "r"(mb + MISC_CS + i * 32 + t4 * 8));
                hv[2 * i] = pack_bf16(silu2(hrstd[0] * fmaf(nmean[0], cs.x, acc[4 * i])), silu2(hrstd[0] * fmaf(nmean[0], cs.y, acc[4 * i + 1])));
                hv[2 * i + 1] = pack_bf16(silu2(hrstd[1] * fmaf(nmean[1], cs.x, acc[4 * i + 2])), silu2(hrstd[1] * fmaf(nmean[1], cs.y, acc[4 * i + 3])));
            }
            uint4* hb = g_Hf + (mt1 * 88 + (sl >> 1) * 11) * 128 + t128;
            if (sl & 1) {
                stg64(reinterpret_cast<uint2*>(hb + 5 * 128) + 1, hv[0], hv[1]);
#pragma unroll
                for (int i = 0; i < 5; i++) stg128(hb + (6 + i) * 128, hv[2 + 4 * i], hv[3 + 4 * i], hv[4 + 4 * i], hv[5 + 4 * i]);
            } else {
#pragma unroll
                for (int i = 0; i < 5; i++) stg128(hb + i * 128, hv[4 * i], hv[4 * i + 1], hv[4 * i + 2], hv[4 * i + 3]);
                stg64(hb + 5 * 128, hv[20], hv[21]);
            }
            TS(10);
        }
    }
#pragma unroll
    for (int h = 0; h < 2; h++) {
        uint32_t v0 = hk[h], v1 = hk[2 + h], v2 = hk[4 + h], v3 = hk[6 + h];
        const bool o1 = t4 & 1, o2 = t4 & 2;
        uint32_t a = __shfl_xor_sync(0xffffffffu, o1 ? v0 : v1, 1), c = __shfl_xor_sync(0xffffffffu, o1 ? v2 : v3, 1);
        if (o1) { v0 = a; v2 = c; } else { v1 = a; v3 = c; }
        a = __shfl_xor_sync(0xffffffffu, o2 ? v0 : v2, 2); c = __shfl_xor_sync(0xffffffffu, o2 ? v1 : v3, 2);
        if (o2) { v0 = a; v1 = c; } else { v2 = a; v3 = c; }
        *reinterpret_cast<uint4*>(P.out + (size_t)(row0 + 8 * h) * D + j * 64 + q * 32 + t4 * 8) = make_uint4(v0, v1, v2, v3);
    }
    TS(12);
}

typedef CUresult (*EncodeFn)(CUtensorMap*, CUtensorMapDataType, cuuint32_t, void*, const cuuint64_t*, const cuuint64_t*, const cuuint32_t*,
                             const cuuint32_t*, CUtensorMapInterleave, CUtensorMapSwizzle, CUtensorMapL2promotion, CUtensorMapFloatOOBfill);

void encode2d(EncodeFn fn, CUtensorMap* tm, const void* ptr, int rows, int cols, int box_rows, int box_cols, CUtensorMapSwizzle sw) {
    cuuint64_t dims[2] = {(cuuint64_t)cols, (cuuint64_t)rows};
    cuuint64_t strides[1] = {(cuuint64_t)cols * 2};
    cuuint32_t box[2] = {(cuuint32_t)box_cols, (cuuint32_t)box_rows};
    cuuint32_t es[2] = {1, 1};
    fn(tm, CU_TENSOR_MAP_DATA_TYPE_BFLOAT16, 2, const_cast<void*>(ptr), dims, strides, box, es, CU_TENSOR_MAP_INTERLEAVE_NONE, sw,
       CU_TENSOR_MAP_L2_PROMOTION_L2_128B, CU_TENSOR_MAP_FLOAT_OOB_FILL_NONE);
}

}

extern "C" void kernel_launch(void* const* d_in, const int* in_sizes, int n_in, void* d_out, int out_size) {
    (void)in_sizes; (void)n_in; (void)out_size;
    void* fnp = nullptr;
    cudaDriverEntryPointQueryResult qr;
    cudaGetDriverEntryPoint("cuTensorMapEncodeTiled", &fnp, cudaEnableDefault, &qr);
    EncodeFn fn = (EncodeFn)fnp;
    Params P;
    encode2d(fn, &P.wq, d_in[1], D, D, 128, 64, CU_TENSOR_MAP_SWIZZLE_128B);
    P.wk = (const __nv_bfloat16*)d_in[2];
    P.wv = (const __nv_bfloat16*)d_in[3];
    encode2d(fn, &P.wo, d_in[4], D, D, 64, 64, CU_TENSOR_MAP_SWIZZLE_128B);
    encode2d(fn, &P.w1, d_in[6], D, FF, 128, 32, CU_TENSOR_MAP_SWIZZLE_64B);
    encode2d(fn, &P.w2, d_in[7], FF, D, 64, 64, CU_TENSOR_MAP_SWIZZLE_128B);
    P.x = (const __nv_bfloat16*)d_in[0];
    P.w1p = (const __nv_bfloat16*)d_in[6];
    P.w2p = (const __nv_bfloat16*)d_in[7];
    P.wop = (const __nv_bfloat16*)d_in[4];
    P.wqp = (const __nv_bfloat16*)d_in[1];
    P.out = (__nv_bfloat16*)d_out;
    P.neg1 = 0xFFFFFFFFu;
    cudaFuncSetAttribute(fused_kernel, cudaFuncAttributeMaxDynamicSharedMemorySize, SMEM_BYTES);
    fused_kernel<<<NCTA, 512, SMEM_BYTES>>>(P);
}
```

```cpp
#include <cuda_runtime.h>
#include <cuda_bf16.h>
#include <cuda.h>
#include <stdint.h>

namespace {

constexpr int D = 512, FF = 1376;
constexpr int NMAIN = 128, NHELP = 4, NCTA = NMAIN + NHELP;
constexpr uint32_t SENT = 0xFFFFFFFFu;
constexpr int SPIN_LIMIT = 1 << 22;

constexpr uint32_t KB = 1024;
constexpr uint32_t SM_XN = 0;
constexpr uint32_t SM_WQ = 64 * KB;
constexpr uint32_t SM_WKV = 176 * KB;
constexpr uint32_t SM_K = 0;
constexpr uint32_t SM_V = 64 * KB;
constexpr uint32_t SM_Q = 160 * KB;
constexpr uint32_t SM_SENT = 184 * KB;
constexpr uint32_t SM_MISC = 192 * KB;
constexpr uint32_t SMEM_BYTES = 195 * KB;
constexpr uint32_t MB_WQ = 0;
constexpr uint32_t MB_W1 = 4;
constexpr uint32_t MB_DONE = 8;
constexpr uint32_t MB_KV = 14;
constexpr uint32_t MB_WO = 16;
constexpr uint32_t MB_W2 = 24;
constexpr uint32_t MB_F2 = 46;
constexpr uint32_t MB_CS = 47;
constexpr uint32_t MISC_CNT = 384;
constexpr uint32_t MISC_NRM = 400;
constexpr uint32_t MISC_EPOCH = 416;
constexpr uint32_t MISC_CS = 448;
constexpr uint32_t MISC_RSTD = 448;
constexpr uint32_t MISC_KTMP = 1024;

__host__ __device__ constexpr uint32_t wo_slot(int kb) { return kb < 2 ? 22 + kb : kb - 2; }
__host__ __device__ constexpr uint32_t w2_slot(int kb) { return kb < 2 ? 6 + kb : kb < 4 ? 20 + kb : kb < 10 ? kb - 4 : 8 + (kb - 10) / 3 + 4 * ((kb - 10) % 3); }

struct Small {
    unsigned epoch[NCTA + 4];
    unsigned count1, pad1[31];
    unsigned count2, pad2[31];
    float cs[1408];
    uint4 nrm[NMAIN];
    uint4 kv[8192];
    uint4 kplain[4096];
};
__device__ Small g_s;
constexpr int X_OF = 0, X_HF = 32 * 32 * 128, X_ST = X_HF + 32 * 32 * 128, X_H = X_ST + 32 * 64 * 8, X_END = X_H + 32 * 88 * 128;
constexpr int X_ARM = 16 * 32 * 128, X_SHARE = (X_END - X_ARM) / NMAIN;
__device__ uint4 g_x[X_END];
#define TS(i) do {} while (0)

__device__ __forceinline__ void mbar_init(uint32_t bar, int cnt) { asm volatile("mbarrier.init.shared::cta.b64 [%0], %1;" :: "r"(bar), "r"(cnt) : "memory"); }
__device__ __forceinline__ void mbar_expect(uint32_t bar, uint32_t bytes) { asm volatile("mbarrier.arrive.expect_tx.shared::cta.b64 _, [%0], %1;" :: "r"(bar), "r"(bytes) : "memory"); }
__device__ __forceinline__ void mbar_arrive(uint32_t bar) { asm volatile("mbarrier.arrive.shared::cta.b64 _, [%0];" :: "r"(bar) : "memory"); }
__device__ __forceinline__ void mbar_wait(uint32_t bar) {
    uint32_t done; int spins = 0;
    do {
        asm volatile("{.reg .pred p; mbarrier.try_wait.parity.shared::cta.b64 p, [%1], 0; selp.u32 %0, 1, 0, p;}" : "=r"(done) : "r"(bar) : "memory");
    } while (!__all_sync(0xffffffffu, done) && ++spins < SPIN_LIMIT);
}
__device__ __forceinline__ void tma2d(uint32_t dst, const CUtensorMap* tm, int c0, int c1, uint32_t bar) {
    asm volatile("cp.async.bulk.tensor.2d.shared::cluster.global.mbarrier::complete_tx::bytes [%0], [%1, {%3, %4}], [%2];"
                 :: "r"(dst), "l"(tm), "r"(bar), "r"(c0), "r"(c1) : "memory");
}
__device__ __forceinline__ void bulk_g2s(uint32_t dst, const void* src, uint32_t bytes, uint32_t bar) {
    asm volatile("cp.async.bulk.shared::cluster.global.mbarrier::complete_tx::bytes [%0], [%1], %2, [%3];" :: "r"(dst), "l"(src), "r"(bytes), "r"(bar) : "memory");
}
__device__ __forceinline__ void fence_async_smem() { asm volatile("fence.proxy.async.shared::cta;" ::: "memory"); }
__device__ __forceinline__ void bar_sync(int id, int n) { asm volatile("bar.sync %0, %1;" :: "r"(id), "r"(n) : "memory"); }
__device__ __forceinline__ void bar_arrive(int id, int n) { asm volatile("bar.arrive %0, %1;" :: "r"(id), "r"(n) : "memory"); }
__device__ __forceinline__ void wg_fence() { asm volatile("wgmma.fence.sync.aligned;" ::: "memory"); }
__device__ __forceinline__ void wg_commit() { asm volatile("wgmma.commit_group.sync.aligned;" ::: "memory"); }
template <int N> __device__ __forceinline__ void wg_wait() { asm volatile("wgmma.wait_group.sync.aligned %0;" :: "n"(N) : "memory"); }
template <int N> __device__ __forceinline__ void fence_regs(float (&d)[N]) {
#pragma unroll
    for (int i = 0; i < N; i++) asm volatile("" : "+f"(d[i]) :: "memory");
}
template <int N> __device__ __forceinline__ void fence_regs(uint32_t (&d)[N]) {
#pragma unroll
    for (int i = 0; i < N; i++) asm volatile("" : "+r"(d[i]) :: "memory");
}
__device__ __forceinline__ uint64_t mkdesc(uint32_t addr, uint32_t lbo, uint32_t sbo, uint32_t swz) {
    return (uint64_t)(((addr & 0x3FFFF) >> 4) | ((lbo >> 4) << 16)) | ((uint64_t)((sbo >> 4) | (swz << 30)) << 32);
}
__device__ __forceinline__ float ex2(float x) { float y; asm("ex2.approx.ftz.f32 %0, %1;" : "=f"(y) : "f"(x)); return y; }
__device__ __forceinline__ float rcp(float x) { float y; asm("rcp.approx.ftz.f32 %0, %1;" : "=f"(y) : "f"(x)); return y; }
__device__ __forceinline__ uint32_t pack_bf16(float lo, float hi) { uint32_t r; asm("cvt.rn.bf16x2.f32 %0, %1, %2;" : "=r"(r) : "f"(hi), "f"(lo)); return r; }
__device__ __forceinline__ uint32_t pack_f16(float lo, float hi) { uint32_t r; asm("cvt.rn.f16x2.f32 %0, %1, %2;" : "=r"(r) : "f"(hi), "f"(lo)); return r; }
__device__ __forceinline__ float bf_lo(uint32_t v) { return __uint_as_float(v << 16); }
__device__ __forceinline__ float bf_hi(uint32_t v) { return __uint_as_float(v & 0xFFFF0000u); }
__device__ __forceinline__ uint4 ldg_relaxed(const uint4* p) {
    uint4 v; asm volatile("ld.relaxed.gpu.global.v4.u32 {%0,%1,%2,%3}, [%4];" : "=r"(v.x), "=r"(v.y), "=r"(v.z), "=r"(v.w) : "l"(p) : "memory"); return v;
}
__device__ __forceinline__ void stg128(void* p, uint32_t a, uint32_t b, uint32_t c, uint32_t d) {
    asm volatile("st.relaxed.gpu.global.v4.u32 [%0], {%1,%2,%3,%4};" :: "l"(p), "r"(a), "r"(b), "r"(c), "r"(d) : "memory");
}
__device__ __forceinline__ void stg64(void* p, uint32_t a, uint32_t b) {
    asm volatile("st.relaxed.gpu.global.v2.u32 [%0], {%1,%2};" :: "l"(p), "r"(a), "r"(b) : "memory");
}
__device__ __forceinline__ void sts128(uint32_t a, uint32_t x, uint32_t y, uint32_t z, uint32_t w) {
    asm volatile("st.shared.v4.u32 [%0], {%1,%2,%3,%4};" :: "r"(a), "r"(x), "r"(y), "r"(z), "r"(w) : "memory");
}
__device__ __forceinline__ void sts32(uint32_t a, uint32_t x) { asm volatile("st.shared.u32 [%0], %1;" :: "r"(a), "r"(x) : "memory"); }
__device__ __forceinline__ float4 lds128f(uint32_t a) {
    float4 v; asm volatile("ld.shared.v4.f32 {%0,%1,%2,%3}, [%4];" : "=f"(v.x), "=f"(v.y), "=f"(v.z), "=f"(v.w) : "r"(a) : "memory"); return v;
}
__device__ __forceinline__ uint32_t lds32(uint32_t a) { uint32_t v; asm volatile("ld.shared.u32 %0, [%1];" : "=r"(v) : "r"(a) : "memory"); return v; }
__device__ __forceinline__ bool has_sent(const uint4& v) { return (v.x == SENT) | (v.w == SENT); }
__device__ __forceinline__ bool has_zero(const uint4& v) { return min(min(v.x, v.y), min(v.z, v.w)) == 0u; }
__device__ __forceinline__ uint32_t nonzero(uint32_t w) { return w == 0u ? 0x8000u : w; }
__device__ __forceinline__ void stg32(void* p, uint32_t a) { asm volatile("st.relaxed.gpu.global.u32 [%0], %1;" :: "l"(p), "r"(a) : "memory"); }
__device__ __forceinline__ void wait_count(const unsigned* p, unsigned target) {
    unsigned v; int spins = 0;
    do { asm volatile("ld.acquire.gpu.global.u32 %0, [%1];" : "=r"(v) : "l"(p) : "memory"); } while (__any_sync(0xffffffffu, v != target) && ++spins < SPIN_LIMIT);
}
__device__ __forceinline__ uint32_t warp_arrive(uint32_t cnt) {
    uint32_t old = 0;
    __syncwarp();
    if ((threadIdx.x & 31) == 0) asm volatile("atom.acq_rel.cta.shared.add.u32 %0, [%1], 1;" : "=r"(old) : "r"(cnt) : "memory");
    return __shfl_sync(0xffffffffu, old, 0);
}
__device__ __forceinline__ void warp_done(uint32_t bar) { __syncwarp(); if ((threadIdx.x & 31) == 0) mbar_arrive(bar); }
__device__ __forceinline__ uint32_t mul_bf16x2(uint32_t a, uint32_t b) { uint32_t r; asm("mul.rn.bf16x2 %0, %1, %2;" : "=r"(r) : "r"(a), "r"(b)); return r; }
__device__ __forceinline__ uint32_t fma_bf16x2(uint32_t a, uint32_t b, uint32_t c) { uint32_t r; asm("fma.rn.bf16x2 %0, %1, %2, %3;" : "=r"(r) : "r"(a), "r"(b), "r"(c)); return r; }
__device__ __forceinline__ uint32_t add_bf16x2(uint32_t a, uint32_t b) { uint32_t r; asm("add.rn.bf16x2 %0, %1, %2;" : "=r"(r) : "r"(a), "r"(b)); return r; }

#define R4(d, o) "+f"(d[o + 0]), "+f"(d[o + 1]), "+f"(d[o + 2]), "+f"(d[o + 3])
#define R8(d, o) R4(d, o), R4(d, o + 4)
#define R32(d) R8(d, 0), R8(d, 8), R8(d, 16), R8(d, 24)
#define D32 "{%0,%1,%2,%3,%4,%5,%6,%7,%8,%9,%10,%11,%12,%13,%14,%15,%16,%17,%18,%19,%20,%21,%22,%23,%24,%25,%26,%27,%28,%29,%30,%31}"
#define D44 "{%0,%1,%2,%3,%4,%5,%6,%7,%8,%9,%10,%11,%12,%13,%14,%15,%16,%17,%18,%19,%20,%21,%22,%23,%24,%25,%26,%27,%28,%29,%30,%31,%32,%33,%34,%35,%36,%37,%38,%39,%40,%41,%42,%43}"

__device__ __forceinline__ void mma_qk_f16(float (&d)[32], uint64_t da, uint64_t db) {
    asm volatile("{.reg .pred p; setp.eq.b32 p, 0, 0; wgmma.mma_async.sync.aligned.m64n64k16.f32.f16.f16 " D32 ", %32, %33, p, 1, 1, 0, 0;}"
                 : R32(d) : "l"(da), "l"(db));
}
__device__ __forceinline__ void mma_qk_bf16(float (&d)[32], uint64_t da, uint64_t db) {
    asm volatile("{.reg .pred p; setp.ne.b32 p, 0, 0; wgmma.mma_async.sync.aligned.m64n64k16.f32.bf16.bf16 " D32 ", %32, %33, p, 1, 1, 0, 0;}"
                 : R32(d) : "l"(da), "l"(db));
}
__device__ __forceinline__ void mma_pv(float (&d)[12], const uint32_t* a, uint64_t db) {
    asm volatile("{.reg .pred p; setp.eq.b32 p, 0, 0; wgmma.mma_async.sync.aligned.m64n24k16.f32.bf16.bf16 {%0,%1,%2,%3,%4,%5,%6,%7,%8,%9,%10,%11}, {%12,%13,%14,%15}, %16, p, 1, 1, 1;}"
                 : R8(d, 0), R4(d, 8) : "r"(a[0]), "r"(a[1]), "r"(a[2]), "r"(a[3]), "l"(db));
}
__device__ __forceinline__ void mma_ss64(float (&d)[32], uint64_t da, uint64_t db) {
    asm volatile("{.reg .pred p; setp.eq.b32 p, 0, 0; wgmma.mma_async.sync.aligned.m64n64k16.f32.bf16.bf16 " D32 ", %32, %33, p, 1, 1, 0, 1;}"
                 : R32(d) : "l"(da), "l"(db));
}
__device__ __forceinline__ void mma_ss8(float (&d)[4], uint64_t da, uint64_t db) {
    asm volatile("{.reg .pred p; setp.eq.b32 p, 0, 0; wgmma.mma_async.sync.aligned.m64n8k16.f32.bf16.bf16 {%0,%1,%2,%3}, %4, %5, p, 1, 1, 0, 1;}"
                 : R4(d, 0) : "l"(da), "l"(db));
}
__device__ __forceinline__ void mma_rs(float (&d)[32], const uint4& a, uint64_t db) {
    asm volatile("{.reg .pred p; setp.eq.b32 p, 0, 0; wgmma.mma_async.sync.aligned.m64n64k16.f32.bf16.bf16 " D32 ", {%32,%33,%34,%35}, %36, p, 1, 1, 1;}"
                 : R32(d) : "r"(a.x), "r"(a.y), "r"(a.z), "r"(a.w), "l"(db));
}
__device__ __forceinline__ void mma_rs(float (&d)[44], const uint4& a, uint64_t db) {
    asm volatile("{.reg .pred p; setp.eq.b32 p, 0, 0; wgmma.mma_async.sync.aligned.m64n88k16.f32.bf16.bf16 " D44 ", {%44,%45,%46,%47}, %48, p, 1, 1, 1;}"
                 : R32(d), R8(d, 32), R4(d, 40) : "r"(a.x), "r"(a.y), "r"(a.z), "r"(a.w), "l"(db));
}

constexpr float EXP_MAGIC = 256.0f + 127.0f + 64.0f - 1.58621f + 0.00390625f;
constexpr uint32_t MUFU_MASK = 0x1111u;
__device__ __forceinline__ uint32_t exp2_pair(float y0, float y1, uint32_t cexp, uint32_t neg1) {
    uint32_t w, m, e, r;
    asm("prmt.b32 %0, %1, %2, 0x6521;" : "=r"(w) : "r"(__float_as_uint(y0)), "r"(__float_as_uint(y1)));
    asm("lop3.b32 %0, %1, 0x007F007F, %2, 0xEA;" : "=r"(m) : "r"(w), "r"(cexp));
    asm("mad.lo.u32 %0, %1, %2, %3;" : "=r"(e) : "r"(m), "r"(neg1), "r"(w));
    asm("fma.rn.bf16x2 %0, %1, %2, %3;" : "=r"(r) : "r"(w), "r"(m), "r"(e));
    return r;
}

struct Params {
    const __nv_bfloat16* x;
    const __nv_bfloat16* wk;
    const __nv_bfloat16* wv;
    const __nv_bfloat16* wqp;
    __nv_bfloat16* out;
    uint32_t neg1, pad;
    const __nv_bfloat16* w1p;
    const __nv_bfloat16* w2p;
    CUtensorMap wq, wo, w1, w2;
    const __nv_bfloat16* wop;
};

__device__ __forceinline__ void load_box(uint32_t sb, const CUtensorMap* tm, uint32_t dst, uint32_t bar, uint32_t bytes, int c0, int c1) {
    mbar_expect(sb + SM_MISC + bar * 8, bytes);
    tma2d(sb + dst, tm, c0, c1, sb + SM_MISC + bar * 8);
}
__device__ __forceinline__ void load_wq(uint32_t sb, const Params& P, int gi, int atom) {
    load_box(sb, &P.wq, SM_WQ + atom * 65536 + gi * 16384, MB_WQ + gi, 16384, (blockIdx.x & 3) * 128 + atom * 64, gi * 128);
}
__device__ __forceinline__ void load_wo(uint32_t sb, const Params& P, int kb) { load_box(sb, &P.wo, wo_slot(kb) * 8192, MB_WO + kb, 8192, (blockIdx.x & 7) * 64, kb * 64); }
__device__ __forceinline__ void load_w2(uint32_t sb, const Params& P, int kb, int slot) { load_box(sb, &P.w2, slot * 8192, MB_W2 + kb, 8192, (blockIdx.x & 7) * 64, kb * 64); }
__device__ __forceinline__ void refill_job(uint32_t sb, const Params& P, int gi, int job) {
    const bool w1 = job < 3;
    const int kb = (gi < 3 ? 2 + 2 * gi : 0) + job - 3;
    load_box(sb, w1 ? &P.w1 : gi < 3 ? &P.wo : &P.w2, (w1 ? 8 + gi + 4 * job : 2 * gi + job - 3) * 8192, w1 ? MB_W1 + gi : (gi < 3 ? MB_WO : MB_W2) + kb, 8192,
             w1 ? (blockIdx.x & 15) * 88 + job * 32 : (blockIdx.x & 7) * 64, w1 ? gi * 128 : kb * 64);
}
__device__ __forceinline__ void release_w1(uint32_t sb, const Params& P, int gi) {
    if (warp_arrive(sb + SM_MISC + MISC_CNT + gi * 4) == 15) {
        if ((threadIdx.x & 31) == 0) {
#pragma unroll 1
            for (int a = 0; a < 3; a++) load_w2(sb, P, 10 + 3 * gi + a, 8 + gi + 4 * a);
        }
        __syncwarp();
    }
}

__device__ __forceinline__ void load_batch(uint4 (&buf)[4], const uint4* a) {
#pragma unroll
    for (int s = 0; s < 4; s++) buf[s] = ldg_relaxed(a + s * 128);
}
__device__ __forceinline__ bool batch_bad(const uint4 (&buf)[4]) {
    const uint32_t m = max(max(max(buf[0].x, buf[0].w), max(buf[1].x, buf[1].w)), max(max(buf[2].x, buf[2].w), max(buf[3].x, buf[3].w)));
    return __any_sync(0xffffffffu, m == SENT);
}
__device__ __forceinline__ void check_batch(uint4 (&buf)[4], const uint4* a) {
    if (__builtin_expect(batch_bad(buf), 0)) {
        int spins = 0;
        do load_batch(buf, a); while (batch_bad(buf) && ++spins < SPIN_LIMIT);
    }
}
__device__ __forceinline__ void poll_word(const void* p) {
    uint32_t v; int spins = 0;
    do { asm volatile("ld.relaxed.gpu.global.u32 %0, [%1];" : "=r"(v) : "l"(p) : "memory"); } while (__any_sync(0xffffffffu, v == SENT) && ++spins < SPIN_LIMIT);
}

template <int KIND, int NBLK, int RING, int NACC>
__device__ __forceinline__ void gemm_rs(float (&acc)[NACC], uint4 (&buf)[RING][4], const uint4* a, uint32_t sb, int q, const Params& P) {
    constexpr int ASTR = (KIND == 1) ? 512 : 1024;
    const uint32_t mb = sb + SM_MISC;
#pragma unroll
    for (int i = 0; i < NACC; i++) acc[i] = 0.f;
    fence_regs(acc);
#pragma unroll
    for (int i = 0; i < NBLK; i++) {
        uint64_t db;
        if (KIND == 1) {
            db = mkdesc(sb + (8 + (i >> 1)) * 8192 + (i & 1) * 4096, 32768, 512, 2);
            if ((i & 1) == 0) mbar_wait(mb + (MB_W1 + (i >> 1)) * 8);
        } else {
            const uint32_t slot = KIND == 0 ? (q ? wo_slot(2 * i + 1) : wo_slot(2 * i)) : (q ? w2_slot(2 * i + 1) : w2_slot(2 * i));
            db = mkdesc(sb + slot * 8192, 16, 1024, 1);
            mbar_wait(mb + ((KIND == 0 ? MB_WO : MB_W2) + 2 * i + q) * 8);
        }
        check_batch(buf[i % RING], a + i * ASTR);
        wg_fence();
#pragma unroll
        for (int s = 0; s < 4; s++) mma_rs(acc, buf[i % RING][s], db + s * (KIND == 1 ? 64 : 128));
        wg_commit();
        const bool rel = KIND == 1 && i >= 2 && !(i & 1);
        if (i >= 1 && (i - 1 + RING < NBLK || rel)) {
            wg_wait<1>();
            if (i - 1 + RING < NBLK) load_batch(buf[(i - 1) % RING], a + (i - 1 + RING) * ASTR);
            if (rel) release_w1(sb, P, (i >> 1) - 1);
        }
    }
    wg_wait<0>();
    fence_regs(acc);
}

__device__ __forceinline__ void pair_reduce(const float (&acc)[32], float (&r)[16], uint32_t buf, int q, int barid) {
    if (q) {
#pragma unroll
        for (int j = 0; j < 4; j++) sts128(buf + j * 2048, __float_as_uint(acc[4 * j]), __float_as_uint(acc[4 * j + 1]), __float_as_uint(acc[4 * j + 2]), __float_as_uint(acc[4 * j + 3]));
        bar_sync(barid, 256);
        bar_sync(barid, 256);
#pragma unroll
        for (int j = 0; j < 4; j++) {
            float4 v = lds128f(buf + j * 2048);
            r[4 * j] = acc[16 + 4 * j] + v.x; r[4 * j + 1] = acc[17 + 4 * j] + v.y; r[4 * j + 2] = acc[18 + 4 * j] + v.z; r[4 * j + 3] = acc[19 + 4 * j] + v.w;
        }
    } else {
        bar_sync(barid, 256);
        float4 v[4];
#pragma unroll
        for (int j = 0; j < 4; j++) v[j] = lds128f(buf + j * 2048);
#pragma unroll
        for (int j = 0; j < 4; j++) sts128(buf + j * 2048, __float_as_uint(acc[16 + 4 * j]), __float_as_uint(acc[17 + 4 * j]), __float_as_uint(acc[18 + 4 * j]), __float_as_uint(acc[19 + 4 * j]));
        bar_arrive(barid, 256);
#pragma unroll
        for (int j = 0; j < 4; j++) {
            r[4 * j] = acc[4 * j] + v[j].x; r[4 * j + 1] = acc[4 * j + 1] + v[j].y; r[4 * j + 2] = acc[4 * j + 2] + v[j].z; r[4 * j + 3] = acc[4 * j + 3] + v[j].w;
        }
    }
}

__device__ __forceinline__ float quad_sum(float v) { v += __shfl_xor_sync(0xffffffffu, v, 1); v += __shfl_xor_sync(0xffffffffu, v, 2); return v; }
__device__ __forceinline__ float silu2(float h) { float t; asm("tanh.approx.f32 %0, %1;" : "=f"(t) : "f"(h)); return fmaf(h, t, h); }

#define TS_ARG
#define TS_PASS

template <bool SAFE>
__device__ __forceinline__ void attention(const Params& P, uint32_t sb, int warp TS_ARG) {
    const uint32_t mb = sb + SM_MISC;
    const int tid = threadIdx.x, lane = tid & 31, b = blockIdx.x;
    const int wg = warp >> 2, ww = warp & 3, job = 3 - wg + 4 * ww;
    const uint32_t cexp = 0x9F809F80u + (tid >> 12);
    const uint32_t neg1 = P.neg1;
    unsigned cnt = 0;
    if (SAFE && warp == 8) asm volatile("ld.relaxed.gpu.global.u32 %0, [%1];" : "=r"(cnt) : "l"(&g_s.count1) : "memory");
    if (lane == 0) {
        if (job < 9) {
            asm volatile("cp.async.bulk.global.shared::cta.bulk_group [%0], [%1], %2;"
                         :: "l"(g_x + X_ARM + b * X_SHARE + job * 512), "r"(sb + SM_SENT), "r"(job < 8 ? 8192 : (X_SHARE - 4096) * 16) : "memory");
            asm volatile("cp.async.bulk.commit_group;" ::: "memory");
        } else if (job == 9) load_wo(sb, P, 0);
    }
    __syncwarp();
#pragma unroll 1
    for (int pass = 0; pass < 2; pass++) {
    float o[12], s[32];
    const uint64_t dq = mkdesc(sb + SM_Q + (pass * 4 + wg) * 2048, 128, 256, 0);
    uint64_t dk = mkdesc(sb + SM_K, 128, 256, 0), dv = mkdesc(sb + SM_V, 128, 32768, 0);
    float m0 = -INFINITY, m1 = -INFINITY;
#pragma unroll
    for (int i = 0; i < 12; i++) o[i] = 0.f;
#pragma unroll
    for (int i = 0; i < 32; i++) s[i] = ((MUFU_MASK >> (i / 2)) & 1) ? 0.f : EXP_MAGIC;
    fence_regs(s); fence_regs(o);
    wg_fence();
    if (SAFE) mma_qk_f16(s, dq, dk + 31 * 128); else mma_qk_bf16(s, dq, dk + 31 * 128);
    wg_commit();
    wg_wait<0>(); fence_regs(s);
#pragma unroll 1
    for (int u = pass ? 3 : (wg == 2) ? 0 : 1; u < (pass ? 8 : 3); u++) {
        int n = 2 * ((((wg == 2) ? 0x22444C31u : 0x22444C40u) >> (4 * u)) & 15);
#pragma unroll 1
        do {
            uint32_t p[16];
            if (SAFE) {
#pragma unroll
                for (int j = 0; j < 16; j++) {
                    if ((MUFU_MASK >> j) & 1) p[j] = pack_bf16(ex2(s[2 * j]), ex2(s[2 * j + 1]));
                    else p[j] = exp2_pair(s[2 * j], s[2 * j + 1], cexp, neg1);
                }
            } else {
                fence_regs(o);
                float x0 = m0, x1 = m1;
#pragma unroll
                for (int j = 0; j < 8; j++) { x0 = fmaxf(x0, fmaxf(s[4 * j], s[4 * j + 1])); x1 = fmaxf(x1, fmaxf(s[4 * j + 2], s[4 * j + 3])); }
                x0 = fmaxf(x0, __shfl_xor_sync(0xffffffffu, x0, 1)); x0 = fmaxf(x0, __shfl_xor_sync(0xffffffffu, x0, 2));
                x1 = fmaxf(x1, __shfl_xor_sync(0xffffffffu, x1, 1)); x1 = fmaxf(x1, __shfl_xor_sync(0xffffffffu, x1, 2));
                const float c0 = ex2(m0 - x0), c1 = ex2(m1 - x1);
                m0 = x0; m1 = x1;
#pragma unroll
                for (int j = 0; j < 3; j++) { o[4 * j] *= c0; o[4 * j + 1] *= c0; o[4 * j + 2] *= c1; o[4 * j + 3] *= c1; }
#pragma unroll
                for (int j = 0; j < 8; j++) {
                    p[2 * j] = pack_bf16(ex2(s[4 * j] - m0), ex2(s[4 * j + 1] - m0));
                    p[2 * j + 1] = pack_bf16(ex2(s[4 * j + 2] - m1), ex2(s[4 * j + 3] - m1));
                }
                fence_regs(o);
            }
            fence_regs(p);
            wg_fence();
            if (SAFE) mma_qk_f16(s, dq, dk); else mma_qk_bf16(s, dq, dk);
#pragma unroll
            for (int j = 0; j < 4; j++) mma_pv(o, p + 4 * j, dv + j * 16);
            wg_commit();
            dk += 128; dv += 64;
            wg_wait<0>(); fence_regs(s);
        } while (--n > 0);
        if (u == 2 || u == 7) {
            fence_regs(o);
            const float i0 = rcp(o[8]), i1 = rcp(o[10]);
            if (u == 7) mbar_wait(mb + MB_F2 * 8);
            stg128(g_x + X_OF + (((u == 7) * 16 + (b >> 3)) * 32 + (b & 3) * 8 + 2 * wg + (ww >> 1)) * 128 + (((b >> 2) & 1) * 2 + (ww & 1)) * 32 + lane,
                   pack_bf16(o[0] * i0, o[1] * i0), pack_bf16(o[2] * i1, o[3] * i1), pack_bf16(o[4] * i0, o[5] * i0), pack_bf16(o[6] * i1, o[7] * i1));
            if (u == 2) asm volatile("cp.async.bulk.wait_group 0;" ::: "memory");
            warp_done(mb + (MB_DONE + (u == 7) * 4) * 8);
            TS(5 + (u == 7));
        } else if (u >= 3) {
            if (u < 6) warp_done(mb + (MB_DONE + u - 2) * 8);
            if (job < (u == 3 ? 2 : 5)) {
                mbar_wait(mb + (MB_DONE + u - 3) * 8);
                if (lane == 0) {
                    if (u > 3) refill_job(sb, P, u - 4, job);
                    else if (job == 1) load_wo(sb, P, 1);
                    else asm volatile("red.release.gpu.global.add.u32 [%0], 1;" :: "l"(&g_s.count2) : "memory");
                }
            } else if (warp == 11) {
                if (u == 5) asm volatile("ld.relaxed.gpu.global.u32 %0, [%1];" : "=r"(cnt) : "l"(&g_s.count2) : "memory");
                if (u == 6) {
                    const unsigned target = lds32(mb + MISC_EPOCH) * NCTA;
                    if (__any_sync(0xffffffffu, cnt != target)) wait_count(&g_s.count2, target);
                    asm volatile("fence.acquire.gpu;" ::: "memory");
                    warp_done(mb + MB_F2 * 8);
                }
            }
        } else if (SAFE) {
            if (u == 1) mbar_wait(mb + MB_KV * 8);
            else if (warp == 8) {
                const unsigned target = lds32(mb + MISC_EPOCH) * NMAIN;
                if (__any_sync(0xffffffffu, cnt != target)) wait_count(&g_s.count1, target);
                if (lane == 0) {
                    asm volatile("fence.acquire.gpu; fence.proxy.async.global;" ::: "memory");
                    mbar_expect(mb + MB_KV * 8, 47104 + 2 * 24576);
                    bulk_g2s(sb + SM_K + 16384, g_s.kv + 1024, 47104, mb + MB_KV * 8);
                    bulk_g2s(sb + SM_V + 8192, g_s.kv + 4096 + 512, 24576, mb + MB_KV * 8);
                    bulk_g2s(sb + SM_V + 32768 + 8192, g_s.kv + 6144 + 512, 24576, mb + MB_KV * 8);
                }
            }
        }
        __syncwarp();
    }
    }
}

__device__ __noinline__ void helper_cta(const Params& P, uint8_t* smem) {
    const int tid = threadIdx.x, b = blockIdx.x, hi = b - NMAIN;
    const unsigned epoch = g_s.epoch[b] + 1;
    float* red = reinterpret_cast<float*>(smem);
    if (tid < 32) wait_count(&g_s.count1, epoch * NMAIN);
    __syncthreads();
    if (tid == 480) {
        for (int i = 0; i < 8; i++) asm volatile("cp.async.bulk.prefetch.L2.global [%0], %1;" :: "l"((const char*)P.wop + hi * 131072 + i * 16384), "r"(16384) : "memory");
        for (int i = 0; i < 43; i++) asm volatile("cp.async.bulk.prefetch.L2.global [%0], %1;" :: "l"((const char*)P.w2p + hi * 352256 + i * 8192), "r"(8192) : "memory");
    }
    if (tid < 344) {
        const int cg = tid % 43, rp = tid / 43;
        const uint4* src = reinterpret_cast<const uint4*>(P.w1p + (size_t)rp * 64 * FF + (hi * 43 + cg) * 8);
        float s[8] = {0, 0, 0, 0, 0, 0, 0, 0};
#pragma unroll 8
        for (int r = 0; r < 64; r++) {
            uint4 v = __ldg(src + r * (FF / 8));
            s[0] += bf_lo(v.x); s[1] += bf_hi(v.x); s[2] += bf_lo(v.y); s[3] += bf_hi(v.y);
            s[4] += bf_lo(v.z); s[5] += bf_hi(v.z); s[6] += bf_lo(v.w); s[7] += bf_hi(v.w);
        }
        float* part = red + (rp * 43 + cg) * 8;
#pragma unroll
        for (int i = 0; i < 8; i++) part[i] = s[i];
    }
    __syncthreads();
    if (tid < 344) {
        float s = 0.f;
#pragma unroll
        for (int rp = 0; rp < 8; rp++) s += red[rp * 344 + tid];
        g_s.cs[hi * 344 + tid] = s;
    } else if (hi == 3 && tid < 344 + 32) g_s.cs[FF + tid - 344] = 0.f;
    __syncthreads();
    if (tid == 0) {
        asm volatile("red.release.gpu.global.add.u32 [%0], 1;" :: "l"(&g_s.count2) : "memory");
        g_s.epoch[b] = epoch;
    }
}

__global__ void __launch_bounds__(512, 1) fused_kernel(const __grid_constant__ Params P) {
    extern __shared__ __align__(1024) uint8_t smem[];
    const uint32_t sb = (uint32_t)__cvta_generic_to_shared(smem);
    const uint32_t mb = sb + SM_MISC;
    const int tid = threadIdx.x, lane = tid & 31, b = blockIdx.x;
    if (b >= NMAIN) { helper_cta(P, smem); return; }
    const int tg = b >> 2, hg = b & 3;
    const int warp = __shfl_sync(0xffffffffu, tid >> 5, 0);

    uint4 xv[4][2];
    unsigned epoch = 0;
    {
        const int r = (tid >> 5) * 4;
        const uint4* src = reinterpret_cast<const uint4*>(P.x + (size_t)((r & 31) + tg * 32 + (r >> 5) * 1024) * D) + lane;
#pragma unroll
        for (int i = 0; i < 4; i++) { xv[i][0] = ldg_relaxed(src + i * 64); xv[i][1] = ldg_relaxed(src + i * 64 + 32); }
    }
    const uint4 wkv = ldg_relaxed(reinterpret_cast<const uint4*>(hg < 2 ? P.wk : P.wv) + tid * 2 + (hg & 1));
    const int wg = warp >> 2, ww = warp & 3, g = lane >> 2, t4 = lane & 3, t128 = tid & 127;
    if (lane == 0) {
        mbar_init(mb + warp * 8, warp < 4 ? 2 : warp < 8 ? 3 : warp < 14 ? 16 : 1);
        mbar_init(mb + (16 + warp) * 8, 1);
        mbar_init(mb + (32 + warp) * 8, 1);
        if (warp < 4) {
            asm volatile("fence.mbarrier_init.release.cluster;" ::: "memory");
            load_wq(sb, P, warp, 0);
            if (warp < 3) load_wq(sb, P, warp, 1);
        } else if (warp < 7) {
            asm volatile("prefetch.tensormap [%0];" :: "l"(&P.wo + (warp - 4)) : "memory");
        } else if (warp == 7) {
            asm volatile("ld.relaxed.gpu.global.u32 %0, [%1];" : "=r"(epoch) : "l"(g_s.epoch + b) : "memory");
        } else if (warp < 10) {
            sts128(mb + MISC_CNT + (warp - 8) * 16, 0, 0, 0, 0);
        }
    }
    __syncwarp();
    TS(16);
    float dlt[4];
    {
        float st[4];
#pragma unroll
        for (int i = 0; i < 4; i++) {
            const uint32_t s = add_bf16x2(add_bf16x2(add_bf16x2(xv[i][0].x, xv[i][0].y), add_bf16x2(xv[i][0].z, xv[i][0].w)),
                                          add_bf16x2(add_bf16x2(xv[i][1].x, xv[i][1].y), add_bf16x2(xv[i][1].z, xv[i][1].w)));
            st[i] = bf_lo(s) + bf_hi(s);
        }
        TS(13);
#pragma unroll
        for (int o = 16; o > 0; o >>= 1)
#pragma unroll
            for (int i = 0; i < 4; i++) st[i] += __shfl_xor_sync(0xffffffffu, st[i], o);
#pragma unroll
        for (int i = 0; i < 4; i++) {
            const float nmean = st[i] * (-1.0f / D);
            const uint32_t nm = pack_bf16(nmean, nmean);
            dlt[i] = bf_lo(nm) - nmean;
            const int r = warp * 4 + i;
#pragma unroll
            for (int c = 0; c < 2; c++) {
                xv[i][c].x = add_bf16x2(xv[i][c].x, nm); xv[i][c].y = add_bf16x2(xv[i][c].y, nm);
                xv[i][c].z = add_bf16x2(xv[i][c].z, nm); xv[i][c].w = add_bf16x2(xv[i][c].w, nm);
                sts128(sb + SM_XN + ((lane >> 3) + 4 * c) * 8192 + r * 128 + (((lane & 7) ^ (r & 7)) << 4), xv[i][c].x, xv[i][c].y, xv[i][c].z, xv[i][c].w);
            }
        }
    }
    sts128(sb + SM_WKV + tid * 16, wkv.x, wkv.y, wkv.z, wkv.w);
    fence_async_smem();
    TS(0);
    __syncthreads();
    auto variances = [&]() {
        float st[4];
#pragma unroll
        for (int i = 0; i < 4; i++) {
            float v = 0.f;
#pragma unroll
            for (int c = 0; c < 2; c++) {
                const uint32_t a = fma_bf16x2(xv[i][c].x, xv[i][c].x, mul_bf16x2(xv[i][c].y, xv[i][c].y));
                const uint32_t d = fma_bf16x2(xv[i][c].z, xv[i][c].z, mul_bf16x2(xv[i][c].w, xv[i][c].w));
                v += (bf_lo(a) + bf_hi(a)) + (bf_lo(d) + bf_hi(d));
            }
            st[i] = v;
        }
        const bool u16 = lane & 16, u8 = lane & 8;
        float a0 = (u16 ? st[2] : st[0]) + __shfl_xor_sync(0xffffffffu, u16 ? st[0] : st[2], 16);
        float a1 = (u16 ? st[3] : st[1]) + __shfl_xor_sync(0xffffffffu, u16 ? st[1] : st[3], 16);
        float vs = (u8 ? a1 : a0) + __shfl_xor_sync(0xffffffffu, u8 ? a0 : a1, 8);
        vs += __shfl_xor_sync(0xffffffffu, vs, 4); vs += __shfl_xor_sync(0xffffffffu, vs, 2); vs += __shfl_xor_sync(0xffffffffu, vs, 1);
        const float dl = u16 ? (u8 ? dlt[3] : dlt[2]) : (u8 ? dlt[1] : dlt[0]);
        if ((lane & 7) == 0) sts32(mb + MISC_RSTD + (warp * 4 + (lane >> 3)) * 4, __float_as_uint(rsqrtf(fmaxf(vs * (1.0f / D) - dl * dl, 0.f) + 1e-5f)));
    };
    float kv[4] = {0.f, 0.f, 0.f, 0.f};
    if (wg == 2) {
        fence_regs(kv);
        const uint64_t da = mkdesc(sb + SM_XN, 16, 1024, 1), db = mkdesc(sb + SM_WKV, 128, 16, 0);
        wg_fence();
#pragma unroll
        for (int s = 0; s < 32; s++) mma_ss8(kv, da + (s >> 2) * 512 + (s & 3) * 2, db + s * 16);
        wg_commit();
        TS(18);
        variances();
        wg_wait<0>(); fence_regs(kv);
        TS(20);
    } else {
        variances();
        if (tid == 7 * 32) { sts32(mb + MISC_EPOCH, epoch + 1); g_s.epoch[b] = epoch + 1; }
        TS(19);
    }
    __syncthreads();
    constexpr float QSCALE = 0.25f * 1.4426950408889634f;
    uint32_t kvoff[2];
#pragma unroll
    for (int i = 0; i < 2; i++) {
        const int t = ((ww & 1) * 16 + g + 8 * i), c = 2 * tg + (ww >> 1);
        kvoff[i] = hg < 2 ? ((t + 31) & 31) * 2048 + (c >> 3) * 256 + (hg & 1) * 128 + (c & 7) * 16 + t4 * 4
                          : 65536 + (hg & 1) * 32768 + (t * 64 + c) * 16 + t4 * 4;
    }
    float qa[32];
    if (wg < 2) {
#pragma unroll
        for (int i = 0; i < 32; i++) qa[i] = 0.f;
        fence_regs(qa);
        const uint64_t da = mkdesc(sb + SM_XN, 16, 1024, 1), db = mkdesc(sb + SM_WQ + wg * 65536, 16, 1024, 1);
#pragma unroll 1
        for (int i = 0; i < 4; i++) {
            mbar_wait(mb + (MB_WQ + i) * 8);
            if (i == 0) TS(21); if (i == 3) TS(22);
            wg_fence();
#pragma unroll
            for (int s = 0; s < 8; s++) mma_ss64(qa, da + (i * 2 + (s >> 2)) * 512 + (s & 3) * 2, db + (i * 8 + s) * 128);
            wg_commit();
        }
        const float rs0 = __uint_as_float(lds32(mb + MISC_RSTD + (ww * 16 + g) * 4)) * QSCALE, rs1 = __uint_as_float(lds32(mb + MISC_RSTD + (ww * 16 + g + 8) * 4)) * QSCALE;
        wg_wait<0>();
        fence_regs(qa);
        bar_arrive(6, 512);
        TS(1);
        float nn[8];
#pragma unroll
        for (int i = 0; i < 32; i++) qa[i] *= (i & 2) ? rs1 : rs0;
#pragma unroll
        for (int h = 0; h < 4; h++) {
            nn[2 * h] = qa[8 * h] * qa[8 * h] + qa[8 * h + 1] * qa[8 * h + 1] + qa[8 * h + 4] * qa[8 * h + 4] + qa[8 * h + 5] * qa[8 * h + 5];
            nn[2 * h + 1] = qa[8 * h + 2] * qa[8 * h + 2] + qa[8 * h + 3] * qa[8 * h + 3] + qa[8 * h + 6] * qa[8 * h + 6] + qa[8 * h + 7] * qa[8 * h + 7];
        }
#pragma unroll
        for (int o = 1; o < 4; o <<= 1)
#pragma unroll
            for (int i = 0; i < 8; i++) nn[i] += __shfl_xor_sync(0xffffffffu, nn[i], o);
        bar_sync(1, 256);
#pragma unroll
        for (int h = 0; h < 4; h++) {
            const uint32_t base = sb + SM_Q + ((ww >> 1) * 4 + wg * 2 + (h >> 1)) * 2048 + ((h & 1) * 4 + (ww & 1) * 2) * 256 + lane * 4;
            sts32(base, pack_f16(qa[8 * h], qa[8 * h + 1])); sts32(base + 256, pack_f16(qa[8 * h + 2], qa[8 * h + 3]));
            sts32(base + 128, pack_f16(qa[8 * h + 4], qa[8 * h + 5])); sts32(base + 384, pack_f16(qa[8 * h + 6], qa[8 * h + 7]));
        }
        uint32_t nm = 0;
#pragma unroll
        for (int i = 0; i < 8; i++) nm = max(nm, __float_as_uint(nn[i]));
        nm = __reduce_max_sync(0xffffffffu, nm);
        if (lane == 0) asm volatile("red.shared.max.u32 [%0], %1;" :: "r"(mb + MISC_NRM), "r"(nm) : "memory");
    } else if (wg == 2) {
        const float rs0 = __uint_as_float(lds32(mb + MISC_RSTD + (ww * 16 + g) * 4)), rs1 = __uint_as_float(lds32(mb + MISC_RSTD + (ww * 16 + g + 8) * 4));
        kv[0] *= rs0; kv[1] *= rs0; kv[2] *= rs1; kv[3] *= rs1;
        char* img = reinterpret_cast<char*>(g_s.kv);
        const int r0 = ww * 16 + g;
        float2* kt = reinterpret_cast<float2*>(smem + SM_MISC + MISC_KTMP);
        if (hg < 2) { kt[r0 * 4 + t4] = make_float2(kv[0], kv[1]); kt[(r0 + 8) * 4 + t4] = make_float2(kv[2], kv[3]); }
        float n0 = kv[0] * kv[0] + kv[1] * kv[1], n1 = kv[2] * kv[2] + kv[3] * kv[3];
        n0 += __shfl_xor_sync(0xffffffffu, n0, 1); n1 += __shfl_xor_sync(0xffffffffu, n1, 1);
        n0 += __shfl_xor_sync(0xffffffffu, n0, 2); n1 += __shfl_xor_sync(0xffffffffu, n1, 2);
        const uint32_t nm = __reduce_max_sync(0xffffffffu, max(__float_as_uint(n0), __float_as_uint(n1)));
        const uint32_t b0 = pack_bf16(kv[0], kv[1]), b1 = pack_bf16(kv[2], kv[3]);
        uint32_t w0 = b0, w1 = b1;
        if (hg < 2) {
            bar_sync(2, 128);
            float2 p0 = make_float2(0.f, 0.f);
            if (r0 & 31) p0 = kt[(r0 - 1) * 4 + t4];
            const float2 p1 = kt[(r0 + 7) * 4 + t4];
            w0 = pack_f16(kv[0] - p0.x, kv[1] - p0.y); w1 = pack_f16(kv[2] - p1.x, kv[3] - p1.y);
        }
        stg32(img + kvoff[0], nonzero(w0));
        stg32(img + kvoff[1], nonzero(w1));
        if (lane == 0) stg32(reinterpret_cast<uint32_t*>(g_s.nrm + b) + ww, nm | 1u);
        TS(1);
        bar_arrive(5, 256);
        if (hg < 2) { stg32(reinterpret_cast<char*>(g_s.kplain) + kvoff[0], b0); stg32(reinterpret_cast<char*>(g_s.kplain) + kvoff[1], b1); }
        bar_sync(2, 128);
        if (t128 == 0) asm volatile("red.release.gpu.global.add.u32 [%0], 1;" :: "l"(&g_s.count1) : "memory");
        __syncwarp();
        bar_sync(6, 512);
#pragma unroll
        for (int i = 0; i < 16; i++) sts128(sb + SM_V + 65536 + (i * 128 + t128) * 16, 0x3F803F80u, 0x3F803F80u, 0x3F803F80u, 0x3F803F80u);
#pragma unroll
        for (int i = 0; i < 4; i++) sts128(sb + SM_SENT + (i * 128 + t128) * 16, SENT, SENT, SENT, SENT);
    } else {
        if (tid == 13 * 32) load_wq(sb, P, 3, 1);
        __syncwarp();
        bar_sync(5, 256);
        uint4 kc[18];
        auto src = [&](int i) { return i < 8 ? g_s.kv + i * 128 : i < 12 ? g_s.kv + 4096 + (i - 8) * 128 : i < 16 ? g_s.kv + 6144 + (i - 12) * 128 : i == 16 ? g_s.kv + 31 * 128 : g_s.nrm; };
        int spins = 0;
        do { kc[17] = ldg_relaxed(g_s.nrm + t128); } while (__any_sync(0xffffffffu, has_zero(kc[17])) && ++spins < SPIN_LIMIT);
        TS(1);
#pragma unroll
        for (int i = 0; i < 17; i++) kc[i] = ldg_relaxed(src(i) + t128);
        uint32_t nm = max(max(kc[17].x, kc[17].y), max(kc[17].z, kc[17].w));
        nm = max(nm, __shfl_xor_sync(0xffffffffu, nm, 4)); nm = max(nm, __shfl_xor_sync(0xffffffffu, nm, 8)); nm = max(nm, __shfl_xor_sync(0xffffffffu, nm, 16));
        if (lane < 4) asm volatile("red.shared.max.u32 [%0], %1;" :: "r"(mb + MISC_NRM + 4 + min(lane, 2) * 4), "r"(nm) : "memory");
        while (true) {
            uint32_t mn = 1;
#pragma unroll
            for (int i = 0; i < 17; i++) mn = min(min(mn, min(kc[i].x, kc[i].y)), min(kc[i].z, kc[i].w));
            if (__builtin_expect(!__any_sync(0xffffffffu, mn == 0u), 1) || ++spins >= SPIN_LIMIT) break;
#pragma unroll
            for (int i = 0; i < 17; i++) kc[i] = ldg_relaxed(src(i) + t128);
        }
        TS(2);
        bar_sync(6, 512);
#pragma unroll
        for (int i = 0; i < 17; i++) sts128(sb + (uint32_t)(src(i) - g_s.kv + t128) * 16, kc[i].x, kc[i].y, kc[i].z, kc[i].w);
    }
    fence_async_smem();
    TS(3);
    __syncthreads();
    const float4 nr = lds128f(mb + MISC_NRM);
    const bool safe = __all_sync(0xffffffffu, (nr.x * (nr.y + nr.z) <= 3500.0f) && (nr.x <= 65536.0f) && (nr.y + nr.z <= 65536.0f) && (nr.w <= 1e24f));
    TS(4);

    if (__builtin_expect(safe, 1)) {
        attention<true>(P, sb, warp TS_PASS);
    } else {
        if (wg < 2) {
#pragma unroll
            for (int h = 0; h < 4; h++) {
                const uint32_t base = sb + SM_Q + ((ww >> 1) * 4 + wg * 2 + (h >> 1)) * 2048 + ((h & 1) * 4 + (ww & 1) * 2) * 256 + lane * 4;
                sts32(base, pack_bf16(qa[8 * h], qa[8 * h + 1])); sts32(base + 256, pack_bf16(qa[8 * h + 2], qa[8 * h + 3]));
                sts32(base + 128, pack_bf16(qa[8 * h + 4], qa[8 * h + 5])); sts32(base + 384, pack_bf16(qa[8 * h + 6], qa[8 * h + 7]));
            }
            fence_async_smem();
        } else if (warp == 15) {
            wait_count(&g_s.count1, lds32(mb + MISC_EPOCH) * NMAIN);
            if (lane == 0) {
                asm volatile("fence.proxy.async;" ::: "memory");
                mbar_expect(mb + MB_KV * 8, 131072);
                bulk_g2s(sb + SM_K, g_s.kplain, 65536, mb + MB_KV * 8);
                bulk_g2s(sb + SM_V, g_s.kv + 4096, 65536, mb + MB_KV * 8);
            }
            __syncwarp();
        }
        __syncthreads();
        mbar_wait(mb + MB_KV * 8);
        attention<false>(P, sb, warp TS_PASS);
    }

    const int pr = 1 - (wg >> 1), q = wg & 1;
    const int mt = 16 * pr + (b >> 3), j = b & 7;
    const int row0 = mt * 64 + ww * 16 + g;
    const uint32_t xbuf = sb + SM_Q + pr * 8192 + t128 * 16;
    uint32_t hk[8];
    {
        const uint4* a = g_x + X_OF + (mt * 32 + q * 4) * 128 + t128;
        if (pr) {
            if (warp < 5) {
                mbar_wait(mb + (MB_DONE + 4) * 8);
                if (lane == 0) refill_job(sb, P, 3, warp);
            } else if (warp == 5) {
                if (lane < 22) {
                    const uint4 v = ldg_relaxed(reinterpret_cast<const uint4*>(g_s.cs + (b & 15) * 88) + lane);
                    sts128(mb + MISC_CS + lane * 16, v.x, v.y, v.z, v.w);
                }
                warp_done(mb + MB_CS * 8);
            }
            __syncwarp();
            poll_word(a + ((lane >> 2) & 3) * 1024 + (lane & 3) * 128);
        }
        uint4 buf[4][4];
#pragma unroll
        for (int i = 0; i < 4; i++) load_batch(buf[i], a + i * 1024);
        const uint32_t* xp = reinterpret_cast<const uint32_t*>(P.x + (size_t)row0 * D + j * 64 + q * 32 + t4 * 2);
#pragma unroll
        for (int i = 0; i < 4; i++) { hk[2 * i] = __ldg(xp + i * 4); hk[2 * i + 1] = __ldg(xp + i * 4 + 8 * (D / 2)); }
        TS(23);
        float acc[32], r[16];
        gemm_rs<0, 4, 4>(acc, buf, a, sb, q, P);
        TS(7);
        warp_done(mb + (MB_DONE + 5) * 8);
        mbar_wait(mb + (MB_DONE + 4 * pr) * 8);
        pair_reduce(acc, r, xbuf, q, 3 + pr);
#pragma unroll
        for (int i = 0; i < 8; i++) hk[i] = pack_bf16(r[2 * i] + bf_lo(hk[i]), r[2 * i + 1] + bf_hi(hk[i]));
        float s0 = 0.f, s1 = 0.f;
#pragma unroll
        for (int i = 0; i < 8; i++) {
            r[2 * i] = bf_lo(hk[i]); r[2 * i + 1] = bf_hi(hk[i]);
            if (i & 1) s1 += r[2 * i] + r[2 * i + 1]; else s0 += r[2 * i] + r[2 * i + 1];
        }
        s0 += __shfl_xor_sync(0xffffffffu, s0, 1); s1 += __shfl_xor_sync(0xffffffffu, s1, 1);
        s0 += __shfl_xor_sync(0xffffffffu, s0, 2); s1 += __shfl_xor_sync(0xffffffffu, s1, 2);
        const float a0 = s0 * (1.0f / 32), a1 = s1 * (1.0f / 32);
        float v0 = 0.f, v1 = 0.f;
#pragma unroll
        for (int i = 0; i < 8; i++) {
            const float am = (i & 1) ? a1 : a0;
            const float d0 = r[2 * i] - am, d1 = r[2 * i + 1] - am;
            if (i & 1) v1 += d0 * d0 + d1 * d1; else v0 += d0 * d0 + d1 * d1;
        }
        v0 += __shfl_xor_sync(0xffffffffu, v0, 1); v1 += __shfl_xor_sync(0xffffffffu, v1, 1);
        v0 += __shfl_xor_sync(0xffffffffu, v0, 2); v1 += __shfl_xor_sync(0xffffffffu, v1, 2);
        uint4* hp = g_x + X_HF + (mt * 32 + j * 4 + 2 * q) * 128 + t128;
        stg128(hp, hk[0], hk[1], hk[2], hk[3]);
        stg128(hp + 128, hk[4], hk[5], hk[6], hk[7]);
        if (t4 < 2) stg64(reinterpret_cast<float2*>(g_x + X_ST) + (row0 + 8 * t4) * 16 + j * 2 + q, __float_as_uint(t4 ? s1 : s0), __float_as_uint(t4 ? v1 : v0));
        TS(8);
        if (pr) {
            mbar_wait(mb + (MB_DONE + 5) * 8);
            if (lane == 0) load_w2(sb, P, 2 + warp, warp < 2 ? 22 + warp : warp - 2);
            __syncwarp();
        } else if (wg == 2) {
            stg32(reinterpret_cast<char*>(g_s.kv) + kvoff[0], 0u);
            stg32(reinterpret_cast<char*>(g_s.kv) + kvoff[1], 0u);
            if (lane == 0) stg32(reinterpret_cast<uint32_t*>(g_s.nrm + b) + ww, 0u);
        }
    }
    {
        const int mt1 = 16 * pr + (b >> 4) * 2 + q, sl = b & 15;
        const uint4* a = g_x + X_HF + mt1 * 32 * 128 + t128;
        float acc[44], nmean[2], hrstd[2];
        uint4 buf[3][4];
        {
            const uint4* sp = g_x + X_ST + (mt1 * 64 + ww * 16 + g) * 8 + t4 * 2;
            uint4 u[4]; int spins = 0;
            do { u[0] = ldg_relaxed(sp); u[1] = ldg_relaxed(sp + 1); u[2] = ldg_relaxed(sp + 64); u[3] = ldg_relaxed(sp + 65); } while (batch_bad(u) && ++spins < SPIN_LIMIT);
            TS(26);
            float mean[2], m2[2];
#pragma unroll
            for (int i = 0; i < 2; i++) mean[i] = (__uint_as_float(u[2 * i].x) + __uint_as_float(u[2 * i].z)) + (__uint_as_float(u[2 * i + 1].x) + __uint_as_float(u[2 * i + 1].z));
            mean[0] += __shfl_xor_sync(0xffffffffu, mean[0], 1); mean[1] += __shfl_xor_sync(0xffffffffu, mean[1], 1);
            mean[0] += __shfl_xor_sync(0xffffffffu, mean[0], 2); mean[1] += __shfl_xor_sync(0xffffffffu, mean[1], 2);
#pragma unroll
            for (int i = 0; i < 3; i++) load_batch(buf[i], a + i * 512);
#pragma unroll
            for (int i = 0; i < 2; i++) {
                mean[i] *= 1.0f / D;
                const float da = __uint_as_float(u[2 * i].x) * (1.0f / 32) - mean[i], dc = __uint_as_float(u[2 * i].z) * (1.0f / 32) - mean[i];
                const float de = __uint_as_float(u[2 * i + 1].x) * (1.0f / 32) - mean[i], df = __uint_as_float(u[2 * i + 1].z) * (1.0f / 32) - mean[i];
                m2[i] = (__uint_as_float(u[2 * i].y) + __uint_as_float(u[2 * i].w)) + (__uint_as_float(u[2 * i + 1].y) + __uint_as_float(u[2 * i + 1].w)) + 32.0f * (da * da + dc * dc + de * de + df * df);
            }
            m2[0] += __shfl_xor_sync(0xffffffffu, m2[0], 1); m2[1] += __shfl_xor_sync(0xffffffffu, m2[1], 1);
            m2[0] += __shfl_xor_sync(0xffffffffu, m2[0], 2); m2[1] += __shfl_xor_sync(0xffffffffu, m2[1], 2);
#pragma unroll
            for (int i = 0; i < 2; i++) { hrstd[i] = 0.5f * rsqrtf(m2[i] * (1.0f / D) + 1e-5f); nmean[i] = -mean[i]; }
        }
        gemm_rs<1, 8, 3>(acc, buf, a, sb, q, P);
        TS(9);
        mbar_wait(mb + MB_CS * 8);
        uint4* hb = g_x + X_H + (mt1 * 88 + (sl >> 1) * 11) * 128 + t128;
        uint32_t hv[22];
#pragma unroll
        for (int i = 0; i < 11; i++) {
            float2 cs;
            asm volatile("ld.shared.v2.f32 {%0,%1}, [%2];" : "=f"(cs.x), "=f"(cs.y) : "r"(mb + MISC_CS + i * 32 + t4 * 8));
            hv[2 * i] = pack_bf16(silu2(hrstd[0] * fmaf(nmean[0], cs.x, acc[4 * i])), silu2(hrstd[0] * fmaf(nmean[0], cs.y, acc[4 * i + 1])));
            hv[2 * i + 1] = pack_bf16(silu2(hrstd[1] * fmaf(nmean[1], cs.x, acc[4 * i + 2])), silu2(hrstd[1] * fmaf(nmean[1], cs.y, acc[4 * i + 3])));
        }
        if (sl & 1) {
#pragma unroll
            for (int i = 0; i < 5; i++) stg128(hb + (6 + i) * 128, hv[2 + 4 * i], hv[3 + 4 * i], hv[4 + 4 * i], hv[5 + 4 * i]);
            stg64(reinterpret_cast<uint2*>(hb + 5 * 128) + 1, hv[0], hv[1]);
        } else {
#pragma unroll
            for (int i = 0; i < 5; i++) stg128(hb + i * 128, hv[4 * i], hv[4 * i + 1], hv[4 * i + 2], hv[4 * i + 3]);
            stg64(hb + 5 * 128, hv[20], hv[21]);
        }
        TS(10);
        release_w1(sb, P, 3);
    }
    {
        const uint4* a = g_x + X_H + (mt * 88 + q * 4) * 128 + t128;
        poll_word(reinterpret_cast<const uint2*>(g_x + X_H + (mt * 88 + ((lane >> 1) & 7) * 11 + 5) * 128 + t128) + (lane & 1));
        uint4 buf[4][4];
#pragma unroll
        for (int i = 0; i < 4; i++) load_batch(buf[i], a + i * 1024);
        TS(25);
        float acc[32], r[16];
        gemm_rs<2, 11, 4>(acc, buf, a, sb, q, P);
        TS(11);
        pair_reduce(acc, r, xbuf, q, 3 + pr);
#pragma unroll
        for (int i = 0; i < 8; i++) hk[i] = pack_bf16(r[2 * i] + bf_lo(hk[i]), r[2 * i + 1] + bf_hi(hk[i]));
    }
#pragma unroll
    for (int h = 0; h < 2; h++) {
        uint32_t v0 = hk[h], v1 = hk[2 + h], v2 = hk[4 + h], v3 = hk[6 + h];
        const bool o1 = t4 & 1, o2 = t4 & 2;
        uint32_t a = __shfl_xor_sync(0xffffffffu, o1 ? v0 : v1, 1), c = __shfl_xor_sync(0xffffffffu, o1 ? v2 : v3, 1);
        if (o1) { v0 = a; v2 = c; } else { v1 = a; v3 = c; }
        a = __shfl_xor_sync(0xffffffffu, o2 ? v0 : v2, 2); c = __shfl_xor_sync(0xffffffffu, o2 ? v1 : v3, 2);
        if (o2) { v0 = a; v1 = c; } else { v2 = a; v3 = c; }
        *reinterpret_cast<uint4*>(P.out + (size_t)(row0 + 8 * h) * D + j * 64 + q * 32 + t4 * 8) = make_uint4(v0, v1, v2, v3);
    }
    TS(12);
}

typedef CUresult (*EncodeFn)(CUtensorMap*, CUtensorMapDataType, cuuint32_t, void*, const cuuint64_t*, const cuuint64_t*, const cuuint32_t*,
                             const cuuint32_t*, CUtensorMapInterleave, CUtensorMapSwizzle, CUtensorMapL2promotion, CUtensorMapFloatOOBfill);

void encode2d(EncodeFn fn, CUtensorMap* tm, const void* ptr, int rows, int cols, int box_rows, int box_cols, CUtensorMapSwizzle sw) {
    cuuint64_t dims[2] = {(cuuint64_t)cols, (cuuint64_t)rows};
    cuuint64_t strides[1] = {(cuuint64_t)cols * 2};
    cuuint32_t box[2] = {(cuuint32_t)box_cols, (cuuint32_t)box_rows};
    cuuint32_t es[2] = {1, 1};
    fn(tm, CU_TENSOR_MAP_DATA_TYPE_BFLOAT16, 2, const_cast<void*>(ptr), dims, strides, box, es, CU_TENSOR_MAP_INTERLEAVE_NONE, sw,
       CU_TENSOR_MAP_L2_PROMOTION_L2_128B, CU_TENSOR_MAP_FLOAT_OOB_FILL_NONE);
}

}

extern "C" void kernel_launch(void* const* d_in, const int* in_sizes, int n_in, void* d_out, int out_size) {
    (void)in_sizes; (void)n_in; (void)out_size;
    void* fnp = nullptr;
    cudaDriverEntryPointQueryResult qr;
    cudaGetDriverEntryPoint("cuTensorMapEncodeTiled", &fnp, cudaEnableDefault, &qr);
    EncodeFn fn = (EncodeFn)fnp;
    Params P;
    encode2d(fn, &P.wq, d_in[1], D, D, 128, 64, CU_TENSOR_MAP_SWIZZLE_128B);
    P.wk = (const __nv_bfloat16*)d_in[2];
    P.wv = (const __nv_bfloat16*)d_in[3];
    encode2d(fn, &P.wo, d_in[4], D, D, 64, 64, CU_TENSOR_MAP_SWIZZLE_128B);
    encode2d(fn, &P.w1, d_in[6], D, FF, 128, 32, CU_TENSOR_MAP_SWIZZLE_64B);
    encode2d(fn, &P.w2, d_in[7], FF, D, 64, 64, CU_TENSOR_MAP_SWIZZLE_128B);
    P.x = (const __nv_bfloat16*)d_in[0];
    P.w1p = (const __nv_bfloat16*)d_in[6];
    P.w2p = (const __nv_bfloat16*)d_in[7];
    P.wop = (const __nv_bfloat16*)d_in[4];
    P.wqp = (const __nv_bfloat16*)d_in[1];
    P.out = (__nv_bfloat16*)d_out;
    P.neg1 = 0xFFFFFFFFu; P.pad = 0;
    cudaFuncSetAttribute(fused_kernel, cudaFuncAttributeMaxDynamicSharedMemorySize, SMEM_BYTES);
    fused_kernel<<<NCTA, 512, SMEM_BYTES>>>(P);
}
```

```cpp
#include <cuda_runtime.h>
#include <cuda_bf16.h>
#include <cuda.h>
#include <stdint.h>

namespace {

constexpr int D = 512, FF = 1376;
constexpr int NMAIN = 128, NHELP = 4, NCTA = NMAIN + NHELP;
constexpr uint32_t SENT = 0xFFFFFFFFu;
constexpr int SPIN_LIMIT = 1 << 22;

constexpr uint32_t KB = 1024;
constexpr uint32_t SM_XN = 0;
constexpr uint32_t SM_WQ = 64 * KB;
constexpr uint32_t SM_WKV = 176 * KB;
constexpr uint32_t SM_K = 0;
constexpr uint32_t SM_V = 64 * KB;
constexpr uint32_t SM_Q = 160 * KB;
constexpr uint32_t SM_SENT = 184 * KB;
constexpr uint32_t SM_MISC = 192 * KB;
constexpr uint32_t SMEM_BYTES = 195 * KB;
constexpr uint32_t MB_WQ = 0;
constexpr uint32_t MB_W1 = 4;
constexpr uint32_t MB_DONE = 8;
constexpr uint32_t MB_KV = 14;
constexpr uint32_t MB_WO = 16;
constexpr uint32_t MB_W2 = 24;
constexpr uint32_t MB_F2 = 46;
constexpr uint32_t MB_CS = 47;
constexpr uint32_t MISC_CNT = 384;
constexpr uint32_t MISC_NRM = 400;
constexpr uint32_t MISC_EPOCH = 416;
constexpr uint32_t MISC_CS = 448;
constexpr uint32_t MISC_RSTD = 448;
constexpr uint32_t MISC_KTMP = 1024;

__host__ __device__ constexpr uint32_t wo_slot(int kb) { return kb < 2 ? 22 + kb : kb - 2; }
__host__ __device__ constexpr uint32_t w2_slot(int kb) { return kb < 2 ? 6 + kb : kb < 4 ? 20 + kb : kb < 10 ? kb - 4 : 8 + (kb - 10) / 3 + 4 * ((kb - 10) % 3); }

struct alignas(128) Small {
    unsigned epoch[160];
    unsigned count1, pad1[31];
    unsigned count2, pad2[31];
    unsigned hint[100][32];
    float cs[1408];
    uint4 nrm[NMAIN];
    uint4 kv[8192];
    uint4 kplain[4096];
};
__device__ Small g_s;
constexpr int X_OF = 0, X_HF = 32 * 32 * 128, X_ST = X_HF + 32 * 32 * 128, X_H = X_ST + 32 * 64 * 8, X_END = X_H + 32 * 88 * 128;
constexpr int X_ARM = 16 * 32 * 128, X_SHARE = (X_END - X_ARM) / NMAIN;
__device__ uint4 g_x[X_END];
#define TS(i) do {} while (0)

__device__ __forceinline__ void mbar_init(uint32_t bar, int cnt) { asm volatile("mbarrier.init.shared::cta.b64 [%0], %1;" :: "r"(bar), "r"(cnt) : "memory"); }
__device__ __forceinline__ void mbar_expect(uint32_t bar, uint32_t bytes) { asm volatile("mbarrier.arrive.expect_tx.shared::cta.b64 _, [%0], %1;" :: "r"(bar), "r"(bytes) : "memory"); }
__device__ __forceinline__ void mbar_arrive(uint32_t bar) { asm volatile("mbarrier.arrive.shared::cta.b64 _, [%0];" :: "r"(bar) : "memory"); }
__device__ __forceinline__ void mbar_wait(uint32_t bar) {
    uint32_t done; int spins = 0;
    do {
        asm volatile("{.reg .pred p; mbarrier.try_wait.parity.shared::cta.b64 p, [%1], 0; selp.u32 %0, 1, 0, p;}" : "=r"(done) : "r"(bar) : "memory");
    } while (!__all_sync(0xffffffffu, done) && ++spins < SPIN_LIMIT);
}
__device__ __forceinline__ void tma2d(uint32_t dst, const CUtensorMap* tm, int c0, int c1, uint32_t bar) {
    asm volatile("cp.async.bulk.tensor.2d.shared::cluster.global.mbarrier::complete_tx::bytes [%0], [%1, {%3, %4}], [%2];"
                 :: "r"(dst), "l"(tm), "r"(bar), "r"(c0), "r"(c1) : "memory");
}
__device__ __forceinline__ void bulk_g2s(uint32_t dst, const void* src, uint32_t bytes, uint32_t bar) {
    asm volatile("cp.async.bulk.shared::cluster.global.mbarrier::complete_tx::bytes [%0], [%1], %2, [%3];" :: "r"(dst), "l"(src), "r"(bytes), "r"(bar) : "memory");
}
__device__ __forceinline__ void fence_async_smem() { asm volatile("fence.proxy.async.shared::cta;" ::: "memory"); }
__device__ __forceinline__ void bar_sync(int id, int n) { asm volatile("bar.sync %0, %1;" :: "r"(id), "r"(n) : "memory"); }
__device__ __forceinline__ void bar_arrive(int id, int n) { asm volatile("bar.arrive %0, %1;" :: "r"(id), "r"(n) : "memory"); }
__device__ __forceinline__ void wg_fence() { asm volatile("wgmma.fence.sync.aligned;" ::: "memory"); }
__device__ __forceinline__ void wg_commit() { asm volatile("wgmma.commit_group.sync.aligned;" ::: "memory"); }
template <int N> __device__ __forceinline__ void wg_wait() { asm volatile("wgmma.wait_group.sync.aligned %0;" :: "n"(N) : "memory"); }
template <int N> __device__ __forceinline__ void fence_regs(float (&d)[N]) {
#pragma unroll
    for (int i = 0; i < N; i++) asm volatile("" : "+f"(d[i]) :: "memory");
}
template <int N> __device__ __forceinline__ void fence_regs(uint32_t (&d)[N]) {
#pragma unroll
    for (int i = 0; i < N; i++) asm volatile("" : "+r"(d[i]) :: "memory");
}
__device__ __forceinline__ uint64_t mkdesc(uint32_t addr, uint32_t lbo, uint32_t sbo, uint32_t swz) {
    return (uint64_t)(((addr & 0x3FFFF) >> 4) | ((lbo >> 4) << 16)) | ((uint64_t)((sbo >> 4) | (swz << 30)) << 32);
}
__device__ __forceinline__ float ex2(float x) { float y; asm("ex2.approx.ftz.f32 %0, %1;" : "=f"(y) : "f"(x)); return y; }
__device__ __forceinline__ float rcp(float x) { float y; asm("rcp.approx.ftz.f32 %0, %1;" : "=f"(y) : "f"(x)); return y; }
__device__ __forceinline__ uint32_t pack_bf16(float lo, float hi) { uint32_t r; asm("cvt.rn.bf16x2.f32 %0, %1, %2;" : "=r"(r) : "f"(hi), "f"(lo)); return r; }
__device__ __forceinline__ uint32_t pack_f16(float lo, float hi) { uint32_t r; asm("cvt.rn.f16x2.f32 %0, %1, %2;" : "=r"(r) : "f"(hi), "f"(lo)); return r; }
__device__ __forceinline__ float bf_lo(uint32_t v) { return __uint_as_float(v << 16); }
__device__ __forceinline__ float bf_hi(uint32_t v) { return __uint_as_float(v & 0xFFFF0000u); }
__device__ __forceinline__ uint4 ldg_relaxed(const uint4* p) {
    uint4 v; asm volatile("ld.relaxed.gpu.global.v4.u32 {%0,%1,%2,%3}, [%4];" : "=r"(v.x), "=r"(v.y), "=r"(v.z), "=r"(v.w) : "l"(p) : "memory"); return v;
}
__device__ __forceinline__ void stg128(void* p, uint32_t a, uint32_t b, uint32_t c, uint32_t d) {
    asm volatile("st.relaxed.gpu.global.v4.u32 [%0], {%1,%2,%3,%4};" :: "l"(p), "r"(a), "r"(b), "r"(c), "r"(d) : "memory");
}
__device__ __forceinline__ void stg64(void* p, uint32_t a, uint32_t b) {
    asm volatile("st.relaxed.gpu.global.v2.u32 [%0], {%1,%2};" :: "l"(p), "r"(a), "r"(b) : "memory");
}
__device__ __forceinline__ void sts128(uint32_t a, uint32_t x, uint32_t y, uint32_t z, uint32_t w) {
    asm volatile("st.shared.v4.u32 [%0], {%1,%2,%3,%4};" :: "r"(a), "r"(x), "r"(y), "r"(z), "r"(w) : "memory");
}
__device__ __forceinline__ void sts32(uint32_t a, uint32_t x) { asm volatile("st.shared.u32 [%0], %1;" :: "r"(a), "r"(x) : "memory"); }
__device__ __forceinline__ float4 lds128f(uint32_t a) {
    float4 v; asm volatile("ld.shared.v4.f32 {%0,%1,%2,%3}, [%4];" : "=f"(v.x), "=f"(v.y), "=f"(v.z), "=f"(v.w) : "r"(a) : "memory"); return v;
}
__device__ __forceinline__ uint32_t lds32(uint32_t a) { uint32_t v; asm volatile("ld.shared.u32 %0, [%1];" : "=r"(v) : "r"(a) : "memory"); return v; }
__device__ __forceinline__ bool has_sent(const uint4& v) { return (v.x == SENT) | (v.w == SENT); }
__device__ __forceinline__ bool has_zero(const uint4& v) { return min(min(v.x, v.y), min(v.z, v.w)) == 0u; }
__device__ __forceinline__ uint32_t nonzero(uint32_t w) { return w == 0u ? 0x8000u : w; }
__device__ __forceinline__ void stg32(void* p, uint32_t a) { asm volatile("st.relaxed.gpu.global.u32 [%0], %1;" :: "l"(p), "r"(a) : "memory"); }
__device__ __forceinline__ void wait_count(const unsigned* p, unsigned target) {
    unsigned v; int spins = 0;
    do { asm volatile("ld.acquire.gpu.global.u32 %0, [%1];" : "=r"(v) : "l"(p) : "memory"); } while (__any_sync(0xffffffffu, v != target) && ++spins < SPIN_LIMIT);
}
__device__ __forceinline__ uint32_t warp_arrive(uint32_t cnt) {
    uint32_t old = 0;
    __syncwarp();
    if ((threadIdx.x & 31) == 0) asm volatile("atom.acq_rel.cta.shared.add.u32 %0, [%1], 1;" : "=r"(old) : "r"(cnt) : "memory");
    return __shfl_sync(0xffffffffu, old, 0);
}
__device__ __forceinline__ void warp_done(uint32_t bar) { __syncwarp(); if ((threadIdx.x & 31) == 0) mbar_arrive(bar); }
__device__ __forceinline__ uint32_t mul_bf16x2(uint32_t a, uint32_t b) { uint32_t r; asm("mul.rn.bf16x2 %0, %1, %2;" : "=r"(r) : "r"(a), "r"(b)); return r; }
__device__ __forceinline__ uint32_t fma_bf16x2(uint32_t a, uint32_t b, uint32_t c) { uint32_t r; asm("fma.rn.bf16x2 %0, %1, %2, %3;" : "=r"(r) : "r"(a), "r"(b), "r"(c)); return r; }
__device__ __forceinline__ uint32_t add_bf16x2(uint32_t a, uint32_t b) { uint32_t r; asm("add.rn.bf16x2 %0, %1, %2;" : "=r"(r) : "r"(a), "r"(b)); return r; }

#define R4(d, o) "+f"(d[o + 0]), "+f"(d[o + 1]), "+f"(d[o + 2]), "+f"(d[o + 3])
#define R8(d, o) R4(d, o), R4(d, o + 4)
#define R32(d) R8(d, 0), R8(d, 8), R8(d, 16), R8(d, 24)
#define D32 "{%0,%1,%2,%3,%4,%5,%6,%7,%8,%9,%10,%11,%12,%13,%14,%15,%16,%17,%18,%19,%20,%21,%22,%23,%24,%25,%26,%27,%28,%29,%30,%31}"
#define D44 "{%0,%1,%2,%3,%4,%5,%6,%7,%8,%9,%10,%11,%12,%13,%14,%15,%16,%17,%18,%19,%20,%21,%22,%23,%24,%25,%26,%27,%28,%29,%30,%31,%32,%33,%34,%35,%36,%37,%38,%39,%40,%41,%42,%43}"

__device__ __forceinline__ void mma_qk_f16(float (&d)[32], uint64_t da, uint64_t db) {
    asm volatile("{.reg .pred p; setp.eq.b32 p, 0, 0; wgmma.mma_async.sync.aligned.m64n64k16.f32.f16.f16 " D32 ", %32, %33, p, 1, 1, 0, 0;}"
                 : R32(d) : "l"(da), "l"(db));
}
__device__ __forceinline__ void mma_qk_bf16(float (&d)[32], uint64_t da, uint64_t db) {
    asm volatile("{.reg .pred p; setp.ne.b32 p, 0, 0; wgmma.mma_async.sync.aligned.m64n64k16.f32.bf16.bf16 " D32 ", %32, %33, p, 1, 1, 0, 0;}"
                 : R32(d) : "l"(da), "l"(db));
}
__device__ __forceinline__ void mma_pv(float (&d)[12], const uint32_t* a, uint64_t db) {
    asm volatile("{.reg .pred p; setp.eq.b32 p, 0, 0; wgmma.mma_async.sync.aligned.m64n24k16.f32.bf16.bf16 {%0,%1,%2,%3,%4,%5,%6,%7,%8,%9,%10,%11}, {%12,%13,%14,%15}, %16, p, 1, 1, 1;}"
                 : R8(d, 0), R4(d, 8) : "r"(a[0]), "r"(a[1]), "r"(a[2]), "r"(a[3]), "l"(db));
}
__device__ __forceinline__ void mma_ss64(float (&d)[32], uint64_t da, uint64_t db) {
    asm volatile("{.reg .pred p; setp.eq.b32 p, 0, 0; wgmma.mma_async.sync.aligned.m64n64k16.f32.bf16.bf16 " D32 ", %32, %33, p, 1, 1, 0, 1;}"
                 : R32(d) : "l"(da), "l"(db));
}
__device__ __forceinline__ void mma_ss8(float (&d)[4], uint64_t da, uint64_t db) {
    asm volatile("{.reg .pred p; setp.eq.b32 p, 0, 0; wgmma.mma_async.sync.aligned.m64n8k16.f32.bf16.bf16 {%0,%1,%2,%3}, %4, %5, p, 1, 1, 0, 1;}"
                 : R4(d, 0) : "l"(da), "l"(db));
}
__device__ __forceinline__ void mma_rs(float (&d)[32], const uint4& a, uint64_t db) {
    asm volatile("{.reg .pred p; setp.eq.b32 p, 0, 0; wgmma.mma_async.sync.aligned.m64n64k16.f32.bf16.bf16 " D32 ", {%32,%33,%34,%35}, %36, p, 1, 1, 1;}"
                 : R32(d) : "r"(a.x), "r"(a.y), "r"(a.z), "r"(a.w), "l"(db));
}
__device__ __forceinline__ void mma_rs(float (&d)[44], const uint4& a, uint64_t db) {
    asm volatile("{.reg .pred p; setp.eq.b32 p, 0, 0; wgmma.mma_async.sync.aligned.m64n88k16.f32.bf16.bf16 " D44 ", {%44,%45,%46,%47}, %48, p, 1, 1, 1;}"
                 : R32(d), R8(d, 32), R4(d, 40) : "r"(a.x), "r"(a.y), "r"(a.z), "r"(a.w), "l"(db));
}

constexpr float EXP_MAGIC = 256.0f + 127.0f + 64.0f - 1.58621f + 0.00390625f;
constexpr uint32_t MUFU_MASK = 0x1111u;
__device__ __forceinline__ uint32_t exp2_pair(float y0, float y1, uint32_t cexp, uint32_t neg1) {
    uint32_t w, m, e, r;
    asm("prmt.b32 %0, %1, %2, 0x6521;" : "=r"(w) : "r"(__float_as_uint(y0)), "r"(__float_as_uint(y1)));
    asm("lop3.b32 %0, %1, 0x007F007F, %2, 0xEA;" : "=r"(m) : "r"(w), "r"(cexp));
    asm("mad.lo.u32 %0, %1, %2, %3;" : "=r"(e) : "r"(m), "r"(neg1), "r"(w));
    asm("fma.rn.bf16x2 %0, %1, %2, %3;" : "=r"(r) : "r"(w), "r"(m), "r"(e));
    return r;
}

struct Params {
    const __nv_bfloat16* x;
    const __nv_bfloat16* wk;
    const __nv_bfloat16* wv;
    const __nv_bfloat16* wqp;
    __nv_bfloat16* out;
    uint32_t neg1, pad;
    const __nv_bfloat16* w1p;
    const __nv_bfloat16* w2p;
    CUtensorMap wq, wo, w1, w2;
    const __nv_bfloat16* wop;
};

__device__ __forceinline__ void load_box(uint32_t sb, const CUtensorMap* tm, uint32_t dst, uint32_t bar, uint32_t bytes, int c0, int c1) {
    mbar_expect(sb + SM_MISC + bar * 8, bytes);
    tma2d(sb + dst, tm, c0, c1, sb + SM_MISC + bar * 8);
}
__device__ __forceinline__ void load_wq(uint32_t sb, const Params& P, int gi, int atom) {
    load_box(sb, &P.wq, SM_WQ + atom * 65536 + gi * 16384, MB_WQ + gi, 16384, (blockIdx.x & 3) * 128 + atom * 64, gi * 128);
}
__device__ __forceinline__ void load_wo(uint32_t sb, const Params& P, int kb) { load_box(sb, &P.wo, wo_slot(kb) * 8192, MB_WO + kb, 8192, (blockIdx.x & 7) * 64, kb * 64); }
__device__ __forceinline__ void load_w2(uint32_t sb, const Params& P, int kb, int slot) { load_box(sb, &P.w2, slot * 8192, MB_W2 + kb, 8192, (blockIdx.x & 7) * 64, kb * 64); }
__device__ __forceinline__ void refill_job(uint32_t sb, const Params& P, int gi, int job) {
    const bool w1 = job < 3;
    const int kb = (gi < 3 ? 2 + 2 * gi : 0) + job - 3;
    load_box(sb, w1 ? &P.w1 : gi < 3 ? &P.wo : &P.w2, (w1 ? 8 + gi + 4 * job : 2 * gi + job - 3) * 8192, w1 ? MB_W1 + gi : (gi < 3 ? MB_WO : MB_W2) + kb, 8192,
             w1 ? (blockIdx.x & 15) * 88 + job * 32 : (blockIdx.x & 7) * 64, w1 ? gi * 128 : kb * 64);
}
__device__ __forceinline__ void release_w1(uint32_t sb, const Params& P, int gi) {
    if (warp_arrive(sb + SM_MISC + MISC_CNT + gi * 4) == 15) {
        if ((threadIdx.x & 31) == 0) {
#pragma unroll 1
            for (int a = 0; a < 3; a++) load_w2(sb, P, 10 + 3 * gi + a, 8 + gi + 4 * a);
        }
        __syncwarp();
    }
}

__device__ __forceinline__ void load_batch(uint4 (&buf)[4], const uint4* a) {
#pragma unroll
    for (int s = 0; s < 4; s++) buf[s] = ldg_relaxed(a + s * 128);
}
__device__ __forceinline__ bool batch_bad(const uint4 (&buf)[4]) {
    const uint32_t m = max(max(max(buf[0].x, buf[0].w), max(buf[1].x, buf[1].w)), max(max(buf[2].x, buf[2].w), max(buf[3].x, buf[3].w)));
    return __any_sync(0xffffffffu, m == SENT);
}
__device__ __forceinline__ void check_batch(uint4 (&buf)[4], const uint4* a) {
    if (__builtin_expect(batch_bad(buf), 0)) {
        int spins = 0;
        do load_batch(buf, a); while (batch_bad(buf) && ++spins < SPIN_LIMIT);
    }
}
constexpr int H_KV = 0, H_O = 1 - 16, H_H1 = 17, H_H2 = 49;
__device__ __forceinline__ void hint_arrive(int id) {
    if ((threadIdx.x & 31) == 0) asm volatile("red.relaxed.gpu.global.add.u32 [%0], 1;" :: "l"(g_s.hint[id]) : "memory");
}
__device__ __forceinline__ void hint_wait(int id, unsigned target) {
    uint32_t v; int spins = 0;
    do { asm volatile("ld.relaxed.gpu.global.u32 %0, [%1];" : "=r"(v) : "l"(g_s.hint[id]) : "memory"); } while (__any_sync(0xffffffffu, v != target) && ++spins < SPIN_LIMIT);
}

template <int KIND, int NBLK, int RING, int NACC>
__device__ __forceinline__ void gemm_rs(float (&acc)[NACC], uint4 (&buf)[RING][4], const uint4* a, uint32_t sb, int q, const Params& P) {
    constexpr int ASTR = (KIND == 1) ? 512 : 1024;
    const uint32_t mb = sb + SM_MISC;
#pragma unroll
    for (int i = 0; i < NACC; i++) acc[i] = 0.f;
    fence_regs(acc);
#pragma unroll
    for (int i = 0; i < NBLK; i++) {
        uint64_t db;
        if (KIND == 1) {
            db = mkdesc(sb + (8 + (i >> 1)) * 8192 + (i & 1) * 4096, 32768, 512, 2);
            if ((i & 1) == 0) mbar_wait(mb + (MB_W1 + (i >> 1)) * 8);
        } else {
            const uint32_t slot = KIND == 0 ? (q ? wo_slot(2 * i + 1) : wo_slot(2 * i)) : (q ? w2_slot(2 * i + 1) : w2_slot(2 * i));
            db = mkdesc(sb + slot * 8192, 16, 1024, 1);
            mbar_wait(mb + ((KIND == 0 ? MB_WO : MB_W2) + 2 * i + q) * 8);
        }
        check_batch(buf[i % RING], a + i * ASTR);
        wg_fence();
#pragma unroll
        for (int s = 0; s < 4; s++) mma_rs(acc, buf[i % RING][s], db + s * (KIND == 1 ? 64 : 128));
        wg_commit();
        const bool rel = KIND == 1 && i >= 2 && !(i & 1);
        if (i >= 1 && (i - 1 + RING < NBLK || rel)) {
            wg_wait<1>();
            if (i - 1 + RING < NBLK) load_batch(buf[(i - 1) % RING], a + (i - 1 + RING) * ASTR);
            if (rel) release_w1(sb, P, (i >> 1) - 1);
        }
    }
    wg_wait<0>();
    fence_regs(acc);
}

__device__ __forceinline__ void pair_reduce(const float (&acc)[32], float (&r)[16], uint32_t buf, int q, int barid) {
    if (q) {
#pragma unroll
        for (int j = 0; j < 4; j++) sts128(buf + j * 2048, __float_as_uint(acc[4 * j]), __float_as_uint(acc[4 * j + 1]), __float_as_uint(acc[4 * j + 2]), __float_as_uint(acc[4 * j + 3]));
        bar_sync(barid, 256);
        bar_sync(barid, 256);
#pragma unroll
        for (int j = 0; j < 4; j++) {
            float4 v = lds128f(buf + j * 2048);
            r[4 * j] = acc[16 + 4 * j] + v.x; r[4 * j + 1] = acc[17 + 4 * j] + v.y; r[4 * j + 2] = acc[18 + 4 * j] + v.z; r[4 * j + 3] = acc[19 + 4 * j] + v.w;
        }
    } else {
        bar_sync(barid, 256);
        float4 v[4];
#pragma unroll
        for (int j = 0; j < 4; j++) v[j] = lds128f(buf + j * 2048);
#pragma unroll
        for (int j = 0; j < 4; j++) sts128(buf + j * 2048, __float_as_uint(acc[16 + 4 * j]), __float_as_uint(acc[17 + 4 * j]), __float_as_uint(acc[18 + 4 * j]), __float_as_uint(acc[19 + 4 * j]));
        bar_arrive(barid, 256);
#pragma unroll
        for (int j = 0; j < 4; j++) {
            r[4 * j] = acc[4 * j] + v[j].x; r[4 * j + 1] = acc[4 * j + 1] + v[j].y; r[4 * j + 2] = acc[4 * j + 2] + v[j].z; r[4 * j + 3] = acc[4 * j + 3] + v[j].w;
        }
    }
}

__device__ __forceinline__ float quad_sum(float v) { v += __shfl_xor_sync(0xffffffffu, v, 1); v += __shfl_xor_sync(0xffffffffu, v, 2); return v; }
__device__ __forceinline__ float silu2(float h) { float t; asm("tanh.approx.f32 %0, %1;" : "=f"(t) : "f"(h)); return fmaf(h, t, h); }

#define TS_ARG
#define TS_PASS

template <bool SAFE>
__device__ __forceinline__ void attention(const Params& P, uint32_t sb, int warp TS_ARG) {
    const uint32_t mb = sb + SM_MISC;
    const int tid = threadIdx.x, lane = tid & 31, b = blockIdx.x;
    const int wg = warp >> 2, ww = warp & 3, job = 3 - wg + 4 * ww;
    const uint32_t cexp = 0x9F809F80u + (tid >> 12);
    const uint32_t neg1 = P.neg1;
    unsigned cnt = 0;
    if (SAFE && warp == 8) asm volatile("ld.relaxed.gpu.global.u32 %0, [%1];" : "=r"(cnt) : "l"(&g_s.count1) : "memory");
#pragma unroll 1
    for (int pass = 0; pass < 2; pass++) {
    float o[12], s[32];
    const uint64_t dq = mkdesc(sb + SM_Q + (pass * 4 + wg) * 2048, 128, 256, 0);
    uint64_t dk = mkdesc(sb + SM_K, 128, 256, 0), dv = mkdesc(sb + SM_V, 128, 32768, 0);
    float m0 = -INFINITY, m1 = -INFINITY;
#pragma unroll
    for (int i = 0; i < 12; i++) o[i] = 0.f;
#pragma unroll
    for (int i = 0; i < 32; i++) s[i] = ((MUFU_MASK >> (i / 2)) & 1) ? 0.f : EXP_MAGIC;
    fence_regs(s); fence_regs(o);
    wg_fence();
    if (SAFE) mma_qk_f16(s, dq, dk + 31 * 128); else mma_qk_bf16(s, dq, dk + 31 * 128);
    wg_commit();
    wg_wait<0>(); fence_regs(s);
#pragma unroll 1
    for (int u = pass ? 3 : (wg == 2) ? 0 : 1; u < (pass ? 8 : 3); u++) {
        int n = 2 * ((((wg == 2) ? 0x22444C31u : 0x22444C40u) >> (4 * u)) & 15);
#pragma unroll 1
        do {
            uint32_t p[16];
            if (SAFE) {
#pragma unroll
                for (int j = 0; j < 16; j++) {
                    if ((MUFU_MASK >> j) & 1) p[j] = pack_bf16(ex2(s[2 * j]), ex2(s[2 * j + 1]));
                    else p[j] = exp2_pair(s[2 * j], s[2 * j + 1], cexp, neg1);
                }
            } else {
                fence_regs(o);
                float x0 = m0, x1 = m1;
#pragma unroll
                for (int j = 0; j < 8; j++) { x0 = fmaxf(x0, fmaxf(s[4 * j], s[4 * j + 1])); x1 = fmaxf(x1, fmaxf(s[4 * j + 2], s[4 * j + 3])); }
                x0 = fmaxf(x0, __shfl_xor_sync(0xffffffffu, x0, 1)); x0 = fmaxf(x0, __shfl_xor_sync(0xffffffffu, x0, 2));
                x1 = fmaxf(x1, __shfl_xor_sync(0xffffffffu, x1, 1)); x1 = fmaxf(x1, __shfl_xor_sync(0xffffffffu, x1, 2));
                const float c0 = ex2(m0 - x0), c1 = ex2(m1 - x1);
                m0 = x0; m1 = x1;
#pragma unroll
                for (int j = 0; j < 3; j++) { o[4 * j] *= c0; o[4 * j + 1] *= c0; o[4 * j + 2] *= c1; o[4 * j + 3] *= c1; }
#pragma unroll
                for (int j = 0; j < 8; j++) {
                    p[2 * j] = pack_bf16(ex2(s[4 * j] - m0), ex2(s[4 * j + 1] - m0));
                    p[2 * j + 1] = pack_bf16(ex2(s[4 * j + 2] - m1), ex2(s[4 * j + 3] - m1));
                }
                fence_regs(o);
            }
            fence_regs(p);
            wg_fence();
            if (SAFE) mma_qk_f16(s, dq, dk); else mma_qk_bf16(s, dq, dk);
#pragma unroll
            for (int j = 0; j < 4; j++) mma_pv(o, p + 4 * j, dv + j * 16);
            wg_commit();
            dk += 128; dv += 64;
            wg_wait<0>(); fence_regs(s);
        } while (--n > 0);
        if (u == 2 || u == 7) {
            fence_regs(o);
            const float i0 = rcp(o[8]), i1 = rcp(o[10]);
            if (u == 7) mbar_wait(mb + MB_F2 * 8);
            stg128(g_x + X_OF + (((u == 7) * 16 + (b >> 3)) * 32 + (b & 3) * 8 + 2 * wg + (ww >> 1)) * 128 + (((b >> 2) & 1) * 2 + (ww & 1)) * 32 + lane,
                   pack_bf16(o[0] * i0, o[1] * i0), pack_bf16(o[2] * i1, o[3] * i1), pack_bf16(o[4] * i0, o[5] * i0), pack_bf16(o[6] * i1, o[7] * i1));
            if (u == 2) asm volatile("cp.async.bulk.wait_group 0;" ::: "memory");
            else hint_arrive(H_O + 16 + (b >> 3));
            warp_done(mb + (MB_DONE + (u == 7) * 4) * 8);
            TS(5 + (u == 7));
        } else if (u >= 3) {
            if (u < 6) warp_done(mb + (MB_DONE + u - 2) * 8);
            if (job < (u == 3 ? 2 : 5)) {
                mbar_wait(mb + (MB_DONE + u - 3) * 8);
                if (lane == 0) {
                    if (u > 3) refill_job(sb, P, u - 4, job);
                    else if (job == 1) load_wo(sb, P, 1);
                    else asm volatile("red.release.gpu.global.add.u32 [%0], 1;" :: "l"(&g_s.count2) : "memory");
                }
            } else if (warp == 11) {
                if (u == 5) asm volatile("ld.relaxed.gpu.global.u32 %0, [%1];" : "=r"(cnt) : "l"(&g_s.count2) : "memory");
                if (u == 6) {
                    const unsigned target = lds32(mb + MISC_EPOCH) * NCTA;
                    if (__any_sync(0xffffffffu, cnt != target)) wait_count(&g_s.count2, target);
                    asm volatile("fence.acquire.gpu;" ::: "memory");
                    warp_done(mb + MB_F2 * 8);
                }
            }
        } else if (u == 1) {
            if (SAFE) mbar_wait(mb + MB_KV * 8);
            TS(17);
    if (lane == 0) {
        if (job < 9) {
            asm volatile("cp.async.bulk.global.shared::cta.bulk_group [%0], [%1], %2;"
                         :: "l"(g_x + X_ARM + b * X_SHARE + job * 512), "r"(sb + SM_SENT), "r"(job < 8 ? 8192 : (X_SHARE - 4096) * 16) : "memory");
            asm volatile("cp.async.bulk.commit_group;" ::: "memory");
        } else if (job == 9) load_wo(sb, P, 0);
    }
        } else if (SAFE) {
            if (warp == 8) {
                const unsigned target = lds32(mb + MISC_EPOCH) * NMAIN;
                if (__any_sync(0xffffffffu, cnt != target)) wait_count(&g_s.count1, target);
                if (lane == 0) {
                    asm volatile("fence.acquire.gpu; fence.proxy.async.global;" ::: "memory");
                    mbar_expect(mb + MB_KV * 8, 47104 + 2 * 24576);
                    bulk_g2s(sb + SM_K + 16384, g_s.kv + 1024, 47104, mb + MB_KV * 8);
                    bulk_g2s(sb + SM_V + 8192, g_s.kv + 4096 + 512, 24576, mb + MB_KV * 8);
                    bulk_g2s(sb + SM_V + 32768 + 8192, g_s.kv + 6144 + 512, 24576, mb + MB_KV * 8);
                }
            }
        }
        __syncwarp();
    }
    }
}

__device__ __noinline__ void helper_cta(const Params& P, uint8_t* smem) {
    const int tid = threadIdx.x, b = blockIdx.x, hi = b - NMAIN;
    const unsigned epoch = g_s.epoch[b] + 1;
    float* red = reinterpret_cast<float*>(smem);
    if (tid < 32) wait_count(&g_s.count1, epoch * NMAIN);
    __syncthreads();
    if (tid == 480) {
        for (int i = 0; i < 8; i++) asm volatile("cp.async.bulk.prefetch.L2.global [%0], %1;" :: "l"((const char*)P.wop + hi * 131072 + i * 16384), "r"(16384) : "memory");
        for (int i = 0; i < 43; i++) asm volatile("cp.async.bulk.prefetch.L2.global [%0], %1;" :: "l"((const char*)P.w2p + hi * 352256 + i * 8192), "r"(8192) : "memory");
    }
    if (tid < 344) {
        const int cg = tid % 43, rp = tid / 43;
        const uint4* src = reinterpret_cast<const uint4*>(P.w1p + (size_t)rp * 64 * FF + (hi * 43 + cg) * 8);
        float s[8] = {0, 0, 0, 0, 0, 0, 0, 0};
#pragma unroll 8
        for (int r = 0; r < 64; r++) {
            uint4 v = __ldg(src + r * (FF / 8));
            s[0] += bf_lo(v.x); s[1] += bf_hi(v.x); s[2] += bf_lo(v.y); s[3] += bf_hi(v.y);
            s[4] += bf_lo(v.z); s[5] += bf_hi(v.z); s[6] += bf_lo(v.w); s[7] += bf_hi(v.w);
        }
        float* part = red + (rp * 43 + cg) * 8;
#pragma unroll
        for (int i = 0; i < 8; i++) part[i] = s[i];
    }
    __syncthreads();
    if (tid < 344) {
        float s = 0.f;
#pragma unroll
        for (int rp = 0; rp < 8; rp++) s += red[rp * 344 + tid];
        g_s.cs[hi * 344 + tid] = s;
    } else if (hi == 3 && tid < 344 + 32) g_s.cs[FF + tid - 344] = 0.f;
    __syncthreads();
    if (tid == 0) {
        asm volatile("red.release.gpu.global.add.u32 [%0], 1;" :: "l"(&g_s.count2) : "memory");
        g_s.epoch[b] = epoch;
    }
}

__global__ void __launch_bounds__(512, 1) fused_kernel(const __grid_constant__ Params P) {
    extern __shared__ __align__(1024) uint8_t smem[];
    const uint32_t sb = (uint32_t)__cvta_generic_to_shared(smem);
    const uint32_t mb = sb + SM_MISC;
    const int tid = threadIdx.x, lane = tid & 31, b = blockIdx.x;
    if (b >= NMAIN) { helper_cta(P, smem); return; }
    const int tg = b >> 2, hg = b & 3;
    const int warp = __shfl_sync(0xffffffffu, tid >> 5, 0);

    uint4 xv[4][2];
    unsigned epoch = 0;
    {
        const int r = (tid >> 5) * 4;
        const uint4* src = reinterpret_cast<const uint4*>(P.x + (size_t)((r & 31) + tg * 32 + (r >> 5) * 1024) * D) + lane;
#pragma unroll
        for (int i = 0; i < 4; i++) { xv[i][0] = ldg_relaxed(src + i * 64); xv[i][1] = ldg_relaxed(src + i * 64 + 32); }
    }
    const uint4 wkv = ldg_relaxed(reinterpret_cast<const uint4*>(hg < 2 ? P.wk : P.wv) + tid * 2 + (hg & 1));
    const int wg = warp >> 2, ww = warp & 3, g = lane >> 2, t4 = lane & 3, t128 = tid & 127;
    if (lane == 0) {
        mbar_init(mb + warp * 8, warp < 4 ? 2 : warp < 8 ? 3 : warp < 14 ? 16 : 1);
        mbar_init(mb + (16 + warp) * 8, 1);
        mbar_init(mb + (32 + warp) * 8, 1);
        if (warp < 4) {
            asm volatile("fence.mbarrier_init.release.cluster;" ::: "memory");
            load_wq(sb, P, warp, 0);
            if (warp < 3) load_wq(sb, P, warp, 1);
        } else if (warp < 7) {
            asm volatile("prefetch.tensormap [%0];" :: "l"(&P.wo + (warp - 4)) : "memory");
        } else if (warp == 7) {
            asm volatile("ld.relaxed.gpu.global.u32 %0, [%1];" : "=r"(epoch) : "l"(g_s.epoch + b) : "memory");
        } else if (warp < 10) {
            sts128(mb + MISC_CNT + (warp - 8) * 16, 0, 0, 0, 0);
        }
    }
    __syncwarp();
    TS(16);
    float dlt[4];
    {
        float st[4];
#pragma unroll
        for (int i = 0; i < 4; i++) {
            const uint32_t s = add_bf16x2(add_bf16x2(add_bf16x2(xv[i][0].x, xv[i][0].y), add_bf16x2(xv[i][0].z, xv[i][0].w)),
                                          add_bf16x2(add_bf16x2(xv[i][1].x, xv[i][1].y), add_bf16x2(xv[i][1].z, xv[i][1].w)));
            st[i] = bf_lo(s) + bf_hi(s);
        }
        TS(13);
#pragma unroll
        for (int o = 16; o > 0; o >>= 1)
#pragma unroll
            for (int i = 0; i < 4; i++) st[i] += __shfl_xor_sync(0xffffffffu, st[i], o);
#pragma unroll
        for (int i = 0; i < 4; i++) {
            const float nmean = st[i] * (-1.0f / D);
            const uint32_t nm = pack_bf16(nmean, nmean);
            dlt[i] = bf_lo(nm) - nmean;
            const int r = warp * 4 + i;
#pragma unroll
            for (int c = 0; c < 2; c++) {
                xv[i][c].x = add_bf16x2(xv[i][c].x, nm); xv[i][c].y = add_bf16x2(xv[i][c].y, nm);
                xv[i][c].z = add_bf16x2(xv[i][c].z, nm); xv[i][c].w = add_bf16x2(xv[i][c].w, nm);
                sts128(sb + SM_XN + ((lane >> 3) + 4 * c) * 8192 + r * 128 + (((lane & 7) ^ (r & 7)) << 4), xv[i][c].x, xv[i][c].y, xv[i][c].z, xv[i][c].w);
            }
        }
    }
    sts128(sb + SM_WKV + tid * 16, wkv.x, wkv.y, wkv.z, wkv.w);
    fence_async_smem();
    TS(0);
    __syncthreads();
    auto variances = [&]() {
        float st[4];
#pragma unroll
        for (int i = 0; i < 4; i++) {
            float v = 0.f;
#pragma unroll
            for (int c = 0; c < 2; c++) {
                const uint32_t a = fma_bf16x2(xv[i][c].x, xv[i][c].x, mul_bf16x2(xv[i][c].y, xv[i][c].y));
                const uint32_t d = fma_bf16x2(xv[i][c].z, xv[i][c].z, mul_bf16x2(xv[i][c].w, xv[i][c].w));
                v += (bf_lo(a) + bf_hi(a)) + (bf_lo(d) + bf_hi(d));
            }
            st[i] = v;
        }
        const bool u16 = lane & 16, u8 = lane & 8;
        float a0 = (u16 ? st[2] : st[0]) + __shfl_xor_sync(0xffffffffu, u16 ? st[0] : st[2], 16);
        float a1 = (u16 ? st[3] : st[1]) + __shfl_xor_sync(0xffffffffu, u16 ? st[1] : st[3], 16);
        float vs = (u8 ? a1 : a0) + __shfl_xor_sync(0xffffffffu, u8 ? a0 : a1, 8);
        vs += __shfl_xor_sync(0xffffffffu, vs, 4); vs += __shfl_xor_sync(0xffffffffu, vs, 2); vs += __shfl_xor_sync(0xffffffffu, vs, 1);
        const float dl = u16 ? (u8 ? dlt[3] : dlt[2]) : (u8 ? dlt[1] : dlt[0]);
        if ((lane & 7) == 0) sts32(mb + MISC_RSTD + (warp * 4 + (lane >> 3)) * 4, __float_as_uint(rsqrtf(fmaxf(vs * (1.0f / D) - dl * dl, 0.f) + 1e-5f)));
    };
    float kv[4] = {0.f, 0.f, 0.f, 0.f};
    if (wg == 2) {
        fence_regs(kv);
        const uint64_t da = mkdesc(sb + SM_XN, 16, 1024, 1), db = mkdesc(sb + SM_WKV, 128, 16, 0);
        wg_fence();
#pragma unroll
        for (int s = 0; s < 32; s++) mma_ss8(kv, da + (s >> 2) * 512 + (s & 3) * 2, db + s * 16);
        wg_commit();
        TS(18);
        variances();
        wg_wait<0>(); fence_regs(kv);
        TS(20);
    } else {
        variances();
        if (tid == 7 * 32) { sts32(mb + MISC_EPOCH, epoch + 1); g_s.epoch[b] = epoch + 1; }
        TS(19);
    }
    __syncthreads();
    constexpr float QSCALE = 0.25f * 1.4426950408889634f;
    uint32_t kvoff[2];
#pragma unroll
    for (int i = 0; i < 2; i++) {
        const int t = ((ww & 1) * 16 + g + 8 * i), c = 2 * tg + (ww >> 1);
        kvoff[i] = hg < 2 ? ((t + 31) & 31) * 2048 + (c >> 3) * 256 + (hg & 1) * 128 + (c & 7) * 16 + t4 * 4
                          : 65536 + (hg & 1) * 32768 + (t * 64 + c) * 16 + t4 * 4;
    }
    float qa[32];
    if (wg < 2) {
#pragma unroll
        for (int i = 0; i < 32; i++) qa[i] = 0.f;
        fence_regs(qa);
        const uint64_t da = mkdesc(sb + SM_XN, 16, 1024, 1), db = mkdesc(sb + SM_WQ + wg * 65536, 16, 1024, 1);
#pragma unroll 1
        for (int i = 0; i < 4; i++) {
            mbar_wait(mb + (MB_WQ + i) * 8);
            if (i == 0) TS(21); if (i == 3) TS(22);
            wg_fence();
#pragma unroll
            for (int s = 0; s < 8; s++) mma_ss64(qa, da + (i * 2 + (s >> 2)) * 512 + (s & 3) * 2, db + (i * 8 + s) * 128);
            wg_commit();
        }
        const float rs0 = __uint_as_float(lds32(mb + MISC_RSTD + (ww * 16 + g) * 4)) * QSCALE, rs1 = __uint_as_float(lds32(mb + MISC_RSTD + (ww * 16 + g + 8) * 4)) * QSCALE;
        wg_wait<0>();
        fence_regs(qa);
        bar_arrive(5, 384); bar_arrive(6, 384);
        TS(1);
        float nn[8];
#pragma unroll
        for (int i = 0; i < 32; i++) qa[i] *= (i & 2) ? rs1 : rs0;
#pragma unroll
        for (int h = 0; h < 4; h++) {
            nn[2 * h] = qa[8 * h] * qa[8 * h] + qa[8 * h + 1] * qa[8 * h + 1] + qa[8 * h + 4] * qa[8 * h + 4] + qa[8 * h + 5] * qa[8 * h + 5];
            nn[2 * h + 1] = qa[8 * h + 2] * qa[8 * h + 2] + qa[8 * h + 3] * qa[8 * h + 3] + qa[8 * h + 6] * qa[8 * h + 6] + qa[8 * h + 7] * qa[8 * h + 7];
        }
#pragma unroll
        for (int o = 1; o < 4; o <<= 1)
#pragma unroll
            for (int i = 0; i < 8; i++) nn[i] += __shfl_xor_sync(0xffffffffu, nn[i], o);
        bar_sync(1, 256);
#pragma unroll
        for (int h = 0; h < 4; h++) {
            const uint32_t base = sb + SM_Q + ((ww >> 1) * 4 + wg * 2 + (h >> 1)) * 2048 + ((h & 1) * 4 + (ww & 1) * 2) * 256 + lane * 4;
            sts32(base, pack_f16(qa[8 * h], qa[8 * h + 1])); sts32(base + 256, pack_f16(qa[8 * h + 2], qa[8 * h + 3]));
            sts32(base + 128, pack_f16(qa[8 * h + 4], qa[8 * h + 5])); sts32(base + 384, pack_f16(qa[8 * h + 6], qa[8 * h + 7]));
        }
        uint32_t nm = 0;
#pragma unroll
        for (int i = 0; i < 8; i++) nm = max(nm, __float_as_uint(nn[i]));
        nm = __reduce_max_sync(0xffffffffu, nm);
        if (lane == 0) asm volatile("red.shared.max.u32 [%0], %1;" :: "r"(mb + MISC_NRM), "r"(nm) : "memory");
    } else if (wg == 2) {
        const float rs0 = __uint_as_float(lds32(mb + MISC_RSTD + (ww * 16 + g) * 4)), rs1 = __uint_as_float(lds32(mb + MISC_RSTD + (ww * 16 + g + 8) * 4));
        kv[0] *= rs0; kv[1] *= rs0; kv[2] *= rs1; kv[3] *= rs1;
        char* img = reinterpret_cast<char*>(g_s.kv);
        const int r0 = ww * 16 + g;
        float2* kt = reinterpret_cast<float2*>(smem + SM_MISC + MISC_KTMP);
        if (hg < 2) { kt[r0 * 4 + t4] = make_float2(kv[0], kv[1]); kt[(r0 + 8) * 4 + t4] = make_float2(kv[2], kv[3]); }
        float n0 = kv[0] * kv[0] + kv[1] * kv[1], n1 = kv[2] * kv[2] + kv[3] * kv[3];
        n0 += __shfl_xor_sync(0xffffffffu, n0, 1); n1 += __shfl_xor_sync(0xffffffffu, n1, 1);
        n0 += __shfl_xor_sync(0xffffffffu, n0, 2); n1 += __shfl_xor_sync(0xffffffffu, n1, 2);
        const uint32_t nm = __reduce_max_sync(0xffffffffu, max(__float_as_uint(n0), __float_as_uint(n1)));
        const uint32_t b0 = pack_bf16(kv[0], kv[1]), b1 = pack_bf16(kv[2], kv[3]);
        uint32_t w0 = b0, w1 = b1;
        if (hg < 2) {
            bar_sync(2, 128);
            float2 p0 = make_float2(0.f, 0.f);
            if (r0 & 31) p0 = kt[(r0 - 1) * 4 + t4];
            const float2 p1 = kt[(r0 + 7) * 4 + t4];
            w0 = pack_f16(kv[0] - p0.x, kv[1] - p0.y); w1 = pack_f16(kv[2] - p1.x, kv[3] - p1.y);
        }
        stg32(img + kvoff[0], nonzero(w0));
        stg32(img + kvoff[1], nonzero(w1));
        if (lane == 0) stg32(reinterpret_cast<uint32_t*>(g_s.nrm + b) + ww, nm | 1u);
        hint_arrive(H_KV);
        TS(1);
        if (hg < 2) { stg32(reinterpret_cast<char*>(g_s.kplain) + kvoff[0], b0); stg32(reinterpret_cast<char*>(g_s.kplain) + kvoff[1], b1); }
        bar_sync(2, 128);
        if (t128 == 0) asm volatile("red.release.gpu.global.add.u32 [%0], 1;" :: "l"(&g_s.count1) : "memory");
        __syncwarp();
        bar_sync(5, 384);
#pragma unroll
        for (int i = 0; i < 16; i++) sts128(sb + SM_V + 65536 + (i * 128 + t128) * 16, 0x3F803F80u, 0x3F803F80u, 0x3F803F80u, 0x3F803F80u);
#pragma unroll
        for (int i = 0; i < 4; i++) sts128(sb + SM_SENT + (i * 128 + t128) * 16, SENT, SENT, SENT, SENT);
    } else {
        if (tid == 13 * 32) load_wq(sb, P, 3, 1);
        __syncwarp();
        uint4 kc[18];
        auto src = [&](int i) { return i < 8 ? g_s.kv + i * 128 : i < 12 ? g_s.kv + 4096 + (i - 8) * 128 : i < 16 ? g_s.kv + 6144 + (i - 12) * 128 : i == 16 ? g_s.kv + 31 * 128 : g_s.nrm; };
        hint_wait(H_KV, lds32(mb + MISC_EPOCH) * (NMAIN * 4));
        TS(1);
        int spins = 0;
        while (true) {
#pragma unroll
            for (int i = 0; i < 18; i++) kc[i] = ldg_relaxed(src(i) + t128);
            uint32_t mn = 1;
#pragma unroll
            for (int i = 0; i < 18; i++) mn = min(min(mn, min(kc[i].x, kc[i].y)), min(kc[i].z, kc[i].w));
            if (!__any_sync(0xffffffffu, mn == 0u) || ++spins >= SPIN_LIMIT) break;
        }
        uint32_t nm = max(max(kc[17].x, kc[17].y), max(kc[17].z, kc[17].w));
        nm = max(nm, __shfl_xor_sync(0xffffffffu, nm, 4)); nm = max(nm, __shfl_xor_sync(0xffffffffu, nm, 8)); nm = max(nm, __shfl_xor_sync(0xffffffffu, nm, 16));
        if (lane < 4) asm volatile("red.shared.max.u32 [%0], %1;" :: "r"(mb + MISC_NRM + 4 + min(lane, 2) * 4), "r"(nm) : "memory");
        TS(2);
        bar_sync(6, 384);
#pragma unroll
        for (int i = 0; i < 17; i++) sts128(sb + (uint32_t)(src(i) - g_s.kv + t128) * 16, kc[i].x, kc[i].y, kc[i].z, kc[i].w);
    }
    fence_async_smem();
    TS(3);
    __syncthreads();
    const float4 nr = lds128f(mb + MISC_NRM);
    const bool safe = __all_sync(0xffffffffu, (nr.x * (nr.y + nr.z) <= 3500.0f) && (nr.x <= 65536.0f) && (nr.y + nr.z <= 65536.0f) && (nr.w <= 1e24f));
    TS(4);

    if (__builtin_expect(safe, 1)) {
        attention<true>(P, sb, warp TS_PASS);
    } else {
        if (wg < 2) {
#pragma unroll
            for (int h = 0; h < 4; h++) {
                const uint32_t base = sb + SM_Q + ((ww >> 1) * 4 + wg * 2 + (h >> 1)) * 2048 + ((h & 1) * 4 + (ww & 1) * 2) * 256 + lane * 4;
                sts32(base, pack_bf16(qa[8 * h], qa[8 * h + 1])); sts32(base + 256, pack_bf16(qa[8 * h + 2], qa[8 * h + 3]));
                sts32(base + 128, pack_bf16(qa[8 * h + 4], qa[8 * h + 5])); sts32(base + 384, pack_bf16(qa[8 * h + 6], qa[8 * h + 7]));
            }
            fence_async_smem();
        } else if (warp == 15) {
            wait_count(&g_s.count1, lds32(mb + MISC_EPOCH) * NMAIN);
            if (lane == 0) {
                asm volatile("fence.proxy.async;" ::: "memory");
                mbar_expect(mb + MB_KV * 8, 131072);
                bulk_g2s(sb + SM_K, g_s.kplain, 65536, mb + MB_KV * 8);
                bulk_g2s(sb + SM_V, g_s.kv + 4096, 65536, mb + MB_KV * 8);
            }
            __syncwarp();
        }
        __syncthreads();
        mbar_wait(mb + MB_KV * 8);
        attention<false>(P, sb, warp TS_PASS);
    }

    const int pr = 1 - (wg >> 1), q = wg & 1;
    const int mt = 16 * pr + (b >> 3), j = b & 7;
    const int row0 = mt * 64 + ww * 16 + g;
    const uint32_t xbuf = sb + SM_Q + pr * 8192 + t128 * 16;
    uint32_t hk[8];
    epoch = lds32(mb + MISC_EPOCH);
    {
        const uint4* a = g_x + X_OF + (mt * 32 + q * 4) * 128 + t128;
        if (pr) {
            if (warp < 5) {
                mbar_wait(mb + (MB_DONE + 4) * 8);
                if (lane == 0) refill_job(sb, P, 3, warp);
            } else if (warp == 5) {
                if (lane < 22) {
                    const uint4 v = ldg_relaxed(reinterpret_cast<const uint4*>(g_s.cs + (b & 15) * 88) + lane);
                    sts128(mb + MISC_CS + lane * 16, v.x, v.y, v.z, v.w);
                }
                warp_done(mb + MB_CS * 8);
            }
            __syncwarp();
            hint_wait(H_O + mt, epoch * 128);
        }
        uint4 buf[4][4];
#pragma unroll
        for (int i = 0; i < 4; i++) load_batch(buf[i], a + i * 1024);
        const uint32_t* xp = reinterpret_cast<const uint32_t*>(P.x + (size_t)row0 * D + j * 64 + q * 32 + t4 * 2);
#pragma unroll
        for (int i = 0; i < 4; i++) { hk[2 * i] = __ldg(xp + i * 4); hk[2 * i + 1] = __ldg(xp + i * 4 + 8 * (D / 2)); }
        TS(23);
        float acc[32], r[16];
        gemm_rs<0, 4, 4>(acc, buf, a, sb, q, P);
        TS(7);
        warp_done(mb + (MB_DONE + 5) * 8);
        mbar_wait(mb + (MB_DONE + 4 * pr) * 8);
        pair_reduce(acc, r, xbuf, q, 3 + pr);
#pragma unroll
        for (int i = 0; i < 8; i++) hk[i] = pack_bf16(r[2 * i] + bf_lo(hk[i]), r[2 * i + 1] + bf_hi(hk[i]));
        float s0 = 0.f, s1 = 0.f;
#pragma unroll
        for (int i = 0; i < 8; i++) {
            r[2 * i] = bf_lo(hk[i]); r[2 * i + 1] = bf_hi(hk[i]);
            if (i & 1) s1 += r[2 * i] + r[2 * i + 1]; else s0 += r[2 * i] + r[2 * i + 1];
        }
        s0 += __shfl_xor_sync(0xffffffffu, s0, 1); s1 += __shfl_xor_sync(0xffffffffu, s1, 1);
        s0 += __shfl_xor_sync(0xffffffffu, s0, 2); s1 += __shfl_xor_sync(0xffffffffu, s1, 2);
        const float a0 = s0 * (1.0f / 32), a1 = s1 * (1.0f / 32);
        float v0 = 0.f, v1 = 0.f;
#pragma unroll
        for (int i = 0; i < 8; i++) {
            const float am = (i & 1) ? a1 : a0;
            const float d0 = r[2 * i] - am, d1 = r[2 * i + 1] - am;
            if (i & 1) v1 += d0 * d0 + d1 * d1; else v0 += d0 * d0 + d1 * d1;
        }
        v0 += __shfl_xor_sync(0xffffffffu, v0, 1); v1 += __shfl_xor_sync(0xffffffffu, v1, 1);
        v0 += __shfl_xor_sync(0xffffffffu, v0, 2); v1 += __shfl_xor_sync(0xffffffffu, v1, 2);
        uint4* hp = g_x + X_HF + (mt * 32 + j * 4 + 2 * q) * 128 + t128;
        stg128(hp, hk[0], hk[1], hk[2], hk[3]);
        stg128(hp + 128, hk[4], hk[5], hk[6], hk[7]);
        if (t4 < 2) stg64(reinterpret_cast<float2*>(g_x + X_ST) + (row0 + 8 * t4) * 16 + j * 2 + q, __float_as_uint(t4 ? s1 : s0), __float_as_uint(t4 ? v1 : v0));
        hint_arrive(H_H1 + mt);
        TS(8);
        if (pr) {
            mbar_wait(mb + (MB_DONE + 5) * 8);
            if (lane == 0) load_w2(sb, P, 2 + warp, warp < 2 ? 22 + warp : warp - 2);
            __syncwarp();
        } else if (wg == 2) {
            stg32(reinterpret_cast<char*>(g_s.kv) + kvoff[0], 0u);
            stg32(reinterpret_cast<char*>(g_s.kv) + kvoff[1], 0u);
            if (lane == 0) stg32(reinterpret_cast<uint32_t*>(g_s.nrm + b) + ww, 0u);
        }
    }
    {
        const int mt1 = 16 * pr + (b >> 4) * 2 + q, sl = b & 15;
        const uint4* a = g_x + X_HF + mt1 * 32 * 128 + t128;
        float acc[44], nmean[2], hrstd[2];
        uint4 buf[3][4];
        {
            const uint4* sp = g_x + X_ST + (mt1 * 64 + ww * 16 + g) * 8 + t4 * 2;
            hint_wait(H_H1 + mt1, epoch * 64);
            TS(24);
            uint4 u[4]; int spins = 0;
            u[0] = ldg_relaxed(sp); u[1] = ldg_relaxed(sp + 1); u[2] = ldg_relaxed(sp + 64); u[3] = ldg_relaxed(sp + 65);
#pragma unroll
            for (int i = 0; i < 3; i++) load_batch(buf[i], a + i * 512);
            while (__builtin_expect(batch_bad(u), 0) && ++spins < SPIN_LIMIT) { u[0] = ldg_relaxed(sp); u[1] = ldg_relaxed(sp + 1); u[2] = ldg_relaxed(sp + 64); u[3] = ldg_relaxed(sp + 65); }
            TS(26);
            float mean[2], m2[2];
#pragma unroll
            for (int i = 0; i < 2; i++) mean[i] = (__uint_as_float(u[2 * i].x) + __uint_as_float(u[2 * i].z)) + (__uint_as_float(u[2 * i + 1].x) + __uint_as_float(u[2 * i + 1].z));
            mean[0] += __shfl_xor_sync(0xffffffffu, mean[0], 1); mean[1] += __shfl_xor_sync(0xffffffffu, mean[1], 1);
            mean[0] += __shfl_xor_sync(0xffffffffu, mean[0], 2); mean[1] += __shfl_xor_sync(0xffffffffu, mean[1], 2);
#pragma unroll
            for (int i = 0; i < 2; i++) {
                mean[i] *= 1.0f / D;
                const float da = __uint_as_float(u[2 * i].x) * (1.0f / 32) - mean[i], dc = __uint_as_float(u[2 * i].z) * (1.0f / 32) - mean[i];
                const float de = __uint_as_float(u[2 * i + 1].x) * (1.0f / 32) - mean[i], df = __uint_as_float(u[2 * i + 1].z) * (1.0f / 32) - mean[i];
                m2[i] = (__uint_as_float(u[2 * i].y) + __uint_as_float(u[2 * i].w)) + (__uint_as_float(u[2 * i + 1].y) + __uint_as_float(u[2 * i + 1].w)) + 32.0f * (da * da + dc * dc + de * de + df * df);
            }
            m2[0] += __shfl_xor_sync(0xffffffffu, m2[0], 1); m2[1] += __shfl_xor_sync(0xffffffffu, m2[1], 1);
            m2[0] += __shfl_xor_sync(0xffffffffu, m2[0], 2); m2[1] += __shfl_xor_sync(0xffffffffu, m2[1], 2);
#pragma unroll
            for (int i = 0; i < 2; i++) { hrstd[i] = 0.5f * rsqrtf(m2[i] * (1.0f / D) + 1e-5f); nmean[i] = -mean[i]; }
        }
        gemm_rs<1, 8, 3>(acc, buf, a, sb, q, P);
        TS(9);
        mbar_wait(mb + MB_CS * 8);
        uint4* hb = g_x + X_H + (mt1 * 88 + (sl >> 1) * 11) * 128 + t128;
        uint32_t hv[22];
#pragma unroll
        for (int i = 0; i < 11; i++) {
            float2 cs;
            asm volatile("ld.shared.v2.f32 {%0,%1}, [%2];" : "=f"(cs.x), "=f"(cs.y) : "r"(mb + MISC_CS + i * 32 + t4 * 8));
            hv[2 * i] = pack_bf16(silu2(hrstd[0] * fmaf(nmean[0], cs.x, acc[4 * i])), silu2(hrstd[0] * fmaf(nmean[0], cs.y, acc[4 * i + 1])));
            hv[2 * i + 1] = pack_bf16(silu2(hrstd[1] * fmaf(nmean[1], cs.x, acc[4 * i + 2])), silu2(hrstd[1] * fmaf(nmean[1], cs.y, acc[4 * i + 3])));
        }
        if (sl & 1) {
#pragma unroll
            for (int i = 0; i < 5; i++) stg128(hb + (6 + i) * 128, hv[2 + 4 * i], hv[3 + 4 * i], hv[4 + 4 * i], hv[5 + 4 * i]);
            stg64(reinterpret_cast<uint2*>(hb + 5 * 128) + 1, hv[0], hv[1]);
        } else {
#pragma unroll
            for (int i = 0; i < 5; i++) stg128(hb + i * 128, hv[4 * i], hv[4 * i + 1], hv[4 * i + 2], hv[4 * i + 3]);
            stg64(hb + 5 * 128, hv[20], hv[21]);
        }
        hint_arrive(H_H2 + mt1);
        TS(10);
        release_w1(sb, P, 3);
    }
    {
        const uint4* a = g_x + X_H + (mt * 88 + q * 4) * 128 + t128;
        hint_wait(H_H2 + mt, epoch * 64);
        uint4 buf[4][4];
#pragma unroll
        for (int i = 0; i < 4; i++) load_batch(buf[i], a + i * 1024);
        TS(25);
        float acc[32], r[16];
        gemm_rs<2, 11, 4>(acc, buf, a, sb, q, P);
        TS(11);
        pair_reduce(acc, r, xbuf, q, 3 + pr);
#pragma unroll
        for (int i = 0; i < 8; i++) hk[i] = pack_bf16(r[2 * i] + bf_lo(hk[i]), r[2 * i + 1] + bf_hi(hk[i]));
    }
#pragma unroll
    for (int h = 0; h < 2; h++) {
        uint32_t v0 = hk[h], v1 = hk[2 + h], v2 = hk[4 + h], v3 = hk[6 + h];
        const bool o1 = t4 & 1, o2 = t4 & 2;
        uint32_t a = __shfl_xor_sync(0xffffffffu, o1 ? v0 : v1, 1), c = __shfl_xor_sync(0xffffffffu, o1 ? v2 : v3, 1);
        if (o1) { v0 = a; v2 = c; } else { v1 = a; v3 = c; }
        a = __shfl_xor_sync(0xffffffffu, o2 ? v0 : v2, 2); c = __shfl_xor_sync(0xffffffffu, o2 ? v1 : v3, 2);
        if (o2) { v0 = a; v1 = c; } else { v2 = a; v3 = c; }
        *reinterpret_cast<uint4*>(P.out + (size_t)(row0 + 8 * h) * D + j * 64 + q * 32 + t4 * 8) = make_uint4(v0, v1, v2, v3);
    }
    TS(12);
}

typedef CUresult (*EncodeFn)(CUtensorMap*, CUtensorMapDataType, cuuint32_t, void*, const cuuint64_t*, const cuuint64_t*, const cuuint32_t*,
                             const cuuint32_t*, CUtensorMapInterleave, CUtensorMapSwizzle, CUtensorMapL2promotion, CUtensorMapFloatOOBfill);

void encode2d(EncodeFn fn, CUtensorMap* tm, const void* ptr, int rows, int cols, int box_rows, int box_cols, CUtensorMapSwizzle sw) {
    cuuint64_t dims[2] = {(cuuint64_t)cols, (cuuint64_t)rows};
    cuuint64_t strides[1] = {(cuuint64_t)cols * 2};
    cuuint32_t box[2] = {(cuuint32_t)box_cols, (cuuint32_t)box_rows};
    cuuint32_t es[2] = {1, 1};
    fn(tm, CU_TENSOR_MAP_DATA_TYPE_BFLOAT16, 2, const_cast<void*>(ptr), dims, strides, box, es, CU_TENSOR_MAP_INTERLEAVE_NONE, sw,
       CU_TENSOR_MAP_L2_PROMOTION_L2_128B, CU_TENSOR_MAP_FLOAT_OOB_FILL_NONE);
}

}

extern "C" void kernel_launch(void* const* d_in, const int* in_sizes, int n_in, void* d_out, int out_size) {
    (void)in_sizes; (void)n_in; (void)out_size;
    void* fnp = nullptr;
    cudaDriverEntryPointQueryResult qr;
    cudaGetDriverEntryPoint("cuTensorMapEncodeTiled", &fnp, cudaEnableDefault, &qr);
    EncodeFn fn = (EncodeFn)fnp;
    Params P;
    encode2d(fn, &P.wq, d_in[1], D, D, 128, 64, CU_TENSOR_MAP_SWIZZLE_128B);
    P.wk = (const __nv_bfloat16*)d_in[2];
    P.wv = (const __nv_bfloat16*)d_in[3];
    encode2d(fn, &P.wo, d_in[4], D, D, 64, 64, CU_TENSOR_MAP_SWIZZLE_128B);
    encode2d(fn, &P.w1, d_in[6], D, FF, 128, 32, CU_TENSOR_MAP_SWIZZLE_64B);
    encode2d(fn, &P.w2, d_in[7], FF, D, 64, 64, CU_TENSOR_MAP_SWIZZLE_128B);
    P.x = (const __nv_bfloat16*)d_in[0];
    P.w1p = (const __nv_bfloat16*)d_in[6];
    P.w2p = (const __nv_bfloat16*)d_in[7];
    P.wop = (const __nv_bfloat16*)d_in[4];
    P.wqp = (const __nv_bfloat16*)d_in[1];
    P.out = (__nv_bfloat16*)d_out;
    P.neg1 = 0xFFFFFFFFu; P.pad = 0;
    cudaFuncSetAttribute(fused_kernel, cudaFuncAttributeMaxDynamicSharedMemorySize, SMEM_BYTES);
    fused_kernel<<<NCTA, 512, SMEM_BYTES>>>(P);
}
```

```cpp
#include <cuda_runtime.h>
#include <cuda_bf16.h>
#include <cuda.h>
#include <stdint.h>

namespace {

constexpr int D = 512, FF = 1376;
constexpr int NMAIN = 128, NHELP = 4, NCTA = NMAIN + NHELP;
constexpr uint32_t SENT = 0xFFFFFFFFu;
constexpr int SPIN_LIMIT = 1 << 22;

constexpr uint32_t KB = 1024;
constexpr uint32_t SM_XN = 0;
constexpr uint32_t SM_WQ = 64 * KB;
constexpr uint32_t SM_WKV = 176 * KB;
constexpr uint32_t SM_K = 0;
constexpr uint32_t SM_V = 64 * KB;
constexpr uint32_t SM_Q = 160 * KB;
constexpr uint32_t SM_SENT = 184 * KB;
constexpr uint32_t SM_MISC = 192 * KB;
constexpr uint32_t SMEM_BYTES = 195 * KB;
constexpr uint32_t MB_WQ = 0;
constexpr uint32_t MB_W1 = 4;
constexpr uint32_t MB_DONE = 8;
constexpr uint32_t MB_KV = 14;
constexpr uint32_t MB_WO = 16;
constexpr uint32_t MB_W2 = 24;
constexpr uint32_t MB_F2 = 46;
constexpr uint32_t MB_CS = 47;
constexpr uint32_t MISC_CNT = 384;
constexpr uint32_t MISC_NRM = 400;
constexpr uint32_t MISC_EPOCH = 416;
constexpr uint32_t MISC_WNRM = 432;
constexpr uint32_t MISC_CS = 1024;
constexpr uint32_t MISC_RSTD = 448;
constexpr uint32_t MISC_KTMP = 1024;

__host__ __device__ constexpr uint32_t wo_slot(int kb) { return kb < 2 ? 22 + kb : kb - 2; }
__host__ __device__ constexpr uint32_t w2_slot(int kb) { return kb < 2 ? 6 + kb : kb < 4 ? 20 + kb : kb < 10 ? kb - 4 : 8 + (kb - 10) / 3 + 4 * ((kb - 10) % 3); }

struct alignas(128) Small {
    unsigned epoch[160];
    unsigned count1, pad1[31];
    unsigned count2, pad2[31];
    unsigned hint[100][32];
    float cs[1440];
    uint4 nrm[NMAIN * 2];
    uint4 kv[8192];
    uint4 kplain[4096];
};
__device__ Small g_s;
constexpr int X_OF = 0, X_HF = 32 * 32 * 128, X_ST = X_HF + 32 * 32 * 128, X_H = X_ST + 32 * 64 * 8, X_END = X_H + 32 * 88 * 128;
constexpr int X_ARM = 16 * 32 * 128, X_SHARE = (X_END - X_ARM) / NMAIN;
__device__ uint4 g_x[X_END];
#define TS(i) do {} while (0)

__device__ __forceinline__ void mbar_init(uint32_t bar, int cnt) { asm volatile("mbarrier.init.shared::cta.b64 [%0], %1;" :: "r"(bar), "r"(cnt) : "memory"); }
__device__ __forceinline__ void mbar_expect(uint32_t bar, uint32_t bytes) { asm volatile("mbarrier.arrive.expect_tx.shared::cta.b64 _, [%0], %1;" :: "r"(bar), "r"(bytes) : "memory"); }
__device__ __forceinline__ void mbar_arrive(uint32_t bar) { asm volatile("mbarrier.arrive.shared::cta.b64 _, [%0];" :: "r"(bar) : "memory"); }
__device__ __forceinline__ void mbar_wait(uint32_t bar) {
    uint32_t done; int spins = 0;
    do {
        asm volatile("{.reg .pred p; mbarrier.try_wait.parity.shared::cta.b64 p, [%1], 0; selp.u32 %0, 1, 0, p;}" : "=r"(done) : "r"(bar) : "memory");
    } while (!__all_sync(0xffffffffu, done) && ++spins < SPIN_LIMIT);
}
__device__ __forceinline__ void tma2d(uint32_t dst, const CUtensorMap* tm, int c0, int c1, uint32_t bar) {
    asm volatile("cp.async.bulk.tensor.2d.shared::cluster.global.mbarrier::complete_tx::bytes [%0], [%1, {%3, %4}], [%2];"
                 :: "r"(dst), "l"(tm), "r"(bar), "r"(c0), "r"(c1) : "memory");
}
__device__ __forceinline__ void bulk_g2s(uint32_t dst, const void* src, uint32_t bytes, uint32_t bar) {
    asm volatile("cp.async.bulk.shared::cluster.global.mbarrier::complete_tx::bytes [%0], [%1], %2, [%3];" :: "r"(dst), "l"(src), "r"(bytes), "r"(bar) : "memory");
}
__device__ __forceinline__ void fence_async_smem() { asm volatile("fence.proxy.async.shared::cta;" ::: "memory"); }
__device__ __forceinline__ void bar_sync(int id, int n) { asm volatile("bar.sync %0, %1;" :: "r"(id), "r"(n) : "memory"); }
__device__ __forceinline__ void bar_arrive(int id, int n) { asm volatile("bar.arrive %0, %1;" :: "r"(id), "r"(n) : "memory"); }
__device__ __forceinline__ void wg_fence() { asm volatile("wgmma.fence.sync.aligned;" ::: "memory"); }
__device__ __forceinline__ void wg_commit() { asm volatile("wgmma.commit_group.sync.aligned;" ::: "memory"); }
template <int N> __device__ __forceinline__ void wg_wait() { asm volatile("wgmma.wait_group.sync.aligned %0;" :: "n"(N) : "memory"); }
template <int N> __device__ __forceinline__ void fence_regs(float (&d)[N]) {
#pragma unroll
    for (int i = 0; i < N; i++) asm volatile("" : "+f"(d[i]) :: "memory");
}
template <int N> __device__ __forceinline__ void fence_regs(uint32_t (&d)[N]) {
#pragma unroll
    for (int i = 0; i < N; i++) asm volatile("" : "+r"(d[i]) :: "memory");
}
__device__ __forceinline__ uint64_t mkdesc(uint32_t addr, uint32_t lbo, uint32_t sbo, uint32_t swz) {
    return (uint64_t)(((addr & 0x3FFFF) >> 4) | ((lbo >> 4) << 16)) | ((uint64_t)((sbo >> 4) | (swz << 30)) << 32);
}
__device__ __forceinline__ float ex2(float x) { float y; asm("ex2.approx.ftz.f32 %0, %1;" : "=f"(y) : "f"(x)); return y; }
__device__ __forceinline__ float rcp(float x) { float y; asm("rcp.approx.ftz.f32 %0, %1;" : "=f"(y) : "f"(x)); return y; }
__device__ __forceinline__ uint32_t pack_bf16(float lo, float hi) { uint32_t r; asm("cvt.rn.bf16x2.f32 %0, %1, %2;" : "=r"(r) : "f"(hi), "f"(lo)); return r; }
__device__ __forceinline__ uint32_t pack_f16(float lo, float hi) { uint32_t r; asm("cvt.rn.f16x2.f32 %0, %1, %2;" : "=r"(r) : "f"(hi), "f"(lo)); return r; }
__device__ __forceinline__ float bf_lo(uint32_t v) { return __uint_as_float(v << 16); }
__device__ __forceinline__ float bf_hi(uint32_t v) { return __uint_as_float(v & 0xFFFF0000u); }
__device__ __forceinline__ uint4 ldg_relaxed(const uint4* p) {
    uint4 v; asm volatile("ld.relaxed.gpu.global.v4.u32 {%0,%1,%2,%3}, [%4];" : "=r"(v.x), "=r"(v.y), "=r"(v.z), "=r"(v.w) : "l"(p) : "memory"); return v;
}
__device__ __forceinline__ void stg128(void* p, uint32_t a, uint32_t b, uint32_t c, uint32_t d) {
    asm volatile("st.relaxed.gpu.global.v4.u32 [%0], {%1,%2,%3,%4};" :: "l"(p), "r"(a), "r"(b), "r"(c), "r"(d) : "memory");
}
__device__ __forceinline__ void stg64(void* p, uint32_t a, uint32_t b) {
    asm volatile("st.relaxed.gpu.global.v2.u32 [%0], {%1,%2};" :: "l"(p), "r"(a), "r"(b) : "memory");
}
__device__ __forceinline__ void sts128(uint32_t a, uint32_t x, uint32_t y, uint32_t z, uint32_t w) {
    asm volatile("st.shared.v4.u32 [%0], {%1,%2,%3,%4};" :: "r"(a), "r"(x), "r"(y), "r"(z), "r"(w) : "memory");
}
__device__ __forceinline__ void sts32(uint32_t a, uint32_t x) { asm volatile("st.shared.u32 [%0], %1;" :: "r"(a), "r"(x) : "memory"); }
__device__ __forceinline__ float4 lds128f(uint32_t a) {
    float4 v; asm volatile("ld.shared.v4.f32 {%0,%1,%2,%3}, [%4];" : "=f"(v.x), "=f"(v.y), "=f"(v.z), "=f"(v.w) : "r"(a) : "memory"); return v;
}
__device__ __forceinline__ uint32_t lds32(uint32_t a) { uint32_t v; asm volatile("ld.shared.u32 %0, [%1];" : "=r"(v) : "r"(a) : "memory"); return v; }
__device__ __forceinline__ bool has_sent(const uint4& v) { return (v.x == SENT) | (v.w == SENT); }
__device__ __forceinline__ bool has_zero(const uint4& v) { return min(min(v.x, v.y), min(v.z, v.w)) == 0u; }
__device__ __forceinline__ uint32_t nonzero(uint32_t w) { return w == 0u ? 0x8000u : w; }
__device__ __forceinline__ void stg32(void* p, uint32_t a) { asm volatile("st.relaxed.gpu.global.u32 [%0], %1;" :: "l"(p), "r"(a) : "memory"); }
__device__ __forceinline__ void wait_count(const unsigned* p, unsigned target) {
    unsigned v; int spins = 0;
    do { asm volatile("ld.acquire.gpu.global.u32 %0, [%1];" : "=r"(v) : "l"(p) : "memory"); } while (__any_sync(0xffffffffu, v != target) && ++spins < SPIN_LIMIT);
}
__device__ __forceinline__ uint32_t warp_arrive(uint32_t cnt) {
    uint32_t old = 0;
    __syncwarp();
    if ((threadIdx.x & 31) == 0) asm volatile("atom.acq_rel.cta.shared.add.u32 %0, [%1], 1;" : "=r"(old) : "r"(cnt) : "memory");
    return __shfl_sync(0xffffffffu, old, 0);
}
__device__ __forceinline__ void warp_done(uint32_t bar) { __syncwarp(); if ((threadIdx.x & 31) == 0) mbar_arrive(bar); }
__device__ __forceinline__ uint32_t mul_bf16x2(uint32_t a, uint32_t b) { uint32_t r; asm("mul.rn.bf16x2 %0, %1, %2;" : "=r"(r) : "r"(a), "r"(b)); return r; }
__device__ __forceinline__ uint32_t fma_bf16x2(uint32_t a, uint32_t b, uint32_t c) { uint32_t r; asm("fma.rn.bf16x2 %0, %1, %2, %3;" : "=r"(r) : "r"(a), "r"(b), "r"(c)); return r; }
__device__ __forceinline__ uint32_t add_bf16x2(uint32_t a, uint32_t b) { uint32_t r; asm("add.rn.bf16x2 %0, %1, %2;" : "=r"(r) : "r"(a), "r"(b)); return r; }

#define R4(d, o) "+f"(d[o + 0]), "+f"(d[o + 1]), "+f"(d[o + 2]), "+f"(d[o + 3])
#define R8(d, o) R4(d, o), R4(d, o + 4)
#define R32(d) R8(d, 0), R8(d, 8), R8(d, 16), R8(d, 24)
#define D32 "{%0,%1,%2,%3,%4,%5,%6,%7,%8,%9,%10,%11,%12,%13,%14,%15,%16,%17,%18,%19,%20,%21,%22,%23,%24,%25,%26,%27,%28,%29,%30,%31}"
#define D48 "{%0,%1,%2,%3,%4,%5,%6,%7,%8,%9,%10,%11,%12,%13,%14,%15,%16,%17,%18,%19,%20,%21,%22,%23,%24,%25,%26,%27,%28,%29,%30,%31,%32,%33,%34,%35,%36,%37,%38,%39,%40,%41,%42,%43,%44,%45,%46,%47}"

__device__ __forceinline__ void mma_qk_f16(float (&d)[32], uint64_t da, uint64_t db) {
    asm volatile("{.reg .pred p; setp.eq.b32 p, 0, 0; wgmma.mma_async.sync.aligned.m64n64k16.f32.f16.f16 " D32 ", %32, %33, p, 1, 1, 0, 0;}"
                 : R32(d) : "l"(da), "l"(db));
}
__device__ __forceinline__ void mma_qk_bf16(float (&d)[32], uint64_t da, uint64_t db) {
    asm volatile("{.reg .pred p; setp.ne.b32 p, 0, 0; wgmma.mma_async.sync.aligned.m64n64k16.f32.bf16.bf16 " D32 ", %32, %33, p, 1, 1, 0, 0;}"
                 : R32(d) : "l"(da), "l"(db));
}
__device__ __forceinline__ void mma_pv(float (&d)[12], const uint32_t* a, uint64_t db) {
    asm volatile("{.reg .pred p; setp.eq.b32 p, 0, 0; wgmma.mma_async.sync.aligned.m64n24k16.f32.bf16.bf16 {%0,%1,%2,%3,%4,%5,%6,%7,%8,%9,%10,%11}, {%12,%13,%14,%15}, %16, p, 1, 1, 1;}"
                 : R8(d, 0), R4(d, 8) : "r"(a[0]), "r"(a[1]), "r"(a[2]), "r"(a[3]), "l"(db));
}
__device__ __forceinline__ void mma_ss64(float (&d)[32], uint64_t da, uint64_t db) {
    asm volatile("{.reg .pred p; setp.eq.b32 p, 0, 0; wgmma.mma_async.sync.aligned.m64n64k16.f32.bf16.bf16 " D32 ", %32, %33, p, 1, 1, 0, 1;}"
                 : R32(d) : "l"(da), "l"(db));
}
__device__ __forceinline__ void mma_ss8(float (&d)[4], uint64_t da, uint64_t db) {
    asm volatile("{.reg .pred p; setp.eq.b32 p, 0, 0; wgmma.mma_async.sync.aligned.m64n8k16.f32.bf16.bf16 {%0,%1,%2,%3}, %4, %5, p, 1, 1, 0, 1;}"
                 : R4(d, 0) : "l"(da), "l"(db));
}
__device__ __forceinline__ void mma_rs(float (&d)[32], const uint4& a, uint64_t db) {
    asm volatile("{.reg .pred p; setp.eq.b32 p, 0, 0; wgmma.mma_async.sync.aligned.m64n64k16.f32.bf16.bf16 " D32 ", {%32,%33,%34,%35}, %36, p, 1, 1, 1;}"
                 : R32(d) : "r"(a.x), "r"(a.y), "r"(a.z), "r"(a.w), "l"(db));
}
__device__ __forceinline__ void mma_rs(float (&d)[48], const uint4& a, uint64_t db) {
    asm volatile("{.reg .pred p; setp.eq.b32 p, 0, 0; wgmma.mma_async.sync.aligned.m64n96k16.f32.bf16.bf16 " D48 ", {%48,%49,%50,%51}, %52, p, 1, 1, 1;}"
                 : R32(d), R8(d, 32), R8(d, 40) : "r"(a.x), "r"(a.y), "r"(a.z), "r"(a.w), "l"(db));
}

constexpr float EXP_MAGIC = 256.0f + 127.0f + 64.0f - 1.58621f + 0.00390625f;
constexpr uint32_t MUFU_MASK = 0x1111u;
__device__ __forceinline__ uint32_t exp2_pair(float y0, float y1, uint32_t cexp, uint32_t neg1) {
    uint32_t w, m, e, r;
    asm("prmt.b32 %0, %1, %2, 0x6521;" : "=r"(w) : "r"(__float_as_uint(y0)), "r"(__float_as_uint(y1)));
    asm("lop3.b32 %0, %1, 0x007F007F, %2, 0xEA;" : "=r"(m) : "r"(w), "r"(cexp));
    asm("mad.lo.u32 %0, %1, %2, %3;" : "=r"(e) : "r"(m), "r"(neg1), "r"(w));
    asm("fma.rn.bf16x2 %0, %1, %2, %3;" : "=r"(r) : "r"(w), "r"(m), "r"(e));
    return r;
}

struct Params {
    const __nv_bfloat16* x;
    const __nv_bfloat16* wk;
    long long wv_off;
    const __nv_bfloat16* wqp;
    __nv_bfloat16* out;
    uint32_t neg1, pad;
    const __nv_bfloat16* w1p;
    const __nv_bfloat16* w2p;
    CUtensorMap wq, wo, w1, w2;
    const __nv_bfloat16* wop;
};

__device__ __forceinline__ int f1_col0() { return ((blockIdx.x & 15) >> 1) * 176 + (blockIdx.x & 1) * 96; }
__device__ __forceinline__ void load_box(uint32_t sb, const CUtensorMap* tm, uint32_t dst, uint32_t bar, uint32_t bytes, int c0, int c1) {
    mbar_expect(sb + SM_MISC + bar * 8, bytes);
    tma2d(sb + dst, tm, c0, c1, sb + SM_MISC + bar * 8);
}
__device__ __forceinline__ void load_wq(uint32_t sb, const Params& P, int gi, int atom) {
    load_box(sb, &P.wq, SM_WQ + atom * 65536 + gi * 16384, MB_WQ + gi, 16384, (blockIdx.x & 3) * 128 + atom * 64, gi * 128);
}
__device__ __forceinline__ void load_wo(uint32_t sb, const Params& P, int kb) { load_box(sb, &P.wo, wo_slot(kb) * 8192, MB_WO + kb, 8192, (blockIdx.x & 7) * 64, kb * 64); }
__device__ __forceinline__ void load_w2(uint32_t sb, const Params& P, int kb, int slot) { load_box(sb, &P.w2, slot * 8192, MB_W2 + kb, 8192, (blockIdx.x & 7) * 64, kb * 64); }
__device__ __forceinline__ void refill_job(uint32_t sb, const Params& P, int gi, int job) {
    const bool w1 = job < 3;
    const int kb = (gi < 3 ? 2 + 2 * gi : 0) + job - 3;
    load_box(sb, w1 ? &P.w1 : gi < 3 ? &P.wo : &P.w2, (w1 ? 8 + gi + 4 * job : 2 * gi + job - 3) * 8192, w1 ? MB_W1 + gi : (gi < 3 ? MB_WO : MB_W2) + kb, 8192,
             w1 ? f1_col0() + job * 32 : (blockIdx.x & 7) * 64, w1 ? gi * 128 : kb * 64);
}
__device__ __forceinline__ void release_w1(uint32_t sb, const Params& P, int gi) {
    if (warp_arrive(sb + SM_MISC + MISC_CNT + gi * 4) == 15) {
        if ((threadIdx.x & 31) == 0) {
#pragma unroll 1
            for (int a = 0; a < 3; a++) load_w2(sb, P, 10 + 3 * gi + a, 8 + gi + 4 * a);
        }
        __syncwarp();
    }
}

__device__ __forceinline__ void load_batch(uint4 (&buf)[4], const uint4* a) {
#pragma unroll
    for (int s = 0; s < 4; s++) buf[s] = ldg_relaxed(a + s * 128);
}
__device__ __forceinline__ bool batch_bad(const uint4 (&buf)[4]) {
    const uint32_t m = max(max(buf[0].x, buf[1].x), max(buf[2].x, buf[3].x));
    return __any_sync(0xffffffffu, m == SENT);
}
__device__ __forceinline__ void check_batch(uint4 (&buf)[4], const uint4* a) {
    if (__builtin_expect(batch_bad(buf), 0)) {
        int spins = 0;
        do load_batch(buf, a); while (batch_bad(buf) && ++spins < SPIN_LIMIT);
    }
}
constexpr int H_KV = 0, H_O = 1 - 16, H_H1 = 17, H_H2 = 49;
__device__ __forceinline__ void hint_arrive(int id) {
    if ((threadIdx.x & 31) == 0) asm volatile("red.relaxed.gpu.global.add.u32 [%0], 1;" :: "l"(g_s.hint[id]) : "memory");
}
__device__ __forceinline__ void hint_wait(int id, unsigned target) {
    uint32_t v; int spins = 0;
    do { asm volatile("ld.relaxed.gpu.global.u32 %0, [%1];" : "=r"(v) : "l"(g_s.hint[id]) : "memory"); } while (__any_sync(0xffffffffu, v != target) && ++spins < SPIN_LIMIT);
}

template <int KIND, int NBLK, int RING, int NACC>
__device__ __forceinline__ void gemm_rs(float (&acc)[NACC], uint4 (&buf)[RING][4], const uint4* a, uint32_t sb, int q, const Params& P) {
    constexpr int ASTR = (KIND == 1) ? 512 : 1024;
    const uint32_t mb = sb + SM_MISC;
#pragma unroll
    for (int i = 0; i < NACC; i++) acc[i] = 0.f;
    fence_regs(acc);
#pragma unroll
    for (int i = 0; i < NBLK; i++) {
        uint64_t db;
        if (KIND == 1) {
            db = mkdesc(sb + (8 + (i >> 1)) * 8192 + (i & 1) * 4096, 32768, 512, 2);
            if ((i & 1) == 0) mbar_wait(mb + (MB_W1 + (i >> 1)) * 8);
        } else {
            const uint32_t slot = KIND == 0 ? (q ? wo_slot(2 * i + 1) : wo_slot(2 * i)) : (q ? w2_slot(2 * i + 1) : w2_slot(2 * i));
            db = mkdesc(sb + slot * 8192, 16, 1024, 1);
            mbar_wait(mb + ((KIND == 0 ? MB_WO : MB_W2) + 2 * i + q) * 8);
        }
        check_batch(buf[i % RING], a + i * ASTR);
        wg_fence();
#pragma unroll
        for (int s = 0; s < 4; s++) mma_rs(acc, buf[i % RING][s], db + s * (KIND == 1 ? 64 : 128));
        wg_commit();
        const bool rel = KIND == 1 && i >= 2 && !(i & 1);
        if (i >= 1 && (i - 1 + RING < NBLK || rel)) {
            wg_wait<1>();
            if (i - 1 + RING < NBLK) load_batch(buf[(i - 1) % RING], a + (i - 1 + RING) * ASTR);
            if (rel) release_w1(sb, P, (i >> 1) - 1);
        }
    }
    wg_wait<0>();
    fence_regs(acc);
}

__device__ __forceinline__ void pair_reduce(const float (&acc)[32], float (&r)[16], uint32_t buf, int q, int barid) {
    if (q) {
#pragma unroll
        for (int j = 0; j < 4; j++) sts128(buf + j * 2048, __float_as_uint(acc[4 * j]), __float_as_uint(acc[4 * j + 1]), __float_as_uint(acc[4 * j + 2]), __float_as_uint(acc[4 * j + 3]));
        bar_sync(barid, 256);
        bar_sync(barid, 256);
#pragma unroll
        for (int j = 0; j < 4; j++) {
            float4 v = lds128f(buf + j * 2048);
            r[4 * j] = acc[16 + 4 * j] + v.x; r[4 * j + 1] = acc[17 + 4 * j] + v.y; r[4 * j + 2] = acc[18 + 4 * j] + v.z; r[4 * j + 3] = acc[19 + 4 * j] + v.w;
        }
    } else {
        bar_sync(barid, 256);
        float4 v[4];
#pragma unroll
        for (int j = 0; j < 4; j++) v[j] = lds128f(buf + j * 2048);
#pragma unroll
        for (int j = 0; j < 4; j++) sts128(buf + j * 2048, __float_as_uint(acc[16 + 4 * j]), __float_as_uint(acc[17 + 4 * j]), __float_as_uint(acc[18 + 4 * j]), __float_as_uint(acc[19 + 4 * j]));
        bar_arrive(barid, 256);
#pragma unroll
        for (int j = 0; j < 4; j++) {
            r[4 * j] = acc[4 * j] + v[j].x; r[4 * j + 1] = acc[4 * j + 1] + v[j].y; r[4 * j + 2] = acc[4 * j + 2] + v[j].z; r[4 * j + 3] = acc[4 * j + 3] + v[j].w;
        }
    }
}

__device__ __forceinline__ float quad_sum(float v) { v += __shfl_xor_sync(0xffffffffu, v, 1); v += __shfl_xor_sync(0xffffffffu, v, 2); return v; }
__device__ __forceinline__ float reduce4(const float (&st)[4], int lane) {
    const bool u16 = lane & 16, u8 = lane & 8;
    const float a0 = (u16 ? st[2] : st[0]) + __shfl_xor_sync(0xffffffffu, u16 ? st[0] : st[2], 16);
    const float a1 = (u16 ? st[3] : st[1]) + __shfl_xor_sync(0xffffffffu, u16 ? st[1] : st[3], 16);
    float v = (u8 ? a1 : a0) + __shfl_xor_sync(0xffffffffu, u8 ? a0 : a1, 8);
    v += __shfl_xor_sync(0xffffffffu, v, 4); v += __shfl_xor_sync(0xffffffffu, v, 2); v += __shfl_xor_sync(0xffffffffu, v, 1);
    return v;
}
__device__ __forceinline__ float silu2(float h) { float t; asm("tanh.approx.f32 %0, %1;" : "=f"(t) : "f"(h)); return fmaf(h, t, h); }

#define TS_ARG
#define TS_PASS

template <bool SAFE>
__device__ __forceinline__ void attention(const Params& P, uint32_t sb, int warp TS_ARG) {
    const uint32_t mb = sb + SM_MISC;
    const int tid = threadIdx.x, lane = tid & 31, b = blockIdx.x;
    const int wg = warp >> 2, ww = warp & 3, job = 3 - wg + 4 * ww;
    const uint32_t cexp = 0x9F809F80u + (tid >> 12);
    const uint32_t neg1 = P.neg1;
    unsigned cnt = 0;
    if (SAFE && warp == 8) asm volatile("ld.relaxed.gpu.global.u32 %0, [%1];" : "=r"(cnt) : "l"(&g_s.count1) : "memory");
#pragma unroll 1
    for (int pass = 0; pass < 2; pass++) {
    float o[12], s[32];
    const uint64_t dq = mkdesc(sb + SM_Q + (pass * 4 + wg) * 2048, 128, 256, 0);
    uint64_t dk = mkdesc(sb + SM_K, 128, 256, 0), dv = mkdesc(sb + SM_V, 128, 32768, 0);
    float m0 = -INFINITY, m1 = -INFINITY;
#pragma unroll
    for (int i = 0; i < 12; i++) o[i] = 0.f;
#pragma unroll
    for (int i = 0; i < 32; i++) s[i] = ((MUFU_MASK >> (i / 2)) & 1) ? 0.f : EXP_MAGIC;
    fence_regs(s); fence_regs(o);
    wg_fence();
    if (SAFE) mma_qk_f16(s, dq, dk + 31 * 128); else mma_qk_bf16(s, dq, dk + 31 * 128);
    wg_commit();
    wg_wait<0>(); fence_regs(s);
#pragma unroll 1
    for (int u = pass ? 3 : (wg == 2) ? 0 : 1; u < (pass ? 8 : 3); u++) {
        int n = 2 * ((((wg == 2) ? 0x22444C31u : 0x22444C40u) >> (4 * u)) & 15);
#pragma unroll 1
        do {
            uint32_t p[16];
            if (SAFE) {
#pragma unroll
                for (int j = 0; j < 16; j++) {
                    if ((MUFU_MASK >> j) & 1) p[j] = pack_bf16(ex2(s[2 * j]), ex2(s[2 * j + 1]));
                    else p[j] = exp2_pair(s[2 * j], s[2 * j + 1], cexp, neg1);
                }
            } else {
                fence_regs(o);
                float x0 = m0, x1 = m1;
#pragma unroll
                for (int j = 0; j < 8; j++) { x0 = fmaxf(x0, fmaxf(s[4 * j], s[4 * j + 1])); x1 = fmaxf(x1, fmaxf(s[4 * j + 2], s[4 * j + 3])); }
                x0 = fmaxf(x0, __shfl_xor_sync(0xffffffffu, x0, 1)); x0 = fmaxf(x0, __shfl_xor_sync(0xffffffffu, x0, 2));
                x1 = fmaxf(x1, __shfl_xor_sync(0xffffffffu, x1, 1)); x1 = fmaxf(x1, __shfl_xor_sync(0xffffffffu, x1, 2));
                const float c0 = ex2(m0 - x0), c1 = ex2(m1 - x1);
                m0 = x0; m1 = x1;
#pragma unroll
                for (int j = 0; j < 3; j++) { o[4 * j] *= c0; o[4 * j + 1] *= c0; o[4 * j + 2] *= c1; o[4 * j + 3] *= c1; }
#pragma unroll
                for (int j = 0; j < 8; j++) {
                    p[2 * j] = pack_bf16(ex2(s[4 * j] - m0), ex2(s[4 * j + 1] - m0));
                    p[2 * j + 1] = pack_bf16(ex2(s[4 * j + 2] - m1), ex2(s[4 * j + 3] - m1));
                }
                fence_regs(o);
            }
            fence_regs(p);
            wg_fence();
            if (SAFE) mma_qk_f16(s, dq, dk); else mma_qk_bf16(s, dq, dk);
#pragma unroll
            for (int j = 0; j < 4; j++) mma_pv(o, p + 4 * j, dv + j * 16);
            wg_commit();
            dk += 128; dv += 64;
            wg_wait<0>(); fence_regs(s);
        } while (--n > 0);
        if (u == 2 || u == 7) {
            fence_regs(o);
            const float i0 = rcp(o[8]), i1 = rcp(o[10]);
            if (u == 7) mbar_wait(mb + MB_F2 * 8);
            stg128(g_x + X_OF + (((u == 7) * 16 + (b >> 3)) * 32 + (b & 3) * 8 + 2 * wg + (ww >> 1)) * 128 + (((b >> 2) & 1) * 2 + (ww & 1)) * 32 + lane,
                   pack_bf16(o[0] * i0, o[1] * i0), pack_bf16(o[2] * i1, o[3] * i1), pack_bf16(o[4] * i0, o[5] * i0), pack_bf16(o[6] * i1, o[7] * i1));
            if (u == 2) asm volatile("cp.async.bulk.wait_group 0;" ::: "memory");
            else hint_arrive(H_O + 16 + (b >> 3));
            warp_done(mb + (MB_DONE + (u == 7) * 4) * 8);
            TS(5 + (u == 7));
        } else if (u >= 3) {
            if (u < 6) warp_done(mb + (MB_DONE + u - 2) * 8);
            if (job < (u == 3 ? 2 : 5)) {
                mbar_wait(mb + (MB_DONE + u - 3) * 8);
                if (lane == 0) {
                    if (u > 3) refill_job(sb, P, u - 4, job);
                    else if (job == 1) load_wo(sb, P, 1);
                    else asm volatile("red.release.gpu.global.add.u32 [%0], 1;" :: "l"(&g_s.count2) : "memory");
                }
            } else if (warp == 11) {
                if (u == 5) asm volatile("ld.relaxed.gpu.global.u32 %0, [%1];" : "=r"(cnt) : "l"(&g_s.count2) : "memory");
                if (u == 6) {
                    const unsigned target = lds32(mb + MISC_EPOCH) * NCTA;
                    if (__any_sync(0xffffffffu, cnt != target)) wait_count(&g_s.count2, target);
                    asm volatile("fence.acquire.gpu;" ::: "memory");
                    warp_done(mb + MB_F2 * 8);
                }
            }
        } else if (u == 1) {
            if (SAFE) mbar_wait(mb + MB_KV * 8);
            TS(17);
    if (lane == 0) {
        if (job < 9) {
            asm volatile("cp.async.bulk.global.shared::cta.bulk_group [%0], [%1], %2;"
                         :: "l"(g_x + X_ARM + b * X_SHARE + job * 512), "r"(sb + SM_SENT), "r"(job < 8 ? 8192 : (X_SHARE - 4096) * 16) : "memory");
            asm volatile("cp.async.bulk.commit_group;" ::: "memory");
        } else if (job == 9) load_wo(sb, P, 0);
    }
        } else if (SAFE) {
            if (warp == 8) {
                const unsigned target = lds32(mb + MISC_EPOCH) * NMAIN;
                if (__any_sync(0xffffffffu, cnt != target)) wait_count(&g_s.count1, target);
                if (lane == 0) {
                    asm volatile("fence.acquire.gpu; fence.proxy.async.global;" ::: "memory");
                    mbar_expect(mb + MB_KV * 8, 47104 + 2 * 24576);
                    bulk_g2s(sb + SM_K + 16384, g_s.kv + 1024, 47104, mb + MB_KV * 8);
                    bulk_g2s(sb + SM_V + 8192, g_s.kv + 4096 + 512, 24576, mb + MB_KV * 8);
                    bulk_g2s(sb + SM_V + 32768 + 8192, g_s.kv + 6144 + 512, 24576, mb + MB_KV * 8);
                }
            }
        }
        __syncwarp();
    }
    }
}

__device__ __noinline__ void helper_cta(const Params& P, uint8_t* smem) {
    const int tid = threadIdx.x, b = blockIdx.x, hi = b - NMAIN;
    const unsigned epoch = g_s.epoch[b] + 1;
    float* red = reinterpret_cast<float*>(smem);
    if (tid < 32) wait_count(&g_s.count1, epoch * NMAIN);
    __syncthreads();
    if (tid == 480) {
        for (int i = 0; i < 8; i++) asm volatile("cp.async.bulk.prefetch.L2.global [%0], %1;" :: "l"((const char*)P.wop + hi * 131072 + i * 16384), "r"(16384) : "memory");
        for (int i = 0; i < 43; i++) asm volatile("cp.async.bulk.prefetch.L2.global [%0], %1;" :: "l"((const char*)P.w2p + hi * 352256 + i * 8192), "r"(8192) : "memory");
    }
    if (tid < 344) {
        const int cg = tid % 43, rp = tid / 43;
        const uint4* src = reinterpret_cast<const uint4*>(P.w1p + (size_t)rp * 64 * FF + (hi * 43 + cg) * 8);
        float s[8] = {0, 0, 0, 0, 0, 0, 0, 0};
#pragma unroll 8
        for (int r = 0; r < 64; r++) {
            uint4 v = __ldg(src + r * (FF / 8));
            s[0] += bf_lo(v.x); s[1] += bf_hi(v.x); s[2] += bf_lo(v.y); s[3] += bf_hi(v.y);
            s[4] += bf_lo(v.z); s[5] += bf_hi(v.z); s[6] += bf_lo(v.w); s[7] += bf_hi(v.w);
        }
        float* part = red + (rp * 43 + cg) * 8;
#pragma unroll
        for (int i = 0; i < 8; i++) part[i] = s[i];
    }
    __syncthreads();
    if (tid < 344) {
        float s = 0.f;
#pragma unroll
        for (int rp = 0; rp < 8; rp++) s += red[rp * 344 + tid];
        g_s.cs[hi * 344 + tid] = s;
    } else if (hi == 3 && tid < 344 + 64) g_s.cs[FF + tid - 344] = 0.f;
    __syncthreads();
    if (tid == 0) {
        asm volatile("red.release.gpu.global.add.u32 [%0], 1;" :: "l"(&g_s.count2) : "memory");
        g_s.epoch[b] = epoch;
    }
}

__global__ void __launch_bounds__(512, 1) fused_kernel(const __grid_constant__ Params P) {
    extern __shared__ __align__(1024) uint8_t smem[];
    const uint32_t sb = (uint32_t)__cvta_generic_to_shared(smem);
    const uint32_t mb = sb + SM_MISC;
    const int tid = threadIdx.x, lane = tid & 31, b = blockIdx.x;
    if (b >= NMAIN) { helper_cta(P, smem); return; }
    const int tg = b >> 2, hg = b & 3;
    const int warp = __shfl_sync(0xffffffffu, tid >> 5, 0);

    uint4 xv[4][2];
    unsigned epoch = 0;
    {
        const int r = (tid >> 5) * 4;
        const uint4* src = reinterpret_cast<const uint4*>(P.x + (size_t)((r & 31) + tg * 32 + (r >> 5) * 1024) * D) + lane;
#pragma unroll
        for (int i = 0; i < 4; i++) { xv[i][0] = ldg_relaxed(src + i * 64); xv[i][1] = ldg_relaxed(src + i * 64 + 32); }
    }
    const uint4 wkv = ldg_relaxed(reinterpret_cast<const uint4*>(reinterpret_cast<const char*>(P.wk) + (hg < 2 ? 0 : P.wv_off)) + tid * 2 + (hg & 1));
    const int wg = warp >> 2, ww = warp & 3, g = lane >> 2, t4 = lane & 3, t128 = tid & 127;
    if (lane == 0) {
        mbar_init(mb + warp * 8, warp < 4 ? 2 : warp < 8 ? 3 : warp < 14 ? 16 : 1);
        mbar_init(mb + (16 + warp) * 8, 1);
        mbar_init(mb + (32 + warp) * 8, 1);
        if (warp < 4) {
            asm volatile("fence.mbarrier_init.release.cluster;" ::: "memory");
            load_wq(sb, P, warp, 0);
            if (warp < 3) load_wq(sb, P, warp, 1);
        } else if (warp < 7) {
            asm volatile("prefetch.tensormap [%0];" :: "l"(&P.wo + (warp - 4)) : "memory");
        } else if (warp == 7) {
            asm volatile("ld.relaxed.gpu.global.u32 %0, [%1];" : "=r"(epoch) : "l"(g_s.epoch + b) : "memory");
        } else if (warp < 10) {
            sts128(mb + MISC_CNT + (warp - 8) * 16, 0, 0, 0, 0);
        }
    }
    __syncwarp();
    TS(16);
    float dlt;
    {
        float st[4];
#pragma unroll
        for (int i = 0; i < 4; i++) {
            const uint32_t s = add_bf16x2(add_bf16x2(add_bf16x2(xv[i][0].x, xv[i][0].y), add_bf16x2(xv[i][0].z, xv[i][0].w)),
                                          add_bf16x2(add_bf16x2(xv[i][1].x, xv[i][1].y), add_bf16x2(xv[i][1].z, xv[i][1].w)));
            st[i] = bf_lo(s) + bf_hi(s);
        }
        TS(13);
        const float tot = reduce4(st, lane) * (-1.0f / D);
        const uint32_t nmr = pack_bf16(tot, tot);
        dlt = bf_lo(nmr) - tot;
        const uint32_t xa = sb + SM_XN + (lane >> 3) * 8192 + warp * 512;
#pragma unroll
        for (int i = 0; i < 4; i++) {
            const uint32_t nm = __shfl_sync(0xffffffffu, nmr, i * 8);
            const uint32_t addr = xa + i * 128 + (((lane & 7) ^ ((warp & 1) * 4 + i)) << 4);
#pragma unroll
            for (int c = 0; c < 2; c++) {
                xv[i][c].x = add_bf16x2(xv[i][c].x, nm); xv[i][c].y = add_bf16x2(xv[i][c].y, nm);
                xv[i][c].z = add_bf16x2(xv[i][c].z, nm); xv[i][c].w = add_bf16x2(xv[i][c].w, nm);
                sts128(addr + c * 32768, xv[i][c].x, xv[i][c].y, xv[i][c].z, xv[i][c].w);
            }
        }
    }
    sts128(sb + SM_WKV + tid * 16, wkv.x, wkv.y, wkv.z, wkv.w);
    fence_async_smem();
    TS(0);
    __syncthreads();
    auto variances = [&]() {
        float st[4];
#pragma unroll
        for (int i = 0; i < 4; i++) {
            float v = 0.f;
#pragma unroll
            for (int c = 0; c < 2; c++) {
                const uint32_t a = fma_bf16x2(xv[i][c].x, xv[i][c].x, mul_bf16x2(xv[i][c].y, xv[i][c].y));
                const uint32_t d = fma_bf16x2(xv[i][c].z, xv[i][c].z, mul_bf16x2(xv[i][c].w, xv[i][c].w));
                v += (bf_lo(a) + bf_hi(a)) + (bf_lo(d) + bf_hi(d));
            }
            st[i] = v;
        }
        const float vs = reduce4(st, lane), dl = dlt;
        if ((lane & 7) == 0) sts32(mb + MISC_RSTD + (warp * 4 + (lane >> 3)) * 4, __float_as_uint(rsqrtf(fmaxf(vs * (1.0f / D) - dl * dl, 0.f) + 1e-5f)));
    };
    float kv[4] = {0.f, 0.f, 0.f, 0.f};
    if (wg == 2) {
        fence_regs(kv);
        const uint64_t da = mkdesc(sb + SM_XN, 16, 1024, 1), db = mkdesc(sb + SM_WKV, 128, 16, 0);
        wg_fence();
#pragma unroll
        for (int s = 0; s < 32; s++) mma_ss8(kv, da + (s >> 2) * 512 + (s & 3) * 2, db + s * 16);
        wg_commit();
        TS(18);
        variances();
        wg_wait<0>(); fence_regs(kv);
        TS(20);
    } else {
        variances();
        if (tid == 7 * 32) { sts32(mb + MISC_EPOCH, epoch + 1); g_s.epoch[b] = epoch + 1; }
        TS(19);
    }
    __syncthreads();
    constexpr float QSCALE = 0.25f * 1.4426950408889634f;
    int kvoff;
    {
        const int t = (t128 & 63) >> 1, c = 2 * tg + (t128 & 1);
        kvoff = hg < 2 ? ((t + 31) & 31) * 128 + (c >> 3) * 16 + (hg & 1) * 8 + (c & 7) : 4096 + (hg & 1) * 2048 + t * 64 + c;
    }
    float qa[32];
    if (wg < 2) {
#pragma unroll
        for (int i = 0; i < 32; i++) qa[i] = 0.f;
        fence_regs(qa);
        const uint64_t da = mkdesc(sb + SM_XN, 16, 1024, 1), db = mkdesc(sb + SM_WQ + wg * 65536, 16, 1024, 1);
#pragma unroll 1
        for (int i = 0; i < 4; i++) {
            mbar_wait(mb + (MB_WQ + i) * 8);
            if (i == 0) TS(21); if (i == 3) TS(22);
            wg_fence();
#pragma unroll
            for (int s = 0; s < 8; s++) mma_ss64(qa, da + (i * 2 + (s >> 2)) * 512 + (s & 3) * 2, db + (i * 8 + s) * 128);
            wg_commit();
        }
        const float rs0 = __uint_as_float(lds32(mb + MISC_RSTD + (ww * 16 + g) * 4)) * QSCALE, rs1 = __uint_as_float(lds32(mb + MISC_RSTD + (ww * 16 + g + 8) * 4)) * QSCALE;
        wg_wait<0>();
        fence_regs(qa);
        bar_arrive(5, 384); bar_arrive(6, 384);
        TS(1);
        float nn[8];
#pragma unroll
        for (int i = 0; i < 32; i++) qa[i] *= (i & 2) ? rs1 : rs0;
#pragma unroll
        for (int h = 0; h < 4; h++) {
            nn[2 * h] = qa[8 * h] * qa[8 * h] + qa[8 * h + 1] * qa[8 * h + 1] + qa[8 * h + 4] * qa[8 * h + 4] + qa[8 * h + 5] * qa[8 * h + 5];
            nn[2 * h + 1] = qa[8 * h + 2] * qa[8 * h + 2] + qa[8 * h + 3] * qa[8 * h + 3] + qa[8 * h + 6] * qa[8 * h + 6] + qa[8 * h + 7] * qa[8 * h + 7];
        }
#pragma unroll
        for (int o = 1; o < 4; o <<= 1)
#pragma unroll
            for (int i = 0; i < 8; i++) nn[i] += __shfl_xor_sync(0xffffffffu, nn[i], o);
        bar_sync(1, 256);
#pragma unroll
        for (int h = 0; h < 4; h++) {
            const uint32_t base = sb + SM_Q + ((ww >> 1) * 4 + wg * 2 + (h >> 1)) * 2048 + ((h & 1) * 4 + (ww & 1) * 2) * 256 + lane * 4;
            sts32(base, pack_f16(qa[8 * h], qa[8 * h + 1])); sts32(base + 256, pack_f16(qa[8 * h + 2], qa[8 * h + 3]));
            sts32(base + 128, pack_f16(qa[8 * h + 4], qa[8 * h + 5])); sts32(base + 384, pack_f16(qa[8 * h + 6], qa[8 * h + 7]));
        }
        uint32_t nm = 0;
#pragma unroll
        for (int i = 0; i < 8; i++) nm = max(nm, __float_as_uint(nn[i]));
        nm = __reduce_max_sync(0xffffffffu, nm);
        if (lane == 0) asm volatile("red.shared.max.u32 [%0], %1;" :: "r"(mb + MISC_NRM), "r"(nm) : "memory");
    } else if (wg == 2) {
        const float rs0 = __uint_as_float(lds32(mb + MISC_RSTD + (ww * 16 + g) * 4)), rs1 = __uint_as_float(lds32(mb + MISC_RSTD + (ww * 16 + g + 8) * 4));
        kv[0] *= rs0; kv[1] *= rs0; kv[2] *= rs1; kv[3] *= rs1;
        float2* kt = reinterpret_cast<float2*>(smem + SM_MISC + MISC_KTMP);
        kt[(ww * 16 + g) * 4 + t4] = make_float2(kv[0], kv[1]); kt[(ww * 16 + g + 8) * 4 + t4] = make_float2(kv[2], kv[3]);
        float n0 = kv[0] * kv[0] + kv[1] * kv[1], n1 = kv[2] * kv[2] + kv[3] * kv[3];
        n0 += __shfl_xor_sync(0xffffffffu, n0, 1); n1 += __shfl_xor_sync(0xffffffffu, n1, 1);
        n0 += __shfl_xor_sync(0xffffffffu, n0, 2); n1 += __shfl_xor_sync(0xffffffffu, n1, 2);
        const uint32_t nm = __reduce_max_sync(0xffffffffu, max(__float_as_uint(n0), __float_as_uint(n1)));
        if (lane == 0) sts32(mb + MISC_WNRM + ww * 4, nm | 1u);
        bar_sync(2, 128);
        const uint32_t ra = mb + MISC_KTMP + ((t128 & 1) * 32 + ((t128 & 63) >> 1)) * 32;
        const float4 c0 = lds128f(ra), c1 = lds128f(ra + 16);
        if (ww < 2) {
            if (hg < 2) {
                float4 p0 = lds128f(ra - 32), p1 = lds128f(ra - 16);
                if (t128 < 2) { p0 = make_float4(0.f, 0.f, 0.f, 0.f); p1 = p0; }
                stg128(g_s.kv + kvoff, nonzero(pack_f16(c0.x - p0.x, c0.y - p0.y)), pack_f16(c0.z - p0.z, c0.w - p0.w), pack_f16(c1.x - p1.x, c1.y - p1.y), pack_f16(c1.z - p1.z, c1.w - p1.w));
            } else {
                stg128(g_s.kv + kvoff, nonzero(pack_bf16(c0.x, c0.y)), pack_bf16(c0.z, c0.w), pack_bf16(c1.x, c1.y), pack_bf16(c1.z, c1.w));
            }
            if (t128 < 2) { const float4 w = lds128f(mb + MISC_WNRM); stg128(g_s.nrm + b * 2 + t128, __float_as_uint(w.x), __float_as_uint(w.y), __float_as_uint(w.z), __float_as_uint(w.w)); }
            hint_arrive(H_KV);
        } else if (hg < 2) {
            stg128(g_s.kplain + kvoff, pack_bf16(c0.x, c0.y), pack_bf16(c0.z, c0.w), pack_bf16(c1.x, c1.y), pack_bf16(c1.z, c1.w));
        }
        TS(1);
        bar_sync(2, 128);
        if (t128 == 96) asm volatile("red.release.gpu.global.add.u32 [%0], 1;" :: "l"(&g_s.count1) : "memory");
        __syncwarp();
        bar_sync(5, 384);
#pragma unroll
        for (int i = 0; i < 16; i++) sts128(sb + SM_V + 65536 + (i * 128 + t128) * 16, 0x3F803F80u, 0x3F803F80u, 0x3F803F80u, 0x3F803F80u);
#pragma unroll
        for (int i = 0; i < 4; i++) sts128(sb + SM_SENT + (i * 128 + t128) * 16, SENT, SENT, SENT, SENT);
    } else {
        if (tid == 13 * 32) load_wq(sb, P, 3, 1);
        __syncwarp();
        uint4 kc[18];
        auto src = [&](int i) { return i < 8 ? g_s.kv + i * 128 : i < 12 ? g_s.kv + 4096 + (i - 8) * 128 : i < 16 ? g_s.kv + 6144 + (i - 12) * 128 : i == 16 ? g_s.kv + 31 * 128 : g_s.nrm + t128; };
        hint_wait(H_KV, lds32(mb + MISC_EPOCH) * (NMAIN * 2));
        TS(1);
        int spins = 0;
        while (true) {
#pragma unroll
            for (int i = 0; i < 18; i++) kc[i] = ldg_relaxed(src(i) + t128);
            uint32_t mn = 1;
#pragma unroll
            for (int i = 0; i < 18; i++) mn = min(mn, kc[i].x);
            if (!__any_sync(0xffffffffu, mn == 0u) || ++spins >= SPIN_LIMIT) break;
        }
        uint32_t nm = max(max(kc[17].x, kc[17].y), max(kc[17].z, kc[17].w));
        nm = max(nm, __shfl_xor_sync(0xffffffffu, nm, 4)); nm = max(nm, __shfl_xor_sync(0xffffffffu, nm, 8)); nm = max(nm, __shfl_xor_sync(0xffffffffu, nm, 16));
        if (lane < 4) asm volatile("red.shared.max.u32 [%0], %1;" :: "r"(mb + MISC_NRM + 4 + min(lane, 2) * 4), "r"(nm) : "memory");
        TS(2);
        bar_sync(6, 384);
#pragma unroll
        for (int i = 0; i < 17; i++) sts128(sb + (uint32_t)(src(i) - g_s.kv + t128) * 16, kc[i].x, kc[i].y, kc[i].z, kc[i].w);
    }
    fence_async_smem();
    TS(3);
    __syncthreads();
    const float4 nr = lds128f(mb + MISC_NRM);
    const bool safe = __all_sync(0xffffffffu, (nr.x * (nr.y + nr.z) <= 3500.0f) && (nr.x <= 65536.0f) && (nr.y + nr.z <= 65536.0f) && (nr.w <= 1e24f));
    TS(4);

    if (__builtin_expect(safe, 1)) {
        attention<true>(P, sb, warp TS_PASS);
    } else {
        if (wg < 2) {
#pragma unroll
            for (int h = 0; h < 4; h++) {
                const uint32_t base = sb + SM_Q + ((ww >> 1) * 4 + wg * 2 + (h >> 1)) * 2048 + ((h & 1) * 4 + (ww & 1) * 2) * 256 + lane * 4;
                sts32(base, pack_bf16(qa[8 * h], qa[8 * h + 1])); sts32(base + 256, pack_bf16(qa[8 * h + 2], qa[8 * h + 3]));
                sts32(base + 128, pack_bf16(qa[8 * h + 4], qa[8 * h + 5])); sts32(base + 384, pack_bf16(qa[8 * h + 6], qa[8 * h + 7]));
            }
            fence_async_smem();
        } else if (warp == 15) {
            wait_count(&g_s.count1, lds32(mb + MISC_EPOCH) * NMAIN);
            if (lane == 0) {
                asm volatile("fence.proxy.async;" ::: "memory");
                mbar_expect(mb + MB_KV * 8, 131072);
                bulk_g2s(sb + SM_K, g_s.kplain, 65536, mb + MB_KV * 8);
                bulk_g2s(sb + SM_V, g_s.kv + 4096, 65536, mb + MB_KV * 8);
            }
            __syncwarp();
        }
        __syncthreads();
        mbar_wait(mb + MB_KV * 8);
        attention<false>(P, sb, warp TS_PASS);
    }

    const int pr = 1 - (wg >> 1), q = wg & 1;
    const int mt = 16 * pr + (b >> 3), j = b & 7;
    const int row0 = mt * 64 + ww * 16 + g;
    const uint32_t xbuf = sb + SM_Q + pr * 8192 + t128 * 16;
    uint32_t hk[8];
    epoch = lds32(mb + MISC_EPOCH);
    {
        const uint4* a = g_x + X_OF + (mt * 32 + q * 4) * 128 + t128;
        if (pr) {
            if (warp < 5) {
                mbar_wait(mb + (MB_DONE + 4) * 8);
                if (lane == 0) refill_job(sb, P, 3, warp);
            } else if (warp == 5) {
                if (lane < 24) {
                    const uint4 v = ldg_relaxed(reinterpret_cast<const uint4*>(g_s.cs + f1_col0()) + lane);
                    sts128(mb + MISC_CS + lane * 16, v.x, v.y, v.z, v.w);
                }
                warp_done(mb + MB_CS * 8);
            }
            __syncwarp();
            hint_wait(H_O + mt, epoch * 128);
        }
        uint4 buf[4][4];
#pragma unroll
        for (int i = 0; i < 4; i++) load_batch(buf[i], a + i * 1024);
        const uint32_t* xp = reinterpret_cast<const uint32_t*>(P.x + (size_t)row0 * D + j * 64 + q * 32 + t4 * 2);
#pragma unroll
        for (int i = 0; i < 4; i++) { hk[2 * i] = __ldg(xp + i * 4); hk[2 * i + 1] = __ldg(xp + i * 4 + 8 * (D / 2)); }
        TS(23);
        float acc[32], r[16];
        gemm_rs<0, 4, 4>(acc, buf, a, sb, q, P);
        TS(7);
        warp_done(mb + (MB_DONE + 5) * 8);
        mbar_wait(mb + (MB_DONE + 4 * pr) * 8);
        pair_reduce(acc, r, xbuf, q, 3 + pr);
#pragma unroll
        for (int i = 0; i < 8; i++) hk[i] = pack_bf16(r[2 * i] + bf_lo(hk[i]), r[2 * i + 1] + bf_hi(hk[i]));
        float s0 = 0.f, s1 = 0.f;
#pragma unroll
        for (int i = 0; i < 8; i++) {
            r[2 * i] = bf_lo(hk[i]); r[2 * i + 1] = bf_hi(hk[i]);
            if (i & 1) s1 += r[2 * i] + r[2 * i + 1]; else s0 += r[2 * i] + r[2 * i + 1];
        }
        s0 += __shfl_xor_sync(0xffffffffu, s0, 1); s1 += __shfl_xor_sync(0xffffffffu, s1, 1);
        s0 += __shfl_xor_sync(0xffffffffu, s0, 2); s1 += __shfl_xor_sync(0xffffffffu, s1, 2);
        const float a0 = s0 * (1.0f / 32), a1 = s1 * (1.0f / 32);
        float v0 = 0.f, v1 = 0.f;
#pragma unroll
        for (int i = 0; i < 8; i++) {
            const float am = (i & 1) ? a1 : a0;
            const float d0 = r[2 * i] - am, d1 = r[2 * i + 1] - am;
            if (i & 1) v1 += d0 * d0 + d1 * d1; else v0 += d0 * d0 + d1 * d1;
        }
        v0 += __shfl_xor_sync(0xffffffffu, v0, 1); v1 += __shfl_xor_sync(0xffffffffu, v1, 1);
        v0 += __shfl_xor_sync(0xffffffffu, v0, 2); v1 += __shfl_xor_sync(0xffffffffu, v1, 2);
        uint4* hp = g_x + X_HF + (mt * 32 + j * 4 + 2 * q) * 128 + t128;
        stg128(hp, hk[0], hk[1], hk[2], hk[3]);
        stg128(hp + 128, hk[4], hk[5], hk[6], hk[7]);
        if (t4 == 0) stg128(g_x + X_ST + (mt * 16 + j * 2 + q) * 32 + ww * 8 + g, __float_as_uint(s0), __float_as_uint(v0), __float_as_uint(s1), __float_as_uint(v1));
        hint_arrive(H_H1 + mt);
        TS(8);
        if (pr) {
            mbar_wait(mb + (MB_DONE + 5) * 8);
            if (lane == 0) load_w2(sb, P, 2 + warp, warp < 2 ? 22 + warp : warp - 2);
            __syncwarp();
        } else if (warp == 8 || warp == 9) {
            stg128(g_s.kv + kvoff, 0u, 0u, 0u, 0u);
            if (t128 < 2) stg128(g_s.nrm + b * 2 + t128, 0u, 0u, 0u, 0u);
        }
    }
    {
        const int mt1 = 16 * pr + (b >> 4) * 2 + q, sl = b & 15;
        const uint4* a = g_x + X_HF + mt1 * 32 * 128 + t128;
        float acc[48], nmean[2], hrstd[2];
        uint4 buf[3][4];
        {
            const uint4* sp = g_x + X_ST + (mt1 * 16 + t4) * 32 + ww * 8 + g;
            hint_wait(H_H1 + mt1, epoch * 64);
            TS(24);
            uint4 u[4];
            load_batch(u, sp);
#pragma unroll
            for (int i = 0; i < 3; i++) load_batch(buf[i], a + i * 512);
            check_batch(u, sp);
            TS(26);
            float mean[2], m2[2];
            mean[0] = (__uint_as_float(u[0].x) + __uint_as_float(u[1].x)) + (__uint_as_float(u[2].x) + __uint_as_float(u[3].x));
            mean[1] = (__uint_as_float(u[0].z) + __uint_as_float(u[1].z)) + (__uint_as_float(u[2].z) + __uint_as_float(u[3].z));
            mean[0] += __shfl_xor_sync(0xffffffffu, mean[0], 1); mean[1] += __shfl_xor_sync(0xffffffffu, mean[1], 1);
            mean[0] += __shfl_xor_sync(0xffffffffu, mean[0], 2); mean[1] += __shfl_xor_sync(0xffffffffu, mean[1], 2);
            mean[0] *= 1.0f / D; mean[1] *= 1.0f / D;
            m2[0] = 0.f; m2[1] = 0.f;
#pragma unroll
            for (int i = 0; i < 4; i++) {
                const float d0 = __uint_as_float(u[i].x) * (1.0f / 32) - mean[0], d1 = __uint_as_float(u[i].z) * (1.0f / 32) - mean[1];
                m2[0] += fmaf(32.0f * d0, d0, __uint_as_float(u[i].y)); m2[1] += fmaf(32.0f * d1, d1, __uint_as_float(u[i].w));
            }
            m2[0] += __shfl_xor_sync(0xffffffffu, m2[0], 1); m2[1] += __shfl_xor_sync(0xffffffffu, m2[1], 1);
            m2[0] += __shfl_xor_sync(0xffffffffu, m2[0], 2); m2[1] += __shfl_xor_sync(0xffffffffu, m2[1], 2);
#pragma unroll
            for (int i = 0; i < 2; i++) { hrstd[i] = 0.5f * rsqrtf(m2[i] * (1.0f / D) + 1e-5f); nmean[i] = -mean[i]; }
        }
        gemm_rs<1, 8, 3>(acc, buf, a, sb, q, P);
        TS(9);
        mbar_wait(mb + MB_CS * 8);
        uint4* hb = g_x + X_H + (mt1 * 88 + (sl >> 1) * 11 + (sl & 1) * 6) * 128 + t128;
#pragma unroll
        for (int k = 0; k < 6; k++) {
            if (k == 5 && (sl & 1)) break;
            uint32_t hv[4];
#pragma unroll
            for (int i = 0; i < 2; i++) {
                float2 cs;
                asm volatile("ld.shared.v2.f32 {%0,%1}, [%2];" : "=f"(cs.x), "=f"(cs.y) : "r"(mb + MISC_CS + (2 * k + i) * 32 + t4 * 8));
                const float* z = acc + 8 * k + 4 * i;
                hv[2 * i] = pack_bf16(silu2(hrstd[0] * fmaf(nmean[0], cs.x, z[0])), silu2(hrstd[0] * fmaf(nmean[0], cs.y, z[1])));
                hv[2 * i + 1] = pack_bf16(silu2(hrstd[1] * fmaf(nmean[1], cs.x, z[2])), silu2(hrstd[1] * fmaf(nmean[1], cs.y, z[3])));
            }
            stg128(hb + k * 128, hv[0], hv[1], hv[2], hv[3]);
        }
        hint_arrive(H_H2 + mt1);
        TS(10);
        release_w1(sb, P, 3);
    }
    {
        const uint4* a = g_x + X_H + (mt * 88 + q * 4) * 128 + t128;
        hint_wait(H_H2 + mt, epoch * 64);
        uint4 buf[4][4];
#pragma unroll
        for (int i = 0; i < 4; i++) load_batch(buf[i], a + i * 1024);
        TS(25);
        float acc[32], r[16];
        gemm_rs<2, 11, 4>(acc, buf, a, sb, q, P);
        TS(11);
        pair_reduce(acc, r, xbuf, q, 3 + pr);
#pragma unroll
        for (int i = 0; i < 8; i++) hk[i] = pack_bf16(r[2 * i] + bf_lo(hk[i]), r[2 * i + 1] + bf_hi(hk[i]));
    }
#pragma unroll
    for (int h = 0; h < 2; h++) {
        uint32_t v0 = hk[h], v1 = hk[2 + h], v2 = hk[4 + h], v3 = hk[6 + h];
        const bool o1 = t4 & 1, o2 = t4 & 2;
        uint32_t a = __shfl_xor_sync(0xffffffffu, o1 ? v0 : v1, 1), c = __shfl_xor_sync(0xffffffffu, o1 ? v2 : v3, 1);
        if (o1) { v0 = a; v2 = c; } else { v1 = a; v3 = c; }
        a = __shfl_xor_sync(0xffffffffu, o2 ? v0 : v2, 2); c = __shfl_xor_sync(0xffffffffu, o2 ? v1 : v3, 2);
        if (o2) { v0 = a; v1 = c; } else { v2 = a; v3 = c; }
        *reinterpret_cast<uint4*>(P.out + (size_t)(row0 + 8 * h) * D + j * 64 + q * 32 + t4 * 8) = make_uint4(v0, v1, v2, v3);
    }
    TS(12);
}

typedef CUresult (*EncodeFn)(CUtensorMap*, CUtensorMapDataType, cuuint32_t, void*, const cuuint64_t*, const cuuint64_t*, const cuuint32_t*,
                             const cuuint32_t*, CUtensorMapInterleave, CUtensorMapSwizzle, CUtensorMapL2promotion, CUtensorMapFloatOOBfill);

void encode2d(EncodeFn fn, CUtensorMap* tm, const void* ptr, int rows, int cols, int box_rows, int box_cols, CUtensorMapSwizzle sw) {
    cuuint64_t dims[2] = {(cuuint64_t)cols, (cuuint64_t)rows};
    cuuint64_t strides[1] = {(cuuint64_t)cols * 2};
    cuuint32_t box[2] = {(cuuint32_t)box_cols, (cuuint32_t)box_rows};
    cuuint32_t es[2] = {1, 1};
    fn(tm, CU_TENSOR_MAP_DATA_TYPE_BFLOAT16, 2, const_cast<void*>(ptr), dims, strides, box, es, CU_TENSOR_MAP_INTERLEAVE_NONE, sw,
       CU_TENSOR_MAP_L2_PROMOTION_L2_128B, CU_TENSOR_MAP_FLOAT_OOB_FILL_NONE);
}

}

extern "C" void kernel_launch(void* const* d_in, const int* in_sizes, int n_in, void* d_out, int out_size) {
    (void)in_sizes; (void)n_in; (void)out_size;
    void* fnp = nullptr;
    cudaDriverEntryPointQueryResult qr;
    cudaGetDriverEntryPoint("cuTensorMapEncodeTiled", &fnp, cudaEnableDefault, &qr);
    EncodeFn fn = (EncodeFn)fnp;
    Params P;
    encode2d(fn, &P.wq, d_in[1], D, D, 128, 64, CU_TENSOR_MAP_SWIZZLE_128B);
    P.wk = (const __nv_bfloat16*)d_in[2];
    P.wv_off = (const char*)d_in[3] - (const char*)d_in[2];
    encode2d(fn, &P.wo, d_in[4], D, D, 64, 64, CU_TENSOR_MAP_SWIZZLE_128B);
    encode2d(fn, &P.w1, d_in[6], D, FF, 128, 32, CU_TENSOR_MAP_SWIZZLE_64B);
    encode2d(fn, &P.w2, d_in[7], FF, D, 64, 64, CU_TENSOR_MAP_SWIZZLE_128B);
    P.x = (const __nv_bfloat16*)d_in[0];
    P.w1p = (const __nv_bfloat16*)d_in[6];
    P.w2p = (const __nv_bfloat16*)d_in[7];
    P.wop = (const __nv_bfloat16*)d_in[4];
    P.wqp = (const __nv_bfloat16*)d_in[1];
    P.out = (__nv_bfloat16*)d_out;
    P.neg1 = 0xFFFFFFFFu; P.pad = 0;
    cudaFuncSetAttribute(fused_kernel, cudaFuncAttributeMaxDynamicSharedMemorySize, SMEM_BYTES);
    fused_kernel<<<NCTA, 512, SMEM_BYTES>>>(P);
}
```

```cpp
#include <cuda_runtime.h>
#include <cuda_bf16.h>
#include <cuda.h>
#include <stdint.h>

namespace {

constexpr int D = 512, FF = 1376;
constexpr int NMAIN = 128, NHELP = 4, NCTA = NMAIN + NHELP;
constexpr uint32_t SENT = 0xFFFFFFFFu;
constexpr int SPIN_LIMIT = 1 << 22;

constexpr uint32_t KB = 1024;
constexpr uint32_t SM_XN = 0;
constexpr uint32_t SM_WQ = 64 * KB;
constexpr uint32_t SM_WKV = 176 * KB;
constexpr uint32_t SM_K = 0;
constexpr uint32_t SM_V = 64 * KB;
constexpr uint32_t SM_Q = 160 * KB;
constexpr uint32_t SM_SENT = 184 * KB;
constexpr uint32_t SM_MISC = 192 * KB;
constexpr uint32_t SMEM_BYTES = 195 * KB;
constexpr uint32_t MB_WQ = 0;
constexpr uint32_t MB_W1 = 4;
constexpr uint32_t MB_DONE = 8;
constexpr uint32_t MB_KV = 14;
constexpr uint32_t MB_WO = 16;
constexpr uint32_t MB_W2 = 24;
constexpr uint32_t MB_F2 = 46;
constexpr uint32_t MB_CS = 47;
constexpr uint32_t MISC_CNT = 384;
constexpr uint32_t MISC_NRM = 400;
constexpr uint32_t MISC_EPOCH = 416;
constexpr uint32_t MISC_WNRM = 432;
constexpr uint32_t MISC_CS = 1024;
constexpr uint32_t MISC_RSTD = 448;
constexpr uint32_t MISC_KTMP = 1024;

__host__ __device__ constexpr uint32_t wo_slot(int kb) { return kb < 2 ? 22 + kb : kb - 2; }
__host__ __device__ constexpr uint32_t w2_slot(int kb) { return kb < 2 ? 6 + kb : kb < 4 ? 20 + kb : kb < 10 ? kb - 4 : 8 + (kb - 10) / 3 + 4 * ((kb - 10) % 3); }

struct alignas(128) Small {
    unsigned epoch[160];
    unsigned count1, pad1[31];
    unsigned count2, pad2[31];
    unsigned hint[100][32];
    float cs[1440];
    uint4 nrm[NMAIN * 2];
    uint4 kv[8192];
    uint4 kplain[4096];
};
__device__ Small g_s;
constexpr int X_OF = 0, X_HF = 32 * 32 * 128, X_ST = X_HF + 32 * 32 * 128, X_H = X_ST + 32 * 64 * 8, X_END = X_H + 32 * 88 * 128;
constexpr int X_ARM = 16 * 32 * 128, X_SHARE = (X_END - X_ARM) / NMAIN;
__device__ uint4 g_x[X_END];
#define TS(i) do {} while (0)

__device__ __forceinline__ void mbar_init(uint32_t bar, int cnt) { asm volatile("mbarrier.init.shared::cta.b64 [%0], %1;" :: "r"(bar), "r"(cnt) : "memory"); }
__device__ __forceinline__ void mbar_expect(uint32_t bar, uint32_t bytes) { asm volatile("mbarrier.arrive.expect_tx.shared::cta.b64 _, [%0], %1;" :: "r"(bar), "r"(bytes) : "memory"); }
__device__ __forceinline__ void mbar_arrive(uint32_t bar) { asm volatile("mbarrier.arrive.shared::cta.b64 _, [%0];" :: "r"(bar) : "memory"); }
__device__ __forceinline__ void mbar_wait(uint32_t bar) {
    uint32_t done; int spins = 0;
    do {
        asm volatile("{.reg .pred p; mbarrier.try_wait.parity.shared::cta.b64 p, [%1], 0; selp.u32 %0, 1, 0, p;}" : "=r"(done) : "r"(bar) : "memory");
    } while (!__all_sync(0xffffffffu, done) && ++spins < SPIN_LIMIT);
}
__device__ __forceinline__ void tma2d(uint32_t dst, const CUtensorMap* tm, int c0, int c1, uint32_t bar) {
    asm volatile("cp.async.bulk.tensor.2d.shared::cluster.global.mbarrier::complete_tx::bytes [%0], [%1, {%3, %4}], [%2];"
                 :: "r"(dst), "l"(tm), "r"(bar), "r"(c0), "r"(c1) : "memory");
}
__device__ __forceinline__ void bulk_g2s(uint32_t dst, const void* src, uint32_t bytes, uint32_t bar) {
    asm volatile("cp.async.bulk.shared::cluster.global.mbarrier::complete_tx::bytes [%0], [%1], %2, [%3];" :: "r"(dst), "l"(src), "r"(bytes), "r"(bar) : "memory");
}
__device__ __forceinline__ void fence_async_smem() { asm volatile("fence.proxy.async.shared::cta;" ::: "memory"); }
__device__ __forceinline__ void bar_sync(int id, int n) { asm volatile("bar.sync %0, %1;" :: "r"(id), "r"(n) : "memory"); }
__device__ __forceinline__ void bar_arrive(int id, int n) { asm volatile("bar.arrive %0, %1;" :: "r"(id), "r"(n) : "memory"); }
__device__ __forceinline__ void wg_fence() { asm volatile("wgmma.fence.sync.aligned;" ::: "memory"); }
__device__ __forceinline__ void wg_commit() { asm volatile("wgmma.commit_group.sync.aligned;" ::: "memory"); }
template <int N> __device__ __forceinline__ void wg_wait() { asm volatile("wgmma.wait_group.sync.aligned %0;" :: "n"(N) : "memory"); }
template <int N> __device__ __forceinline__ void fence_regs(float (&d)[N]) {
#pragma unroll
    for (int i = 0; i < N; i++) asm volatile("" : "+f"(d[i]) :: "memory");
}
template <int N> __device__ __forceinline__ void fence_regs(uint32_t (&d)[N]) {
#pragma unroll
    for (int i = 0; i < N; i++) asm volatile("" : "+r"(d[i]) :: "memory");
}
__device__ __forceinline__ uint64_t mkdesc(uint32_t addr, uint32_t lbo, uint32_t sbo, uint32_t swz) {
    return (uint64_t)(((addr & 0x3FFFF) >> 4) | ((lbo >> 4) << 16)) | ((uint64_t)((sbo >> 4) | (swz << 30)) << 32);
}
__device__ __forceinline__ float ex2(float x) { float y; asm("ex2.approx.ftz.f32 %0, %1;" : "=f"(y) : "f"(x)); return y; }
__device__ __forceinline__ float rcp(float x) { float y; asm("rcp.approx.ftz.f32 %0, %1;" : "=f"(y) : "f"(x)); return y; }
__device__ __forceinline__ uint32_t pack_bf16(float lo, float hi) { uint32_t r; asm("cvt.rn.bf16x2.f32 %0, %1, %2;" : "=r"(r) : "f"(hi), "f"(lo)); return r; }
__device__ __forceinline__ uint32_t pack_f16(float lo, float hi) { uint32_t r; asm("cvt.rn.f16x2.f32 %0, %1, %2;" : "=r"(r) : "f"(hi), "f"(lo)); return r; }
__device__ __forceinline__ float bf_lo(uint32_t v) { return __uint_as_float(v << 16); }
__device__ __forceinline__ float bf_hi(uint32_t v) { return __uint_as_float(v & 0xFFFF0000u); }
__device__ __forceinline__ uint4 ldg_relaxed(const uint4* p) {
    uint4 v; asm volatile("ld.relaxed.gpu.global.v4.u32 {%0,%1,%2,%3}, [%4];" : "=r"(v.x), "=r"(v.y), "=r"(v.z), "=r"(v.w) : "l"(p) : "memory"); return v;
}
__device__ __forceinline__ void stg128(void* p, uint32_t a, uint32_t b, uint32_t c, uint32_t d) {
    asm volatile("st.relaxed.gpu.global.v4.u32 [%0], {%1,%2,%3,%4};" :: "l"(p), "r"(a), "r"(b), "r"(c), "r"(d) : "memory");
}
__device__ __forceinline__ void stg64(void* p, uint32_t a, uint32_t b) {
    asm volatile("st.relaxed.gpu.global.v2.u32 [%0], {%1,%2};" :: "l"(p), "r"(a), "r"(b) : "memory");
}
__device__ __forceinline__ void sts128(uint32_t a, uint32_t x, uint32_t y, uint32_t z, uint32_t w) {
    asm volatile("st.shared.v4.u32 [%0], {%1,%2,%3,%4};" :: "r"(a), "r"(x), "r"(y), "r"(z), "r"(w) : "memory");
}
__device__ __forceinline__ void sts32(uint32_t a, uint32_t x) { asm volatile("st.shared.u32 [%0], %1;" :: "r"(a), "r"(x) : "memory"); }
__device__ __forceinline__ float4 lds128f(uint32_t a) {
    float4 v; asm volatile("ld.shared.v4.f32 {%0,%1,%2,%3}, [%4];" : "=f"(v.x), "=f"(v.y), "=f"(v.z), "=f"(v.w) : "r"(a) : "memory"); return v;
}
__device__ __forceinline__ uint32_t lds32(uint32_t a) { uint32_t v; asm volatile("ld.shared.u32 %0, [%1];" : "=r"(v) : "r"(a) : "memory"); return v; }
__device__ __forceinline__ bool has_sent(const uint4& v) { return (v.x == SENT) | (v.w == SENT); }
__device__ __forceinline__ bool has_zero(const uint4& v) { return min(min(v.x, v.y), min(v.z, v.w)) == 0u; }
__device__ __forceinline__ uint32_t nonzero(uint32_t w) { return w == 0u ? 0x8000u : w; }
__device__ __forceinline__ void stg32(void* p, uint32_t a) { asm volatile("st.relaxed.gpu.global.u32 [%0], %1;" :: "l"(p), "r"(a) : "memory"); }
__device__ __forceinline__ void wait_count(const unsigned* p, unsigned target) {
    unsigned v; int spins = 0;
    do { asm volatile("ld.acquire.gpu.global.u32 %0, [%1];" : "=r"(v) : "l"(p) : "memory"); } while (__any_sync(0xffffffffu, v != target) && ++spins < SPIN_LIMIT);
}
__device__ __forceinline__ uint32_t warp_arrive(uint32_t cnt) {
    uint32_t old = 0;
    __syncwarp();
    if ((threadIdx.x & 31) == 0) asm volatile("atom.acq_rel.cta.shared.add.u32 %0, [%1], 1;" : "=r"(old) : "r"(cnt) : "memory");
    return __shfl_sync(0xffffffffu, old, 0);
}
__device__ __forceinline__ void warp_done(uint32_t bar) { __syncwarp(); if ((threadIdx.x & 31) == 0) mbar_arrive(bar); }
__device__ __forceinline__ uint32_t mul_bf16x2(uint32_t a, uint32_t b) { uint32_t r; asm("mul.rn.bf16x2 %0, %1, %2;" : "=r"(r) : "r"(a), "r"(b)); return r; }
__device__ __forceinline__ uint32_t fma_bf16x2(uint32_t a, uint32_t b, uint32_t c) { uint32_t r; asm("fma.rn.bf16x2 %0, %1, %2, %3;" : "=r"(r) : "r"(a), "r"(b), "r"(c)); return r; }
__device__ __forceinline__ uint32_t add_bf16x2(uint32_t a, uint32_t b) { uint32_t r; asm("add.rn.bf16x2 %0, %1, %2;" : "=r"(r) : "r"(a), "r"(b)); return r; }

#define R4(d, o) "+f"(d[o + 0]), "+f"(d[o + 1]), "+f"(d[o + 2]), "+f"(d[o + 3])
#define R8(d, o) R4(d, o), R4(d, o + 4)
#define R32(d) R8(d, 0), R8(d, 8), R8(d, 16), R8(d, 24)
#define D32 "{%0,%1,%2,%3,%4,%5,%6,%7,%8,%9,%10,%11,%12,%13,%14,%15,%16,%17,%18,%19,%20,%21,%22,%23,%24,%25,%26,%27,%28,%29,%30,%31}"
#define D64 "{%0,%1,%2,%3,%4,%5,%6,%7,%8,%9,%10,%11,%12,%13,%14,%15,%16,%17,%18,%19,%20,%21,%22,%23,%24,%25,%26,%27,%28,%29,%30,%31,%32,%33,%34,%35,%36,%37,%38,%39,%40,%41,%42,%43,%44,%45,%46,%47,%48,%49,%50,%51,%52,%53,%54,%55,%56,%57,%58,%59,%60,%61,%62,%63}"
#define D48 "{%0,%1,%2,%3,%4,%5,%6,%7,%8,%9,%10,%11,%12,%13,%14,%15,%16,%17,%18,%19,%20,%21,%22,%23,%24,%25,%26,%27,%28,%29,%30,%31,%32,%33,%34,%35,%36,%37,%38,%39,%40,%41,%42,%43,%44,%45,%46,%47}"

__device__ __forceinline__ void mma_qk_f16(float (&d)[32], uint64_t da, uint64_t db) {
    asm volatile("{.reg .pred p; setp.eq.b32 p, 0, 0; wgmma.mma_async.sync.aligned.m64n64k16.f32.f16.f16 " D32 ", %32, %33, p, 1, 1, 0, 0;}"
                 : R32(d) : "l"(da), "l"(db));
}
__device__ __forceinline__ void mma_qk_bf16(float (&d)[32], uint64_t da, uint64_t db) {
    asm volatile("{.reg .pred p; setp.ne.b32 p, 0, 0; wgmma.mma_async.sync.aligned.m64n64k16.f32.bf16.bf16 " D32 ", %32, %33, p, 1, 1, 0, 0;}"
                 : R32(d) : "l"(da), "l"(db));
}
__device__ __forceinline__ void mma_pv(float (&d)[12], const uint32_t* a, uint64_t db) {
    asm volatile("{.reg .pred p; setp.eq.b32 p, 0, 0; wgmma.mma_async.sync.aligned.m64n24k16.f32.bf16.bf16 {%0,%1,%2,%3,%4,%5,%6,%7,%8,%9,%10,%11}, {%12,%13,%14,%15}, %16, p, 1, 1, 1;}"
                 : R8(d, 0), R4(d, 8) : "r"(a[0]), "r"(a[1]), "r"(a[2]), "r"(a[3]), "l"(db));
}
__device__ __forceinline__ void mma_ss128(float (&d)[64], uint64_t da, uint64_t db) {
    asm volatile("{.reg .pred p; setp.eq.b32 p, 0, 0; wgmma.mma_async.sync.aligned.m64n128k16.f32.bf16.bf16 " D64 ", %64, %65, p, 1, 1, 0, 1;}"
                 : R32(d), R8(d, 32), R8(d, 40), R8(d, 48), R8(d, 56) : "l"(da), "l"(db));
}
__device__ __forceinline__ void stsm4(uint32_t addr, uint32_t a, uint32_t b, uint32_t c, uint32_t d) {
    asm volatile("stmatrix.sync.aligned.m8n8.x4.shared.b16 [%0], {%1,%2,%3,%4};" :: "r"(addr), "r"(a), "r"(b), "r"(c), "r"(d) : "memory");
}
__device__ __forceinline__ void mma_ss8(float (&d)[4], uint64_t da, uint64_t db) {
    asm volatile("{.reg .pred p; setp.eq.b32 p, 0, 0; wgmma.mma_async.sync.aligned.m64n8k16.f32.bf16.bf16 {%0,%1,%2,%3}, %4, %5, p, 1, 1, 0, 1;}"
                 : R4(d, 0) : "l"(da), "l"(db));
}
__device__ __forceinline__ void mma_rs(float (&d)[32], const uint4& a, uint64_t db) {
    asm volatile("{.reg .pred p; setp.eq.b32 p, 0, 0; wgmma.mma_async.sync.aligned.m64n64k16.f32.bf16.bf16 " D32 ", {%32,%33,%34,%35}, %36, p, 1, 1, 1;}"
                 : R32(d) : "r"(a.x), "r"(a.y), "r"(a.z), "r"(a.w), "l"(db));
}
__device__ __forceinline__ void mma_rs(float (&d)[48], const uint4& a, uint64_t db) {
    asm volatile("{.reg .pred p; setp.eq.b32 p, 0, 0; wgmma.mma_async.sync.aligned.m64n96k16.f32.bf16.bf16 " D48 ", {%48,%49,%50,%51}, %52, p, 1, 1, 1;}"
                 : R32(d), R8(d, 32), R8(d, 40) : "r"(a.x), "r"(a.y), "r"(a.z), "r"(a.w), "l"(db));
}

constexpr float EXP_MAGIC = 256.0f + 127.0f + 64.0f - 1.58621f + 0.00390625f;
constexpr uint32_t MUFU_MASK = 0x1111u;
__device__ __forceinline__ uint32_t exp2_pair(float y0, float y1, uint32_t cexp, uint32_t neg1) {
    uint32_t w, m, e, r;
    asm("prmt.b32 %0, %1, %2, 0x6521;" : "=r"(w) : "r"(__float_as_uint(y0)), "r"(__float_as_uint(y1)));
    asm("lop3.b32 %0, %1, 0x007F007F, %2, 0xEA;" : "=r"(m) : "r"(w), "r"(cexp));
    asm("mad.lo.u32 %0, %1, %2, %3;" : "=r"(e) : "r"(m), "r"(neg1), "r"(w));
    asm("fma.rn.bf16x2 %0, %1, %2, %3;" : "=r"(r) : "r"(w), "r"(m), "r"(e));
    return r;
}

struct Params {
    const __nv_bfloat16* x;
    const __nv_bfloat16* wk;
    long long wv_off;
    const __nv_bfloat16* wqp;
    __nv_bfloat16* out;
    uint32_t neg1, pad;
    const __nv_bfloat16* w1p;
    const __nv_bfloat16* w2p;
    CUtensorMap wq, wo, w1, w2;
    const __nv_bfloat16* wop;
};

__device__ __forceinline__ int f1_col0() { return ((blockIdx.x & 15) >> 1) * 176 + (blockIdx.x & 1) * 96; }
__device__ __forceinline__ void load_box(uint32_t sb, const CUtensorMap* tm, uint32_t dst, uint32_t bar, uint32_t bytes, int c0, int c1) {
    mbar_expect(sb + SM_MISC + bar * 8, bytes);
    tma2d(sb + dst, tm, c0, c1, sb + SM_MISC + bar * 8);
}
__device__ __forceinline__ void load_wq(uint32_t sb, const Params& P, int gi, int atom) {
    load_box(sb, &P.wq, SM_WQ + atom * 65536 + gi * 16384, MB_WQ + gi, 16384, (blockIdx.x & 3) * 128 + atom * 64, gi * 128);
}
__device__ __forceinline__ void load_wo(uint32_t sb, const Params& P, int kb) { load_box(sb, &P.wo, wo_slot(kb) * 8192, MB_WO + kb, 8192, (blockIdx.x & 7) * 64, kb * 64); }
__device__ __forceinline__ void load_w2(uint32_t sb, const Params& P, int kb, int slot) { load_box(sb, &P.w2, slot * 8192, MB_W2 + kb, 8192, (blockIdx.x & 7) * 64, kb * 64); }
__device__ __forceinline__ void refill_job(uint32_t sb, const Params& P, int gi, int job) {
    const bool w1 = job < 3;
    const int kb = (gi < 3 ? 2 + 2 * gi : 0) + job - 3;
    load_box(sb, w1 ? &P.w1 : gi < 3 ? &P.wo : &P.w2, (w1 ? 8 + gi + 4 * job : 2 * gi + job - 3) * 8192, w1 ? MB_W1 + gi : (gi < 3 ? MB_WO : MB_W2) + kb, 8192,
             w1 ? f1_col0() + job * 32 : (blockIdx.x & 7) * 64, w1 ? gi * 128 : kb * 64);
}
__device__ __forceinline__ void release_w1(uint32_t sb, const Params& P, int gi) {
    if (warp_arrive(sb + SM_MISC + MISC_CNT + gi * 4) == 15) {
        if ((threadIdx.x & 31) == 0) {
#pragma unroll 1
            for (int a = 0; a < 3; a++) load_w2(sb, P, 10 + 3 * gi + a, 8 + gi + 4 * a);
        }
        __syncwarp();
    }
}

__device__ __forceinline__ void load_batch(uint4 (&buf)[4], const uint4* a) {
#pragma unroll
    for (int s = 0; s < 4; s++) buf[s] = ldg_relaxed(a + s * 128);
}
__device__ __forceinline__ bool batch_bad(const uint4 (&buf)[4]) {
    const uint32_t m = max(max(buf[0].x, buf[1].x), max(buf[2].x, buf[3].x));
    return __any_sync(0xffffffffu, m == SENT);
}
__device__ __forceinline__ void check_batch(uint4 (&buf)[4], const uint4* a) {
    if (__builtin_expect(batch_bad(buf), 0)) {
        int spins = 0;
        do load_batch(buf, a); while (batch_bad(buf) && ++spins < SPIN_LIMIT);
    }
}
constexpr int H_KV = 0, H_O = 1 - 16, H_H1 = 17, H_H2 = 49;
__device__ __forceinline__ void hint_arrive(int id) {
    if ((threadIdx.x & 31) == 0) asm volatile("red.relaxed.gpu.global.add.u32 [%0], 1;" :: "l"(g_s.hint[id]) : "memory");
}
__device__ __forceinline__ void hint_wait(int id, unsigned target) {
    uint32_t v; int spins = 0;
    do { asm volatile("ld.relaxed.gpu.global.u32 %0, [%1];" : "=r"(v) : "l"(g_s.hint[id]) : "memory"); } while (__any_sync(0xffffffffu, v != target) && ++spins < SPIN_LIMIT);
}

template <int KIND, int NBLK, int RING, int NACC>
__device__ __forceinline__ void gemm_rs(float (&acc)[NACC], uint4 (&buf)[RING][4], const uint4* a, uint32_t sb, int q, const Params& P) {
    constexpr int ASTR = (KIND == 1) ? 512 : 1024;
    const uint32_t mb = sb + SM_MISC;
#pragma unroll
    for (int i = 0; i < NACC; i++) acc[i] = 0.f;
    fence_regs(acc);
#pragma unroll
    for (int i = 0; i < NBLK; i++) {
        uint64_t db;
        if (KIND == 1) {
            db = mkdesc(sb + (8 + (i >> 1)) * 8192 + (i & 1) * 4096, 32768, 512, 2);
            if ((i & 1) == 0) mbar_wait(mb + (MB_W1 + (i >> 1)) * 8);
        } else {
            const uint32_t slot = KIND == 0 ? (q ? wo_slot(2 * i + 1) : wo_slot(2 * i)) : (q ? w2_slot(2 * i + 1) : w2_slot(2 * i));
            db = mkdesc(sb + slot * 8192, 16, 1024, 1);
            mbar_wait(mb + ((KIND == 0 ? MB_WO : MB_W2) + 2 * i + q) * 8);
        }
        check_batch(buf[i % RING], a + i * ASTR);
        wg_fence();
#pragma unroll
        for (int s = 0; s < 4; s++) mma_rs(acc, buf[i % RING][s], db + s * (KIND == 1 ? 64 : 128));
        wg_commit();
        const bool rel = KIND == 1 && i >= 2 && !(i & 1);
        if (i >= 1 && (i - 1 + RING < NBLK || rel)) {
            wg_wait<1>();
            if (i - 1 + RING < NBLK) load_batch(buf[(i - 1) % RING], a + (i - 1 + RING) * ASTR);
            if (rel) release_w1(sb, P, (i >> 1) - 1);
        }
    }
    wg_wait<0>();
    fence_regs(acc);
}

__device__ __forceinline__ void pair_reduce(const float (&acc)[32], float (&r)[16], uint32_t buf, int q, int barid) {
    if (q) {
#pragma unroll
        for (int j = 0; j < 4; j++) sts128(buf + j * 2048, __float_as_uint(acc[4 * j]), __float_as_uint(acc[4 * j + 1]), __float_as_uint(acc[4 * j + 2]), __float_as_uint(acc[4 * j + 3]));
        bar_sync(barid, 256);
        bar_sync(barid, 256);
#pragma unroll
        for (int j = 0; j < 4; j++) {
            float4 v = lds128f(buf + j * 2048);
            r[4 * j] = acc[16 + 4 * j] + v.x; r[4 * j + 1] = acc[17 + 4 * j] + v.y; r[4 * j + 2] = acc[18 + 4 * j] + v.z; r[4 * j + 3] = acc[19 + 4 * j] + v.w;
        }
    } else {
        bar_sync(barid, 256);
        float4 v[4];
#pragma unroll
        for (int j = 0; j < 4; j++) v[j] = lds128f(buf + j * 2048);
#pragma unroll
        for (int j = 0; j < 4; j++) sts128(buf + j * 2048, __float_as_uint(acc[16 + 4 * j]), __float_as_uint(acc[17 + 4 * j]), __float_as_uint(acc[18 + 4 * j]), __float_as_uint(acc[19 + 4 * j]));
        bar_arrive(barid, 256);
#pragma unroll
        for (int j = 0; j < 4; j++) {
            r[4 * j] = acc[4 * j] + v[j].x; r[4 * j + 1] = acc[4 * j + 1] + v[j].y; r[4 * j + 2] = acc[4 * j + 2] + v[j].z; r[4 * j + 3] = acc[4 * j + 3] + v[j].w;
        }
    }
}

__device__ __forceinline__ float quad_sum(float v) { v += __shfl_xor_sync(0xffffffffu, v, 1); v += __shfl_xor_sync(0xffffffffu, v, 2); return v; }
__device__ __forceinline__ float reduce4(const float (&st)[4], int lane) {
    const bool u16 = lane & 16, u8 = lane & 8;
    const float a0 = (u16 ? st[2] : st[0]) + __shfl_xor_sync(0xffffffffu, u16 ? st[0] : st[2], 16);
    const float a1 = (u16 ? st[3] : st[1]) + __shfl_xor_sync(0xffffffffu, u16 ? st[1] : st[3], 16);
    float v = (u8 ? a1 : a0) + __shfl_xor_sync(0xffffffffu, u8 ? a0 : a1, 8);
    v += __shfl_xor_sync(0xffffffffu, v, 4); v += __shfl_xor_sync(0xffffffffu, v, 2); v += __shfl_xor_sync(0xffffffffu, v, 1);
    return v;
}
__device__ __forceinline__ float silu2(float h) { float t; asm("tanh.approx.f32 %0, %1;" : "=f"(t) : "f"(h)); return fmaf(h, t, h); }

#define TS_ARG
#define TS_PASS

template <bool SAFE>
__device__ __forceinline__ void attention(const Params& P, uint32_t sb, int warp TS_ARG) {
    const uint32_t mb = sb + SM_MISC;
    const int tid = threadIdx.x, lane = tid & 31, b = blockIdx.x;
    const int wg = warp >> 2, ww = warp & 3, job = 3 - wg + 4 * ww;
    const uint32_t cexp = 0x9F809F80u + (tid >> 12);
    const uint32_t neg1 = P.neg1;
    unsigned cnt = 0;
    if (SAFE && warp == 8) asm volatile("ld.relaxed.gpu.global.u32 %0, [%1];" : "=r"(cnt) : "l"(&g_s.count1) : "memory");
#pragma unroll 1
    for (int pass = 0; pass < 2; pass++) {
    float o[12], s[32];
    const uint64_t dq = mkdesc(sb + SM_Q + (pass * 4 + wg) * 2048, 128, 256, 0);
    uint64_t dk = mkdesc(sb + SM_K, 128, 256, 0), dv = mkdesc(sb + SM_V, 128, 32768, 0);
    float m0 = -INFINITY, m1 = -INFINITY;
#pragma unroll
    for (int i = 0; i < 12; i++) o[i] = 0.f;
#pragma unroll
    for (int i = 0; i < 32; i++) s[i] = ((MUFU_MASK >> (i / 2)) & 1) ? 0.f : EXP_MAGIC;
    fence_regs(s); fence_regs(o);
    wg_fence();
    if (SAFE) mma_qk_f16(s, dq, dk + 31 * 128); else mma_qk_bf16(s, dq, dk + 31 * 128);
    wg_commit();
    wg_wait<0>(); fence_regs(s);
#pragma unroll 1
    for (int u = pass ? 3 : (wg == 2) ? 0 : 1; u < (pass ? 8 : 3); u++) {
        int n = 2 * ((((wg == 2) ? 0x22444C31u : 0x22444C40u) >> (4 * u)) & 15);
#pragma unroll 1
        do {
            uint32_t p[16];
            if (SAFE) {
#pragma unroll
                for (int j = 0; j < 16; j++) {
                    if ((MUFU_MASK >> j) & 1) p[j] = pack_bf16(ex2(s[2 * j]), ex2(s[2 * j + 1]));
                    else p[j] = exp2_pair(s[2 * j], s[2 * j + 1], cexp, neg1);
                }
            } else {
                fence_regs(o);
                float x0 = m0, x1 = m1;
#pragma unroll
                for (int j = 0; j < 8; j++) { x0 = fmaxf(x0, fmaxf(s[4 * j], s[4 * j + 1])); x1 = fmaxf(x1, fmaxf(s[4 * j + 2], s[4 * j + 3])); }
                x0 = fmaxf(x0, __shfl_xor_sync(0xffffffffu, x0, 1)); x0 = fmaxf(x0, __shfl_xor_sync(0xffffffffu, x0, 2));
                x1 = fmaxf(x1, __shfl_xor_sync(0xffffffffu, x1, 1)); x1 = fmaxf(x1, __shfl_xor_sync(0xffffffffu, x1, 2));
                const float c0 = ex2(m0 - x0), c1 = ex2(m1 - x1);
                m0 = x0; m1 = x1;
#pragma unroll
                for (int j = 0; j < 3; j++) { o[4 * j] *= c0; o[4 * j + 1] *= c0; o[4 * j + 2] *= c1; o[4 * j + 3] *= c1; }
#pragma unroll
                for (int j = 0; j < 8; j++) {
                    p[2 * j] = pack_bf16(ex2(s[4 * j] - m0), ex2(s[4 * j + 1] - m0));
                    p[2 * j + 1] = pack_bf16(ex2(s[4 * j + 2] - m1), ex2(s[4 * j + 3] - m1));
                }
                fence_regs(o);
            }
            fence_regs(p);
            wg_fence();
            if (SAFE) mma_qk_f16(s, dq, dk); else mma_qk_bf16(s, dq, dk);
#pragma unroll
            for (int j = 0; j < 4; j++) mma_pv(o, p + 4 * j, dv + j * 16);
            wg_commit();
            dk += 128; dv += 64;
            wg_wait<0>(); fence_regs(s);
        } while (--n > 0);
        if (u == 2 || u == 7) {
            fence_regs(o);
            const float i0 = rcp(o[8]), i1 = rcp(o[10]);
            if (u == 7) mbar_wait(mb + MB_F2 * 8);
            stg128(g_x + X_OF + (((u == 7) * 16 + (b >> 3)) * 32 + (b & 3) * 8 + 2 * wg + (ww >> 1)) * 128 + (((b >> 2) & 1) * 2 + (ww & 1)) * 32 + lane,
                   pack_bf16(o[0] * i0, o[1] * i0), pack_bf16(o[2] * i1, o[3] * i1), pack_bf16(o[4] * i0, o[5] * i0), pack_bf16(o[6] * i1, o[7] * i1));
            if (u == 2) asm volatile("cp.async.bulk.wait_group 0;" ::: "memory");
            else hint_arrive(H_O + 16 + (b >> 3));
            warp_done(mb + (MB_DONE + (u == 7) * 4) * 8);
            TS(5 + (u == 7));
        } else if (u >= 3) {
            if (u < 6) warp_done(mb + (MB_DONE + u - 2) * 8);
            if (job < (u == 3 ? 2 : 5)) {
                mbar_wait(mb + (MB_DONE + u - 3) * 8);
                if (lane == 0) {
                    if (u > 3) refill_job(sb, P, u - 4, job);
                    else if (job == 1) load_wo(sb, P, 1);
                    else asm volatile("red.release.gpu.global.add.u32 [%0], 1;" :: "l"(&g_s.count2) : "memory");
                }
            } else if (warp == 11) {
                if (u == 5) asm volatile("ld.relaxed.gpu.global.u32 %0, [%1];" : "=r"(cnt) : "l"(&g_s.count2) : "memory");
                if (u == 6) {
                    const unsigned target = lds32(mb + MISC_EPOCH) * NCTA;
                    if (__any_sync(0xffffffffu, cnt != target)) wait_count(&g_s.count2, target);
                    asm volatile("fence.acquire.gpu;" ::: "memory");
                    warp_done(mb + MB_F2 * 8);
                }
            }
        } else if (u == 1) {
            if (SAFE) mbar_wait(mb + MB_KV * 8);
            TS(17);
    if (lane == 0) {
        if (job < 9) {
            asm volatile("cp.async.bulk.global.shared::cta.bulk_group [%0], [%1], %2;"
                         :: "l"(g_x + X_ARM + b * X_SHARE + job * 512), "r"(sb + SM_SENT), "r"(job < 8 ? 8192 : (X_SHARE - 4096) * 16) : "memory");
            asm volatile("cp.async.bulk.commit_group;" ::: "memory");
        } else if (job == 9) load_wo(sb, P, 0);
    }
        } else if (SAFE) {
            if (warp == 8) {
                const unsigned target = lds32(mb + MISC_EPOCH) * NMAIN;
                if (__any_sync(0xffffffffu, cnt != target)) wait_count(&g_s.count1, target);
                if (lane == 0) {
                    asm volatile("fence.acquire.gpu; fence.proxy.async.global;" ::: "memory");
                    mbar_expect(mb + MB_KV * 8, 47104 + 2 * 24576);
                    bulk_g2s(sb + SM_K + 16384, g_s.kv + 1024, 47104, mb + MB_KV * 8);
                    bulk_g2s(sb + SM_V + 8192, g_s.kv + 4096 + 512, 24576, mb + MB_KV * 8);
                    bulk_g2s(sb + SM_V + 32768 + 8192, g_s.kv + 6144 + 512, 24576, mb + MB_KV * 8);
                }
            }
        }
        __syncwarp();
    }
    }
}

__device__ __noinline__ void helper_cta(const Params& P, uint8_t* smem) {
    const int tid = threadIdx.x, b = blockIdx.x, hi = b - NMAIN;
    const unsigned epoch = g_s.epoch[b] + 1;
    float* red = reinterpret_cast<float*>(smem);
    if (tid < 32) wait_count(&g_s.count1, epoch * NMAIN);
    __syncthreads();
    if (tid == 480) {
        for (int i = 0; i < 8; i++) asm volatile("cp.async.bulk.prefetch.L2.global [%0], %1;" :: "l"((const char*)P.wop + hi * 131072 + i * 16384), "r"(16384) : "memory");
        for (int i = 0; i < 43; i++) asm volatile("cp.async.bulk.prefetch.L2.global [%0], %1;" :: "l"((const char*)P.w2p + hi * 352256 + i * 8192), "r"(8192) : "memory");
    }
    if (tid < 344) {
        const int cg = tid % 43, rp = tid / 43;
        const uint4* src = reinterpret_cast<const uint4*>(P.w1p + (size_t)rp * 64 * FF + (hi * 43 + cg) * 8);
        float s[8] = {0, 0, 0, 0, 0, 0, 0, 0};
#pragma unroll 8
        for (int r = 0; r < 64; r++) {
            uint4 v = __ldg(src + r * (FF / 8));
            s[0] += bf_lo(v.x); s[1] += bf_hi(v.x); s[2] += bf_lo(v.y); s[3] += bf_hi(v.y);
            s[4] += bf_lo(v.z); s[5] += bf_hi(v.z); s[6] += bf_lo(v.w); s[7] += bf_hi(v.w);
        }
        float* part = red + (rp * 43 + cg) * 8;
#pragma unroll
        for (int i = 0; i < 8; i++) part[i] = s[i];
    }
    __syncthreads();
    if (tid < 344) {
        float s = 0.f;
#pragma unroll
        for (int rp = 0; rp < 8; rp++) s += red[rp * 344 + tid];
        g_s.cs[hi * 344 + tid] = s;
    } else if (hi == 3 && tid < 344 + 64) g_s.cs[FF + tid - 344] = 0.f;
    __syncthreads();
    if (tid == 0) {
        asm volatile("red.release.gpu.global.add.u32 [%0], 1;" :: "l"(&g_s.count2) : "memory");
        g_s.epoch[b] = epoch;
    }
}

__global__ void __launch_bounds__(512, 1) fused_kernel(const __grid_constant__ Params P) {
    extern __shared__ __align__(1024) uint8_t smem[];
    const uint32_t sb = (uint32_t)__cvta_generic_to_shared(smem);
    const uint32_t mb = sb + SM_MISC;
    const int tid = threadIdx.x, lane = tid & 31, b = blockIdx.x;
    if (b >= NMAIN) { helper_cta(P, smem); return; }
    const int tg = b >> 2, hg = b & 3;
    const int warp = __shfl_sync(0xffffffffu, tid >> 5, 0);

    uint4 xv[4][2];
    unsigned epoch = 0;
    {
        const int r = (tid >> 5) * 4;
        const uint4* src = reinterpret_cast<const uint4*>(P.x + (size_t)((r & 31) + tg * 32 + (r >> 5) * 1024) * D) + lane;
#pragma unroll
        for (int i = 0; i < 4; i++) { xv[i][0] = ldg_relaxed(src + i * 64); xv[i][1] = ldg_relaxed(src + i * 64 + 32); }
    }
    const uint4 wkv = ldg_relaxed(reinterpret_cast<const uint4*>(reinterpret_cast<const char*>(P.wk) + (hg < 2 ? 0 : P.wv_off)) + tid * 2 + (hg & 1));
    const int wg = warp >> 2, ww = warp & 3, g = lane >> 2, t4 = lane & 3, t128 = tid & 127;
    if (lane == 0) {
        mbar_init(mb + warp * 8, warp < 4 ? 2 : warp < 8 ? 3 : warp < 14 ? 16 : 1);
        mbar_init(mb + (16 + warp) * 8, 1);
        mbar_init(mb + (32 + warp) * 8, 1);
        if (warp < 4) {
            asm volatile("fence.mbarrier_init.release.cluster;" ::: "memory");
            load_wq(sb, P, warp, 0);
            if (warp < 3) load_wq(sb, P, warp, 1);
        } else if (warp < 7) {
            asm volatile("prefetch.tensormap [%0];" :: "l"(&P.wo + (warp - 4)) : "memory");
        } else if (warp == 7) {
            asm volatile("ld.relaxed.gpu.global.u32 %0, [%1];" : "=r"(epoch) : "l"(g_s.epoch + b) : "memory");
        } else if (warp < 10) {
            sts128(mb + MISC_CNT + (warp - 8) * 16, 0, 0, 0, 0);
        }
    }
    __syncwarp();
    TS(16);
    float dlt;
    {
        float st[4];
#pragma unroll
        for (int i = 0; i < 4; i++) {
            const uint32_t s = add_bf16x2(add_bf16x2(add_bf16x2(xv[i][0].x, xv[i][0].y), add_bf16x2(xv[i][0].z, xv[i][0].w)),
                                          add_bf16x2(add_bf16x2(xv[i][1].x, xv[i][1].y), add_bf16x2(xv[i][1].z, xv[i][1].w)));
            st[i] = bf_lo(s) + bf_hi(s);
        }
        TS(13);
        const float tot = reduce4(st, lane) * (-1.0f / D);
        const uint32_t nmr = pack_bf16(tot, tot);
        dlt = bf_lo(nmr) - tot;
        const uint32_t xa = sb + SM_XN + (lane >> 3) * 8192 + warp * 512;
#pragma unroll
        for (int i = 0; i < 4; i++) {
            const uint32_t nm = __shfl_sync(0xffffffffu, nmr, i * 8);
            const uint32_t addr = xa + i * 128 + (((lane & 7) ^ ((warp & 1) * 4 + i)) << 4);
#pragma unroll
            for (int c = 0; c < 2; c++) {
                xv[i][c].x = add_bf16x2(xv[i][c].x, nm); xv[i][c].y = add_bf16x2(xv[i][c].y, nm);
                xv[i][c].z = add_bf16x2(xv[i][c].z, nm); xv[i][c].w = add_bf16x2(xv[i][c].w, nm);
                sts128(addr + c * 32768, xv[i][c].x, xv[i][c].y, xv[i][c].z, xv[i][c].w);
            }
        }
    }
    sts128(sb + SM_WKV + tid * 16, wkv.x, wkv.y, wkv.z, wkv.w);
    fence_async_smem();
    TS(0);
    __syncthreads();
    auto variances = [&]() {
        float st[4];
#pragma unroll
        for (int i = 0; i < 4; i++) {
            float v = 0.f;
#pragma unroll
            for (int c = 0; c < 2; c++) {
                const uint32_t a = fma_bf16x2(xv[i][c].x, xv[i][c].x, mul_bf16x2(xv[i][c].y, xv[i][c].y));
                const uint32_t d = fma_bf16x2(xv[i][c].z, xv[i][c].z, mul_bf16x2(xv[i][c].w, xv[i][c].w));
                v += (bf_lo(a) + bf_hi(a)) + (bf_lo(d) + bf_hi(d));
            }
            st[i] = v;
        }
        const float vs = reduce4(st, lane), dl = dlt;
        if ((lane & 7) == 0) sts32(mb + MISC_RSTD + (warp * 4 + (lane >> 3)) * 4, __float_as_uint(rsqrtf(fmaxf(vs * (1.0f / D) - dl * dl, 0.f) + 1e-5f)));
    };
    float kv[4] = {0.f, 0.f, 0.f, 0.f};
    if (wg == 2) {
        fence_regs(kv);
        const uint64_t da = mkdesc(sb + SM_XN, 16, 1024, 1), db = mkdesc(sb + SM_WKV, 128, 16, 0);
        wg_fence();
#pragma unroll
        for (int s = 0; s < 32; s++) mma_ss8(kv, da + (s >> 2) * 512 + (s & 3) * 2, db + s * 16);
        wg_commit();
        TS(18);
        variances();
        wg_wait<0>(); fence_regs(kv);
        TS(20);
    } else {
        variances();
        if (tid == 7 * 32) { sts32(mb + MISC_EPOCH, epoch + 1); g_s.epoch[b] = epoch + 1; }
        TS(19);
    }
    __syncthreads();
    constexpr float QSCALE = 0.25f * 1.4426950408889634f;
    int kvoff;
    {
        const int t = (t128 & 63) >> 1, c = 2 * tg + (t128 & 1);
        kvoff = hg < 2 ? ((t + 31) & 31) * 128 + (c >> 3) * 16 + (hg & 1) * 8 + (c & 7) : 4096 + (hg & 1) * 2048 + t * 64 + c;
    }
    float qa[64];
    const uint32_t qbase = sb + SM_Q + (ww >> 1) * 8192 + (ww & 1) * 512 + lane * 16;
    if (wg == 0) {
#pragma unroll
        for (int i = 0; i < 64; i++) qa[i] = 0.f;
        fence_regs(qa);
        const uint64_t da = mkdesc(sb + SM_XN, 16, 1024, 1), db = mkdesc(sb + SM_WQ, 65536, 1024, 1);
#pragma unroll 1
        for (int i = 0; i < 4; i++) {
            mbar_wait(mb + (MB_WQ + i) * 8);
            if (i == 0) TS(21); if (i == 3) TS(22);
            wg_fence();
#pragma unroll
            for (int s = 0; s < 8; s++) mma_ss128(qa, da + (i * 2 + (s >> 2)) * 512 + (s & 3) * 2, db + (i * 8 + s) * 128);
            wg_commit();
        }
        const float rs0 = __uint_as_float(lds32(mb + MISC_RSTD + (ww * 16 + g) * 4)) * QSCALE, rs1 = __uint_as_float(lds32(mb + MISC_RSTD + (ww * 16 + g + 8) * 4)) * QSCALE;
        wg_wait<0>();
        fence_regs(qa);
        bar_arrive(6, 256);
        bar_sync(5, 256);
        TS(1);
        uint32_t nm = 0;
#pragma unroll
        for (int h = 0; h < 8; h++) {
#pragma unroll
            for (int i = 0; i < 8; i++) qa[8 * h + i] *= (i & 2) ? rs1 : rs0;
            stsm4(qbase + h * 1024, pack_f16(qa[8 * h], qa[8 * h + 1]), pack_f16(qa[8 * h + 4], qa[8 * h + 5]), pack_f16(qa[8 * h + 2], qa[8 * h + 3]), pack_f16(qa[8 * h + 6], qa[8 * h + 7]));
            const float n0 = qa[8 * h] * qa[8 * h] + qa[8 * h + 1] * qa[8 * h + 1] + qa[8 * h + 4] * qa[8 * h + 4] + qa[8 * h + 5] * qa[8 * h + 5];
            const float n1 = qa[8 * h + 2] * qa[8 * h + 2] + qa[8 * h + 3] * qa[8 * h + 3] + qa[8 * h + 6] * qa[8 * h + 6] + qa[8 * h + 7] * qa[8 * h + 7];
            nm = max(nm, max(__float_as_uint(n0), __float_as_uint(n1)));
        }
        nm = __reduce_max_sync(0xffffffffu, __float_as_uint(quad_sum(__uint_as_float(nm))));
        if (lane == 0) asm volatile("red.shared.max.u32 [%0], %1;" :: "r"(mb + MISC_NRM), "r"(nm) : "memory");
    } else if (wg == 1) {
        bar_sync(5, 256);
#pragma unroll
        for (int i = 0; i < 16; i++) sts128(sb + SM_V + 65536 + (i * 128 + t128) * 16, 0x3F803F80u, 0x3F803F80u, 0x3F803F80u, 0x3F803F80u);
#pragma unroll
        for (int i = 0; i < 4; i++) sts128(sb + SM_SENT + (i * 128 + t128) * 16, SENT, SENT, SENT, SENT);
    } else if (wg == 2) {
        const float rs0 = __uint_as_float(lds32(mb + MISC_RSTD + (ww * 16 + g) * 4)), rs1 = __uint_as_float(lds32(mb + MISC_RSTD + (ww * 16 + g + 8) * 4));
        kv[0] *= rs0; kv[1] *= rs0; kv[2] *= rs1; kv[3] *= rs1;
        float2* kt = reinterpret_cast<float2*>(smem + SM_MISC + MISC_KTMP);
        kt[(ww * 16 + g) * 4 + t4] = make_float2(kv[0], kv[1]); kt[(ww * 16 + g + 8) * 4 + t4] = make_float2(kv[2], kv[3]);
        float n0 = kv[0] * kv[0] + kv[1] * kv[1], n1 = kv[2] * kv[2] + kv[3] * kv[3];
        n0 += __shfl_xor_sync(0xffffffffu, n0, 1); n1 += __shfl_xor_sync(0xffffffffu, n1, 1);
        n0 += __shfl_xor_sync(0xffffffffu, n0, 2); n1 += __shfl_xor_sync(0xffffffffu, n1, 2);
        const uint32_t nm = __reduce_max_sync(0xffffffffu, max(__float_as_uint(n0), __float_as_uint(n1)));
        if (lane == 0) sts32(mb + MISC_WNRM + ww * 4, nm | 1u);
        bar_sync(2, 128);
        const uint32_t ra = mb + MISC_KTMP + ((t128 & 1) * 32 + ((t128 & 63) >> 1)) * 32;
        const float4 c0 = lds128f(ra), c1 = lds128f(ra + 16);
        if (ww < 2) {
            if (hg < 2) {
                float4 p0 = lds128f(ra - 32), p1 = lds128f(ra - 16);
                if (t128 < 2) { p0 = make_float4(0.f, 0.f, 0.f, 0.f); p1 = p0; }
                stg128(g_s.kv + kvoff, nonzero(pack_f16(c0.x - p0.x, c0.y - p0.y)), pack_f16(c0.z - p0.z, c0.w - p0.w), pack_f16(c1.x - p1.x, c1.y - p1.y), pack_f16(c1.z - p1.z, c1.w - p1.w));
            } else {
                stg128(g_s.kv + kvoff, nonzero(pack_bf16(c0.x, c0.y)), pack_bf16(c0.z, c0.w), pack_bf16(c1.x, c1.y), pack_bf16(c1.z, c1.w));
            }
            if (t128 < 2) { const float4 w = lds128f(mb + MISC_WNRM); stg128(g_s.nrm + b * 2 + t128, __float_as_uint(w.x), __float_as_uint(w.y), __float_as_uint(w.z), __float_as_uint(w.w)); }
            hint_arrive(H_KV);
        } else if (hg < 2) {
            stg128(g_s.kplain + kvoff, pack_bf16(c0.x, c0.y), pack_bf16(c0.z, c0.w), pack_bf16(c1.x, c1.y), pack_bf16(c1.z, c1.w));
        }
        TS(1);
        bar_sync(2, 128);
        if (t128 == 96) asm volatile("red.release.gpu.global.add.u32 [%0], 1;" :: "l"(&g_s.count1) : "memory");
        __syncwarp();
    } else {
        if (tid == 13 * 32) load_wq(sb, P, 3, 1);
        __syncwarp();
        uint4 kc[18];
        auto src = [&](int i) { return i < 8 ? g_s.kv + i * 128 : i < 12 ? g_s.kv + 4096 + (i - 8) * 128 : i < 16 ? g_s.kv + 6144 + (i - 12) * 128 : i == 16 ? g_s.kv + 31 * 128 : g_s.nrm + t128; };
        hint_wait(H_KV, lds32(mb + MISC_EPOCH) * (NMAIN * 2));
        TS(1);
        int spins = 0;
        while (true) {
#pragma unroll
            for (int i = 0; i < 18; i++) kc[i] = ldg_relaxed(src(i) + t128);
            uint32_t mn = 1;
#pragma unroll
            for (int i = 0; i < 18; i++) mn = min(mn, kc[i].x);
            if (!__any_sync(0xffffffffu, mn == 0u) || ++spins >= SPIN_LIMIT) break;
        }
        uint32_t nm = max(max(kc[17].x, kc[17].y), max(kc[17].z, kc[17].w));
        nm = max(nm, __shfl_xor_sync(0xffffffffu, nm, 4)); nm = max(nm, __shfl_xor_sync(0xffffffffu, nm, 8)); nm = max(nm, __shfl_xor_sync(0xffffffffu, nm, 16));
        if (lane < 4) asm volatile("red.shared.max.u32 [%0], %1;" :: "r"(mb + MISC_NRM + 4 + min(lane, 2) * 4), "r"(nm) : "memory");
        TS(2);
        bar_sync(6, 256);
#pragma unroll
        for (int i = 0; i < 17; i++) sts128(sb + (uint32_t)(src(i) - g_s.kv + t128) * 16, kc[i].x, kc[i].y, kc[i].z, kc[i].w);
    }
    fence_async_smem();
    TS(3);
    __syncthreads();
    const float4 nr = lds128f(mb + MISC_NRM);
    const bool safe = __all_sync(0xffffffffu, (nr.x * (nr.y + nr.z) <= 3500.0f) && (nr.x <= 65536.0f) && (nr.y + nr.z <= 65536.0f) && (nr.w <= 1e24f));
    TS(4);

    if (__builtin_expect(safe, 1)) {
        attention<true>(P, sb, warp TS_PASS);
    } else {
        if (wg == 0) {
#pragma unroll
            for (int h = 0; h < 8; h++)
                stsm4(qbase + h * 1024, pack_bf16(qa[8 * h], qa[8 * h + 1]), pack_bf16(qa[8 * h + 4], qa[8 * h + 5]), pack_bf16(qa[8 * h + 2], qa[8 * h + 3]), pack_bf16(qa[8 * h + 6], qa[8 * h + 7]));
            fence_async_smem();
        } else if (warp == 15) {
            wait_count(&g_s.count1, lds32(mb + MISC_EPOCH) * NMAIN);
            if (lane == 0) {
                asm volatile("fence.proxy.async;" ::: "memory");
                mbar_expect(mb + MB_KV * 8, 131072);
                bulk_g2s(sb + SM_K, g_s.kplain, 65536, mb + MB_KV * 8);
                bulk_g2s(sb + SM_V, g_s.kv + 4096, 65536, mb + MB_KV * 8);
            }
            __syncwarp();
        }
        __syncthreads();
        mbar_wait(mb + MB_KV * 8);
        attention<false>(P, sb, warp TS_PASS);
    }

    const int pr = 1 - (wg >> 1), q = wg & 1;
    const int mt = 16 * pr + (b >> 3), j = b & 7;
    const int row0 = mt * 64 + ww * 16 + g;
    const uint32_t xbuf = sb + SM_Q + pr * 8192 + t128 * 16;
    uint32_t hk[8];
    epoch = lds32(mb + MISC_EPOCH);
    {
        const uint4* a = g_x + X_OF + (mt * 32 + q * 4) * 128 + t128;
        if (pr) {
            if (warp < 5) {
                mbar_wait(mb + (MB_DONE + 4) * 8);
                if (lane == 0) refill_job(sb, P, 3, warp);
            } else if (warp == 5) {
                if (lane < 24) {
                    const uint4 v = ldg_relaxed(reinterpret_cast<const uint4*>(g_s.cs + f1_col0()) + lane);
                    sts128(mb + MISC_CS + lane * 16, v.x, v.y, v.z, v.w);
                }
                warp_done(mb + MB_CS * 8);
            }
            __syncwarp();
            hint_wait(H_O + mt, epoch * 128);
        }
        uint4 buf[4][4];
#pragma unroll
        for (int i = 0; i < 4; i++) load_batch(buf[i], a + i * 1024);
        const uint32_t* xp = reinterpret_cast<const uint32_t*>(P.x + (size_t)row0 * D + j * 64 + q * 32 + t4 * 2);
#pragma unroll
        for (int i = 0; i < 4; i++) { hk[2 * i] = __ldg(xp + i * 4); hk[2 * i + 1] = __ldg(xp + i * 4 + 8 * (D / 2)); }
        TS(23);
        float acc[32], r[16];
        gemm_rs<0, 4, 4>(acc, buf, a, sb, q, P);
        TS(7);
        warp_done(mb + (MB_DONE + 5) * 8);
        mbar_wait(mb + (MB_DONE + 4 * pr) * 8);
        pair_reduce(acc, r, xbuf, q, 3 + pr);
#pragma unroll
        for (int i = 0; i < 8; i++) hk[i] = pack_bf16(r[2 * i] + bf_lo(hk[i]), r[2 * i + 1] + bf_hi(hk[i]));
        float s0 = 0.f, s1 = 0.f;
#pragma unroll
        for (int i = 0; i < 8; i++) {
            r[2 * i] = bf_lo(hk[i]); r[2 * i + 1] = bf_hi(hk[i]);
            if (i & 1) s1 += r[2 * i] + r[2 * i + 1]; else s0 += r[2 * i] + r[2 * i + 1];
        }
        s0 += __shfl_xor_sync(0xffffffffu, s0, 1); s1 += __shfl_xor_sync(0xffffffffu, s1, 1);
        s0 += __shfl_xor_sync(0xffffffffu, s0, 2); s1 += __shfl_xor_sync(0xffffffffu, s1, 2);
        const float a0 = s0 * (1.0f / 32), a1 = s1 * (1.0f / 32);
        float v0 = 0.f, v1 = 0.f;
#pragma unroll
        for (int i = 0; i < 8; i++) {
            const float am = (i & 1) ? a1 : a0;
            const float d0 = r[2 * i] - am, d1 = r[2 * i + 1] - am;
            if (i & 1) v1 += d0 * d0 + d1 * d1; else v0 += d0 * d0 + d1 * d1;
        }
        v0 += __shfl_xor_sync(0xffffffffu, v0, 1); v1 += __shfl_xor_sync(0xffffffffu, v1, 1);
        v0 += __shfl_xor_sync(0xffffffffu, v0, 2); v1 += __shfl_xor_sync(0xffffffffu, v1, 2);
        uint4* hp = g_x + X_HF + (mt * 32 + j * 4 + 2 * q) * 128 + t128;
        stg128(hp, hk[0], hk[1], hk[2], hk[3]);
        stg128(hp + 128, hk[4], hk[5], hk[6], hk[7]);
        if (t4 == 0) stg128(g_x + X_ST + (mt * 16 + j * 2 + q) * 32 + ww * 8 + g, __float_as_uint(s0), __float_as_uint(v0), __float_as_uint(s1), __float_as_uint(v1));
        hint_arrive(H_H1 + mt);
        TS(8);
        if (pr) {
            mbar_wait(mb + (MB_DONE + 5) * 8);
            if (lane == 0) load_w2(sb, P, 2 + warp, warp < 2 ? 22 + warp : warp - 2);
            __syncwarp();
        } else if (warp == 8 || warp == 9) {
            stg128(g_s.kv + kvoff, 0u, 0u, 0u, 0u);
            if (t128 < 2) stg128(g_s.nrm + b * 2 + t128, 0u, 0u, 0u, 0u);
        }
    }
    {
        const int mt1 = 16 * pr + (b >> 4) * 2 + q, sl = b & 15;
        const uint4* a = g_x + X_HF + mt1 * 32 * 128 + t128;
        float acc[48], nmean[2], hrstd[2];
        uint4 buf[3][4];
        {
            const uint4* sp = g_x + X_ST + (mt1 * 16 + t4) * 32 + ww * 8 + g;
            hint_wait(H_H1 + mt1, epoch * 64);
            TS(24);
            uint4 u[4];
            load_batch(u, sp);
#pragma unroll
            for (int i = 0; i < 3; i++) load_batch(buf[i], a + i * 512);
            check_batch(u, sp);
            TS(26);
            float mean[2], m2[2];
            mean[0] = (__uint_as_float(u[0].x) + __uint_as_float(u[1].x)) + (__uint_as_float(u[2].x) + __uint_as_float(u[3].x));
            mean[1] = (__uint_as_float(u[0].z) + __uint_as_float(u[1].z)) + (__uint_as_float(u[2].z) + __uint_as_float(u[3].z));
            mean[0] += __shfl_xor_sync(0xffffffffu, mean[0], 1); mean[1] += __shfl_xor_sync(0xffffffffu, mean[1], 1);
            mean[0] += __shfl_xor_sync(0xffffffffu, mean[0], 2); mean[1] += __shfl_xor_sync(0xffffffffu, mean[1], 2);
            mean[0] *= 1.0f / D; mean[1] *= 1.0f / D;
            m2[0] = 0.f; m2[1] = 0.f;
#pragma unroll
            for (int i = 0; i < 4; i++) {
                const float d0 = __uint_as_float(u[i].x) * (1.0f / 32) - mean[0], d1 = __uint_as_float(u[i].z) * (1.0f / 32) - mean[1];
                m2[0] += fmaf(32.0f * d0, d0, __uint_as_float(u[i].y)); m2[1] += fmaf(32.0f * d1, d1, __uint_as_float(u[i].w));
            }
            m2[0] += __shfl_xor_sync(0xffffffffu, m2[0], 1); m2[1] += __shfl_xor_sync(0xffffffffu, m2[1], 1);
            m2[0] += __shfl_xor_sync(0xffffffffu, m2[0], 2); m2[1] += __shfl_xor_sync(0xffffffffu, m2[1], 2);
#pragma unroll
            for (int i = 0; i < 2; i++) { hrstd[i] = 0.5f * rsqrtf(m2[i] * (1.0f / D) + 1e-5f); nmean[i] = -mean[i]; }
        }
        gemm_rs<1, 8, 3>(acc, buf, a, sb, q, P);
        TS(9);
        mbar_wait(mb + MB_CS * 8);
        uint4* hb = g_x + X_H + (mt1 * 88 + (sl >> 1) * 11 + (sl & 1) * 6) * 128 + t128;
#pragma unroll
        for (int k = 0; k < 6; k++) {
            if (k == 5 && (sl & 1)) break;
            uint32_t hv[4];
#pragma unroll
            for (int i = 0; i < 2; i++) {
                float2 cs;
                asm volatile("ld.shared.v2.f32 {%0,%1}, [%2];" : "=f"(cs.x), "=f"(cs.y) : "r"(mb + MISC_CS + (2 * k + i) * 32 + t4 * 8));
                const float* z = acc + 8 * k + 4 * i;
                hv[2 * i] = pack_bf16(silu2(hrstd[0] * fmaf(nmean[0], cs.x, z[0])), silu2(hrstd[0] * fmaf(nmean[0], cs.y, z[1])));
                hv[2 * i + 1] = pack_bf16(silu2(hrstd[1] * fmaf(nmean[1], cs.x, z[2])), silu2(hrstd[1] * fmaf(nmean[1], cs.y, z[3])));
            }
            stg128(hb + k * 128, hv[0], hv[1], hv[2], hv[3]);
        }
        hint_arrive(H_H2 + mt1);
        TS(10);
        release_w1(sb, P, 3);
    }
    {
        const uint4* a = g_x + X_H + (mt * 88 + q * 4) * 128 + t128;
        hint_wait(H_H2 + mt, epoch * 64);
        uint4 buf[4][4];
#pragma unroll
        for (int i = 0; i < 4; i++) load_batch(buf[i], a + i * 1024);
        TS(25);
        float acc[32], r[16];
        gemm_rs<2, 11, 4>(acc, buf, a, sb, q, P);
        TS(11);
        pair_reduce(acc, r, xbuf, q, 3 + pr);
#pragma unroll
        for (int i = 0; i < 8; i++) hk[i] = pack_bf16(r[2 * i] + bf_lo(hk[i]), r[2 * i + 1] + bf_hi(hk[i]));
    }
#pragma unroll
    for (int h = 0; h < 2; h++) {
        uint32_t v0 = hk[h], v1 = hk[2 + h], v2 = hk[4 + h], v3 = hk[6 + h];
        const bool o1 = t4 & 1, o2 = t4 & 2;
        uint32_t a = __shfl_xor_sync(0xffffffffu, o1 ? v0 : v1, 1), c = __shfl_xor_sync(0xffffffffu, o1 ? v2 : v3, 1);
        if (o1) { v0 = a; v2 = c; } else { v1 = a; v3 = c; }
        a = __shfl_xor_sync(0xffffffffu, o2 ? v0 : v2, 2); c = __shfl_xor_sync(0xffffffffu, o2 ? v1 : v3, 2);
        if (o2) { v0 = a; v1 = c; } else { v2 = a; v3 = c; }
        *reinterpret_cast<uint4*>(P.out + (size_t)(row0 + 8 * h) * D + j * 64 + q * 32 + t4 * 8) = make_uint4(v0, v1, v2, v3);
    }
    TS(12);
}

typedef CUresult (*EncodeFn)(CUtensorMap*, CUtensorMapDataType, cuuint32_t, void*, const cuuint64_t*, const cuuint64_t*, const cuuint32_t*,
                             const cuuint32_t*, CUtensorMapInterleave, CUtensorMapSwizzle, CUtensorMapL2promotion, CUtensorMapFloatOOBfill);

void encode2d(EncodeFn fn, CUtensorMap* tm, const void* ptr, int rows, int cols, int box_rows, int box_cols, CUtensorMapSwizzle sw) {
    cuuint64_t dims[2] = {(cuuint64_t)cols, (cuuint64_t)rows};
    cuuint64_t strides[1] = {(cuuint64_t)cols * 2};
    cuuint32_t box[2] = {(cuuint32_t)box_cols, (cuuint32_t)box_rows};
    cuuint32_t es[2] = {1, 1};
    fn(tm, CU_TENSOR_MAP_DATA_TYPE_BFLOAT16, 2, const_cast<void*>(ptr), dims, strides, box, es, CU_TENSOR_MAP_INTERLEAVE_NONE, sw,
       CU_TENSOR_MAP_L2_PROMOTION_L2_128B, CU_TENSOR_MAP_FLOAT_OOB_FILL_NONE);
}

}

extern "C" void kernel_launch(void* const* d_in, const int* in_sizes, int n_in, void* d_out, int out_size) {
    (void)in_sizes; (void)n_in; (void)out_size;
    void* fnp = nullptr;
    cudaDriverEntryPointQueryResult qr;
    cudaGetDriverEntryPoint("cuTensorMapEncodeTiled", &fnp, cudaEnableDefault, &qr);
    EncodeFn fn = (EncodeFn)fnp;
    Params P;
    encode2d(fn, &P.wq, d_in[1], D, D, 128, 64, CU_TENSOR_MAP_SWIZZLE_128B);
    P.wk = (const __nv_bfloat16*)d_in[2];
    P.wv_off = (const char*)d_in[3] - (const char*)d_in[2];
    encode2d(fn, &P.wo, d_in[4], D, D, 64, 64, CU_TENSOR_MAP_SWIZZLE_128B);
    encode2d(fn, &P.w1, d_in[6], D, FF, 128, 32, CU_TENSOR_MAP_SWIZZLE_64B);
    encode2d(fn, &P.w2, d_in[7], FF, D, 64, 64, CU_TENSOR_MAP_SWIZZLE_128B);
    P.x = (const __nv_bfloat16*)d_in[0];
    P.w1p = (const __nv_bfloat16*)d_in[6];
    P.w2p = (const __nv_bfloat16*)d_in[7];
    P.wop = (const __nv_bfloat16*)d_in[4];
    P.wqp = (const __nv_bfloat16*)d_in[1];
    P.out = (__nv_bfloat16*)d_out;
    P.neg1 = 0xFFFFFFFFu; P.pad = 0;
    cudaFuncSetAttribute(fused_kernel, cudaFuncAttributeMaxDynamicSharedMemorySize, SMEM_BYTES);
    fused_kernel<<<NCTA, 512, SMEM_BYTES>>>(P);
}
```

```cpp
#include <cuda_runtime.h>
#include <cuda_bf16.h>
#include <cuda.h>
#include <stdint.h>

namespace {

constexpr int D = 512, FF = 1376;
constexpr int NMAIN = 128, NHELP = 4, NCTA = NMAIN + NHELP;
constexpr uint32_t SENT = 0xFFFFFFFFu;
constexpr int SPIN_LIMIT = 1 << 22;

constexpr uint32_t KB = 1024;
constexpr uint32_t SM_XN = 0;
constexpr uint32_t SM_WQ = 64 * KB;
constexpr uint32_t SM_WKV = 176 * KB;
constexpr uint32_t SM_K = 0;
constexpr uint32_t SM_V = 64 * KB;
constexpr uint32_t SM_Q = 160 * KB;
constexpr uint32_t SM_SENT = 184 * KB;
constexpr uint32_t SM_MISC = 192 * KB;
constexpr uint32_t SMEM_BYTES = 195 * KB;
constexpr uint32_t MB_WQ = 0;
constexpr uint32_t MB_W1 = 4;
constexpr uint32_t MB_DONE = 8;
constexpr uint32_t MB_KV = 14;
constexpr uint32_t MB_WO = 16;
constexpr uint32_t MB_W2 = 24;
constexpr uint32_t MB_F2 = 46;
constexpr uint32_t MB_CS = 47;
constexpr uint32_t MB_REL = 48;
constexpr uint32_t MISC_NRM = 416;
constexpr uint32_t MISC_WNRM = 432;
constexpr uint32_t MISC_EPOCH = 704;
constexpr uint32_t MISC_CS = 1024;
constexpr uint32_t MISC_RSTD = 448;
constexpr uint32_t MISC_KTMP = 1024;

__host__ __device__ constexpr uint32_t wo_slot(int kb) { return kb < 2 ? 22 + kb : kb - 2; }
__host__ __device__ constexpr uint32_t w2_slot(int kb) { return kb < 2 ? 6 + kb : kb < 4 ? 20 + kb : kb < 10 ? kb - 4 : 8 + (kb - 10) / 3 + 4 * ((kb - 10) % 3); }

struct alignas(128) Small {
    unsigned epoch[160];
    unsigned count1, pad1[31];
    unsigned count2, pad2[31];
    unsigned hint[100][32];
    float cs[1440];
    uint4 nrm[NMAIN * 2];
    uint4 kv[8192];
    uint4 kplain[4096];
};
__device__ Small g_s;
constexpr int X_OF = 0, X_HF = 32 * 32 * 128, X_ST = X_HF + 32 * 32 * 128, X_H = X_ST + 32 * 64 * 8, X_END = X_H + 32 * 88 * 128;
constexpr int X_ARM = 16 * 32 * 128, X_SHARE = (X_END - X_ARM) / NMAIN;
__device__ uint4 g_x[X_END];
#define TS(i) do {} while (0)

#define TS_ARG
#define TS_PASS

__device__ __forceinline__ void mbar_init(uint32_t bar, int cnt) { asm volatile("mbarrier.init.shared::cta.b64 [%0], %1;" :: "r"(bar), "r"(cnt) : "memory"); }
__device__ __forceinline__ void mbar_expect(uint32_t bar, uint32_t bytes) { asm volatile("mbarrier.arrive.expect_tx.shared::cta.b64 _, [%0], %1;" :: "r"(bar), "r"(bytes) : "memory"); }
__device__ __forceinline__ void mbar_arrive(uint32_t bar) { asm volatile("mbarrier.arrive.shared::cta.b64 _, [%0];" :: "r"(bar) : "memory"); }
__device__ __forceinline__ void mbar_wait(uint32_t bar) {
    uint32_t done; int spins = 0;
    do {
        asm volatile("{.reg .pred p; mbarrier.try_wait.parity.shared::cta.b64 p, [%1], 0; selp.u32 %0, 1, 0, p;}" : "=r"(done) : "r"(bar) : "memory");
    } while (!__all_sync(0xffffffffu, done) && ++spins < SPIN_LIMIT);
}
__device__ __forceinline__ void tma2d(uint32_t dst, const CUtensorMap* tm, int c0, int c1, uint32_t bar) {
    asm volatile("cp.async.bulk.tensor.2d.shared::cluster.global.mbarrier::complete_tx::bytes [%0], [%1, {%3, %4}], [%2];"
                 :: "r"(dst), "l"(tm), "r"(bar), "r"(c0), "r"(c1) : "memory");
}
__device__ __forceinline__ void bulk_g2s(uint32_t dst, const void* src, uint32_t bytes, uint32_t bar) {
    asm volatile("cp.async.bulk.shared::cluster.global.mbarrier::complete_tx::bytes [%0], [%1], %2, [%3];" :: "r"(dst), "l"(src), "r"(bytes), "r"(bar) : "memory");
}
__device__ __forceinline__ void fence_async_smem() { asm volatile("fence.proxy.async.shared::cta;" ::: "memory"); }
__device__ __forceinline__ void bar_sync(int id, int n) { asm volatile("bar.sync %0, %1;" :: "r"(id), "r"(n) : "memory"); }
__device__ __forceinline__ void bar_arrive(int id, int n) { asm volatile("bar.arrive %0, %1;" :: "r"(id), "r"(n) : "memory"); }
__device__ __forceinline__ void wg_fence() { asm volatile("wgmma.fence.sync.aligned;" ::: "memory"); }
__device__ __forceinline__ void wg_commit() { asm volatile("wgmma.commit_group.sync.aligned;" ::: "memory"); }
template <int N> __device__ __forceinline__ void wg_wait() { asm volatile("wgmma.wait_group.sync.aligned %0;" :: "n"(N) : "memory"); }
template <int N> __device__ __forceinline__ void fence_regs(float (&d)[N]) {
#pragma unroll
    for (int i = 0; i < N; i++) asm volatile("" : "+f"(d[i]) :: "memory");
}
template <int N> __device__ __forceinline__ void fence_regs(uint32_t (&d)[N]) {
#pragma unroll
    for (int i = 0; i < N; i++) asm volatile("" : "+r"(d[i]) :: "memory");
}
__device__ __forceinline__ uint64_t mkdesc(uint32_t addr, uint32_t lbo, uint32_t sbo, uint32_t swz) {
    return (uint64_t)(((addr & 0x3FFFF) >> 4) | ((lbo >> 4) << 16)) | ((uint64_t)((sbo >> 4) | (swz << 30)) << 32);
}
__device__ __forceinline__ float ex2(float x) { float y; asm("ex2.approx.ftz.f32 %0, %1;" : "=f"(y) : "f"(x)); return y; }
__device__ __forceinline__ float rcp(float x) { float y; asm("rcp.approx.ftz.f32 %0, %1;" : "=f"(y) : "f"(x)); return y; }
__device__ __forceinline__ uint32_t pack_bf16(float lo, float hi) { uint32_t r; asm("cvt.rn.bf16x2.f32 %0, %1, %2;" : "=r"(r) : "f"(hi), "f"(lo)); return r; }
__device__ __forceinline__ uint32_t pack_f16(float lo, float hi) { uint32_t r; asm("cvt.rn.f16x2.f32 %0, %1, %2;" : "=r"(r) : "f"(hi), "f"(lo)); return r; }
__device__ __forceinline__ float bf_lo(uint32_t v) { return __uint_as_float(v << 16); }
__device__ __forceinline__ float bf_hi(uint32_t v) { return __uint_as_float(v & 0xFFFF0000u); }
__device__ __forceinline__ uint4 ldg_relaxed(const uint4* p) {
    uint4 v; asm volatile("ld.relaxed.gpu.global.v4.u32 {%0,%1,%2,%3}, [%4];" : "=r"(v.x), "=r"(v.y), "=r"(v.z), "=r"(v.w) : "l"(p) : "memory"); return v;
}
__device__ __forceinline__ void stg128(void* p, uint32_t a, uint32_t b, uint32_t c, uint32_t d) {
    asm volatile("st.relaxed.gpu.global.v4.u32 [%0], {%1,%2,%3,%4};" :: "l"(p), "r"(a), "r"(b), "r"(c), "r"(d) : "memory");
}
__device__ __forceinline__ void stg64(void* p, uint32_t a, uint32_t b) {
    asm volatile("st.relaxed.gpu.global.v2.u32 [%0], {%1,%2};" :: "l"(p), "r"(a), "r"(b) : "memory");
}
__device__ __forceinline__ void sts128(uint32_t a, uint32_t x, uint32_t y, uint32_t z, uint32_t w) {
    asm volatile("st.shared.v4.u32 [%0], {%1,%2,%3,%4};" :: "r"(a), "r"(x), "r"(y), "r"(z), "r"(w) : "memory");
}
__device__ __forceinline__ void sts32(uint32_t a, uint32_t x) { asm volatile("st.shared.u32 [%0], %1;" :: "r"(a), "r"(x) : "memory"); }
__device__ __forceinline__ float4 lds128f(uint32_t a) {
    float4 v; asm volatile("ld.shared.v4.f32 {%0,%1,%2,%3}, [%4];" : "=f"(v.x), "=f"(v.y), "=f"(v.z), "=f"(v.w) : "r"(a) : "memory"); return v;
}
__device__ __forceinline__ uint32_t lds32(uint32_t a) { uint32_t v; asm volatile("ld.shared.u32 %0, [%1];" : "=r"(v) : "r"(a) : "memory"); return v; }
__device__ __forceinline__ bool has_sent(const uint4& v) { return (v.x == SENT) | (v.w == SENT); }
__device__ __forceinline__ bool has_zero(const uint4& v) { return min(min(v.x, v.y), min(v.z, v.w)) == 0u; }
__device__ __forceinline__ uint32_t nonzero(uint32_t w) { return w == 0u ? 0x8000u : w; }
__device__ __forceinline__ void stg32(void* p, uint32_t a) { asm volatile("st.relaxed.gpu.global.u32 [%0], %1;" :: "l"(p), "r"(a) : "memory"); }
__device__ __forceinline__ void wait_count(const unsigned* p, unsigned target) {
    unsigned v; int spins = 0;
    do { asm volatile("ld.acquire.gpu.global.u32 %0, [%1];" : "=r"(v) : "l"(p) : "memory"); } while (__any_sync(0xffffffffu, v != target) && ++spins < SPIN_LIMIT);
}
__device__ __forceinline__ void warp_done(uint32_t bar) {
    __syncwarp();
    asm volatile("{.reg .pred p; setp.eq.u32 p, %1, 0; @p mbarrier.arrive.shared::cta.b64 _, [%0];}" :: "r"(bar), "r"(threadIdx.x & 31) : "memory");
}
__device__ __forceinline__ uint32_t mul_bf16x2(uint32_t a, uint32_t b) { uint32_t r; asm("mul.rn.bf16x2 %0, %1, %2;" : "=r"(r) : "r"(a), "r"(b)); return r; }
__device__ __forceinline__ uint32_t fma_bf16x2(uint32_t a, uint32_t b, uint32_t c) { uint32_t r; asm("fma.rn.bf16x2 %0, %1, %2, %3;" : "=r"(r) : "r"(a), "r"(b), "r"(c)); return r; }
__device__ __forceinline__ uint32_t add_bf16x2(uint32_t a, uint32_t b) { uint32_t r; asm("add.rn.bf16x2 %0, %1, %2;" : "=r"(r) : "r"(a), "r"(b)); return r; }

#define R4(d, o) "+f"(d[o + 0]), "+f"(d[o + 1]), "+f"(d[o + 2]), "+f"(d[o + 3])
#define R8(d, o) R4(d, o), R4(d, o + 4)
#define R32(d) R8(d, 0), R8(d, 8), R8(d, 16), R8(d, 24)
#define D32 "{%0,%1,%2,%3,%4,%5,%6,%7,%8,%9,%10,%11,%12,%13,%14,%15,%16,%17,%18,%19,%20,%21,%22,%23,%24,%25,%26,%27,%28,%29,%30,%31}"
#define D64 "{%0,%1,%2,%3,%4,%5,%6,%7,%8,%9,%10,%11,%12,%13,%14,%15,%16,%17,%18,%19,%20,%21,%22,%23,%24,%25,%26,%27,%28,%29,%30,%31,%32,%33,%34,%35,%36,%37,%38,%39,%40,%41,%42,%43,%44,%45,%46,%47,%48,%49,%50,%51,%52,%53,%54,%55,%56,%57,%58,%59,%60,%61,%62,%63}"
#define D48 "{%0,%1,%2,%3,%4,%5,%6,%7,%8,%9,%10,%11,%12,%13,%14,%15,%16,%17,%18,%19,%20,%21,%22,%23,%24,%25,%26,%27,%28,%29,%30,%31,%32,%33,%34,%35,%36,%37,%38,%39,%40,%41,%42,%43,%44,%45,%46,%47}"

__device__ __forceinline__ void mma_qk_f16(float (&d)[32], uint64_t da, uint64_t db) {
    asm volatile("{.reg .pred p; setp.eq.b32 p, 0, 0; wgmma.mma_async.sync.aligned.m64n64k16.f32.f16.f16 " D32 ", %32, %33, p, 1, 1, 0, 0;}"
                 : R32(d) : "l"(da), "l"(db));
}
__device__ __forceinline__ void mma_qk_bf16(float (&d)[32], uint64_t da, uint64_t db) {
    asm volatile("{.reg .pred p; setp.ne.b32 p, 0, 0; wgmma.mma_async.sync.aligned.m64n64k16.f32.bf16.bf16 " D32 ", %32, %33, p, 1, 1, 0, 0;}"
                 : R32(d) : "l"(da), "l"(db));
}
__device__ __forceinline__ void mma_pv(float (&d)[12], const uint32_t* a, uint64_t db) {
    asm volatile("{.reg .pred p; setp.eq.b32 p, 0, 0; wgmma.mma_async.sync.aligned.m64n24k16.f32.bf16.bf16 {%0,%1,%2,%3,%4,%5,%6,%7,%8,%9,%10,%11}, {%12,%13,%14,%15}, %16, p, 1, 1, 1;}"
                 : R8(d, 0), R4(d, 8) : "r"(a[0]), "r"(a[1]), "r"(a[2]), "r"(a[3]), "l"(db));
}
__device__ __forceinline__ void mma_ss128(float (&d)[64], uint64_t da, uint64_t db) {
    asm volatile("{.reg .pred p; setp.eq.b32 p, 0, 0; wgmma.mma_async.sync.aligned.m64n128k16.f32.bf16.bf16 " D64 ", %64, %65, p, 1, 1, 0, 1;}"
                 : R32(d), R8(d, 32), R8(d, 40), R8(d, 48), R8(d, 56) : "l"(da), "l"(db));
}
__device__ __forceinline__ void stsm4(uint32_t addr, uint32_t a, uint32_t b, uint32_t c, uint32_t d) {
    asm volatile("stmatrix.sync.aligned.m8n8.x4.shared.b16 [%0], {%1,%2,%3,%4};" :: "r"(addr), "r"(a), "r"(b), "r"(c), "r"(d) : "memory");
}
__device__ __forceinline__ void mma_ss8(float (&d)[4], uint64_t da, uint64_t db) {
    asm volatile("{.reg .pred p; setp.eq.b32 p, 0, 0; wgmma.mma_async.sync.aligned.m64n8k16.f32.bf16.bf16 {%0,%1,%2,%3}, %4, %5, p, 1, 1, 0, 1;}"
                 : R4(d, 0) : "l"(da), "l"(db));
}
__device__ __forceinline__ void mma_rs(float (&d)[32], const uint4& a, uint64_t db) {
    asm volatile("{.reg .pred p; setp.eq.b32 p, 0, 0; wgmma.mma_async.sync.aligned.m64n64k16.f32.bf16.bf16 " D32 ", {%32,%33,%34,%35}, %36, p, 1, 1, 1;}"
                 : R32(d) : "r"(a.x), "r"(a.y), "r"(a.z), "r"(a.w), "l"(db));
}
__device__ __forceinline__ void mma_rs(float (&d)[48], const uint4& a, uint64_t db) {
    asm volatile("{.reg .pred p; setp.eq.b32 p, 0, 0; wgmma.mma_async.sync.aligned.m64n96k16.f32.bf16.bf16 " D48 ", {%48,%49,%50,%51}, %52, p, 1, 1, 1;}"
                 : R32(d), R8(d, 32), R8(d, 40) : "r"(a.x), "r"(a.y), "r"(a.z), "r"(a.w), "l"(db));
}

constexpr float EXP_MAGIC = 256.0f + 127.0f + 64.0f - 1.58621f + 0.00390625f;
constexpr uint32_t MUFU_MASK = 0x1111u;
__device__ __forceinline__ uint32_t exp2_pair(float y0, float y1, uint32_t cexp, uint32_t neg1) {
    uint32_t w, m, e, r;
    asm("prmt.b32 %0, %1, %2, 0x6521;" : "=r"(w) : "r"(__float_as_uint(y0)), "r"(__float_as_uint(y1)));
    asm("lop3.b32 %0, %1, 0x007F007F, %2, 0xEA;" : "=r"(m) : "r"(w), "r"(cexp));
    asm("mad.lo.u32 %0, %1, %2, %3;" : "=r"(e) : "r"(m), "r"(neg1), "r"(w));
    asm("fma.rn.bf16x2 %0, %1, %2, %3;" : "=r"(r) : "r"(w), "r"(m), "r"(e));
    return r;
}

struct Params {
    const __nv_bfloat16* x;
    const __nv_bfloat16* wk;
    long long wv_off;
    const __nv_bfloat16* wqp;
    __nv_bfloat16* out;
    uint32_t neg1, pad;
    const __nv_bfloat16* w1p;
    const __nv_bfloat16* w2p;
    CUtensorMap wq, wo, w1, w2;
    const __nv_bfloat16* wop;
};

__device__ __forceinline__ int f1_col0() { return ((blockIdx.x & 15) >> 1) * 176 + (blockIdx.x & 1) * 96; }
__device__ __forceinline__ void load_box(uint32_t sb, const CUtensorMap* tm, uint32_t dst, uint32_t bar, uint32_t bytes, int c0, int c1) {
    mbar_expect(sb + SM_MISC + bar * 8, bytes);
    tma2d(sb + dst, tm, c0, c1, sb + SM_MISC + bar * 8);
}
__device__ __forceinline__ void load_wq(uint32_t sb, const Params& P, int gi, int atom) {
    load_box(sb, &P.wq, SM_WQ + atom * 65536 + gi * 16384, MB_WQ + gi, 16384, (blockIdx.x & 3) * 128 + atom * 64, gi * 128);
}
__device__ __forceinline__ void load_wo(uint32_t sb, const Params& P, int kb) { load_box(sb, &P.wo, wo_slot(kb) * 8192, MB_WO + kb, 8192, (blockIdx.x & 7) * 64, kb * 64); }
__device__ __forceinline__ void load_w2(uint32_t sb, const Params& P, int kb, int slot) { load_box(sb, &P.w2, slot * 8192, MB_W2 + kb, 8192, (blockIdx.x & 7) * 64, kb * 64); }
__device__ __forceinline__ void refill_job(uint32_t sb, const Params& P, int gi, int job) {
    const bool w1 = job < 3;
    const int kb = (gi < 3 ? 2 + 2 * gi : 0) + job - 3;
    load_box(sb, w1 ? &P.w1 : gi < 3 ? &P.wo : &P.w2, (w1 ? 8 + gi + 4 * job : 2 * gi + job - 3) * 8192, w1 ? MB_W1 + gi : (gi < 3 ? MB_WO : MB_W2) + kb, 8192,
             w1 ? f1_col0() + job * 32 : (blockIdx.x & 7) * 64, w1 ? gi * 128 : kb * 64);
}
constexpr int H_KV = 0, H_O = 1 - 16, H_H1 = 17, H_H2 = 49;
__device__ __forceinline__ void hint_arrive(int id) {
    if ((threadIdx.x & 31) == 0) asm volatile("red.relaxed.gpu.global.add.u32 [%0], 1;" :: "l"(g_s.hint[id]) : "memory");
}
__device__ __forceinline__ void hint_wait(int id, unsigned target) {
    uint32_t v; int spins = 0;
    do { asm volatile("ld.relaxed.gpu.global.u32 %0, [%1];" : "=r"(v) : "l"(g_s.hint[id]) : "memory"); } while (__any_sync(0xffffffffu, v != target) && ++spins < SPIN_LIMIT);
}

template <int KIND> __host__ __device__ constexpr int a_off(int st) { return KIND == 1 ? st * 128 : (st >> 2) * 1024 + (st & 3) * 128; }
template <int KIND, int S0, int N, int BS>
__device__ __forceinline__ void load_batch(uint4 (&buf)[BS], const uint4* a) {
#pragma unroll
    for (int s = 0; s < N; s++) buf[s] = ldg_relaxed(a + a_off<KIND>(S0 + s));
}
template <int N, int BS>
__device__ __forceinline__ bool batch_bad(const uint4 (&buf)[BS]) {
    uint32_t m = 0;
#pragma unroll
    for (int s = 0; s < N; s++) m = max(m, buf[s].x);
    return __any_sync(0xffffffffu, m == SENT);
}
template <int KIND, int S0, int N, int BS>
__device__ __forceinline__ void check_batch(uint4 (&buf)[BS], const uint4* a) {
    if (__builtin_expect(batch_bad<N>(buf), 0)) {
        int spins = 0;
        do load_batch<KIND, S0, N>(buf, a); while (batch_bad<N>(buf) && ++spins < SPIN_LIMIT);
    }
}
template <int KIND, int NST, int BS, int I, int NACC, class Mid>
__device__ __forceinline__ void gemm_batch(float (&acc)[NACC], uint4 (&cur)[BS], uint4 (&nxt)[BS], const uint4* a, uint32_t sb, int q, Mid&& mid TS_ARG) {
    constexpr int S0 = I * BS, N = (NST - S0 < BS) ? NST - S0 : BS, S1 = S0 + BS, N1 = (NST - S1 < BS) ? NST - S1 : BS;
    const uint32_t mb = sb + SM_MISC;
    if (KIND == 2) {
#pragma unroll
        for (int blk = S0 / 4; blk < (S0 + N) / 4; blk++) mbar_wait(mb + (MB_W2 + 2 * blk + q) * 8);
    }
    check_batch<KIND, S0, N>(cur, a);
    if constexpr (I >= 1 && S1 < NST) {
        wg_wait<0>();
        load_batch<KIND, S1, N1>(nxt, a);
        if (KIND == 1 && S0 / 8 > (S0 - BS) / 8) warp_done(mb + (MB_REL + S0 / 8 - 1) * 8);
    }
    wg_fence();
#pragma unroll
    for (int s = 0; s < N; s++) {
        const int st = S0 + s, blk = st >> 2;
        if (KIND == 1) mma_rs(acc, cur[s], mkdesc(sb + (8 + (st >> 3)) * 8192 + (st & 7) * 1024, 32768, 512, 2));
        else mma_rs(acc, cur[s], mkdesc(sb + (KIND == 0 ? (q ? wo_slot(2 * blk + 1) : wo_slot(2 * blk)) : (q ? w2_slot(2 * blk + 1) : w2_slot(2 * blk))) * 8192 + (st & 3) * 2048, 16, 1024, 1));
    }
    wg_commit();
    if constexpr (S1 < NST) {
        mid(I);
        gemm_batch<KIND, NST, BS, I + 1>(acc, nxt, cur, a, sb, q, mid TS_PASS);
    } else {
        mid(I);
    }
}
template <int KIND, int NST, int BS, int NACC, class Mid>
__device__ __forceinline__ void gemm_rs(float (&acc)[NACC], const uint4* a, uint32_t sb, int q, Mid&& mid TS_ARG) {
    uint4 b0[BS], b1[BS];
    load_batch<KIND, 0, BS>(b0, a);
    load_batch<KIND, BS, BS>(b1, a);
#pragma unroll
    for (int i = 0; i < NACC; i++) acc[i] = 0.f;
    fence_regs(acc);
    gemm_batch<KIND, NST, BS, 0>(acc, b0, b1, a, sb, q, mid TS_PASS);
    wg_wait<0>();
    fence_regs(acc);
}

__device__ __forceinline__ void pair_reduce(const float (&acc)[32], float (&r)[16], uint32_t buf, int q, int barid) {
    if (q) {
#pragma unroll
        for (int j = 0; j < 4; j++) sts128(buf + j * 2048, __float_as_uint(acc[4 * j]), __float_as_uint(acc[4 * j + 1]), __float_as_uint(acc[4 * j + 2]), __float_as_uint(acc[4 * j + 3]));
        bar_sync(barid, 256);
        bar_sync(barid, 256);
#pragma unroll
        for (int j = 0; j < 4; j++) {
            float4 v = lds128f(buf + j * 2048);
            r[4 * j] = acc[16 + 4 * j] + v.x; r[4 * j + 1] = acc[17 + 4 * j] + v.y; r[4 * j + 2] = acc[18 + 4 * j] + v.z; r[4 * j + 3] = acc[19 + 4 * j] + v.w;
        }
    } else {
        bar_sync(barid, 256);
        float4 v[4];
#pragma unroll
        for (int j = 0; j < 4; j++) v[j] = lds128f(buf + j * 2048);
#pragma unroll
        for (int j = 0; j < 4; j++) sts128(buf + j * 2048, __float_as_uint(acc[16 + 4 * j]), __float_as_uint(acc[17 + 4 * j]), __float_as_uint(acc[18 + 4 * j]), __float_as_uint(acc[19 + 4 * j]));
        bar_arrive(barid, 256);
#pragma unroll
        for (int j = 0; j < 4; j++) {
            r[4 * j] = acc[4 * j] + v[j].x; r[4 * j + 1] = acc[4 * j + 1] + v[j].y; r[4 * j + 2] = acc[4 * j + 2] + v[j].z; r[4 * j + 3] = acc[4 * j + 3] + v[j].w;
        }
    }
}

__device__ __forceinline__ float quad_sum(float v) { v += __shfl_xor_sync(0xffffffffu, v, 1); v += __shfl_xor_sync(0xffffffffu, v, 2); return v; }
__device__ __forceinline__ float reduce4(const float (&st)[4], int lane) {
    const bool u16 = lane & 16, u8 = lane & 8;
    const float a0 = (u16 ? st[2] : st[0]) + __shfl_xor_sync(0xffffffffu, u16 ? st[0] : st[2], 16);
    const float a1 = (u16 ? st[3] : st[1]) + __shfl_xor_sync(0xffffffffu, u16 ? st[1] : st[3], 16);
    float v = (u8 ? a1 : a0) + __shfl_xor_sync(0xffffffffu, u8 ? a0 : a1, 8);
    v += __shfl_xor_sync(0xffffffffu, v, 4); v += __shfl_xor_sync(0xffffffffu, v, 2); v += __shfl_xor_sync(0xffffffffu, v, 1);
    return v;
}
__device__ __forceinline__ float silu2(float h) { float t; asm("tanh.approx.f32 %0, %1;" : "=f"(t) : "f"(h)); return fmaf(h, t, h); }

template <bool SAFE>
__device__ __forceinline__ void attention(const Params& P, uint32_t sb, int warp TS_ARG) {
    const uint32_t mb = sb + SM_MISC;
    const int tid = threadIdx.x, lane = tid & 31, b = blockIdx.x;
    const int wg = warp >> 2, ww = warp & 3, job = 3 - wg + 4 * ww;
    const uint32_t cexp = 0x9F809F80u + (tid >> 12);
    const uint32_t neg1 = P.neg1;
    unsigned cnt = 0;
    if (SAFE && warp == 8) asm volatile("ld.relaxed.gpu.global.u32 %0, [%1];" : "=r"(cnt) : "l"(&g_s.count1) : "memory");
#pragma unroll 1
    for (int pass = 0; pass < 2; pass++) {
    float o[12], s[32];
    const uint64_t dq = mkdesc(sb + SM_Q + (pass * 4 + wg) * 2048, 128, 256, 0);
    uint64_t dk = mkdesc(sb + SM_K, 128, 256, 0), dv = mkdesc(sb + SM_V, 128, 32768, 0);
    float m0 = -INFINITY, m1 = -INFINITY;
#pragma unroll
    for (int i = 0; i < 12; i++) o[i] = 0.f;
#pragma unroll
    for (int i = 0; i < 32; i++) s[i] = ((MUFU_MASK >> (i / 2)) & 1) ? 0.f : EXP_MAGIC;
    fence_regs(s); fence_regs(o);
    wg_fence();
    if (SAFE) mma_qk_f16(s, dq, dk + 31 * 128); else mma_qk_bf16(s, dq, dk + 31 * 128);
    wg_commit();
    wg_wait<0>(); fence_regs(s);
#pragma unroll 1
    for (int u = pass ? 3 : (wg == 2) ? 0 : 1; u < (pass ? 8 : 3); u++) {
        int n = 2 * ((((wg == 2) ? 0x22444C31u : 0x22444C40u) >> (4 * u)) & 15);
#pragma unroll 1
        do {
            uint32_t p[16];
            if (SAFE) {
#pragma unroll
                for (int j = 0; j < 16; j++) {
                    if ((MUFU_MASK >> j) & 1) p[j] = pack_bf16(ex2(s[2 * j]), ex2(s[2 * j + 1]));
                    else p[j] = exp2_pair(s[2 * j], s[2 * j + 1], cexp, neg1);
                }
            } else {
                fence_regs(o);
                float x0 = m0, x1 = m1;
#pragma unroll
                for (int j = 0; j < 8; j++) { x0 = fmaxf(x0, fmaxf(s[4 * j], s[4 * j + 1])); x1 = fmaxf(x1, fmaxf(s[4 * j + 2], s[4 * j + 3])); }
                x0 = fmaxf(x0, __shfl_xor_sync(0xffffffffu, x0, 1)); x0 = fmaxf(x0, __shfl_xor_sync(0xffffffffu, x0, 2));
                x1 = fmaxf(x1, __shfl_xor_sync(0xffffffffu, x1, 1)); x1 = fmaxf(x1, __shfl_xor_sync(0xffffffffu, x1, 2));
                const float c0 = ex2(m0 - x0), c1 = ex2(m1 - x1);
                m0 = x0; m1 = x1;
#pragma unroll
                for (int j = 0; j < 3; j++) { o[4 * j] *= c0; o[4 * j + 1] *= c0; o[4 * j + 2] *= c1; o[4 * j + 3] *= c1; }
#pragma unroll
                for (int j = 0; j < 8; j++) {
                    p[2 * j] = pack_bf16(ex2(s[4 * j] - m0), ex2(s[4 * j + 1] - m0));
                    p[2 * j + 1] = pack_bf16(ex2(s[4 * j + 2] - m1), ex2(s[4 * j + 3] - m1));
                }
                fence_regs(o);
            }
            fence_regs(p);
            wg_fence();
            if (SAFE) mma_qk_f16(s, dq, dk); else mma_qk_bf16(s, dq, dk);
#pragma unroll
            for (int j = 0; j < 4; j++) mma_pv(o, p + 4 * j, dv + j * 16);
            wg_commit();
            dk += 128; dv += 64;
            wg_wait<0>(); fence_regs(s);
        } while (--n > 0);
        if (u == 2 || u == 7) {
            fence_regs(o);
            const float i0 = rcp(o[8]), i1 = rcp(o[10]);
            if (u == 7) mbar_wait(mb + MB_F2 * 8);
            stg128(g_x + X_OF + (((u == 7) * 16 + (b >> 3)) * 32 + (b & 3) * 8 + 2 * wg + (ww >> 1)) * 128 + (((b >> 2) & 1) * 2 + (ww & 1)) * 32 + lane,
                   pack_bf16(o[0] * i0, o[1] * i0), pack_bf16(o[2] * i1, o[3] * i1), pack_bf16(o[4] * i0, o[5] * i0), pack_bf16(o[6] * i1, o[7] * i1));
            if (u == 2) asm volatile("cp.async.bulk.wait_group 0;" ::: "memory");
            else hint_arrive(H_O + 16 + (b >> 3));
            warp_done(mb + (MB_DONE + (u == 7) * 4) * 8);
            TS(5 + (u == 7));
        } else if (u >= 3) {
            if (u < 6) warp_done(mb + (MB_DONE + u - 2) * 8);
            if (job < (u == 3 ? 2 : 5)) {
                mbar_wait(mb + (MB_DONE + u - 3) * 8);
                if (lane == 0) {
                    if (u > 3) refill_job(sb, P, u - 4, job);
                    else if (job == 1) load_wo(sb, P, 1);
                    else asm volatile("red.release.gpu.global.add.u32 [%0], 1;" :: "l"(&g_s.count2) : "memory");
                }
            } else if (warp == 11) {
                if (u == 5) asm volatile("ld.relaxed.gpu.global.u32 %0, [%1];" : "=r"(cnt) : "l"(&g_s.count2) : "memory");
                if (u == 6) {
                    const unsigned target = lds32(mb + MISC_EPOCH) * NCTA;
                    if (__any_sync(0xffffffffu, cnt != target)) wait_count(&g_s.count2, target);
                    asm volatile("fence.acquire.gpu;" ::: "memory");
                    warp_done(mb + MB_F2 * 8);
                }
            }
        } else if (u == 1) {
            if (SAFE) mbar_wait(mb + MB_KV * 8);
            TS(17);
    if (lane == 0) {
        if (job < 9) {
            asm volatile("cp.async.bulk.global.shared::cta.bulk_group [%0], [%1], %2;"
                         :: "l"(g_x + X_ARM + b * X_SHARE + job * 512), "r"(sb + SM_SENT), "r"(job < 8 ? 8192 : (X_SHARE - 4096) * 16) : "memory");
            asm volatile("cp.async.bulk.commit_group;" ::: "memory");
        } else if (job == 9) load_wo(sb, P, 0);
    }
        } else if (SAFE) {
            if (warp == 8) {
                const unsigned target = lds32(mb + MISC_EPOCH) * NMAIN;
                if (__any_sync(0xffffffffu, cnt != target)) wait_count(&g_s.count1, target);
                if (lane == 0) {
                    asm volatile("fence.acquire.gpu; fence.proxy.async.global;" ::: "memory");
                    mbar_expect(mb + MB_KV * 8, 47104 + 2 * 24576);
                    bulk_g2s(sb + SM_K + 16384, g_s.kv + 1024, 47104, mb + MB_KV * 8);
                    bulk_g2s(sb + SM_V + 8192, g_s.kv + 4096 + 512, 24576, mb + MB_KV * 8);
                    bulk_g2s(sb + SM_V + 32768 + 8192, g_s.kv + 6144 + 512, 24576, mb + MB_KV * 8);
                }
            }
        }
        __syncwarp();
    }
    }
}

__device__ __noinline__ void helper_cta(const Params& P, uint8_t* smem) {
    const int tid = threadIdx.x, b = blockIdx.x, hi = b - NMAIN;
    const unsigned epoch = g_s.epoch[b] + 1;
    float* red = reinterpret_cast<float*>(smem);
    if (tid < 32) wait_count(&g_s.count1, epoch * NMAIN);
    __syncthreads();
    if (tid == 480) {
        for (int i = 0; i < 8; i++) asm volatile("cp.async.bulk.prefetch.L2.global [%0], %1;" :: "l"((const char*)P.wop + hi * 131072 + i * 16384), "r"(16384) : "memory");
        for (int i = 0; i < 43; i++) asm volatile("cp.async.bulk.prefetch.L2.global [%0], %1;" :: "l"((const char*)P.w2p + hi * 352256 + i * 8192), "r"(8192) : "memory");
    }
    if (tid < 344) {
        const int cg = tid % 43, rp = tid / 43;
        const uint4* src = reinterpret_cast<const uint4*>(P.w1p + (size_t)rp * 64 * FF + (hi * 43 + cg) * 8);
        float s[8] = {0, 0, 0, 0, 0, 0, 0, 0};
#pragma unroll 8
        for (int r = 0; r < 64; r++) {
            uint4 v = __ldg(src + r * (FF / 8));
            s[0] += bf_lo(v.x); s[1] += bf_hi(v.x); s[2] += bf_lo(v.y); s[3] += bf_hi(v.y);
            s[4] += bf_lo(v.z); s[5] += bf_hi(v.z); s[6] += bf_lo(v.w); s[7] += bf_hi(v.w);
        }
        float* part = red + (rp * 43 + cg) * 8;
#pragma unroll
        for (int i = 0; i < 8; i++) part[i] = s[i];
    }
    __syncthreads();
    if (tid < 344) {
        float s = 0.f;
#pragma unroll
        for (int rp = 0; rp < 8; rp++) s += red[rp * 344 + tid];
        g_s.cs[hi * 344 + tid] = s;
    } else if (hi == 3 && tid < 344 + 64) g_s.cs[FF + tid - 344] = 0.f;
    __syncthreads();
    if (tid == 0) {
        asm volatile("red.release.gpu.global.add.u32 [%0], 1;" :: "l"(&g_s.count2) : "memory");
        g_s.epoch[b] = epoch;
    }
}

__global__ void __launch_bounds__(512, 1) fused_kernel(const __grid_constant__ Params P) {
    extern __shared__ __align__(1024) uint8_t smem[];
    const uint32_t sb = (uint32_t)__cvta_generic_to_shared(smem);
    const uint32_t mb = sb + SM_MISC;
    const int tid = threadIdx.x, lane = tid & 31, b = blockIdx.x;
    if (b >= NMAIN) { helper_cta(P, smem); return; }
    const int tg = b >> 2, hg = b & 3;
    const int warp = __shfl_sync(0xffffffffu, tid >> 5, 0);

    uint4 xv[4][2];
    unsigned epoch = 0;
    {
        const int r = (tid >> 5) * 4;
        const uint4* src = reinterpret_cast<const uint4*>(P.x + (size_t)((r & 31) + tg * 32 + (r >> 5) * 1024) * D) + lane;
#pragma unroll
        for (int i = 0; i < 4; i++) { xv[i][0] = ldg_relaxed(src + i * 64); xv[i][1] = ldg_relaxed(src + i * 64 + 32); }
    }
    const uint4 wkv = ldg_relaxed(reinterpret_cast<const uint4*>(reinterpret_cast<const char*>(P.wk) + (hg < 2 ? 0 : P.wv_off)) + tid * 2 + (hg & 1));
    const int wg = warp >> 2, ww = warp & 3, g = lane >> 2, t4 = lane & 3, t128 = tid & 127;
    if (lane == 0) {
        mbar_init(mb + warp * 8, warp < 4 ? 2 : warp < 8 ? 3 : warp < 14 ? 16 : 1);
        mbar_init(mb + (16 + warp) * 8, 1);
        mbar_init(mb + (32 + warp) * 8, 1);
        if (warp >= 12) mbar_init(mb + (MB_REL - 12 + warp) * 8, 16);
        if (warp < 4) {
            asm volatile("fence.mbarrier_init.release.cluster;" ::: "memory");
            load_wq(sb, P, warp, 0);
            if (warp < 3) load_wq(sb, P, warp, 1);
        } else if (warp < 7) {
            asm volatile("prefetch.tensormap [%0];" :: "l"(&P.wo + (warp - 4)) : "memory");
        } else if (warp == 7) {
            asm volatile("ld.relaxed.gpu.global.u32 %0, [%1];" : "=r"(epoch) : "l"(g_s.epoch + b) : "memory");
        } else if (warp == 8) {
            sts128(mb + MISC_NRM, 0, 0, 0, 0);
        }
    }
    __syncwarp();
    TS(16);
    float dlt;
    {
        float st[4];
#pragma unroll
        for (int i = 0; i < 4; i++) {
            const uint32_t s = add_bf16x2(add_bf16x2(add_bf16x2(xv[i][0].x, xv[i][0].y), add_bf16x2(xv[i][0].z, xv[i][0].w)),
                                          add_bf16x2(add_bf16x2(xv[i][1].x, xv[i][1].y), add_bf16x2(xv[i][1].z, xv[i][1].w)));
            st[i] = bf_lo(s) + bf_hi(s);
        }
        TS(13);
        const float tot = reduce4(st, lane) * (-1.0f / D);
        const uint32_t nmr = pack_bf16(tot, tot);
        dlt = bf_lo(nmr) - tot;
        const uint32_t xa = sb + SM_XN + (lane >> 3) * 8192 + warp * 512;
#pragma unroll
        for (int i = 0; i < 4; i++) {
            const uint32_t nm = __shfl_sync(0xffffffffu, nmr, i * 8);
            const uint32_t addr = xa + i * 128 + (((lane & 7) ^ ((warp & 1) * 4 + i)) << 4);
#pragma unroll
            for (int c = 0; c < 2; c++) {
                xv[i][c].x = add_bf16x2(xv[i][c].x, nm); xv[i][c].y = add_bf16x2(xv[i][c].y, nm);
                xv[i][c].z = add_bf16x2(xv[i][c].z, nm); xv[i][c].w = add_bf16x2(xv[i][c].w, nm);
                sts128(addr + c * 32768, xv[i][c].x, xv[i][c].y, xv[i][c].z, xv[i][c].w);
            }
        }
    }
    sts128(sb + SM_WKV + tid * 16, wkv.x, wkv.y, wkv.z, wkv.w);
    fence_async_smem();
    TS(0);
    __syncthreads();
    auto variances = [&]() {
        float st[4];
#pragma unroll
        for (int i = 0; i < 4; i++) {
            float v = 0.f;
#pragma unroll
            for (int c = 0; c < 2; c++) {
                const uint32_t a = fma_bf16x2(xv[i][c].x, xv[i][c].x, mul_bf16x2(xv[i][c].y, xv[i][c].y));
                const uint32_t d = fma_bf16x2(xv[i][c].z, xv[i][c].z, mul_bf16x2(xv[i][c].w, xv[i][c].w));
                v += (bf_lo(a) + bf_hi(a)) + (bf_lo(d) + bf_hi(d));
            }
            st[i] = v;
        }
        const float vs = reduce4(st, lane), dl = dlt;
        if ((lane & 7) == 0) sts32(mb + MISC_RSTD + (warp * 4 + (lane >> 3)) * 4, __float_as_uint(rsqrtf(fmaxf(vs * (1.0f / D) - dl * dl, 0.f) + 1e-5f)));
    };
    float kv[4] = {0.f, 0.f, 0.f, 0.f};
    if (wg == 2) {
        fence_regs(kv);
        const uint64_t da = mkdesc(sb + SM_XN, 16, 1024, 1), db = mkdesc(sb + SM_WKV, 128, 16, 0);
        wg_fence();
#pragma unroll
        for (int s = 0; s < 32; s++) mma_ss8(kv, da + (s >> 2) * 512 + (s & 3) * 2, db + s * 16);
        wg_commit();
        TS(18);
        variances();
        wg_wait<0>(); fence_regs(kv);
        TS(20);
    } else {
        variances();
        if (tid == 7 * 32) { sts32(mb + MISC_EPOCH, epoch + 1); g_s.epoch[b] = epoch + 1; }
        TS(19);
    }
    __syncthreads();
    constexpr float QSCALE = 0.25f * 1.4426950408889634f;
    int kvoff;
    {
        const int t = (t128 & 63) >> 1, c = 2 * tg + (t128 & 1);
        kvoff = hg < 2 ? ((t + 31) & 31) * 128 + (c >> 3) * 16 + (hg & 1) * 8 + (c & 7) : 4096 + (hg & 1) * 2048 + t * 64 + c;
    }
    float qa[64];
    const uint32_t qbase = sb + SM_Q + (ww >> 1) * 8192 + (ww & 1) * 512 + lane * 16;
    if (wg == 0) {
#pragma unroll
        for (int i = 0; i < 64; i++) qa[i] = 0.f;
        fence_regs(qa);
        const uint64_t da = mkdesc(sb + SM_XN, 16, 1024, 1), db = mkdesc(sb + SM_WQ, 65536, 1024, 1);
#pragma unroll 1
        for (int i = 0; i < 4; i++) {
            mbar_wait(mb + (MB_WQ + i) * 8);
            if (i == 0) TS(21); if (i == 3) TS(22);
            wg_fence();
#pragma unroll
            for (int s = 0; s < 8; s++) mma_ss128(qa, da + (i * 2 + (s >> 2)) * 512 + (s & 3) * 2, db + (i * 8 + s) * 128);
            wg_commit();
        }
        const float rs0 = __uint_as_float(lds32(mb + MISC_RSTD + (ww * 16 + g) * 4)) * QSCALE, rs1 = __uint_as_float(lds32(mb + MISC_RSTD + (ww * 16 + g + 8) * 4)) * QSCALE;
        wg_wait<0>();
        fence_regs(qa);
        bar_arrive(6, 256);
        bar_sync(5, 256);
        TS(1);
        uint32_t nm = 0;
#pragma unroll
        for (int h = 0; h < 8; h++) {
#pragma unroll
            for (int i = 0; i < 8; i++) qa[8 * h + i] *= (i & 2) ? rs1 : rs0;
            stsm4(qbase + h * 1024, pack_f16(qa[8 * h], qa[8 * h + 1]), pack_f16(qa[8 * h + 4], qa[8 * h + 5]), pack_f16(qa[8 * h + 2], qa[8 * h + 3]), pack_f16(qa[8 * h + 6], qa[8 * h + 7]));
            const float n0 = qa[8 * h] * qa[8 * h] + qa[8 * h + 1] * qa[8 * h + 1] + qa[8 * h + 4] * qa[8 * h + 4] + qa[8 * h + 5] * qa[8 * h + 5];
            const float n1 = qa[8 * h + 2] * qa[8 * h + 2] + qa[8 * h + 3] * qa[8 * h + 3] + qa[8 * h + 6] * qa[8 * h + 6] + qa[8 * h + 7] * qa[8 * h + 7];
            nm = max(nm, max(__float_as_uint(n0), __float_as_uint(n1)));
        }
        nm = __reduce_max_sync(0xffffffffu, __float_as_uint(quad_sum(__uint_as_float(nm))));
        if (lane == 0) asm volatile("red.shared.max.u32 [%0], %1;" :: "r"(mb + MISC_NRM), "r"(nm) : "memory");
    } else if (wg == 1) {
        bar_sync(5, 256);
#pragma unroll
        for (int i = 0; i < 16; i++) sts128(sb + SM_V + 65536 + (i * 128 + t128) * 16, 0x3F803F80u, 0x3F803F80u, 0x3F803F80u, 0x3F803F80u);
#pragma unroll
        for (int i = 0; i < 4; i++) sts128(sb + SM_SENT + (i * 128 + t128) * 16, SENT, SENT, SENT, SENT);
    } else if (wg == 2) {
        const float rs0 = __uint_as_float(lds32(mb + MISC_RSTD + (ww * 16 + g) * 4)), rs1 = __uint_as_float(lds32(mb + MISC_RSTD + (ww * 16 + g + 8) * 4));
        kv[0] *= rs0; kv[1] *= rs0; kv[2] *= rs1; kv[3] *= rs1;
        float2* kt = reinterpret_cast<float2*>(smem + SM_MISC + MISC_KTMP);
        kt[(ww * 16 + g) * 4 + t4] = make_float2(kv[0], kv[1]); kt[(ww * 16 + g + 8) * 4 + t4] = make_float2(kv[2], kv[3]);
        float n0 = kv[0] * kv[0] + kv[1] * kv[1], n1 = kv[2] * kv[2] + kv[3] * kv[3];
        n0 += __shfl_xor_sync(0xffffffffu, n0, 1); n1 += __shfl_xor_sync(0xffffffffu, n1, 1);
        n0 += __shfl_xor_sync(0xffffffffu, n0, 2); n1 += __shfl_xor_sync(0xffffffffu, n1, 2);
        const uint32_t nm = __reduce_max_sync(0xffffffffu, max(__float_as_uint(n0), __float_as_uint(n1)));
        if (lane == 0) sts32(mb + MISC_WNRM + ww * 4, nm | 1u);
        bar_sync(2, 128);
        const uint32_t ra = mb + MISC_KTMP + ((t128 & 1) * 32 + ((t128 & 63) >> 1)) * 32;
        const float4 c0 = lds128f(ra), c1 = lds128f(ra + 16);
        if (ww < 2) {
            if (hg < 2) {
                float4 p0 = lds128f(ra - 32), p1 = lds128f(ra - 16);
                if (t128 < 2) { p0 = make_float4(0.f, 0.f, 0.f, 0.f); p1 = p0; }
                stg128(g_s.kv + kvoff, nonzero(pack_f16(c0.x - p0.x, c0.y - p0.y)), pack_f16(c0.z - p0.z, c0.w - p0.w), pack_f16(c1.x - p1.x, c1.y - p1.y), pack_f16(c1.z - p1.z, c1.w - p1.w));
            } else {
                stg128(g_s.kv + kvoff, nonzero(pack_bf16(c0.x, c0.y)), pack_bf16(c0.z, c0.w), pack_bf16(c1.x, c1.y), pack_bf16(c1.z, c1.w));
            }
            if (t128 < 2) { const float4 w = lds128f(mb + MISC_WNRM); stg128(g_s.nrm + b * 2 + t128, __float_as_uint(w.x), __float_as_uint(w.y), __float_as_uint(w.z), __float_as_uint(w.w)); }
            hint_arrive(H_KV);
        } else if (hg < 2) {
            stg128(g_s.kplain + kvoff, pack_bf16(c0.x, c0.y), pack_bf16(c0.z, c0.w), pack_bf16(c1.x, c1.y), pack_bf16(c1.z, c1.w));
        }
        TS(1);
        bar_sync(2, 128);
        if (t128 == 96) asm volatile("red.release.gpu.global.add.u32 [%0], 1;" :: "l"(&g_s.count1) : "memory");
        __syncwarp();
    } else {
        if (tid == 13 * 32) load_wq(sb, P, 3, 1);
        __syncwarp();
        uint4 kc[18];
        auto src = [&](int i) { return i < 8 ? g_s.kv + i * 128 : i < 12 ? g_s.kv + 4096 + (i - 8) * 128 : i < 16 ? g_s.kv + 6144 + (i - 12) * 128 : i == 16 ? g_s.kv + 31 * 128 : g_s.nrm + t128; };
        hint_wait(H_KV, lds32(mb + MISC_EPOCH) * (NMAIN * 2));
        TS(1);
        int spins = 0;
        while (true) {
#pragma unroll
            for (int i = 0; i < 18; i++) kc[i] = ldg_relaxed(src(i) + t128);
            uint32_t mn = 1;
#pragma unroll
            for (int i = 0; i < 18; i++) mn = min(mn, kc[i].x);
            if (!__any_sync(0xffffffffu, mn == 0u) || ++spins >= SPIN_LIMIT) break;
        }
        uint32_t nm = max(max(kc[17].x, kc[17].y), max(kc[17].z, kc[17].w));
        nm = max(nm, __shfl_xor_sync(0xffffffffu, nm, 4)); nm = max(nm, __shfl_xor_sync(0xffffffffu, nm, 8)); nm = max(nm, __shfl_xor_sync(0xffffffffu, nm, 16));
        if (lane < 4) asm volatile("red.shared.max.u32 [%0], %1;" :: "r"(mb + MISC_NRM + 4 + min(lane, 2) * 4), "r"(nm) : "memory");
        TS(2);
        bar_sync(6, 256);
#pragma unroll
        for (int i = 0; i < 17; i++) sts128(sb + (uint32_t)(src(i) - g_s.kv + t128) * 16, kc[i].x, kc[i].y, kc[i].z, kc[i].w);
    }
    fence_async_smem();
    TS(3);
    __syncthreads();
    const float4 nr = lds128f(mb + MISC_NRM);
    const bool safe = __all_sync(0xffffffffu, (nr.x * (nr.y + nr.z) <= 3500.0f) && (nr.x <= 65536.0f) && (nr.y + nr.z <= 65536.0f) && (nr.w <= 1e24f));
    TS(4);

    if (__builtin_expect(safe, 1)) {
        attention<true>(P, sb, warp TS_PASS);
    } else {
        if (wg == 0) {
#pragma unroll
            for (int h = 0; h < 8; h++)
                stsm4(qbase + h * 1024, pack_bf16(qa[8 * h], qa[8 * h + 1]), pack_bf16(qa[8 * h + 4], qa[8 * h + 5]), pack_bf16(qa[8 * h + 2], qa[8 * h + 3]), pack_bf16(qa[8 * h + 6], qa[8 * h + 7]));
            fence_async_smem();
        } else if (warp == 15) {
            wait_count(&g_s.count1, lds32(mb + MISC_EPOCH) * NMAIN);
            if (lane == 0) {
                asm volatile("fence.proxy.async;" ::: "memory");
                mbar_expect(mb + MB_KV * 8, 131072);
                bulk_g2s(sb + SM_K, g_s.kplain, 65536, mb + MB_KV * 8);
                bulk_g2s(sb + SM_V, g_s.kv + 4096, 65536, mb + MB_KV * 8);
            }
            __syncwarp();
        }
        __syncthreads();
        mbar_wait(mb + MB_KV * 8);
        attention<false>(P, sb, warp TS_PASS);
    }

    const int pr = 1 - (wg >> 1), q = wg & 1;
    const int mt = 16 * pr + (b >> 3), j = b & 7;
    const int row0 = mt * 64 + ww * 16 + g;
    const uint32_t xbuf = sb + SM_Q + pr * 8192 + t128 * 16;
    uint32_t hk[8];
    epoch = lds32(mb + MISC_EPOCH);
    {
        const uint4* a = g_x + X_OF + (mt * 32 + q * 4) * 128 + t128;
        if (pr) {
            if (warp < 5) {
                mbar_wait(mb + (MB_DONE + 4) * 8);
                if (lane == 0) refill_job(sb, P, 3, warp);
            } else if (warp == 5) {
                if (lane < 24) {
                    const uint4 v = ldg_relaxed(reinterpret_cast<const uint4*>(g_s.cs + f1_col0()) + lane);
                    sts128(mb + MISC_CS + lane * 16, v.x, v.y, v.z, v.w);
                }
                warp_done(mb + MB_CS * 8);
            }
            __syncwarp();
        }
        const uint32_t* xp = reinterpret_cast<const uint32_t*>(P.x + (size_t)row0 * D + j * 64 + q * 32 + t4 * 2);
#pragma unroll
        for (int i = 0; i < 4; i++) { hk[2 * i] = __ldg(xp + i * 4); hk[2 * i + 1] = __ldg(xp + i * 4 + 8 * (D / 2)); }
#pragma unroll 1
        for (int i = 0; i < 4; i++) mbar_wait(mb + (MB_WO + 2 * i + q) * 8);
        if (pr) hint_wait(H_O + mt, epoch * 128);
        TS(23);
        float acc[32], r[16];
        gemm_rs<0, 16, 8>(acc, a, sb, q, [](int) {} TS_PASS);
        TS(7);
        warp_done(mb + (MB_DONE + 5) * 8);
        mbar_wait(mb + (MB_DONE + 4 * pr) * 8);
        pair_reduce(acc, r, xbuf, q, 3 + pr);
#pragma unroll
        for (int i = 0; i < 8; i++) hk[i] = pack_bf16(r[2 * i] + bf_lo(hk[i]), r[2 * i + 1] + bf_hi(hk[i]));
        float s0 = 0.f, s1 = 0.f;
#pragma unroll
        for (int i = 0; i < 8; i++) {
            r[2 * i] = bf_lo(hk[i]); r[2 * i + 1] = bf_hi(hk[i]);
            if (i & 1) s1 += r[2 * i] + r[2 * i + 1]; else s0 += r[2 * i] + r[2 * i + 1];
        }
        s0 += __shfl_xor_sync(0xffffffffu, s0, 1); s1 += __shfl_xor_sync(0xffffffffu, s1, 1);
        s0 += __shfl_xor_sync(0xffffffffu, s0, 2); s1 += __shfl_xor_sync(0xffffffffu, s1, 2);
        const float a0 = s0 * (1.0f / 32), a1 = s1 * (1.0f / 32);
        float v0 = 0.f, v1 = 0.f;
#pragma unroll
        for (int i = 0; i < 8; i++) {
            const float am = (i & 1) ? a1 : a0;
            const float d0 = r[2 * i] - am, d1 = r[2 * i + 1] - am;
            if (i & 1) v1 += d0 * d0 + d1 * d1; else v0 += d0 * d0 + d1 * d1;
        }
        v0 += __shfl_xor_sync(0xffffffffu, v0, 1); v1 += __shfl_xor_sync(0xffffffffu, v1, 1);
        v0 += __shfl_xor_sync(0xffffffffu, v0, 2); v1 += __shfl_xor_sync(0xffffffffu, v1, 2);
        uint4* hp = g_x + X_HF + (mt * 32 + j * 4 + 2 * q) * 128 + t128;
        stg128(hp, hk[0], hk[1], hk[2], hk[3]);
        stg128(hp + 128, hk[4], hk[5], hk[6], hk[7]);
        if (t4 == 0) stg128(g_x + X_ST + (mt * 16 + j * 2 + q) * 32 + ww * 8 + g, __float_as_uint(s0), __float_as_uint(v0), __float_as_uint(s1), __float_as_uint(v1));
        hint_arrive(H_H1 + mt);
        TS(8);
        if (pr) {
            mbar_wait(mb + (MB_DONE + 5) * 8);
            if (lane == 0) load_w2(sb, P, 2 + warp, warp < 2 ? 22 + warp : warp - 2);
            __syncwarp();
        } else if (warp == 8 || warp == 9) {
            stg128(g_s.kv + kvoff, 0u, 0u, 0u, 0u);
            if (t128 < 2) stg128(g_s.nrm + b * 2 + t128, 0u, 0u, 0u, 0u);
        }
    }
    {
        const int mt1 = 16 * pr + (b >> 4) * 2 + q, sl = b & 15;
        const uint4* a = g_x + X_HF + mt1 * 32 * 128 + t128;
        float acc[48], nmean[2], hrstd[2];
        const uint4* sp = g_x + X_ST + (mt1 * 16 + t4) * 32 + ww * 8 + g;
        uint4 u[4];
        auto row_stats = [&]() {
            float mean[2], m2[2];
            mean[0] = (__uint_as_float(u[0].x) + __uint_as_float(u[1].x)) + (__uint_as_float(u[2].x) + __uint_as_float(u[3].x));
            mean[1] = (__uint_as_float(u[0].z) + __uint_as_float(u[1].z)) + (__uint_as_float(u[2].z) + __uint_as_float(u[3].z));
            mean[0] += __shfl_xor_sync(0xffffffffu, mean[0], 1); mean[1] += __shfl_xor_sync(0xffffffffu, mean[1], 1);
            mean[0] += __shfl_xor_sync(0xffffffffu, mean[0], 2); mean[1] += __shfl_xor_sync(0xffffffffu, mean[1], 2);
            mean[0] *= 1.0f / D; mean[1] *= 1.0f / D;
            m2[0] = 0.f; m2[1] = 0.f;
#pragma unroll
            for (int i = 0; i < 4; i++) {
                const float d0 = __uint_as_float(u[i].x) * (1.0f / 32) - mean[0], d1 = __uint_as_float(u[i].z) * (1.0f / 32) - mean[1];
                m2[0] += fmaf(32.0f * d0, d0, __uint_as_float(u[i].y)); m2[1] += fmaf(32.0f * d1, d1, __uint_as_float(u[i].w));
            }
            m2[0] += __shfl_xor_sync(0xffffffffu, m2[0], 1); m2[1] += __shfl_xor_sync(0xffffffffu, m2[1], 1);
            m2[0] += __shfl_xor_sync(0xffffffffu, m2[0], 2); m2[1] += __shfl_xor_sync(0xffffffffu, m2[1], 2);
#pragma unroll
            for (int i = 0; i < 2; i++) { hrstd[i] = 0.5f * rsqrtf(m2[i] * (1.0f / D) + 1e-5f); nmean[i] = -mean[i]; }
        };
#pragma unroll 1
        for (int i = 0; i < 4; i++) mbar_wait(mb + (MB_W1 + i) * 8);
        mbar_wait(mb + MB_CS * 8);
        hint_wait(H_H1 + mt1, epoch * 64);
        TS(24);
        gemm_rs<1, 32, 6>(acc, a, sb, q, [&](int i) {
            if (i == 4) load_batch<1, 0, 4>(u, sp);
            if (i == 5) { check_batch<1, 0, 4>(u, sp); row_stats(); }
        } TS_PASS);
        warp_done(mb + (MB_REL + 3) * 8);
        if (pr && warp < 6) {
            mbar_wait(mb + (MB_REL + 2 + (warp >= 3)) * 8);
            if (lane == 0) load_w2(sb, P, 16 + warp, warp < 3 ? 10 + 4 * warp : 4 * warp - 1);
            __syncwarp();
        }
        TS(9);
        uint4* hb = g_x + X_H + (mt1 * 88 + (sl >> 1) * 11 + (sl & 1) * 6) * 128 + t128;
#pragma unroll
        for (int k = 0; k < 6; k++) {
            if (k == 5 && (sl & 1)) break;
            uint32_t hv[4];
#pragma unroll
            for (int i = 0; i < 2; i++) {
                float2 cs;
                asm volatile("ld.shared.v2.f32 {%0,%1}, [%2];" : "=f"(cs.x), "=f"(cs.y) : "r"(mb + MISC_CS + (2 * k + i) * 32 + t4 * 8));
                const float* z = acc + 8 * k + 4 * i;
                hv[2 * i] = pack_bf16(silu2(hrstd[0] * fmaf(nmean[0], cs.x, z[0])), silu2(hrstd[0] * fmaf(nmean[0], cs.y, z[1])));
                hv[2 * i + 1] = pack_bf16(silu2(hrstd[1] * fmaf(nmean[1], cs.x, z[2])), silu2(hrstd[1] * fmaf(nmean[1], cs.y, z[3])));
            }
            stg128(hb + k * 128, hv[0], hv[1], hv[2], hv[3]);
        }
        hint_arrive(H_H2 + mt1);
        TS(10);
        if (!pr && warp < 14) {
            mbar_wait(mb + (MB_REL + (warp >= 11)) * 8);
            if (lane == 0) load_w2(sb, P, 2 + warp, warp < 11 ? 4 * warp - 24 : 4 * warp - 35);
            __syncwarp();
        }
    }
    {
        const uint4* a = g_x + X_H + (mt * 88 + q * 4) * 128 + t128;
        hint_wait(H_H2 + mt, epoch * 64);
        TS(25);
        float acc[32], r[16];
        gemm_rs<2, 44, 8>(acc, a, sb, q, [](int) {} TS_PASS);
        TS(11);
        pair_reduce(acc, r, xbuf, q, 3 + pr);
#pragma unroll
        for (int i = 0; i < 8; i++) hk[i] = pack_bf16(r[2 * i] + bf_lo(hk[i]), r[2 * i + 1] + bf_hi(hk[i]));
    }
#pragma unroll
    for (int h = 0; h < 2; h++) {
        uint32_t v0 = hk[h], v1 = hk[2 + h], v2 = hk[4 + h], v3 = hk[6 + h];
        const bool o1 = t4 & 1, o2 = t4 & 2;
        uint32_t a = __shfl_xor_sync(0xffffffffu, o1 ? v0 : v1, 1), c = __shfl_xor_sync(0xffffffffu, o1 ? v2 : v3, 1);
        if (o1) { v0 = a; v2 = c; } else { v1 = a; v3 = c; }
        a = __shfl_xor_sync(0xffffffffu, o2 ? v0 : v2, 2); c = __shfl_xor_sync(0xffffffffu, o2 ? v1 : v3, 2);
        if (o2) { v0 = a; v1 = c; } else { v2 = a; v3 = c; }
        *reinterpret_cast<uint4*>(P.out + (size_t)(row0 + 8 * h) * D + j * 64 + q * 32 + t4 * 8) = make_uint4(v0, v1, v2, v3);
    }
    TS(12);
}

typedef CUresult (*EncodeFn)(CUtensorMap*, CUtensorMapDataType, cuuint32_t, void*, const cuuint64_t*, const cuuint64_t*, const cuuint32_t*,
                             const cuuint32_t*, CUtensorMapInterleave, CUtensorMapSwizzle, CUtensorMapL2promotion, CUtensorMapFloatOOBfill);

void encode2d(EncodeFn fn, CUtensorMap* tm, const void* ptr, int rows, int cols, int box_rows, int box_cols, CUtensorMapSwizzle sw) {
    cuuint64_t dims[2] = {(cuuint64_t)cols, (cuuint64_t)rows};
    cuuint64_t strides[1] = {(cuuint64_t)cols * 2};
    cuuint32_t box[2] = {(cuuint32_t)box_cols, (cuuint32_t)box_rows};
    cuuint32_t es[2] = {1, 1};
    fn(tm, CU_TENSOR_MAP_DATA_TYPE_BFLOAT16, 2, const_cast<void*>(ptr), dims, strides, box, es, CU_TENSOR_MAP_INTERLEAVE_NONE, sw,
       CU_TENSOR_MAP_L2_PROMOTION_L2_128B, CU_TENSOR_MAP_FLOAT_OOB_FILL_NONE);
}

}

extern "C" void kernel_launch(void* const* d_in, const int* in_sizes, int n_in, void* d_out, int out_size) {
    (void)in_sizes; (void)n_in; (void)out_size;
    void* fnp = nullptr;
    cudaDriverEntryPointQueryResult qr;
    cudaGetDriverEntryPoint("cuTensorMapEncodeTiled", &fnp, cudaEnableDefault, &qr);
    EncodeFn fn = (EncodeFn)fnp;
    Params P;
    encode2d(fn, &P.wq, d_in[1], D, D, 128, 64, CU_TENSOR_MAP_SWIZZLE_128B);
    P.wk = (const __nv_bfloat16*)d_in[2];
    P.wv_off = (const char*)d_in[3] - (const char*)d_in[2];
    encode2d(fn, &P.wo, d_in[4], D, D, 64, 64, CU_TENSOR_MAP_SWIZZLE_128B);
    encode2d(fn, &P.w1, d_in[6], D, FF, 128, 32, CU_TENSOR_MAP_SWIZZLE_64B);
    encode2d(fn, &P.w2, d_in[7], FF, D, 64, 64, CU_TENSOR_MAP_SWIZZLE_128B);
    P.x = (const __nv_bfloat16*)d_in[0];
    P.w1p = (const __nv_bfloat16*)d_in[6];
    P.w2p = (const __nv_bfloat16*)d_in[7];
    P.wop = (const __nv_bfloat16*)d_in[4];
    P.wqp = (const __nv_bfloat16*)d_in[1];
    P.out = (__nv_bfloat16*)d_out;
    P.neg1 = 0xFFFFFFFFu; P.pad = 0;
    cudaFuncSetAttribute(fused_kernel, cudaFuncAttributeMaxDynamicSharedMemorySize, SMEM_BYTES);
    fused_kernel<<<NCTA, 512, SMEM_BYTES>>>(P);
}
```

```cpp
#include <cuda_runtime.h>
#include <cuda_bf16.h>
#include <cuda.h>
#include <stdint.h>

namespace {

constexpr int D = 512, FF = 1376;
constexpr int NMAIN = 128, NHELP = 4, NCTA = NMAIN + NHELP;
constexpr uint32_t SENT = 0xFFFFFFFFu;
constexpr int SPIN_LIMIT = 1 << 22;

constexpr uint32_t KB = 1024;
constexpr uint32_t SM_XN = 0;
constexpr uint32_t SM_WQ = 64 * KB;
constexpr uint32_t SM_WKV = 176 * KB;
constexpr uint32_t SM_K = 0;
constexpr uint32_t SM_V = 64 * KB;
constexpr uint32_t SM_Q = 160 * KB;
constexpr uint32_t SM_SENT = 184 * KB;
constexpr uint32_t SM_MISC = 192 * KB;
constexpr uint32_t SMEM_BYTES = 195 * KB;
constexpr uint32_t MB_WQ = 0;
constexpr uint32_t MB_REL = 4;
constexpr uint32_t MB_DONE = 8;
constexpr uint32_t MB_WO = 14;
constexpr uint32_t MB_W1 = 15;
constexpr uint32_t MB_W2 = 16;
constexpr uint32_t MB_KV = 38;
constexpr uint32_t MB_F2 = 39;
constexpr uint32_t MB_LEAD = 40;
constexpr uint32_t MISC_NRM = 416;
constexpr uint32_t MISC_WNRM = 432;
constexpr uint32_t MISC_EPOCH = 704;
constexpr uint32_t MISC_CS = 1024;
constexpr uint32_t MISC_RSTD = 448;
constexpr uint32_t MISC_KTMP = 1024;

__host__ __device__ constexpr uint32_t wo_slot(int kb) { return kb < 2 ? 22 + kb : kb - 2; }
__host__ __device__ constexpr uint32_t w2_slot(int kb) { return kb < 2 ? 6 + kb : kb < 4 ? 20 + kb : kb < 10 ? kb - 4 : 8 + (kb - 10) / 3 + 4 * ((kb - 10) % 3); }

struct alignas(128) Small {
    unsigned epoch[160];
    unsigned count1, pad1[31];
    unsigned count2, pad2[31];
    unsigned hint[100][32];
    float cs[1440];
    uint4 nrm[NMAIN * 2];
    uint4 kv[8192];
    uint4 kplain[4096];
};
__device__ Small g_s;
constexpr int X_OF = 0, X_HF = 32 * 32 * 128, X_ST = X_HF + 32 * 32 * 128, X_H = X_ST + 32 * 64 * 8, X_END = X_H + 32 * 88 * 128;
constexpr int X_ARM = 16 * 32 * 128, X_SHARE = (X_END - X_ARM) / NMAIN;
__device__ uint4 g_x[X_END];
#define TS(i) do {} while (0)

#define TS_ARG
#define TS_PASS

__device__ __forceinline__ void mbar_init(uint32_t bar, int cnt) { asm volatile("mbarrier.init.shared::cta.b64 [%0], %1;" :: "r"(bar), "r"(cnt) : "memory"); }
__device__ __forceinline__ void mbar_expect(uint32_t bar, uint32_t bytes) { asm volatile("mbarrier.arrive.expect_tx.shared::cta.b64 _, [%0], %1;" :: "r"(bar), "r"(bytes) : "memory"); }
__device__ __forceinline__ void mbar_arrive(uint32_t bar) { asm volatile("mbarrier.arrive.shared::cta.b64 _, [%0];" :: "r"(bar) : "memory"); }
__device__ __forceinline__ void mbar_wait(uint32_t bar) {
    uint32_t done; int spins = 0;
    do {
        asm volatile("{.reg .pred p; mbarrier.try_wait.parity.shared::cta.b64 p, [%1], 0; selp.u32 %0, 1, 0, p;}" : "=r"(done) : "r"(bar) : "memory");
    } while (!__all_sync(0xffffffffu, done) && ++spins < SPIN_LIMIT);
}
__device__ __forceinline__ void tma2d(uint32_t dst, const CUtensorMap* tm, int c0, int c1, uint32_t bar) {
    asm volatile("cp.async.bulk.tensor.2d.shared::cluster.global.mbarrier::complete_tx::bytes [%0], [%1, {%3, %4}], [%2];"
                 :: "r"(dst), "l"(tm), "r"(bar), "r"(c0), "r"(c1) : "memory");
}
__device__ __forceinline__ void bulk_g2s(uint32_t dst, const void* src, uint32_t bytes, uint32_t bar) {
    asm volatile("cp.async.bulk.shared::cluster.global.mbarrier::complete_tx::bytes [%0], [%1], %2, [%3];" :: "r"(dst), "l"(src), "r"(bytes), "r"(bar) : "memory");
}
__device__ __forceinline__ void fence_async_smem() { asm volatile("fence.proxy.async.shared::cta;" ::: "memory"); }
__device__ __forceinline__ void bar_sync(int id, int n) { asm volatile("bar.sync %0, %1;" :: "r"(id), "r"(n) : "memory"); }
__device__ __forceinline__ void bar_arrive(int id, int n) { asm volatile("bar.arrive %0, %1;" :: "r"(id), "r"(n) : "memory"); }
__device__ __forceinline__ void wg_fence() { asm volatile("wgmma.fence.sync.aligned;" ::: "memory"); }
__device__ __forceinline__ void wg_commit() { asm volatile("wgmma.commit_group.sync.aligned;" ::: "memory"); }
template <int N> __device__ __forceinline__ void wg_wait() { asm volatile("wgmma.wait_group.sync.aligned %0;" :: "n"(N) : "memory"); }
template <int N> __device__ __forceinline__ void fence_regs(float (&d)[N]) {
#pragma unroll
    for (int i = 0; i < N; i++) asm volatile("" : "+f"(d[i]) :: "memory");
}
template <int N> __device__ __forceinline__ void fence_regs(uint32_t (&d)[N]) {
#pragma unroll
    for (int i = 0; i < N; i++) asm volatile("" : "+r"(d[i]) :: "memory");
}
__device__ __forceinline__ uint64_t mkdesc(uint32_t addr, uint32_t lbo, uint32_t sbo, uint32_t swz) {
    return (uint64_t)(((addr & 0x3FFFF) >> 4) | ((lbo >> 4) << 16)) | ((uint64_t)((sbo >> 4) | (swz << 30)) << 32);
}
__device__ __forceinline__ float ex2(float x) { float y; asm("ex2.approx.ftz.f32 %0, %1;" : "=f"(y) : "f"(x)); return y; }
__device__ __forceinline__ float rcp(float x) { float y; asm("rcp.approx.ftz.f32 %0, %1;" : "=f"(y) : "f"(x)); return y; }
__device__ __forceinline__ uint32_t pack_bf16(float lo, float hi) { uint32_t r; asm("cvt.rn.bf16x2.f32 %0, %1, %2;" : "=r"(r) : "f"(hi), "f"(lo)); return r; }
__device__ __forceinline__ uint32_t pack_f16(float lo, float hi) { uint32_t r; asm("cvt.rn.f16x2.f32 %0, %1, %2;" : "=r"(r) : "f"(hi), "f"(lo)); return r; }
__device__ __forceinline__ float bf_lo(uint32_t v) { return __uint_as_float(v << 16); }
__device__ __forceinline__ float bf_hi(uint32_t v) { return __uint_as_float(v & 0xFFFF0000u); }
__device__ __forceinline__ uint4 ldg_relaxed(const uint4* p) {
    uint4 v; asm volatile("ld.relaxed.gpu.global.v4.u32 {%0,%1,%2,%3}, [%4];" : "=r"(v.x), "=r"(v.y), "=r"(v.z), "=r"(v.w) : "l"(p) : "memory"); return v;
}
__device__ __forceinline__ void stg128(void* p, uint32_t a, uint32_t b, uint32_t c, uint32_t d) {
    asm volatile("st.relaxed.gpu.global.v4.u32 [%0], {%1,%2,%3,%4};" :: "l"(p), "r"(a), "r"(b), "r"(c), "r"(d) : "memory");
}
__device__ __forceinline__ void stg64(void* p, uint32_t a, uint32_t b) {
    asm volatile("st.relaxed.gpu.global.v2.u32 [%0], {%1,%2};" :: "l"(p), "r"(a), "r"(b) : "memory");
}
__device__ __forceinline__ void sts128(uint32_t a, uint32_t x, uint32_t y, uint32_t z, uint32_t w) {
    asm volatile("st.shared.v4.u32 [%0], {%1,%2,%3,%4};" :: "r"(a), "r"(x), "r"(y), "r"(z), "r"(w) : "memory");
}
__device__ __forceinline__ void sts32(uint32_t a, uint32_t x) { asm volatile("st.shared.u32 [%0], %1;" :: "r"(a), "r"(x) : "memory"); }
__device__ __forceinline__ float4 lds128f(uint32_t a) {
    float4 v; asm volatile("ld.shared.v4.f32 {%0,%1,%2,%3}, [%4];" : "=f"(v.x), "=f"(v.y), "=f"(v.z), "=f"(v.w) : "r"(a) : "memory"); return v;
}
__device__ __forceinline__ uint32_t lds32(uint32_t a) { uint32_t v; asm volatile("ld.shared.u32 %0, [%1];" : "=r"(v) : "r"(a) : "memory"); return v; }
__device__ __forceinline__ bool has_sent(const uint4& v) { return (v.x == SENT) | (v.w == SENT); }
__device__ __forceinline__ bool has_zero(const uint4& v) { return min(min(v.x, v.y), min(v.z, v.w)) == 0u; }
__device__ __forceinline__ uint32_t nonzero(uint32_t w) { return w == 0u ? 0x8000u : w; }
__device__ __forceinline__ void stg32(void* p, uint32_t a) { asm volatile("st.relaxed.gpu.global.u32 [%0], %1;" :: "l"(p), "r"(a) : "memory"); }
__device__ __forceinline__ void wait_count(const unsigned* p, unsigned target) {
    unsigned v; int spins = 0;
    do { asm volatile("ld.acquire.gpu.global.u32 %0, [%1];" : "=r"(v) : "l"(p) : "memory"); } while (__any_sync(0xffffffffu, v != target) && ++spins < SPIN_LIMIT);
}
__device__ __forceinline__ void warp_done(uint32_t bar) {
    __syncwarp();
    asm volatile("{.reg .pred p; setp.eq.u32 p, %1, 0; @p mbarrier.arrive.shared::cta.b64 _, [%0];}" :: "r"(bar), "r"(threadIdx.x & 31) : "memory");
}
__device__ __forceinline__ uint32_t mul_bf16x2(uint32_t a, uint32_t b) { uint32_t r; asm("mul.rn.bf16x2 %0, %1, %2;" : "=r"(r) : "r"(a), "r"(b)); return r; }
__device__ __forceinline__ uint32_t fma_bf16x2(uint32_t a, uint32_t b, uint32_t c) { uint32_t r; asm("fma.rn.bf16x2 %0, %1, %2, %3;" : "=r"(r) : "r"(a), "r"(b), "r"(c)); return r; }
__device__ __forceinline__ uint32_t add_bf16x2(uint32_t a, uint32_t b) { uint32_t r; asm("add.rn.bf16x2 %0, %1, %2;" : "=r"(r) : "r"(a), "r"(b)); return r; }

#define R4(d, o) "+f"(d[o + 0]), "+f"(d[o + 1]), "+f"(d[o + 2]), "+f"(d[o + 3])
#define R8(d, o) R4(d, o), R4(d, o + 4)
#define R32(d) R8(d, 0), R8(d, 8), R8(d, 16), R8(d, 24)
#define D32 "{%0,%1,%2,%3,%4,%5,%6,%7,%8,%9,%10,%11,%12,%13,%14,%15,%16,%17,%18,%19,%20,%21,%22,%23,%24,%25,%26,%27,%28,%29,%30,%31}"
#define D64 "{%0,%1,%2,%3,%4,%5,%6,%7,%8,%9,%10,%11,%12,%13,%14,%15,%16,%17,%18,%19,%20,%21,%22,%23,%24,%25,%26,%27,%28,%29,%30,%31,%32,%33,%34,%35,%36,%37,%38,%39,%40,%41,%42,%43,%44,%45,%46,%47,%48,%49,%50,%51,%52,%53,%54,%55,%56,%57,%58,%59,%60,%61,%62,%63}"
#define D48 "{%0,%1,%2,%3,%4,%5,%6,%7,%8,%9,%10,%11,%12,%13,%14,%15,%16,%17,%18,%19,%20,%21,%22,%23,%24,%25,%26,%27,%28,%29,%30,%31,%32,%33,%34,%35,%36,%37,%38,%39,%40,%41,%42,%43,%44,%45,%46,%47}"

__device__ __forceinline__ void mma_qk_f16(float (&d)[32], uint64_t da, uint64_t db) {
    asm volatile("{.reg .pred p; setp.eq.b32 p, 0, 0; wgmma.mma_async.sync.aligned.m64n64k16.f32.f16.f16 " D32 ", %32, %33, p, 1, 1, 0, 0;}"
                 : R32(d) : "l"(da), "l"(db));
}
__device__ __forceinline__ void mma_qk_bf16(float (&d)[32], uint64_t da, uint64_t db) {
    asm volatile("{.reg .pred p; setp.ne.b32 p, 0, 0; wgmma.mma_async.sync.aligned.m64n64k16.f32.bf16.bf16 " D32 ", %32, %33, p, 1, 1, 0, 0;}"
                 : R32(d) : "l"(da), "l"(db));
}
__device__ __forceinline__ void mma_pv(float (&d)[12], const uint32_t* a, uint64_t db) {
    asm volatile("{.reg .pred p; setp.eq.b32 p, 0, 0; wgmma.mma_async.sync.aligned.m64n24k16.f32.bf16.bf16 {%0,%1,%2,%3,%4,%5,%6,%7,%8,%9,%10,%11}, {%12,%13,%14,%15}, %16, p, 1, 1, 1;}"
                 : R8(d, 0), R4(d, 8) : "r"(a[0]), "r"(a[1]), "r"(a[2]), "r"(a[3]), "l"(db));
}
__device__ __forceinline__ void mma_ss128(float (&d)[64], uint64_t da, uint64_t db) {
    asm volatile("{.reg .pred p; setp.eq.b32 p, 0, 0; wgmma.mma_async.sync.aligned.m64n128k16.f32.bf16.bf16 " D64 ", %64, %65, p, 1, 1, 0, 1;}"
                 : R32(d), R8(d, 32), R8(d, 40), R8(d, 48), R8(d, 56) : "l"(da), "l"(db));
}
__device__ __forceinline__ void stsm4(uint32_t addr, uint32_t a, uint32_t b, uint32_t c, uint32_t d) {
    asm volatile("stmatrix.sync.aligned.m8n8.x4.shared.b16 [%0], {%1,%2,%3,%4};" :: "r"(addr), "r"(a), "r"(b), "r"(c), "r"(d) : "memory");
}
__device__ __forceinline__ void mma_ss8(float (&d)[4], uint64_t da, uint64_t db) {
    asm volatile("{.reg .pred p; setp.eq.b32 p, 0, 0; wgmma.mma_async.sync.aligned.m64n8k16.f32.bf16.bf16 {%0,%1,%2,%3}, %4, %5, p, 1, 1, 0, 1;}"
                 : R4(d, 0) : "l"(da), "l"(db));
}
__device__ __forceinline__ void mma_rs(float (&d)[32], const uint4& a, uint64_t db) {
    asm volatile("{.reg .pred p; setp.eq.b32 p, 0, 0; wgmma.mma_async.sync.aligned.m64n64k16.f32.bf16.bf16 " D32 ", {%32,%33,%34,%35}, %36, p, 1, 1, 1;}"
                 : R32(d) : "r"(a.x), "r"(a.y), "r"(a.z), "r"(a.w), "l"(db));
}
__device__ __forceinline__ void mma_rs(float (&d)[48], const uint4& a, uint64_t db) {
    asm volatile("{.reg .pred p; setp.eq.b32 p, 0, 0; wgmma.mma_async.sync.aligned.m64n96k16.f32.bf16.bf16 " D48 ", {%48,%49,%50,%51}, %52, p, 1, 1, 1;}"
                 : R32(d), R8(d, 32), R8(d, 40) : "r"(a.x), "r"(a.y), "r"(a.z), "r"(a.w), "l"(db));
}

constexpr float EXP_MAGIC = 256.0f + 127.0f + 64.0f - 1.58621f + 0.00390625f;
constexpr uint32_t MUFU_MASK = 0x1111u;
__device__ __forceinline__ uint32_t exp2_pair(float y0, float y1, uint32_t cexp, uint32_t neg1) {
    uint32_t w, m, e, r;
    asm("prmt.b32 %0, %1, %2, 0x6521;" : "=r"(w) : "r"(__float_as_uint(y0)), "r"(__float_as_uint(y1)));
    asm("lop3.b32 %0, %1, 0x007F007F, %2, 0xEA;" : "=r"(m) : "r"(w), "r"(cexp));
    asm("mad.lo.u32 %0, %1, %2, %3;" : "=r"(e) : "r"(m), "r"(neg1), "r"(w));
    asm("fma.rn.bf16x2 %0, %1, %2, %3;" : "=r"(r) : "r"(w), "r"(m), "r"(e));
    return r;
}

struct Params {
    const __nv_bfloat16* x;
    const __nv_bfloat16* wk;
    long long wv_off;
    const __nv_bfloat16* wqp;
    __nv_bfloat16* out;
    uint32_t neg1, pad;
    const __nv_bfloat16* w1p;
    const __nv_bfloat16* w2p;
    CUtensorMap wq, wo, w1, w2;
    const __nv_bfloat16* wop;
};

__device__ __forceinline__ int f1_col0() { return ((blockIdx.x & 15) >> 1) * 176 + (blockIdx.x & 1) * 96; }
__device__ __forceinline__ void load_box(uint32_t sb, const CUtensorMap* tm, uint32_t dst, uint32_t bar, uint32_t bytes, int c0, int c1) {
    mbar_expect(sb + SM_MISC + bar * 8, bytes);
    tma2d(sb + dst, tm, c0, c1, sb + SM_MISC + bar * 8);
}
__device__ __forceinline__ void load_wq(uint32_t sb, const Params& P, int gi, int atom) {
    load_box(sb, &P.wq, SM_WQ + atom * 65536 + gi * 16384, MB_WQ + gi, 16384, (blockIdx.x & 3) * 128 + atom * 64, gi * 128);
}
__device__ __forceinline__ void load_wo(uint32_t sb, const Params& P, int kb) { load_box(sb, &P.wo, wo_slot(kb) * 8192, MB_WO, 8192, (blockIdx.x & 7) * 64, kb * 64); }
__device__ __forceinline__ void load_w2(uint32_t sb, const Params& P, int kb, int slot) { load_box(sb, &P.w2, slot * 8192, MB_W2 + kb, 8192, (blockIdx.x & 7) * 64, kb * 64); }
__device__ __forceinline__ void refill_job(uint32_t sb, const Params& P, int gi, int job) {
    const bool w1 = job < 3;
    load_box(sb, w1 ? &P.w1 : &P.wo, (w1 ? 8 + gi + 4 * job : 2 * gi + job - 3) * 8192, w1 ? MB_W1 : MB_WO, 8192,
             w1 ? f1_col0() + job * 32 : (blockIdx.x & 7) * 64, w1 ? gi * 128 : (2 * gi + job - 1) * 64);
}

constexpr int H_KV = 0, H_O = 1 - 16, H_H1 = 17, H_H2 = 49;
__device__ __forceinline__ void hint_arrive(int id) {
    if ((threadIdx.x & 31) == 0) asm volatile("red.relaxed.gpu.global.add.u32 [%0], 1;" :: "l"(g_s.hint[id]) : "memory");
}
__device__ __forceinline__ void hint_wait(int id, unsigned target) {
    uint32_t v; int spins = 0;
    do { asm volatile("ld.relaxed.gpu.global.u32 %0, [%1];" : "=r"(v) : "l"(g_s.hint[id]) : "memory"); } while (__any_sync(0xffffffffu, v != target) && ++spins < SPIN_LIMIT);
}

template <int KIND> __host__ __device__ constexpr int a_off(int st) { return KIND == 1 ? st * 128 : (st >> 2) * 1024 + (st & 3) * 128; }
template <int KIND, int S0, int N, int BS>
__device__ __forceinline__ void load_batch(uint4 (&buf)[BS], const uint4* a) {
#pragma unroll
    for (int s = 0; s < N; s++) buf[s] = ldg_relaxed(a + a_off<KIND>(S0 + s));
}
template <int N, int BS>
__device__ __forceinline__ bool batch_bad(const uint4 (&buf)[BS]) {
    uint32_t m = 0;
#pragma unroll
    for (int s = 0; s < N; s++) m = max(m, buf[s].x);
    return __any_sync(0xffffffffu, m == SENT);
}
template <int KIND, int S0, int N, int BS>
__device__ __forceinline__ void check_batch(uint4 (&buf)[BS], const uint4* a) {
    if (__builtin_expect(batch_bad<N>(buf), 0)) {
        int spins = 0;
        do load_batch<KIND, S0, N>(buf, a); while (batch_bad<N>(buf) && ++spins < SPIN_LIMIT);
    }
}
template <int KIND, int NST, int BS, int I, int NACC, class Mid>
__device__ __forceinline__ void gemm_batch(float (&acc)[NACC], uint4 (&cur)[BS], uint4 (&nxt)[BS], const uint4* a, uint32_t sb, int q, Mid&& mid TS_ARG) {
    constexpr int S0 = I * BS, N = (NST - S0 < BS) ? NST - S0 : BS, S1 = S0 + BS, N1 = (NST - S1 < BS) ? NST - S1 : BS;
    const uint32_t mb = sb + SM_MISC;
    if (KIND == 2) {
#pragma unroll
        for (int blk = S0 / 4; blk < (S0 + N) / 4; blk++) mbar_wait(mb + (MB_W2 + 2 * blk + q) * 8);
    }
    check_batch<KIND, S0, N>(cur, a);
    if constexpr (I >= 1 && S1 < NST) {
        wg_wait<0>();
        load_batch<KIND, S1, N1>(nxt, a);
        if (KIND == 1 && S0 / 8 > (S0 - BS) / 8) warp_done(mb + (MB_REL + S0 / 8 - 1) * 8);
    }
    wg_fence();
#pragma unroll
    for (int s = 0; s < N; s++) {
        const int st = S0 + s, blk = st >> 2;
        if (KIND == 1) mma_rs(acc, cur[s], mkdesc(sb + (8 + (st >> 3)) * 8192 + (st & 7) * 1024, 32768, 512, 2));
        else mma_rs(acc, cur[s], mkdesc(sb + (KIND == 0 ? (q ? wo_slot(2 * blk + 1) : wo_slot(2 * blk)) : (q ? w2_slot(2 * blk + 1) : w2_slot(2 * blk))) * 8192 + (st & 3) * 2048, 16, 1024, 1));
    }
    wg_commit();
    if constexpr (S1 < NST) {
        mid(I);
        gemm_batch<KIND, NST, BS, I + 1>(acc, nxt, cur, a, sb, q, mid TS_PASS);
    } else {
        mid(I);
    }
}
template <int KIND, int NST, int BS, int NACC, class Mid>
__device__ __forceinline__ void gemm_rs(float (&acc)[NACC], const uint4* a, uint32_t sb, int q, Mid&& mid TS_ARG) {
    uint4 b0[BS], b1[BS];
    load_batch<KIND, 0, BS>(b0, a);
    load_batch<KIND, BS, BS>(b1, a);
    mid(-1);
#pragma unroll
    for (int i = 0; i < NACC; i++) acc[i] = 0.f;
    fence_regs(acc);
    gemm_batch<KIND, NST, BS, 0>(acc, b0, b1, a, sb, q, mid TS_PASS);
    wg_wait<0>();
    fence_regs(acc);
}

__device__ __forceinline__ void pair_reduce(const float (&acc)[32], float (&r)[16], uint32_t buf, int q, int barid) {
#pragma unroll
    for (int j = 0; j < 4; j++) {
        const int i = 4 * j;
        sts128(buf + q * 8192 + j * 2048, __float_as_uint(q ? acc[i] : acc[16 + i]), __float_as_uint(q ? acc[i + 1] : acc[17 + i]),
               __float_as_uint(q ? acc[i + 2] : acc[18 + i]), __float_as_uint(q ? acc[i + 3] : acc[19 + i]));
    }
#pragma unroll
    for (int i = 0; i < 16; i++) r[i] = q ? acc[16 + i] : acc[i];
    bar_sync(barid, 256);
#pragma unroll
    for (int j = 0; j < 4; j++) {
        const float4 v = lds128f(buf + (q ^ 1) * 8192 + j * 2048);
        r[4 * j] += v.x; r[4 * j + 1] += v.y; r[4 * j + 2] += v.z; r[4 * j + 3] += v.w;
    }
}

__device__ __forceinline__ float quad_sum(float v) { v += __shfl_xor_sync(0xffffffffu, v, 1); v += __shfl_xor_sync(0xffffffffu, v, 2); return v; }
__device__ __forceinline__ float reduce4(const float (&st)[4], int lane) {
    const bool u16 = lane & 16, u8 = lane & 8;
    const float a0 = (u16 ? st[2] : st[0]) + __shfl_xor_sync(0xffffffffu, u16 ? st[0] : st[2], 16);
    const float a1 = (u16 ? st[3] : st[1]) + __shfl_xor_sync(0xffffffffu, u16 ? st[1] : st[3], 16);
    float v = (u8 ? a1 : a0) + __shfl_xor_sync(0xffffffffu, u8 ? a0 : a1, 8);
    v += __shfl_xor_sync(0xffffffffu, v, 4); v += __shfl_xor_sync(0xffffffffu, v, 2); v += __shfl_xor_sync(0xffffffffu, v, 1);
    return v;
}
__device__ __forceinline__ float silu2(float h) { float t; asm("tanh.approx.f32 %0, %1;" : "=f"(t) : "f"(h)); return fmaf(h, t, h); }

template <bool SAFE>
__device__ __forceinline__ void attention(const Params& P, uint32_t sb, int warp TS_ARG) {
    const uint32_t mb = sb + SM_MISC;
    const int tid = threadIdx.x, lane = tid & 31, b = blockIdx.x;
    const int wg = warp >> 2, ww = warp & 3, job = 3 - wg + 4 * ww;
    const uint32_t cexp = 0x9F809F80u + (tid >> 12);
    const uint32_t neg1 = P.neg1;
    unsigned cnt = 0;
    if (SAFE && warp == 8) asm volatile("ld.relaxed.gpu.global.u32 %0, [%1];" : "=r"(cnt) : "l"(&g_s.count1) : "memory");
#pragma unroll 1
    for (int pass = 0; pass < 2; pass++) {
    float o[12], s[32];
    const uint64_t dq = mkdesc(sb + SM_Q + (pass * 4 + wg) * 2048, 128, 256, 0);
    uint64_t dk = mkdesc(sb + SM_K, 128, 256, 0), dv = mkdesc(sb + SM_V, 128, 32768, 0);
    float m0 = -INFINITY, m1 = -INFINITY;
#pragma unroll
    for (int i = 0; i < 12; i++) o[i] = 0.f;
#pragma unroll
    for (int i = 0; i < 32; i++) s[i] = ((MUFU_MASK >> (i / 2)) & 1) ? 0.f : EXP_MAGIC;
    fence_regs(s); fence_regs(o);
    wg_fence();
    if (SAFE) mma_qk_f16(s, dq, dk + 31 * 128); else mma_qk_bf16(s, dq, dk + 31 * 128);
    wg_commit();
    wg_wait<0>(); fence_regs(s);
#pragma unroll 1
    for (int u = pass ? 3 : (wg == 2) ? 0 : 1; u < (pass ? 8 : 3); u++) {
        int n = 2 * ((((wg == 2) ? 0x22444C31u : 0x22444C40u) >> (4 * u)) & 15);
#pragma unroll 1
        do {
            uint32_t p[16];
            if (SAFE) {
#pragma unroll
                for (int j = 0; j < 16; j++) {
                    if ((MUFU_MASK >> j) & 1) p[j] = pack_bf16(ex2(s[2 * j]), ex2(s[2 * j + 1]));
                    else p[j] = exp2_pair(s[2 * j], s[2 * j + 1], cexp, neg1);
                }
            } else {
                fence_regs(o);
                float x0 = m0, x1 = m1;
#pragma unroll
                for (int j = 0; j < 8; j++) { x0 = fmaxf(x0, fmaxf(s[4 * j], s[4 * j + 1])); x1 = fmaxf(x1, fmaxf(s[4 * j + 2], s[4 * j + 3])); }
                x0 = fmaxf(x0, __shfl_xor_sync(0xffffffffu, x0, 1)); x0 = fmaxf(x0, __shfl_xor_sync(0xffffffffu, x0, 2));
                x1 = fmaxf(x1, __shfl_xor_sync(0xffffffffu, x1, 1)); x1 = fmaxf(x1, __shfl_xor_sync(0xffffffffu, x1, 2));
                const float c0 = ex2(m0 - x0), c1 = ex2(m1 - x1);
                m0 = x0; m1 = x1;
#pragma unroll
                for (int j = 0; j < 3; j++) { o[4 * j] *= c0; o[4 * j + 1] *= c0; o[4 * j + 2] *= c1; o[4 * j + 3] *= c1; }
#pragma unroll
                for (int j = 0; j < 8; j++) {
                    p[2 * j] = pack_bf16(ex2(s[4 * j] - m0), ex2(s[4 * j + 1] - m0));
                    p[2 * j + 1] = pack_bf16(ex2(s[4 * j + 2] - m1), ex2(s[4 * j + 3] - m1));
                }
                fence_regs(o);
            }
            fence_regs(p);
            wg_fence();
            if (SAFE) mma_qk_f16(s, dq, dk); else mma_qk_bf16(s, dq, dk);
#pragma unroll
            for (int j = 0; j < 4; j++) mma_pv(o, p + 4 * j, dv + j * 16);
            wg_commit();
            dk += 128; dv += 64;
            wg_wait<0>(); fence_regs(s);
        } while (--n > 0);
        if (u == 2 || u == 7) {
            fence_regs(o);
            const float i0 = rcp(o[8]), i1 = rcp(o[10]);
            if (u == 7) mbar_wait(mb + MB_F2 * 8);
            stg128(g_x + X_OF + (((u == 7) * 16 + (b >> 3)) * 32 + (b & 3) * 8 + 2 * wg + (ww >> 1)) * 128 + (((b >> 2) & 1) * 2 + (ww & 1)) * 32 + lane,
                   pack_bf16(o[0] * i0, o[1] * i0), pack_bf16(o[2] * i1, o[3] * i1), pack_bf16(o[4] * i0, o[5] * i0), pack_bf16(o[6] * i1, o[7] * i1));
            if (u == 2) asm volatile("cp.async.bulk.wait_group 0;" ::: "memory");
            else hint_arrive(H_O + 16 + (b >> 3));
            warp_done(mb + (MB_DONE + (u == 7) * 4) * 8);
            TS(5 + (u == 7));
        } else if (u >= 3) {
            if (u < 6) warp_done(mb + (MB_DONE + u - 2) * 8);
            if (job < (u == 3 ? 2 : 5)) {
                mbar_wait(mb + (MB_DONE + u - 3) * 8);
                if (lane == 0) {
                    if (u > 3) refill_job(sb, P, u - 4, job);
                    else if (job == 1) load_wo(sb, P, 1);
                    else asm volatile("red.release.gpu.global.add.u32 [%0], 1;" :: "l"(&g_s.count2) : "memory");
                }
            } else if (warp == 11) {
                if (u == 5) asm volatile("ld.relaxed.gpu.global.u32 %0, [%1];" : "=r"(cnt) : "l"(&g_s.count2) : "memory");
                if (u == 6) {
                    const unsigned target = lds32(mb + MISC_EPOCH) * NCTA;
                    if (__any_sync(0xffffffffu, cnt != target)) wait_count(&g_s.count2, target);
                    asm volatile("fence.acquire.gpu;" ::: "memory");
                    warp_done(mb + MB_F2 * 8);
                }
            }
        } else if (u == 1) {
            if (SAFE) mbar_wait(mb + MB_KV * 8);
            TS(17);
    if (lane == 0) {
        if (job < 9) {
            asm volatile("cp.async.bulk.global.shared::cta.bulk_group [%0], [%1], %2;"
                         :: "l"(g_x + X_ARM + b * X_SHARE + job * 512), "r"(sb + SM_SENT), "r"(job < 8 ? 8192 : (X_SHARE - 4096) * 16) : "memory");
            asm volatile("cp.async.bulk.commit_group;" ::: "memory");
        } else if (job == 9) load_wo(sb, P, 0);
    }
        } else if (SAFE) {
            if (warp == 8) {
                const unsigned target = lds32(mb + MISC_EPOCH) * NMAIN;
                if (__any_sync(0xffffffffu, cnt != target)) wait_count(&g_s.count1, target);
                if (lane == 0) {
                    asm volatile("fence.acquire.gpu; fence.proxy.async.global;" ::: "memory");
                    mbar_expect(mb + MB_KV * 8, 47104 + 2 * 24576);
                    bulk_g2s(sb + SM_K + 16384, g_s.kv + 1024, 47104, mb + MB_KV * 8);
                    bulk_g2s(sb + SM_V + 8192, g_s.kv + 4096 + 512, 24576, mb + MB_KV * 8);
                    bulk_g2s(sb + SM_V + 32768 + 8192, g_s.kv + 6144 + 512, 24576, mb + MB_KV * 8);
                }
            }
        }
        __syncwarp();
    }
    }
}

__device__ __forceinline__ int kv_slot() {
    const int t = (threadIdx.x & 63) >> 1, c = 2 * (blockIdx.x >> 2) + (threadIdx.x & 1), hg = blockIdx.x & 3;
    return hg < 2 ? ((t + 31) & 31) * 128 + (c >> 3) * 16 + (hg & 1) * 8 + (c & 7) : 4096 + (hg & 1) * 2048 + t * 64 + c;
}
#define LEAD_AT 3

__device__ __noinline__ void helper_cta(const Params& P, uint8_t* smem) {
    const int tid = threadIdx.x, b = blockIdx.x, hi = b - NMAIN;
    const unsigned epoch = g_s.epoch[b] + 1;
    float* red = reinterpret_cast<float*>(smem);
    if (tid < 32) wait_count(&g_s.count1, epoch * NMAIN);
    __syncthreads();
    if (tid == 480) {
        for (int i = 0; i < 8; i++) asm volatile("cp.async.bulk.prefetch.L2.global [%0], %1;" :: "l"((const char*)P.wop + hi * 131072 + i * 16384), "r"(16384) : "memory");
        for (int i = 0; i < 43; i++) asm volatile("cp.async.bulk.prefetch.L2.global [%0], %1;" :: "l"((const char*)P.w2p + hi * 352256 + i * 8192), "r"(8192) : "memory");
    }
    if (tid < 344) {
        const int cg = tid % 43, rp = tid / 43;
        const uint4* src = reinterpret_cast<const uint4*>(P.w1p + (size_t)rp * 64 * FF + (hi * 43 + cg) * 8);
        float s[8] = {0, 0, 0, 0, 0, 0, 0, 0};
#pragma unroll 8
        for (int r = 0; r < 64; r++) {
            uint4 v = __ldg(src + r * (FF / 8));
            s[0] += bf_lo(v.x); s[1] += bf_hi(v.x); s[2] += bf_lo(v.y); s[3] += bf_hi(v.y);
            s[4] += bf_lo(v.z); s[5] += bf_hi(v.z); s[6] += bf_lo(v.w); s[7] += bf_hi(v.w);
        }
        float* part = red + (rp * 43 + cg) * 8;
#pragma unroll
        for (int i = 0; i < 8; i++) part[i] = s[i];
    }
    __syncthreads();
    if (tid < 344) {
        float s = 0.f;
#pragma unroll
        for (int rp = 0; rp < 8; rp++) s += red[rp * 344 + tid];
        g_s.cs[hi * 344 + tid] = s;
    } else if (hi == 3 && tid < 344 + 64) g_s.cs[FF + tid - 344] = 0.f;
    __syncthreads();
    if (tid == 0) {
        asm volatile("red.release.gpu.global.add.u32 [%0], 1;" :: "l"(&g_s.count2) : "memory");
        g_s.epoch[b] = epoch;
    }
}

__global__ void __launch_bounds__(512, 1) fused_kernel(const __grid_constant__ Params P) {
    extern __shared__ __align__(1024) uint8_t smem[];
    const uint32_t sb = (uint32_t)__cvta_generic_to_shared(smem);
    const uint32_t mb = sb + SM_MISC;
    const int tid = threadIdx.x, lane = tid & 31, b = blockIdx.x;
    if (b >= NMAIN) { helper_cta(P, smem); return; }
    const int tg = b >> 2, hg = b & 3;
    const int warp = __shfl_sync(0xffffffffu, tid >> 5, 0);

    uint4 xv[4][2];
    unsigned epoch = 0;
    {
        const int r = (tid >> 5) * 4;
        const uint4* src = reinterpret_cast<const uint4*>(P.x + (size_t)((r & 31) + tg * 32 + (r >> 5) * 1024) * D) + lane;
#pragma unroll
        for (int i = 0; i < 4; i++) { xv[i][0] = ldg_relaxed(src + i * 64); xv[i][1] = ldg_relaxed(src + i * 64 + 32); }
    }
    const uint4 wkv = ldg_relaxed(reinterpret_cast<const uint4*>(reinterpret_cast<const char*>(P.wk) + (hg < 2 ? 0 : P.wv_off)) + tid * 2 + (hg & 1));
    const int wg = warp >> 2, ww = warp & 3, g = lane >> 2, t4 = lane & 3, t128 = tid & 127;
    if (lane == 0) {
        mbar_init(mb + warp * 8, warp < 4 ? 2 : warp < 14 ? 16 : warp == 14 ? 8 : 13);
        mbar_init(mb + (16 + warp) * 8, 1);
        if (warp < 10) mbar_init(mb + (32 + warp) * 8, warp < 8 ? 1 : 8);
        if (warp < 4) {
            asm volatile("fence.mbarrier_init.release.cluster;" ::: "memory");
            load_wq(sb, P, warp, 0);
            if (warp < 3) load_wq(sb, P, warp, 1);
        } else if (warp < 7) {
            asm volatile("prefetch.tensormap [%0];" :: "l"(&P.wo + (warp - 4)) : "memory");
        } else if (warp == 7) {
            asm volatile("ld.relaxed.gpu.global.u32 %0, [%1];" : "=r"(epoch) : "l"(g_s.epoch + b) : "memory");
        } else if (warp == 8) {
            sts128(mb + MISC_NRM, 0, 0, 0, 0);
        }
    }
    __syncwarp();
    TS(16);
    float dlt;
    {
        float st[4];
#pragma unroll
        for (int i = 0; i < 4; i++) {
            const uint32_t s = add_bf16x2(add_bf16x2(add_bf16x2(xv[i][0].x, xv[i][0].y), add_bf16x2(xv[i][0].z, xv[i][0].w)),
                                          add_bf16x2(add_bf16x2(xv[i][1].x, xv[i][1].y), add_bf16x2(xv[i][1].z, xv[i][1].w)));
            st[i] = bf_lo(s) + bf_hi(s);
        }
        TS(13);
        const float tot = reduce4(st, lane) * (-1.0f / D);
        const uint32_t nmr = pack_bf16(tot, tot);
        dlt = bf_lo(nmr) - tot;
        const uint32_t xa = sb + SM_XN + (lane >> 3) * 8192 + warp * 512;
#pragma unroll
        for (int i = 0; i < 4; i++) {
            const uint32_t nm = __shfl_sync(0xffffffffu, nmr, i * 8);
            const uint32_t addr = xa + i * 128 + (((lane & 7) ^ ((warp & 1) * 4 + i)) << 4);
#pragma unroll
            for (int c = 0; c < 2; c++) {
                xv[i][c].x = add_bf16x2(xv[i][c].x, nm); xv[i][c].y = add_bf16x2(xv[i][c].y, nm);
                xv[i][c].z = add_bf16x2(xv[i][c].z, nm); xv[i][c].w = add_bf16x2(xv[i][c].w, nm);
                sts128(addr + c * 32768, xv[i][c].x, xv[i][c].y, xv[i][c].z, xv[i][c].w);
            }
        }
    }
    sts128(sb + SM_WKV + tid * 16, wkv.x, wkv.y, wkv.z, wkv.w);
    fence_async_smem();
    TS(0);
    __syncthreads();
    auto variances = [&]() {
        float st[4];
#pragma unroll
        for (int i = 0; i < 4; i++) {
            float v = 0.f;
#pragma unroll
            for (int c = 0; c < 2; c++) {
                const uint32_t a = fma_bf16x2(xv[i][c].x, xv[i][c].x, mul_bf16x2(xv[i][c].y, xv[i][c].y));
                const uint32_t d = fma_bf16x2(xv[i][c].z, xv[i][c].z, mul_bf16x2(xv[i][c].w, xv[i][c].w));
                v += (bf_lo(a) + bf_hi(a)) + (bf_lo(d) + bf_hi(d));
            }
            st[i] = v;
        }
        const float vs = reduce4(st, lane), dl = dlt;
        if ((lane & 7) == 0) sts32(mb + MISC_RSTD + (warp * 4 + (lane >> 3)) * 4, __float_as_uint(rsqrtf(fmaxf(vs * (1.0f / D) - dl * dl, 0.f) + 1e-5f)));
    };
    float kv[4] = {0.f, 0.f, 0.f, 0.f};
    if (wg == 2) {
        fence_regs(kv);
        const uint64_t da = mkdesc(sb + SM_XN, 16, 1024, 1), db = mkdesc(sb + SM_WKV, 128, 16, 0);
        wg_fence();
#pragma unroll
        for (int s = 0; s < 32; s++) mma_ss8(kv, da + (s >> 2) * 512 + (s & 3) * 2, db + s * 16);
        wg_commit();
        TS(18);
        variances();
        wg_wait<0>(); fence_regs(kv);
        TS(20);
    } else {
        variances();
        if (tid == 7 * 32) { sts32(mb + MISC_EPOCH, epoch + 1); g_s.epoch[b] = epoch + 1; }
        TS(19);
    }
    __syncthreads();
    constexpr float QSCALE = 0.25f * 1.4426950408889634f;
    float qa[64];
    const uint32_t qbase = sb + SM_Q + (ww >> 1) * 8192 + (ww & 1) * 512 + lane * 16;
    if (wg == 0) {
#pragma unroll
        for (int i = 0; i < 64; i++) qa[i] = 0.f;
        fence_regs(qa);
        const uint64_t da = mkdesc(sb + SM_XN, 16, 1024, 1), db = mkdesc(sb + SM_WQ, 65536, 1024, 1);
#pragma unroll 1
        for (int i = 0; i < 4; i++) {
            mbar_wait(mb + (MB_WQ + i) * 8);
            if (i == 0) TS(21); if (i == 3) TS(22);
            wg_fence();
#pragma unroll
            for (int s = 0; s < 8; s++) mma_ss128(qa, da + (i * 2 + (s >> 2)) * 512 + (s & 3) * 2, db + (i * 8 + s) * 128);
            wg_commit();
        }
        const float rs0 = __uint_as_float(lds32(mb + MISC_RSTD + (ww * 16 + g) * 4)) * QSCALE, rs1 = __uint_as_float(lds32(mb + MISC_RSTD + (ww * 16 + g + 8) * 4)) * QSCALE;
        wg_wait<0>();
        fence_regs(qa);
        bar_arrive(6, 256);
        bar_sync(5, 256);
        TS(1);
        uint32_t nm = 0;
#pragma unroll
        for (int h = 0; h < 8; h++) {
#pragma unroll
            for (int i = 0; i < 8; i++) qa[8 * h + i] *= (i & 2) ? rs1 : rs0;
            stsm4(qbase + h * 1024, pack_f16(qa[8 * h], qa[8 * h + 1]), pack_f16(qa[8 * h + 4], qa[8 * h + 5]), pack_f16(qa[8 * h + 2], qa[8 * h + 3]), pack_f16(qa[8 * h + 6], qa[8 * h + 7]));
            const float n0 = qa[8 * h] * qa[8 * h] + qa[8 * h + 1] * qa[8 * h + 1] + qa[8 * h + 4] * qa[8 * h + 4] + qa[8 * h + 5] * qa[8 * h + 5];
            const float n1 = qa[8 * h + 2] * qa[8 * h + 2] + qa[8 * h + 3] * qa[8 * h + 3] + qa[8 * h + 6] * qa[8 * h + 6] + qa[8 * h + 7] * qa[8 * h + 7];
            nm = max(nm, max(__float_as_uint(n0), __float_as_uint(n1)));
        }
        nm = __reduce_max_sync(0xffffffffu, __float_as_uint(quad_sum(__uint_as_float(nm))));
        if (lane == 0) asm volatile("red.shared.max.u32 [%0], %1;" :: "r"(mb + MISC_NRM), "r"(nm) : "memory");
    } else if (wg == 1) {
        bar_sync(5, 256);
#pragma unroll
        for (int i = 0; i < 16; i++) sts128(sb + SM_V + 65536 + (i * 128 + t128) * 16, 0x3F803F80u, 0x3F803F80u, 0x3F803F80u, 0x3F803F80u);
#pragma unroll
        for (int i = 0; i < 4; i++) sts128(sb + SM_SENT + (i * 128 + t128) * 16, SENT, SENT, SENT, SENT);
    } else if (wg == 2) {
        const float rs0 = __uint_as_float(lds32(mb + MISC_RSTD + (ww * 16 + g) * 4)), rs1 = __uint_as_float(lds32(mb + MISC_RSTD + (ww * 16 + g + 8) * 4));
        kv[0] *= rs0; kv[1] *= rs0; kv[2] *= rs1; kv[3] *= rs1;
        float2* kt = reinterpret_cast<float2*>(smem + SM_MISC + MISC_KTMP);
        kt[(ww * 16 + g) * 4 + t4] = make_float2(kv[0], kv[1]); kt[(ww * 16 + g + 8) * 4 + t4] = make_float2(kv[2], kv[3]);
        float n0 = kv[0] * kv[0] + kv[1] * kv[1], n1 = kv[2] * kv[2] + kv[3] * kv[3];
        n0 += __shfl_xor_sync(0xffffffffu, n0, 1); n1 += __shfl_xor_sync(0xffffffffu, n1, 1);
        n0 += __shfl_xor_sync(0xffffffffu, n0, 2); n1 += __shfl_xor_sync(0xffffffffu, n1, 2);
        const uint32_t nm = __reduce_max_sync(0xffffffffu, max(__float_as_uint(n0), __float_as_uint(n1)));
        if (lane == 0) sts32(mb + MISC_WNRM + ww * 4, nm | 1u);
        bar_sync(2, 128);
        const uint32_t ra = mb + MISC_KTMP + ((t128 & 1) * 32 + ((t128 & 63) >> 1)) * 32;
        const float4 c0 = lds128f(ra), c1 = lds128f(ra + 16);
        const int kvoff = kv_slot();
        if (ww < 2) {
            if (hg < 2) {
                float4 p0 = lds128f(ra - 32), p1 = lds128f(ra - 16);
                if (t128 < 2) { p0 = make_float4(0.f, 0.f, 0.f, 0.f); p1 = p0; }
                stg128(g_s.kv + kvoff, nonzero(pack_f16(c0.x - p0.x, c0.y - p0.y)), pack_f16(c0.z - p0.z, c0.w - p0.w), pack_f16(c1.x - p1.x, c1.y - p1.y), pack_f16(c1.z - p1.z, c1.w - p1.w));
            } else {
                stg128(g_s.kv + kvoff, nonzero(pack_bf16(c0.x, c0.y)), pack_bf16(c0.z, c0.w), pack_bf16(c1.x, c1.y), pack_bf16(c1.z, c1.w));
            }
            if (t128 < 2) { const float4 w = lds128f(mb + MISC_WNRM); stg128(g_s.nrm + b * 2 + t128, __float_as_uint(w.x), __float_as_uint(w.y), __float_as_uint(w.z), __float_as_uint(w.w)); }
            hint_arrive(H_KV);
        } else if (hg < 2) {
            stg128(g_s.kplain + kvoff, pack_bf16(c0.x, c0.y), pack_bf16(c0.z, c0.w), pack_bf16(c1.x, c1.y), pack_bf16(c1.z, c1.w));
        }
        TS(1);
        bar_sync(2, 128);
        if (t128 == 96) asm volatile("red.release.gpu.global.add.u32 [%0], 1;" :: "l"(&g_s.count1) : "memory");
        __syncwarp();
    } else {
        if (tid == 13 * 32) load_wq(sb, P, 3, 1);
        __syncwarp();
        uint4 kc[18];
        auto src = [&](int i) { return i < 8 ? g_s.kv + i * 128 : i < 12 ? g_s.kv + 4096 + (i - 8) * 128 : i < 16 ? g_s.kv + 6144 + (i - 12) * 128 : i == 16 ? g_s.kv + 31 * 128 : g_s.nrm + t128; };
        hint_wait(H_KV, lds32(mb + MISC_EPOCH) * (NMAIN * 2));
        TS(1);
        int spins = 0;
        while (true) {
#pragma unroll
            for (int i = 0; i < 18; i++) kc[i] = ldg_relaxed(src(i) + t128);
            uint32_t mn = 1;
#pragma unroll
            for (int i = 0; i < 18; i++) mn = min(mn, kc[i].x);
            if (!__any_sync(0xffffffffu, mn == 0u) || ++spins >= SPIN_LIMIT) break;
        }
        uint32_t nm = max(max(kc[17].x, kc[17].y), max(kc[17].z, kc[17].w));
        nm = max(nm, __shfl_xor_sync(0xffffffffu, nm, 4)); nm = max(nm, __shfl_xor_sync(0xffffffffu, nm, 8)); nm = max(nm, __shfl_xor_sync(0xffffffffu, nm, 16));
        if (lane < 4) asm volatile("red.shared.max.u32 [%0], %1;" :: "r"(mb + MISC_NRM + 4 + min(lane, 2) * 4), "r"(nm) : "memory");
        TS(2);
        bar_sync(6, 256);
#pragma unroll
        for (int i = 0; i < 17; i++) sts128(sb + (uint32_t)(src(i) - g_s.kv + t128) * 16, kc[i].x, kc[i].y, kc[i].z, kc[i].w);
    }
    fence_async_smem();
    TS(3);
    __syncthreads();
    const float4 nr = lds128f(mb + MISC_NRM);
    const bool safe = __all_sync(0xffffffffu, (nr.x * (nr.y + nr.z) <= 3500.0f) && (nr.x <= 65536.0f) && (nr.y + nr.z <= 65536.0f) && (nr.w <= 1e24f));
    TS(4);

    if (__builtin_expect(safe, 1)) {
        attention<true>(P, sb, warp TS_PASS);
    } else {
        if (wg == 0) {
#pragma unroll
            for (int h = 0; h < 8; h++)
                stsm4(qbase + h * 1024, pack_bf16(qa[8 * h], qa[8 * h + 1]), pack_bf16(qa[8 * h + 4], qa[8 * h + 5]), pack_bf16(qa[8 * h + 2], qa[8 * h + 3]), pack_bf16(qa[8 * h + 6], qa[8 * h + 7]));
            fence_async_smem();
        } else if (warp == 15) {
            wait_count(&g_s.count1, lds32(mb + MISC_EPOCH) * NMAIN);
            if (lane == 0) {
                asm volatile("fence.proxy.async;" ::: "memory");
                mbar_expect(mb + MB_KV * 8, 131072);
                bulk_g2s(sb + SM_K, g_s.kplain, 65536, mb + MB_KV * 8);
                bulk_g2s(sb + SM_V, g_s.kv + 4096, 65536, mb + MB_KV * 8);
            }
            __syncwarp();
        }
        __syncthreads();
        mbar_wait(mb + MB_KV * 8);
        attention<false>(P, sb, warp TS_PASS);
    }

    const int pr = 1 - (wg >> 1), q = wg & 1;
    const int mt = 16 * pr + (b >> 3), j = b & 7;
    const uint32_t xbuf = sb + (pr ? 6 * 8192 : SM_Q) + t128 * 16;
    uint32_t hk[8];
    epoch = lds32(mb + MISC_EPOCH);
    {
        const uint4* a = g_x + X_OF + (mt * 32 + q * 4) * 128 + t128;
        if (pr) {
            if (warp < 3) {
                mbar_wait(mb + (MB_DONE + 4) * 8);
                if (lane == 0) refill_job(sb, P, 3, warp);
            } else if (warp == 4) {
                if (lane < 24) {
                    const uint4 v = ldg_relaxed(reinterpret_cast<const uint4*>(g_s.cs + f1_col0()) + lane);
                    sts128(mb + MISC_CS + lane * 16, v.x, v.y, v.z, v.w);
                }
                warp_done(mb + MB_W1 * 8);
            }
            __syncwarp();
            hint_wait(H_O + mt, epoch * 128);
        }
        TS(23);
        float acc[32], r[16];
        gemm_rs<0, 16, 8>(acc, a, sb, q, [&](int i) {
            if (i == -1) {
                const uint32_t* xp = reinterpret_cast<const uint32_t*>(P.x + (size_t)(mt * 64 + ww * 16 + g) * D + j * 64 + q * 32 + t4 * 2);
#pragma unroll
                for (int k = 0; k < 4; k++) { hk[2 * k] = __ldg(xp + k * 4); hk[2 * k + 1] = __ldg(xp + k * 4 + 8 * (D / 2)); }
                mbar_wait(mb + MB_WO * 8);
            }
            if (i == 1) mbar_wait(mb + (MB_DONE + 4) * 8);
        } TS_PASS);
        TS(7);
        pair_reduce(acc, r, xbuf, q, 3 + pr);
#pragma unroll
        for (int i = 0; i < 8; i++) hk[i] = pack_bf16(r[2 * i] + bf_lo(hk[i]), r[2 * i + 1] + bf_hi(hk[i]));
        uint4* hp = g_x + X_HF + (mt * 32 + j * 4 + 2 * q) * 128 + t128;
        stg128(hp, hk[0], hk[1], hk[2], hk[3]);
        stg128(hp + 128, hk[4], hk[5], hk[6], hk[7]);
        hint_arrive(H_H1 + mt);
        warp_done(mb + (MB_DONE + 5) * 8);
        TS(8);
        float st[4] = {0.f, 0.f, 0.f, 0.f};
#pragma unroll
        for (int i = 0; i < 8; i++) {
            const float lo = bf_lo(hk[i]), hi = bf_hi(hk[i]);
            st[2 * (i & 1)] += lo + hi;
            st[2 * (i & 1) + 1] = fmaf(lo, lo, fmaf(hi, hi, st[2 * (i & 1) + 1]));
        }
#pragma unroll
        for (int o = 1; o < 4; o <<= 1)
#pragma unroll
            for (int i = 0; i < 4; i++) st[i] += __shfl_xor_sync(0xffffffffu, st[i], o);
        if (t4 == 0) stg128(g_x + X_ST + (mt * 16 + j * 2 + q) * 32 + ww * 8 + g, __float_as_uint(st[0]), __float_as_uint(st[1]), __float_as_uint(st[2]), __float_as_uint(st[3]));
        if (pr) {
            mbar_wait(mb + (MB_DONE + 5) * 8);
            if (lane == 0) { load_w2(sb, P, 2 + warp, warp < 2 ? 22 + warp : warp - 2); if (warp >= 6) load_w2(sb, P, warp - 6, warp); }
            __syncwarp();
        } else if (warp == 8 || warp == 9) {
            stg128(g_s.kv + kv_slot(), 0u, 0u, 0u, 0u);
            if (t128 < 2) stg128(g_s.nrm + b * 2 + t128, 0u, 0u, 0u, 0u);
        }
    }
    {
        const int mt1 = 16 * pr + (b >> 4) * 2 + q, sl = b & 15;
        const uint4* a = g_x + X_HF + mt1 * 32 * 128 + t128;
        float acc[48], nmean[2], hrstd[2];
        uint4 u[4];
        hint_wait(H_H1 + mt1, epoch * 64);
        TS(24);
        gemm_rs<1, 32, 6>(acc, a, sb, q, [&](int i) {
            const uint4* sp = g_x + X_ST + (mt1 * 16 + t4) * 32 + ww * 8 + g;
            if (i == -1) { mbar_wait(mb + MB_W1 * 8); if (pr) mbar_wait(mb + MB_LEAD * 8); TS(26); }
            if (i == LEAD_AT && !pr) warp_done(mb + MB_LEAD * 8);
            if (i == 4) load_batch<1, 0, 4>(u, sp);
            if (i == 5) {
                check_batch<1, 0, 4>(u, sp);
                float st[4];
                st[0] = (__uint_as_float(u[0].x) + __uint_as_float(u[1].x)) + (__uint_as_float(u[2].x) + __uint_as_float(u[3].x));
                st[1] = (__uint_as_float(u[0].y) + __uint_as_float(u[1].y)) + (__uint_as_float(u[2].y) + __uint_as_float(u[3].y));
                st[2] = (__uint_as_float(u[0].z) + __uint_as_float(u[1].z)) + (__uint_as_float(u[2].z) + __uint_as_float(u[3].z));
                st[3] = (__uint_as_float(u[0].w) + __uint_as_float(u[1].w)) + (__uint_as_float(u[2].w) + __uint_as_float(u[3].w));
#pragma unroll
                for (int o = 1; o < 4; o <<= 1)
#pragma unroll
                    for (int k = 0; k < 4; k++) st[k] += __shfl_xor_sync(0xffffffffu, st[k], o);
#pragma unroll
                for (int k = 0; k < 2; k++) {
                    nmean[k] = st[2 * k] * (-1.0f / D);
                    hrstd[k] = 0.5f * rsqrtf(fmaxf(fmaf(-nmean[k], nmean[k], st[2 * k + 1] * (1.0f / D)), 0.f) + 1e-5f);
                }
            }
        } TS_PASS);
        warp_done(mb + (MB_REL + 3) * 8);
        if (pr && warp < 6) {
            mbar_wait(mb + (MB_REL + 2 + (warp >= 3)) * 8);
            if (lane == 0) load_w2(sb, P, 16 + warp, warp < 3 ? 10 + 4 * warp : 4 * warp - 1);
            __syncwarp();
        }
        TS(9);
        uint4* hb = g_x + X_H + (mt1 * 88 + (sl >> 1) * 11 + (sl & 1) * 6) * 128 + t128;
#pragma unroll
        for (int k = 0; k < 6; k++) {
            if (k == 5 && (sl & 1)) break;
            uint32_t hv[4];
#pragma unroll
            for (int i = 0; i < 2; i++) {
                float2 cs;
                asm volatile("ld.shared.v2.f32 {%0,%1}, [%2];" : "=f"(cs.x), "=f"(cs.y) : "r"(mb + MISC_CS + (2 * k + i) * 32 + t4 * 8));
                const float* z = acc + 8 * k + 4 * i;
                hv[2 * i] = pack_bf16(silu2(hrstd[0] * fmaf(nmean[0], cs.x, z[0])), silu2(hrstd[0] * fmaf(nmean[0], cs.y, z[1])));
                hv[2 * i + 1] = pack_bf16(silu2(hrstd[1] * fmaf(nmean[1], cs.x, z[2])), silu2(hrstd[1] * fmaf(nmean[1], cs.y, z[3])));
            }
            stg128(hb + k * 128, hv[0], hv[1], hv[2], hv[3]);
        }
        hint_arrive(H_H2 + mt1);
        TS(10);
        if (!pr && warp < 14) {
            mbar_wait(mb + (MB_REL + (warp >= 11)) * 8);
            if (lane == 0) load_w2(sb, P, 2 + warp, warp < 11 ? 4 * warp - 24 : 4 * warp - 35);
            __syncwarp();
        }
    }
    {
        const uint4* a = g_x + X_H + (mt * 88 + q * 4) * 128 + t128;
        hint_wait(H_H2 + mt, epoch * 64);
        TS(25);
        float acc[32], r[16];
        gemm_rs<2, 44, 8>(acc, a, sb, q, [&](int i) {
            if (i == 1 && !pr) warp_done(mb + (MB_LEAD + 1) * 8);
            if (i == 5 && pr) mbar_wait(mb + (MB_LEAD + 1) * 8);
        } TS_PASS);
        TS(11);
        pair_reduce(acc, r, xbuf, q, 3 + pr);
#pragma unroll
        for (int i = 0; i < 8; i++) hk[i] = pack_bf16(r[2 * i] + bf_lo(hk[i]), r[2 * i + 1] + bf_hi(hk[i]));
    }
    const int row0 = mt * 64 + ww * 16 + g;
#pragma unroll
    for (int h = 0; h < 2; h++) {
        uint32_t v0 = hk[h], v1 = hk[2 + h], v2 = hk[4 + h], v3 = hk[6 + h];
        const bool o1 = t4 & 1, o2 = t4 & 2;
        uint32_t a = __shfl_xor_sync(0xffffffffu, o1 ? v0 : v1, 1), c = __shfl_xor_sync(0xffffffffu, o1 ? v2 : v3, 1);
        if (o1) { v0 = a; v2 = c; } else { v1 = a; v3 = c; }
        a = __shfl_xor_sync(0xffffffffu, o2 ? v0 : v2, 2); c = __shfl_xor_sync(0xffffffffu, o2 ? v1 : v3, 2);
        if (o2) { v0 = a; v1 = c; } else { v2 = a; v3 = c; }
        *reinterpret_cast<uint4*>(P.out + (size_t)(row0 + 8 * h) * D + j * 64 + q * 32 + t4 * 8) = make_uint4(v0, v1, v2, v3);
    }
    TS(12);
}

typedef CUresult (*EncodeFn)(CUtensorMap*, CUtensorMapDataType, cuuint32_t, void*, const cuuint64_t*, const cuuint64_t*, const cuuint32_t*,
                             const cuuint32_t*, CUtensorMapInterleave, CUtensorMapSwizzle, CUtensorMapL2promotion, CUtensorMapFloatOOBfill);

void encode2d(EncodeFn fn, CUtensorMap* tm, const void* ptr, int rows, int cols, int box_rows, int box_cols, CUtensorMapSwizzle sw) {
    cuuint64_t dims[2] = {(cuuint64_t)cols, (cuuint64_t)rows};
    cuuint64_t strides[1] = {(cuuint64_t)cols * 2};
    cuuint32_t box[2] = {(cuuint32_t)box_cols, (cuuint32_t)box_rows};
    cuuint32_t es[2] = {1, 1};
    fn(tm, CU_TENSOR_MAP_DATA_TYPE_BFLOAT16, 2, const_cast<void*>(ptr), dims, strides, box, es, CU_TENSOR_MAP_INTERLEAVE_NONE, sw,
       CU_TENSOR_MAP_L2_PROMOTION_L2_128B, CU_TENSOR_MAP_FLOAT_OOB_FILL_NONE);
}

}

extern "C" void kernel_launch(void* const* d_in, const int* in_sizes, int n_in, void* d_out, int out_size) {
    (void)in_sizes; (void)n_in; (void)out_size;
    void* fnp = nullptr;
    cudaDriverEntryPointQueryResult qr;
    cudaGetDriverEntryPoint("cuTensorMapEncodeTiled", &fnp, cudaEnableDefault, &qr);
    EncodeFn fn = (EncodeFn)fnp;
    Params P;
    encode2d(fn, &P.wq, d_in[1], D, D, 128, 64, CU_TENSOR_MAP_SWIZZLE_128B);
    P.wk = (const __nv_bfloat16*)d_in[2];
    P.wv_off = (const char*)d_in[3] - (const char*)d_in[2];
    encode2d(fn, &P.wo, d_in[4], D, D, 64, 64, CU_TENSOR_MAP_SWIZZLE_128B);
    encode2d(fn, &P.w1, d_in[6], D, FF, 128, 32, CU_TENSOR_MAP_SWIZZLE_64B);
    encode2d(fn, &P.w2, d_in[7], FF, D, 64, 64, CU_TENSOR_MAP_SWIZZLE_128B);
    P.x = (const __nv_bfloat16*)d_in[0];
    P.w1p = (const __nv_bfloat16*)d_in[6];
    P.w2p = (const __nv_bfloat16*)d_in[7];
    P.wop = (const __nv_bfloat16*)d_in[4];
    P.wqp = (const __nv_bfloat16*)d_in[1];
    P.out = (__nv_bfloat16*)d_out;
    P.neg1 = 0xFFFFFFFFu; P.pad = 0;
    cudaFuncSetAttribute(fused_kernel, cudaFuncAttributeMaxDynamicSharedMemorySize, SMEM_BYTES);
    fused_kernel<<<NCTA, 512, SMEM_BYTES>>>(P);
}
```

```cpp
#include <cuda_runtime.h>
#include <cuda_bf16.h>
#include <cuda.h>
#include <stdint.h>

namespace {

constexpr int D = 512, FF = 1376;
constexpr int NMAIN = 128, NHELP = 4, NCTA = NMAIN + NHELP;
constexpr int SPIN_LIMIT = 1 << 22;

constexpr uint32_t KB = 1024, SLOT = 8192;
constexpr uint32_t SM_XN = 0;
constexpr uint32_t SM_WQ = 64 * KB;
constexpr uint32_t SM_WKV = 192 * KB;
constexpr uint32_t SM_K = 0;
constexpr uint32_t SM_Q = 64 * KB;
constexpr uint32_t SM_V = 96 * KB;
constexpr uint32_t SM_MISC = 224 * KB;
constexpr uint32_t SMEM_BYTES = 227 * KB;
constexpr uint32_t MB_WQ = 0;
constexpr uint32_t MB_DONE = 4;
constexpr uint32_t MB_WO = 9;
constexpr uint32_t MB_EMPTY = 10;
constexpr uint32_t MB_W1 = 16;
constexpr uint32_t MB_W2 = 24;
constexpr uint32_t MB_REL = 32;
constexpr uint32_t MB_FULL = 41;
constexpr uint32_t MB_KV = 47;
constexpr uint32_t MB_CS = 48;
constexpr uint32_t MB_TURN = 49;
constexpr uint32_t MISC_NRM = 448;
constexpr uint32_t MISC_WNRM = 464;
constexpr uint32_t MISC_EPOCH = 480;
constexpr uint32_t MISC_RSTD = 512;
constexpr uint32_t MISC_KTMP = 1024;
constexpr uint32_t MISC_CS = 1024;

__host__ __device__ constexpr uint32_t wo_slot(int kb) { return kb < 2 ? 10 + kb : kb - 2; }
__host__ __device__ constexpr uint32_t w1_slot(int kb, int a) { return kb < 4 ? 12 + kb + 4 * a : (kb == 4 ? 6 : kb == 7 ? 9 : 3 * kb - 15) + a; }

struct alignas(128) Small {
    unsigned epoch[160];
    unsigned cnt[100][32];
    float cs[1440];
    uint4 nrm[NMAIN * 2];
    uint4 kv[8192];
    uint4 kplain[4096];
};
__device__ Small g_s;
constexpr int C_KVH = 0, C_KV = 1, C_MID = 2, C_O = 3, C_H1 = 35, C_H2 = 67;
constexpr int X_O = 0, X_H1 = 32 * 32 * 128, X_H2 = 2 * X_H1, X_ST = X_H2 + 32 * 88 * 128, X_END = X_ST + 32 * 8 * 32;
__device__ uint4 g_x[X_END];
#define TS(i) do {} while (0)

#define TS_ARG
#define TS_PASS

__device__ __forceinline__ void mbar_init(uint32_t bar, int cnt) { asm volatile("mbarrier.init.shared::cta.b64 [%0], %1;" :: "r"(bar), "r"(cnt) : "memory"); }
__device__ __forceinline__ void mbar_expect(uint32_t bar, uint32_t bytes) { asm volatile("mbarrier.arrive.expect_tx.shared::cta.b64 _, [%0], %1;" :: "r"(bar), "r"(bytes) : "memory"); }
__device__ __forceinline__ void mbar_arrive(uint32_t bar) { asm volatile("mbarrier.arrive.shared::cta.b64 _, [%0];" :: "r"(bar) : "memory"); }
__device__ __forceinline__ void mbar_wait(uint32_t bar, uint32_t parity = 0) {
    uint32_t done; int spins = 0;
    do {
        asm volatile("{.reg .pred p; mbarrier.try_wait.parity.shared::cta.b64 p, [%1], %2; selp.u32 %0, 1, 0, p;}" : "=r"(done) : "r"(bar), "r"(parity) : "memory");
    } while (!__all_sync(0xffffffffu, done) && ++spins < SPIN_LIMIT);
}
__device__ __forceinline__ void tma2d(uint32_t dst, const CUtensorMap* tm, int c0, int c1, uint32_t bar) {
    asm volatile("cp.async.bulk.tensor.2d.shared::cluster.global.mbarrier::complete_tx::bytes [%0], [%1, {%3, %4}], [%2];"
                 :: "r"(dst), "l"(tm), "r"(bar), "r"(c0), "r"(c1) : "memory");
}
__device__ __forceinline__ void bulk_g2s(uint32_t dst, const void* src, uint32_t bytes, uint32_t bar) {
    asm volatile("cp.async.bulk.shared::cluster.global.mbarrier::complete_tx::bytes [%0], [%1], %2, [%3];" :: "r"(dst), "l"(src), "r"(bytes), "r"(bar) : "memory");
}
__device__ __forceinline__ void fence_async_smem() { asm volatile("fence.proxy.async.shared::cta;" ::: "memory"); }
__device__ __forceinline__ void bar_sync(int id, int n) { asm volatile("bar.sync %0, %1;" :: "r"(id), "r"(n) : "memory"); }
__device__ __forceinline__ void bar_arrive(int id, int n) { asm volatile("bar.arrive %0, %1;" :: "r"(id), "r"(n) : "memory"); }
__device__ __forceinline__ void wg_fence() { asm volatile("wgmma.fence.sync.aligned;" ::: "memory"); }
__device__ __forceinline__ void wg_commit() { asm volatile("wgmma.commit_group.sync.aligned;" ::: "memory"); }
template <int N> __device__ __forceinline__ void wg_wait() { asm volatile("wgmma.wait_group.sync.aligned %0;" :: "n"(N) : "memory"); }
template <int N> __device__ __forceinline__ void fence_regs(float (&d)[N]) {
#pragma unroll
    for (int i = 0; i < N; i++) asm volatile("" : "+f"(d[i]) :: "memory");
}
template <int N> __device__ __forceinline__ void fence_regs(uint32_t (&d)[N]) {
#pragma unroll
    for (int i = 0; i < N; i++) asm volatile("" : "+r"(d[i]) :: "memory");
}
__device__ __forceinline__ uint64_t mkdesc(uint32_t addr, uint32_t lbo, uint32_t sbo, uint32_t swz) {
    return (uint64_t)(((addr & 0x3FFFF) >> 4) | ((lbo >> 4) << 16)) | ((uint64_t)((sbo >> 4) | (swz << 30)) << 32);
}
__device__ __forceinline__ float ex2(float x) { float y; asm("ex2.approx.ftz.f32 %0, %1;" : "=f"(y) : "f"(x)); return y; }
__device__ __forceinline__ float rcp(float x) { float y; asm("rcp.approx.ftz.f32 %0, %1;" : "=f"(y) : "f"(x)); return y; }
__device__ __forceinline__ uint32_t pack_bf16(float lo, float hi) { uint32_t r; asm("cvt.rn.bf16x2.f32 %0, %1, %2;" : "=r"(r) : "f"(hi), "f"(lo)); return r; }
__device__ __forceinline__ uint32_t pack_f16(float lo, float hi) { uint32_t r; asm("cvt.rn.f16x2.f32 %0, %1, %2;" : "=r"(r) : "f"(hi), "f"(lo)); return r; }
__device__ __forceinline__ float bf_lo(uint32_t v) { return __uint_as_float(v << 16); }
__device__ __forceinline__ float bf_hi(uint32_t v) { return __uint_as_float(v & 0xFFFF0000u); }
__device__ __forceinline__ uint4 ldg_relaxed(const uint4* p) {
    uint4 v; asm volatile("ld.relaxed.gpu.global.v4.u32 {%0,%1,%2,%3}, [%4];" : "=r"(v.x), "=r"(v.y), "=r"(v.z), "=r"(v.w) : "l"(p) : "memory"); return v;
}
__device__ __forceinline__ void stg128(void* p, uint32_t a, uint32_t b, uint32_t c, uint32_t d) {
    asm volatile("st.relaxed.gpu.global.v4.u32 [%0], {%1,%2,%3,%4};" :: "l"(p), "r"(a), "r"(b), "r"(c), "r"(d) : "memory");
}
__device__ __forceinline__ void stg64(void* p, uint32_t a, uint32_t b) {
    asm volatile("st.relaxed.gpu.global.v2.u32 [%0], {%1,%2};" :: "l"(p), "r"(a), "r"(b) : "memory");
}
__device__ __forceinline__ void sts128(uint32_t a, uint32_t x, uint32_t y, uint32_t z, uint32_t w) {
    asm volatile("st.shared.v4.u32 [%0], {%1,%2,%3,%4};" :: "r"(a), "r"(x), "r"(y), "r"(z), "r"(w) : "memory");
}
__device__ __forceinline__ void sts32(uint32_t a, uint32_t x) { asm volatile("st.shared.u32 [%0], %1;" :: "r"(a), "r"(x) : "memory"); }
__device__ __forceinline__ float4 lds128f(uint32_t a) {
    float4 v; asm volatile("ld.shared.v4.f32 {%0,%1,%2,%3}, [%4];" : "=f"(v.x), "=f"(v.y), "=f"(v.z), "=f"(v.w) : "r"(a) : "memory"); return v;
}
__device__ __forceinline__ uint32_t lds32(uint32_t a) { uint32_t v; asm volatile("ld.shared.u32 %0, [%1];" : "=r"(v) : "r"(a) : "memory"); return v; }
__device__ __forceinline__ uint32_t nonzero(uint32_t w) { return w == 0u ? 0x8000u : w; }
__device__ __forceinline__ void stg32(void* p, uint32_t a) { asm volatile("st.global.u32 [%0], %1;" :: "l"(p), "r"(a) : "memory"); }
__device__ __forceinline__ uint32_t ldg32_relaxed(const void* p) { uint32_t v; asm volatile("ld.relaxed.gpu.global.u32 %0, [%1];" : "=r"(v) : "l"(p) : "memory"); return v; }
__device__ __forceinline__ void count_hint(int id) {
    if ((threadIdx.x & 31) == 0) asm volatile("red.relaxed.gpu.global.add.u32 [%0], 1;" :: "l"(g_s.cnt[id]) : "memory");
}
__device__ __forceinline__ void count_release(int id) {
    __syncwarp();
    if ((threadIdx.x & 31) == 0) asm volatile("red.release.gpu.global.add.u32 [%0], 1;" :: "l"(g_s.cnt[id]) : "memory");
    __syncwarp();
}
__device__ __forceinline__ void count_wait(int id, unsigned target) {
    uint32_t v; int spins = 0;
    do v = ldg32_relaxed(g_s.cnt[id]); while (__any_sync(0xffffffffu, v != target) && ++spins < SPIN_LIMIT);
    asm volatile("fence.acquire.gpu;" ::: "memory");
}
__device__ __forceinline__ void warp_done(uint32_t bar) {
    __syncwarp();
    asm volatile("{.reg .pred p; setp.eq.u32 p, %1, 0; @p mbarrier.arrive.shared::cta.b64 _, [%0];}" :: "r"(bar), "r"(threadIdx.x & 31) : "memory");
}
__device__ __forceinline__ uint32_t mul_bf16x2(uint32_t a, uint32_t b) { uint32_t r; asm("mul.rn.bf16x2 %0, %1, %2;" : "=r"(r) : "r"(a), "r"(b)); return r; }
__device__ __forceinline__ uint32_t fma_bf16x2(uint32_t a, uint32_t b, uint32_t c) { uint32_t r; asm("fma.rn.bf16x2 %0, %1, %2, %3;" : "=r"(r) : "r"(a), "r"(b), "r"(c)); return r; }
__device__ __forceinline__ uint32_t add_bf16x2(uint32_t a, uint32_t b) { uint32_t r; asm("add.rn.bf16x2 %0, %1, %2;" : "=r"(r) : "r"(a), "r"(b)); return r; }

#define R4(d, o) "+f"(d[o + 0]), "+f"(d[o + 1]), "+f"(d[o + 2]), "+f"(d[o + 3])
#define R8(d, o) R4(d, o), R4(d, o + 4)
#define R32(d) R8(d, 0), R8(d, 8), R8(d, 16), R8(d, 24)
#define D32 "{%0,%1,%2,%3,%4,%5,%6,%7,%8,%9,%10,%11,%12,%13,%14,%15,%16,%17,%18,%19,%20,%21,%22,%23,%24,%25,%26,%27,%28,%29,%30,%31}"
#define D64 "{%0,%1,%2,%3,%4,%5,%6,%7,%8,%9,%10,%11,%12,%13,%14,%15,%16,%17,%18,%19,%20,%21,%22,%23,%24,%25,%26,%27,%28,%29,%30,%31,%32,%33,%34,%35,%36,%37,%38,%39,%40,%41,%42,%43,%44,%45,%46,%47,%48,%49,%50,%51,%52,%53,%54,%55,%56,%57,%58,%59,%60,%61,%62,%63}"

__device__ __forceinline__ void mma_qk_f16(float (&d)[32], uint64_t da, uint64_t db) {
    asm volatile("{.reg .pred p; setp.eq.b32 p, 0, 0; wgmma.mma_async.sync.aligned.m64n64k16.f32.f16.f16 " D32 ", %32, %33, p, 1, 1, 0, 0;}"
                 : R32(d) : "l"(da), "l"(db));
}
__device__ __forceinline__ void mma_qk_bf16(float (&d)[32], uint64_t da, uint64_t db) {
    asm volatile("{.reg .pred p; setp.ne.b32 p, 0, 0; wgmma.mma_async.sync.aligned.m64n64k16.f32.bf16.bf16 " D32 ", %32, %33, p, 1, 1, 0, 0;}"
                 : R32(d) : "l"(da), "l"(db));
}
__device__ __forceinline__ void mma_pv(float (&d)[12], const uint32_t* a, uint64_t db) {
    asm volatile("{.reg .pred p; setp.eq.b32 p, 0, 0; wgmma.mma_async.sync.aligned.m64n24k16.f32.bf16.bf16 {%0,%1,%2,%3,%4,%5,%6,%7,%8,%9,%10,%11}, {%12,%13,%14,%15}, %16, p, 1, 1, 1;}"
                 : R8(d, 0), R4(d, 8) : "r"(a[0]), "r"(a[1]), "r"(a[2]), "r"(a[3]), "l"(db));
}
__device__ __forceinline__ void mma_ss128(float (&d)[64], uint64_t da, uint64_t db) {
    asm volatile("{.reg .pred p; setp.eq.b32 p, 0, 0; wgmma.mma_async.sync.aligned.m64n128k16.f32.bf16.bf16 " D64 ", %64, %65, p, 1, 1, 0, 1;}"
                 : R32(d), R8(d, 32), R8(d, 40), R8(d, 48), R8(d, 56) : "l"(da), "l"(db));
}
__device__ __forceinline__ void stsm4(uint32_t addr, uint32_t a, uint32_t b, uint32_t c, uint32_t d) {
    asm volatile("stmatrix.sync.aligned.m8n8.x4.shared.b16 [%0], {%1,%2,%3,%4};" :: "r"(addr), "r"(a), "r"(b), "r"(c), "r"(d) : "memory");
}
__device__ __forceinline__ void mma_ss8(float (&d)[4], uint64_t da, uint64_t db) {
    asm volatile("{.reg .pred p; setp.eq.b32 p, 0, 0; wgmma.mma_async.sync.aligned.m64n8k16.f32.bf16.bf16 {%0,%1,%2,%3}, %4, %5, p, 1, 1, 0, 1;}"
                 : R4(d, 0) : "l"(da), "l"(db));
}
__device__ __forceinline__ void mma_ss(float (&d)[32], uint64_t da, uint64_t db) {
    asm volatile("{.reg .pred p; setp.eq.b32 p, 0, 0; wgmma.mma_async.sync.aligned.m64n64k16.f32.bf16.bf16 " D32 ", %32, %33, p, 1, 1, 0, 1;}"
                 : R32(d) : "l"(da), "l"(db));
}
__device__ __forceinline__ void mma_ss(float (&d)[88], uint64_t da, uint64_t db) {
    asm volatile("{.reg .pred p; setp.eq.b32 p, 0, 0; wgmma.mma_async.sync.aligned.m64n176k16.f32.bf16.bf16 " "{%0,%1,%2,%3,%4,%5,%6,%7,%8,%9,%10,%11,%12,%13,%14,%15,%16,%17,%18,%19,%20,%21,%22,%23,%24,%25,%26,%27,%28,%29,%30,%31,%32,%33,%34,%35,%36,%37,%38,%39,%40,%41,%42,%43,%44,%45,%46,%47,%48,%49,%50,%51,%52,%53,%54,%55,%56,%57,%58,%59,%60,%61,%62,%63,%64,%65,%66,%67,%68,%69,%70,%71,%72,%73,%74,%75,%76,%77,%78,%79,%80,%81,%82,%83,%84,%85,%86,%87}"
                 ", %88, %89, p, 1, 1, 0, 1;}"
                 : R32(d), R8(d, 32), R8(d, 40), R8(d, 48), R8(d, 56), R8(d, 64), R8(d, 72), R8(d, 80) : "l"(da), "l"(db));
}

constexpr float EXP_MAGIC = 256.0f + 127.0f + 64.0f - 1.58621f + 0.00390625f;
constexpr uint32_t MUFU_MASK = 0x1111u;
__device__ __forceinline__ uint32_t exp2_pair(float y0, float y1, uint32_t cexp, uint32_t neg1) {
    uint32_t w, m, e, r;
    asm("prmt.b32 %0, %1, %2, 0x6521;" : "=r"(w) : "r"(__float_as_uint(y0)), "r"(__float_as_uint(y1)));
    asm("lop3.b32 %0, %1, 0x007F007F, %2, 0xEA;" : "=r"(m) : "r"(w), "r"(cexp));
    asm("mad.lo.u32 %0, %1, %2, %3;" : "=r"(e) : "r"(m), "r"(neg1), "r"(w));
    asm("fma.rn.bf16x2 %0, %1, %2, %3;" : "=r"(r) : "r"(w), "r"(m), "r"(e));
    return r;
}

struct Params {
    const __nv_bfloat16* x;
    const __nv_bfloat16* wk;
    long long wv_off;
    const __nv_bfloat16* wqp;
    __nv_bfloat16* out;
    uint32_t neg1, pad;
    const __nv_bfloat16* w1p;
    const __nv_bfloat16* w2p;
    CUtensorMap wq, wo, w1, w2;
    const __nv_bfloat16* wop;
};

__device__ __forceinline__ void load_box(uint32_t sb, const CUtensorMap* tm, uint32_t dst, uint32_t bar, uint32_t bytes, int c0, int c1) {
    mbar_expect(sb + SM_MISC + bar * 8, bytes);
    tma2d(sb + dst, tm, c0, c1, sb + SM_MISC + bar * 8);
}
__device__ __forceinline__ void load_wq(uint32_t sb, const Params& P, int gi, int atom) {
    load_box(sb, &P.wq, SM_WQ + atom * 65536 + gi * 16384, MB_WQ + gi, 16384, (blockIdx.x & 3) * 128 + atom * 64, gi * 128);
}
__device__ __forceinline__ void load_wo(uint32_t sb, const Params& P, int kb) { load_box(sb, &P.wo, wo_slot(kb) * SLOT, MB_WO, SLOT, (blockIdx.x & 7) * 64, kb * 64); }
__device__ __forceinline__ void load_w1(uint32_t sb, const Params& P, int kb, int a) { load_box(sb, &P.w1, w1_slot(kb, a) * SLOT, MB_W1 + kb, SLOT, (blockIdx.x & 7) * 176 + a * 64, kb * 64); }
__device__ __forceinline__ void refill_job(uint32_t sb, const Params& P, int gi, int job) {
    const bool w1 = job < 3;
    load_box(sb, w1 ? &P.w1 : &P.wo, (w1 ? 12 + gi + 4 * job : 2 * gi + job - 3) * SLOT, w1 ? MB_W1 + gi : MB_WO, SLOT,
             (blockIdx.x & 7) * (w1 ? 176 : 64) + (w1 ? job * 64 : 0), (w1 ? gi : 2 * gi + job - 1) * 64);
}

struct Ring {
    int e, ph;
    int size;
    __device__ __forceinline__ Ring(int n) {
        if (n < 32) { e = n & 3; ph = ((n >> 2) & 1) ? 15 : 0; size = 4; }
        else { e = (n - 32) % 6; size = 6; ph = (((n - 32) / 6) & 1) ? 63 : 0; ph ^= (1 << e) - 1; }
    }
    __device__ __forceinline__ uint32_t slot() const { return e < 4 ? 24 + e : 6 + e; }
    __device__ __forceinline__ uint32_t parity() const { return (ph >> e) & 1; }
    __device__ __forceinline__ void next() { ph ^= 1 << e; e = (e + 1 == size) ? 0 : e + 1; }
};

template <int KIND, int NACC>
__device__ __forceinline__ void gemm_ss(float (&acc)[NACC], uint32_t sb, int pr) {
    const uint32_t mb = sb + SM_MISC;
    constexpr int NBLK = KIND == 2 ? 22 : 8;
    Ring r(16 * KIND + pr * NBLK);
    int prev = 0, kb = 0, a = 0;
#pragma unroll
    for (int i = 0; i < NACC; i++) acc[i] = 0.f;
    fence_regs(acc);
#pragma unroll 1
    for (int i = 0; i < NBLK; i++) {
        uint64_t db;
        if (KIND == 0) db = mkdesc(sb + wo_slot(i) * SLOT, 16, 1024, 1);
        if (KIND == 1) { db = mkdesc(sb + w1_slot(i, 0) * SLOT, i < 4 ? 4 * SLOT : SLOT, 1024, 1); mbar_wait(mb + (MB_W1 + i) * 8); }
        if (KIND == 2) { db = mkdesc(sb + w1_slot(kb, a) * SLOT, 16, 1024, 1); if (a == 0) mbar_wait(mb + (MB_W2 + kb) * 8); if (++a == 3) { a = 0; kb++; } }
        const uint64_t da = mkdesc(sb + r.slot() * SLOT, 128, 256, 0);
        mbar_wait(mb + (MB_FULL + r.e) * 8, r.parity());
        wg_fence();
#pragma unroll
        for (int s = 0; s < 4; s++) mma_ss(acc, da + s * 128, db + s * 128);
        wg_commit();
        if (i > 0) {
            wg_wait<1>();
            warp_done(mb + (MB_EMPTY + prev) * 8);
            if (KIND == 1) warp_done(mb + (MB_REL + i - 1) * 8);
        }
        prev = r.e;
        r.next();
    }
    if (2 * KIND + pr < 5) warp_done(mb + (MB_TURN + 2 * KIND + pr) * 8);
    wg_wait<0>();
    fence_regs(acc);
    warp_done(mb + (MB_EMPTY + prev) * 8);
    if (KIND != 2) warp_done(mb + (MB_REL + 8 - KIND) * 8);
}
__device__ __forceinline__ void store_tile(uint32_t* p, uint32_t r0k0, uint32_t r8k0, uint32_t r0k8, uint32_t r8k8) {
    stg32(p, r0k0); stg32(p + 32, r0k8); stg32(p + 64, r8k0); stg32(p + 96, r8k8);
}

__device__ __forceinline__ float quad_sum(float v) { v += __shfl_xor_sync(0xffffffffu, v, 1); v += __shfl_xor_sync(0xffffffffu, v, 2); return v; }
__device__ __forceinline__ float reduce4(const float (&st)[4], int lane) {
    const bool u16 = lane & 16, u8 = lane & 8;
    const float a0 = (u16 ? st[2] : st[0]) + __shfl_xor_sync(0xffffffffu, u16 ? st[0] : st[2], 16);
    const float a1 = (u16 ? st[3] : st[1]) + __shfl_xor_sync(0xffffffffu, u16 ? st[1] : st[3], 16);
    float v = (u8 ? a1 : a0) + __shfl_xor_sync(0xffffffffu, u8 ? a0 : a1, 8);
    v += __shfl_xor_sync(0xffffffffu, v, 4); v += __shfl_xor_sync(0xffffffffu, v, 2); v += __shfl_xor_sync(0xffffffffu, v, 1);
    return v;
}
__device__ __forceinline__ float silu2(float h) { float t; asm("tanh.approx.f32 %0, %1;" : "=f"(t) : "f"(h)); return fmaf(h, t, h); }

template <bool SAFE>
__device__ __forceinline__ void attention(const Params& P, uint32_t sb, int warp TS_ARG) {
    const uint32_t mb = sb + SM_MISC;
    const int tid = threadIdx.x, lane = tid & 31, b = blockIdx.x;
    const int wg = warp >> 2, ww = warp & 3, job = 3 - wg + 4 * ww;
    const uint32_t cexp = 0x9F809F80u + (tid >> 12);
    const uint32_t neg1 = P.neg1;
    unsigned cnt = 0;
    if (SAFE && warp == 8) cnt = ldg32_relaxed(g_s.cnt[C_KV]);
#pragma unroll 1
    for (int pass = 0; pass < 2; pass++) {
    float o[12], s[32];
    const uint64_t dq = mkdesc(sb + SM_Q + (pass * 4 + wg) * 2048, 128, 256, 0);
    uint64_t dk = mkdesc(sb + SM_K, 128, 256, 0), dv = mkdesc(sb + SM_V, 128, 32768, 0);
    float m0 = -INFINITY, m1 = -INFINITY;
#pragma unroll
    for (int i = 0; i < 12; i++) o[i] = 0.f;
#pragma unroll
    for (int i = 0; i < 32; i++) s[i] = ((MUFU_MASK >> (i / 2)) & 1) ? 0.f : EXP_MAGIC;
    fence_regs(s); fence_regs(o);
    wg_fence();
    if (SAFE) mma_qk_f16(s, dq, dk + 31 * 128); else mma_qk_bf16(s, dq, dk + 31 * 128);
    wg_commit();
    wg_wait<0>(); fence_regs(s);
#pragma unroll 1
    for (int u = pass ? 3 : (wg == 2) ? 0 : 1; u < (pass ? 8 : 3); u++) {
        int n = 2 * ((((wg == 2) ? 0x22444C31u : 0x22444C40u) >> (4 * u)) & 15);
#pragma unroll 1
        do {
            uint32_t p[16];
            if (SAFE) {
#pragma unroll
                for (int j = 0; j < 16; j++) {
                    if ((MUFU_MASK >> j) & 1) p[j] = pack_bf16(ex2(s[2 * j]), ex2(s[2 * j + 1]));
                    else p[j] = exp2_pair(s[2 * j], s[2 * j + 1], cexp, neg1);
                }
            } else {
                fence_regs(o);
                float x0 = m0, x1 = m1;
#pragma unroll
                for (int j = 0; j < 8; j++) { x0 = fmaxf(x0, fmaxf(s[4 * j], s[4 * j + 1])); x1 = fmaxf(x1, fmaxf(s[4 * j + 2], s[4 * j + 3])); }
                x0 = fmaxf(x0, __shfl_xor_sync(0xffffffffu, x0, 1)); x0 = fmaxf(x0, __shfl_xor_sync(0xffffffffu, x0, 2));
                x1 = fmaxf(x1, __shfl_xor_sync(0xffffffffu, x1, 1)); x1 = fmaxf(x1, __shfl_xor_sync(0xffffffffu, x1, 2));
                const float c0 = ex2(m0 - x0), c1 = ex2(m1 - x1);
                m0 = x0; m1 = x1;
#pragma unroll
                for (int j = 0; j < 3; j++) { o[4 * j] *= c0; o[4 * j + 1] *= c0; o[4 * j + 2] *= c1; o[4 * j + 3] *= c1; }
#pragma unroll
                for (int j = 0; j < 8; j++) {
                    p[2 * j] = pack_bf16(ex2(s[4 * j] - m0), ex2(s[4 * j + 1] - m0));
                    p[2 * j + 1] = pack_bf16(ex2(s[4 * j + 2] - m1), ex2(s[4 * j + 3] - m1));
                }
                fence_regs(o);
            }
            fence_regs(p);
            wg_fence();
            if (SAFE) mma_qk_f16(s, dq, dk); else mma_qk_bf16(s, dq, dk);
#pragma unroll
            for (int j = 0; j < 4; j++) mma_pv(o, p + 4 * j, dv + j * 16);
            wg_commit();
            dk += 128; dv += 64;
            wg_wait<0>(); fence_regs(s);
        } while (--n > 0);
        if (u == 2 || u == 7) {
            fence_regs(o);
            const float i0 = rcp(o[8]), i1 = rcp(o[10]);
            store_tile(reinterpret_cast<uint32_t*>(g_x + X_O + (((u == 7) * 16 + (b >> 3)) * 32 + (b & 3) * 8 + 2 * wg + (ww >> 1)) * 128 + (((b >> 2) & 1) * 2 + (ww & 1)) * 32) + lane,
                       pack_bf16(o[0] * i0, o[1] * i0), pack_bf16(o[2] * i1, o[3] * i1), pack_bf16(o[4] * i0, o[5] * i0), pack_bf16(o[6] * i1, o[7] * i1));
            warp_done(mb + (MB_DONE + (u == 7) * 4) * 8);
            TS(5 + (u == 7));
        } else if (u >= 3) {
            if (u < 6) warp_done(mb + (MB_DONE + u - 2) * 8);
            if (job < (u == 3 ? 1 : 5)) {
                mbar_wait(mb + (MB_DONE + u - 3) * 8);
                if (u == 3) { count_release(C_O + (b >> 3)); count_hint(C_MID); }
                else if (lane == 0) refill_job(sb, P, u - 4, job);
            }
        } else if (u == 1) {
            if (SAFE) mbar_wait(mb + MB_KV * 8);
            TS(17);
            if (lane == 0 && job < 2) load_wo(sb, P, job);
        } else if (SAFE) {
            if (warp == 8) {
                const unsigned target = lds32(mb + MISC_EPOCH) * NMAIN;
                if (__any_sync(0xffffffffu, cnt != target)) count_wait(C_KV, target);
                if (lane == 0) {
                    asm volatile("fence.acquire.gpu; fence.proxy.async.global;" ::: "memory");
                    mbar_expect(mb + MB_KV * 8, 47104 + 2 * 24576);
                    bulk_g2s(sb + SM_K + 16384, g_s.kv + 1024, 47104, mb + MB_KV * 8);
                    bulk_g2s(sb + SM_V + 8192, g_s.kv + 4096 + 512, 24576, mb + MB_KV * 8);
                    bulk_g2s(sb + SM_V + 32768 + 8192, g_s.kv + 6144 + 512, 24576, mb + MB_KV * 8);
                }
            }
        }
        __syncwarp();
    }
    }
}

__device__ __forceinline__ int kv_slot() {
    const int t = (threadIdx.x & 63) >> 1, c = 2 * (blockIdx.x >> 2) + (threadIdx.x & 1), hg = blockIdx.x & 3;
    return hg < 2 ? ((t + 31) & 31) * 128 + (c >> 3) * 16 + (hg & 1) * 8 + (c & 7) : 4096 + (hg & 1) * 2048 + t * 64 + c;
}

__device__ __noinline__ void helper_cta(const Params& P, uint8_t* smem) {
    const int tid = threadIdx.x, b = blockIdx.x, hi = b - NMAIN;
    const unsigned epoch = g_s.epoch[b] + 1;
    float* red = reinterpret_cast<float*>(smem);
    if (tid < 32) count_wait(C_KV, epoch * NMAIN);
    __syncthreads();
    if (tid == 480) {
        for (int i = 0; i < 8; i++) asm volatile("cp.async.bulk.prefetch.L2.global [%0], %1;" :: "l"((const char*)P.wop + hi * 131072 + i * 16384), "r"(16384) : "memory");
        for (int i = 0; i < 43; i++) asm volatile("cp.async.bulk.prefetch.L2.global [%0], %1;" :: "l"((const char*)P.w2p + hi * 352256 + i * 8192), "r"(8192) : "memory");
    }
    if (tid < 344) {
        const int cg = tid % 43, rp = tid / 43;
        const uint4* src = reinterpret_cast<const uint4*>(P.w1p + (size_t)rp * 64 * FF + (hi * 43 + cg) * 8);
        float s[8] = {0, 0, 0, 0, 0, 0, 0, 0};
#pragma unroll 8
        for (int r = 0; r < 64; r++) {
            uint4 v = __ldg(src + r * (FF / 8));
            s[0] += bf_lo(v.x); s[1] += bf_hi(v.x); s[2] += bf_lo(v.y); s[3] += bf_hi(v.y);
            s[4] += bf_lo(v.z); s[5] += bf_hi(v.z); s[6] += bf_lo(v.w); s[7] += bf_hi(v.w);
        }
        float* part = red + (rp * 43 + cg) * 8;
#pragma unroll
        for (int i = 0; i < 8; i++) part[i] = s[i];
    }
    __syncthreads();
    if (tid < 344) {
        float s = 0.f;
#pragma unroll
        for (int rp = 0; rp < 8; rp++) s += red[rp * 344 + tid];
        g_s.cs[hi * 344 + tid] = s;
    } else if (hi == 3 && tid < 344 + 64) g_s.cs[FF + tid - 344] = 0.f;
    __syncthreads();
    if (tid < 32) count_release(C_MID);
    if (tid == 0) g_s.epoch[b] = epoch;
}

__global__ void __launch_bounds__(512, 1) fused_kernel(const __grid_constant__ Params P) {
    extern __shared__ __align__(1024) uint8_t smem[];
    const uint32_t sb = (uint32_t)__cvta_generic_to_shared(smem);
    const uint32_t mb = sb + SM_MISC;
    const int tid = threadIdx.x, lane = tid & 31, b = blockIdx.x;
    if (b >= NMAIN) { helper_cta(P, smem); return; }
    const int tg = b >> 2, hg = b & 3;
    const int warp = __shfl_sync(0xffffffffu, tid >> 5, 0);

    uint4 xv[4][2];
    unsigned epoch = 0;
    {
        const int r = (tid >> 5) * 4;
        const uint4* src = reinterpret_cast<const uint4*>(P.x + (size_t)((r & 31) + tg * 32 + (r >> 5) * 1024) * D) + lane;
#pragma unroll
        for (int i = 0; i < 4; i++) { xv[i][0] = ldg_relaxed(src + i * 64); xv[i][1] = ldg_relaxed(src + i * 64 + 32); }
    }
    const uint4 wkv = ldg_relaxed(reinterpret_cast<const uint4*>(reinterpret_cast<const char*>(P.wk) + (hg < 2 ? 0 : P.wv_off)) + tid * 2 + (hg & 1));
    const int wg = warp >> 2, ww = warp & 3, g = lane >> 2, t4 = lane & 3, t128 = tid & 127;
    if (lane == 0) {
        mbar_init(mb + warp * 8, warp < 4 ? 2 : warp < 9 ? 16 : warp == 9 ? 8 : 4);
        mbar_init(mb + (16 + warp) * 8, warp == 15 ? 1 : 3);
        mbar_init(mb + (32 + warp) * 8, warp < 9 ? 8 : 1);
        if (warp < 4) {
            asm volatile("fence.mbarrier_init.release.cluster;" ::: "memory");
            load_wq(sb, P, warp, 0);
            load_wq(sb, P, warp, 1);
        } else if (warp < 7) {
            asm volatile("prefetch.tensormap [%0];" :: "l"(&P.wo + (warp - 4)) : "memory");
        } else if (warp == 7) {
            asm volatile("ld.relaxed.gpu.global.u32 %0, [%1];" : "=r"(epoch) : "l"(g_s.epoch + b) : "memory");
        } else if (warp == 8) {
            sts128(mb + MISC_NRM, 0, 0, 0, 0);
            mbar_init(mb + MB_CS * 8, 2);
        } else if (warp < 14) {
            mbar_init(mb + (MB_TURN - 9 + warp) * 8, 4);
        }
    }
    __syncwarp();
    TS(16);
    float dlt;
    {
        float st[4];
#pragma unroll
        for (int i = 0; i < 4; i++) {
            const uint32_t s = add_bf16x2(add_bf16x2(add_bf16x2(xv[i][0].x, xv[i][0].y), add_bf16x2(xv[i][0].z, xv[i][0].w)),
                                          add_bf16x2(add_bf16x2(xv[i][1].x, xv[i][1].y), add_bf16x2(xv[i][1].z, xv[i][1].w)));
            st[i] = bf_lo(s) + bf_hi(s);
        }
        TS(13);
        const float tot = reduce4(st, lane) * (-1.0f / D);
        const uint32_t nmr = pack_bf16(tot, tot);
        dlt = bf_lo(nmr) - tot;
        const uint32_t xa = sb + SM_XN + (lane >> 3) * 8192 + warp * 512;
#pragma unroll
        for (int i = 0; i < 4; i++) {
            const uint32_t nm = __shfl_sync(0xffffffffu, nmr, i * 8);
            const uint32_t addr = xa + i * 128 + (((lane & 7) ^ ((warp & 1) * 4 + i)) << 4);
#pragma unroll
            for (int c = 0; c < 2; c++) {
                xv[i][c].x = add_bf16x2(xv[i][c].x, nm); xv[i][c].y = add_bf16x2(xv[i][c].y, nm);
                xv[i][c].z = add_bf16x2(xv[i][c].z, nm); xv[i][c].w = add_bf16x2(xv[i][c].w, nm);
                sts128(addr + c * 32768, xv[i][c].x, xv[i][c].y, xv[i][c].z, xv[i][c].w);
            }
        }
    }
    sts128(sb + SM_WKV + tid * 16, wkv.x, wkv.y, wkv.z, wkv.w);
    fence_async_smem();
    TS(0);
    __syncthreads();
    auto variances = [&]() {
        float st[4];
#pragma unroll
        for (int i = 0; i < 4; i++) {
            float v = 0.f;
#pragma unroll
            for (int c = 0; c < 2; c++) {
                const uint32_t a = fma_bf16x2(xv[i][c].x, xv[i][c].x, mul_bf16x2(xv[i][c].y, xv[i][c].y));
                const uint32_t d = fma_bf16x2(xv[i][c].z, xv[i][c].z, mul_bf16x2(xv[i][c].w, xv[i][c].w));
                v += (bf_lo(a) + bf_hi(a)) + (bf_lo(d) + bf_hi(d));
            }
            st[i] = v;
        }
        const float vs = reduce4(st, lane), dl = dlt;
        if ((lane & 7) == 0) sts32(mb + MISC_RSTD + (warp * 4 + (lane >> 3)) * 4, __float_as_uint(rsqrtf(fmaxf(vs * (1.0f / D) - dl * dl, 0.f) + 1e-5f)));
    };
    float kv[4] = {0.f, 0.f, 0.f, 0.f};
    if (wg == 2) {
        fence_regs(kv);
        const uint64_t da = mkdesc(sb + SM_XN, 16, 1024, 1), db = mkdesc(sb + SM_WKV, 128, 16, 0);
        wg_fence();
#pragma unroll
        for (int s = 0; s < 32; s++) mma_ss8(kv, da + (s >> 2) * 512 + (s & 3) * 2, db + s * 16);
        wg_commit();
        variances();
        wg_wait<0>(); fence_regs(kv);
    } else {
        variances();
        if (tid == 7 * 32) { sts32(mb + MISC_EPOCH, epoch + 1); g_s.epoch[b] = epoch + 1; }
    }
    __syncthreads();
    constexpr float QSCALE = 0.25f * 1.4426950408889634f;
    float qa[64];
    const uint32_t qbase = sb + SM_Q + (ww >> 1) * 8192 + (ww & 1) * 512 + lane * 16;
    if (wg == 0) {
#pragma unroll
        for (int i = 0; i < 64; i++) qa[i] = 0.f;
        fence_regs(qa);
        const uint64_t da = mkdesc(sb + SM_XN, 16, 1024, 1), db = mkdesc(sb + SM_WQ, 65536, 1024, 1);
#pragma unroll 1
        for (int i = 0; i < 4; i++) {
            mbar_wait(mb + (MB_WQ + i) * 8);
            wg_fence();
#pragma unroll
            for (int s = 0; s < 8; s++) mma_ss128(qa, da + (i * 2 + (s >> 2)) * 512 + (s & 3) * 2, db + (i * 8 + s) * 128);
            wg_commit();
        }
        const float rs0 = __uint_as_float(lds32(mb + MISC_RSTD + (ww * 16 + g) * 4)) * QSCALE, rs1 = __uint_as_float(lds32(mb + MISC_RSTD + (ww * 16 + g + 8) * 4)) * QSCALE;
        wg_wait<0>();
        fence_regs(qa);
        bar_arrive(6, 256);
        bar_sync(5, 256);
        TS(1);
        uint32_t nm = 0;
#pragma unroll
        for (int h = 0; h < 8; h++) {
#pragma unroll
            for (int i = 0; i < 8; i++) qa[8 * h + i] *= (i & 2) ? rs1 : rs0;
            stsm4(qbase + h * 1024, pack_f16(qa[8 * h], qa[8 * h + 1]), pack_f16(qa[8 * h + 4], qa[8 * h + 5]), pack_f16(qa[8 * h + 2], qa[8 * h + 3]), pack_f16(qa[8 * h + 6], qa[8 * h + 7]));
            const float n0 = qa[8 * h] * qa[8 * h] + qa[8 * h + 1] * qa[8 * h + 1] + qa[8 * h + 4] * qa[8 * h + 4] + qa[8 * h + 5] * qa[8 * h + 5];
            const float n1 = qa[8 * h + 2] * qa[8 * h + 2] + qa[8 * h + 3] * qa[8 * h + 3] + qa[8 * h + 6] * qa[8 * h + 6] + qa[8 * h + 7] * qa[8 * h + 7];
            nm = max(nm, max(__float_as_uint(n0), __float_as_uint(n1)));
        }
        nm = __reduce_max_sync(0xffffffffu, __float_as_uint(quad_sum(__uint_as_float(nm))));
        if (lane == 0) asm volatile("red.shared.max.u32 [%0], %1;" :: "r"(mb + MISC_NRM), "r"(nm) : "memory");
    } else if (wg == 1) {
        bar_sync(5, 256);
#pragma unroll
        for (int i = 0; i < 16; i++) sts128(sb + SM_V + 65536 + (i * 128 + t128) * 16, 0x3F803F80u, 0x3F803F80u, 0x3F803F80u, 0x3F803F80u);
    } else if (wg == 2) {
        const float rs0 = __uint_as_float(lds32(mb + MISC_RSTD + (ww * 16 + g) * 4)), rs1 = __uint_as_float(lds32(mb + MISC_RSTD + (ww * 16 + g + 8) * 4));
        kv[0] *= rs0; kv[1] *= rs0; kv[2] *= rs1; kv[3] *= rs1;
        float2* kt = reinterpret_cast<float2*>(smem + SM_MISC + MISC_KTMP);
        kt[(ww * 16 + g) * 4 + t4] = make_float2(kv[0], kv[1]); kt[(ww * 16 + g + 8) * 4 + t4] = make_float2(kv[2], kv[3]);
        float n0 = kv[0] * kv[0] + kv[1] * kv[1], n1 = kv[2] * kv[2] + kv[3] * kv[3];
        n0 += __shfl_xor_sync(0xffffffffu, n0, 1); n1 += __shfl_xor_sync(0xffffffffu, n1, 1);
        n0 += __shfl_xor_sync(0xffffffffu, n0, 2); n1 += __shfl_xor_sync(0xffffffffu, n1, 2);
        const uint32_t nm = __reduce_max_sync(0xffffffffu, max(__float_as_uint(n0), __float_as_uint(n1)));
        if (lane == 0) sts32(mb + MISC_WNRM + ww * 4, nm | 1u);
        bar_sync(2, 128);
        const uint32_t ra = mb + MISC_KTMP + ((t128 & 1) * 32 + ((t128 & 63) >> 1)) * 32;
        const float4 c0 = lds128f(ra), c1 = lds128f(ra + 16);
        const int kvoff = kv_slot();
        if (ww < 2) {
            if (hg < 2) {
                float4 p0 = lds128f(ra - 32), p1 = lds128f(ra - 16);
                if (t128 < 2) { p0 = make_float4(0.f, 0.f, 0.f, 0.f); p1 = p0; }
                stg128(g_s.kv + kvoff, nonzero(pack_f16(c0.x - p0.x, c0.y - p0.y)), pack_f16(c0.z - p0.z, c0.w - p0.w), pack_f16(c1.x - p1.x, c1.y - p1.y), pack_f16(c1.z - p1.z, c1.w - p1.w));
            } else {
                stg128(g_s.kv + kvoff, nonzero(pack_bf16(c0.x, c0.y)), pack_bf16(c0.z, c0.w), pack_bf16(c1.x, c1.y), pack_bf16(c1.z, c1.w));
            }
            if (t128 < 2) { const float4 w = lds128f(mb + MISC_WNRM); stg128(g_s.nrm + b * 2 + t128, __float_as_uint(w.x), __float_as_uint(w.y), __float_as_uint(w.z), __float_as_uint(w.w)); }
            count_hint(C_KVH);
        } else if (hg < 2) {
            stg128(g_s.kplain + kvoff, pack_bf16(c0.x, c0.y), pack_bf16(c0.z, c0.w), pack_bf16(c1.x, c1.y), pack_bf16(c1.z, c1.w));
        }
        TS(1);
        bar_sync(2, 128);
        if (ww == 3) count_release(C_KV);
    } else {
        uint4 kc[18];
        auto src = [&](int i) { return i < 8 ? g_s.kv + i * 128 : i < 12 ? g_s.kv + 4096 + (i - 8) * 128 : i < 16 ? g_s.kv + 6144 + (i - 12) * 128 : i == 16 ? g_s.kv + 31 * 128 : g_s.nrm + t128; };
        count_wait(C_KVH, lds32(mb + MISC_EPOCH) * (NMAIN * 2));
        TS(1);
        int spins = 0;
        while (true) {
#pragma unroll
            for (int i = 0; i < 18; i++) kc[i] = ldg_relaxed(src(i) + t128);
            uint32_t mn = 1;
#pragma unroll
            for (int i = 0; i < 18; i++) mn = min(mn, kc[i].x);
            if (!__any_sync(0xffffffffu, mn == 0u) || ++spins >= SPIN_LIMIT) break;
        }
        uint32_t nm = max(max(kc[17].x, kc[17].y), max(kc[17].z, kc[17].w));
        nm = max(nm, __shfl_xor_sync(0xffffffffu, nm, 4)); nm = max(nm, __shfl_xor_sync(0xffffffffu, nm, 8)); nm = max(nm, __shfl_xor_sync(0xffffffffu, nm, 16));
        if (lane < 4) asm volatile("red.shared.max.u32 [%0], %1;" :: "r"(mb + MISC_NRM + 4 + min(lane, 2) * 4), "r"(nm) : "memory");
        TS(2);
        bar_sync(6, 256);
#pragma unroll
        for (int i = 0; i < 17; i++) sts128(sb + (uint32_t)(src(i) - g_s.kv + t128) * 16 + ((i >= 8 && i < 16) ? SM_V - 65536 : 0), kc[i].x, kc[i].y, kc[i].z, kc[i].w);
    }
    fence_async_smem();
    TS(3);
    __syncthreads();
    const float4 nr = lds128f(mb + MISC_NRM);
    const bool safe = __all_sync(0xffffffffu, (nr.x * (nr.y + nr.z) <= 3500.0f) && (nr.x <= 65536.0f) && (nr.y + nr.z <= 65536.0f) && (nr.w <= 1e24f));
    TS(4);

    if (__builtin_expect(safe, 1)) {
        attention<true>(P, sb, warp TS_PASS);
    } else {
        if (wg == 0) {
#pragma unroll
            for (int h = 0; h < 8; h++)
                stsm4(qbase + h * 1024, pack_bf16(qa[8 * h], qa[8 * h + 1]), pack_bf16(qa[8 * h + 4], qa[8 * h + 5]), pack_bf16(qa[8 * h + 2], qa[8 * h + 3]), pack_bf16(qa[8 * h + 6], qa[8 * h + 7]));
            fence_async_smem();
        } else if (warp == 15) {
            count_wait(C_KV, lds32(mb + MISC_EPOCH) * NMAIN);
            if (lane == 0) {
                asm volatile("fence.proxy.async;" ::: "memory");
                mbar_expect(mb + MB_KV * 8, 131072);
                bulk_g2s(sb + SM_K, g_s.kplain, 65536, mb + MB_KV * 8);
                bulk_g2s(sb + SM_V, g_s.kv + 4096, 65536, mb + MB_KV * 8);
            }
            __syncwarp();
        }
        __syncthreads();
        mbar_wait(mb + MB_KV * 8);
        attention<false>(P, sb, warp TS_PASS);
    }

    epoch = lds32(mb + MISC_EPOCH);
    const int j = b & 7;
    if (wg == 1) {
        if (ww == 0) { mbar_wait(mb + (MB_DONE + 4) * 8); count_release(C_O + 16 + (b >> 3)); }
    } else if (wg == 2) {
        if (ww == 0) {
            int n = 0;
#pragma unroll 1
            for (int job = 0; job < 6; job++) {
                const int mt = (job & 1) * 16 + (b >> 3), ph = job >> 1;
                const uint4* src = g_x + ph * X_H1 + mt * (ph == 2 ? 88 : 32) * 128;
                Ring r(n);
                count_wait(C_O + 32 * ph + mt, epoch * (ph == 0 ? 8 : 32));
                asm volatile("fence.proxy.async.global;" ::: "memory");
                TS(18 + job);
#pragma unroll 1
                for (int i = 0; i < (ph == 2 ? 22 : 8); i++, n++) {
                    if (n == 36) mbar_wait(mb + (MB_REL + 7) * 8);
                    else if (n >= 4 && n != 37) mbar_wait(mb + (MB_EMPTY + r.e) * 8, r.parity() ^ 1);
                    if (lane == 0) { mbar_expect(mb + (MB_FULL + r.e) * 8, SLOT); bulk_g2s(sb + r.slot() * SLOT, src + i * 512, SLOT, mb + (MB_FULL + r.e) * 8); }
                    __syncwarp();
                    r.next();
                }
            }
        } else if (ww == 1) {
            mbar_wait(mb + (MB_DONE + 4) * 8);
#pragma unroll 1
            for (int i = 9; i < 24; i++) {
                if (i == 15) mbar_wait(mb + (MB_REL + 8) * 8);
                if (lane == 0) load_w1(sb, P, i / 3, i % 3);
                __syncwarp();
            }
#pragma unroll 1
            for (int i = 0; i < 22; i++) {
                const int kb = i / 3, a = i % 3;
                if (a == 0) mbar_wait(mb + (MB_REL + kb) * 8);
                if (lane == 0) load_box(sb, &P.w2, w1_slot(kb, a) * SLOT, MB_W2 + kb, SLOT, j * 64, i * 64);
                __syncwarp();
            }
        } else {
            count_wait(C_MID, epoch * NCTA);
            if (t128 < 64 + 44) {
                const uint4 v = ldg_relaxed(reinterpret_cast<const uint4*>(g_s.cs + j * 176) + t128 - 64);
                sts128(mb + MISC_CS + (t128 - 64) * 16, v.x, v.y, v.z, v.w);
            }
            warp_done(mb + MB_CS * 8);
            stg128(g_s.kv + kv_slot(), 0u, 0u, 0u, 0u);
            if (t128 < 66) stg128(g_s.nrm + b * 2 + t128 - 64, 0u, 0u, 0u, 0u);
        }
    } else {
        const int pr = (wg == 0), mt = 16 * pr + (b >> 3);
        uint32_t* const hp = reinterpret_cast<uint32_t*>(g_x + X_H1 + (mt * 32 + j * 4) * 128 + ww * 32) + lane;
        {
            uint32_t hk[16];
            const uint32_t* xp = reinterpret_cast<const uint32_t*>(P.x + (size_t)(mt * 64 + ww * 16 + g) * D + j * 64 + t4 * 2);
#pragma unroll
            for (int k = 0; k < 8; k++) { hk[2 * k] = __ldg(xp + k * 4); hk[2 * k + 1] = __ldg(xp + k * 4 + 8 * (D / 2)); }
            mbar_wait(mb + MB_WO * 8);
            if (pr) mbar_wait(mb + MB_TURN * 8);
            float acc[32];
            gemm_ss<0>(acc, sb, pr);
            TS(7);
            float st[4] = {0.f, 0.f, 0.f, 0.f};
#pragma unroll
            for (int i = 0; i < 16; i++) {
                hk[i] = pack_bf16(acc[2 * i] + bf_lo(hk[i]), acc[2 * i + 1] + bf_hi(hk[i]));
                const float lo = bf_lo(hk[i]), hi = bf_hi(hk[i]);
                st[2 * (i & 1)] += lo + hi;
                st[2 * (i & 1) + 1] = fmaf(lo, lo, fmaf(hi, hi, st[2 * (i & 1) + 1]));
            }
#pragma unroll
            for (int o = 1; o < 4; o <<= 1)
#pragma unroll
                for (int i = 0; i < 4; i++) st[i] += __shfl_xor_sync(0xffffffffu, st[i], o);
#pragma unroll
            for (int k = 0; k < 4; k++) store_tile(hp + k * 512, hk[4 * k], hk[4 * k + 1], hk[4 * k + 2], hk[4 * k + 3]);
            if (t4 == 0) stg128(g_x + X_ST + (mt * 8 + j) * 32 + ww * 8 + g, __float_as_uint(st[0]), __float_as_uint(st[1]), __float_as_uint(st[2]), __float_as_uint(st[3]));
            count_release(C_H1 + mt);
            TS(8);
        }
        {
            float acc[88];
            mbar_wait(mb + (MB_TURN + 1 + pr) * 8);
            mbar_wait(mb + MB_FULL * 8, 0);
            const uint4 u0 = ldg_relaxed(g_x + X_ST + (mt * 8 + t4) * 32 + ww * 8 + g), u1 = ldg_relaxed(g_x + X_ST + (mt * 8 + 4 + t4) * 32 + ww * 8 + g);
            gemm_ss<1>(acc, sb, pr);
            TS(9);
            float st[4] = {__uint_as_float(u0.x) + __uint_as_float(u1.x), __uint_as_float(u0.y) + __uint_as_float(u1.y),
                           __uint_as_float(u0.z) + __uint_as_float(u1.z), __uint_as_float(u0.w) + __uint_as_float(u1.w)};
#pragma unroll
            for (int o = 1; o < 4; o <<= 1)
#pragma unroll
                for (int k = 0; k < 4; k++) st[k] += __shfl_xor_sync(0xffffffffu, st[k], o);
            float nmean[2], hrstd[2];
#pragma unroll
            for (int k = 0; k < 2; k++) {
                nmean[k] = st[2 * k] * (-1.0f / D);
                hrstd[k] = 0.5f * rsqrtf(fmaxf(fmaf(-nmean[k], nmean[k], st[2 * k + 1] * (1.0f / D)), 0.f) + 1e-5f);
                nmean[k] *= hrstd[k];
            }
            mbar_wait(mb + MB_CS * 8);
            uint32_t* hb = reinterpret_cast<uint32_t*>(g_x + X_H2 + (mt * 88 + j * 11) * 128 + ww * 32) + lane;
#pragma unroll
            for (int i = 0; i < 22; i++) {
                float2 cs;
                asm volatile("ld.shared.v2.f32 {%0,%1}, [%2];" : "=f"(cs.x), "=f"(cs.y) : "r"(mb + MISC_CS + i * 32 + t4 * 8));
                const float* z = acc + 4 * i;
                uint32_t* p = hb + (i >> 1) * 512 + (i & 1) * 32;
                stg32(p, pack_bf16(silu2(fmaf(hrstd[0], z[0], nmean[0] * cs.x)), silu2(fmaf(hrstd[0], z[1], nmean[0] * cs.y))));
                stg32(p + 64, pack_bf16(silu2(fmaf(hrstd[1], z[2], nmean[1] * cs.x)), silu2(fmaf(hrstd[1], z[3], nmean[1] * cs.y))));
            }
            TS(10);
            count_release(C_H2 + mt);
        }
        {
            uint32_t hk[16];
#pragma unroll
            for (int i = 0; i < 16; i++) hk[i] = ldg32_relaxed(hp + (i >> 2) * 512 + ((i & 1) * 2 + ((i >> 1) & 1)) * 32);
            mbar_wait(mb + (MB_TURN + 3 + pr) * 8);
            float acc[32];
            gemm_ss<2>(acc, sb, pr);
            TS(11);
#pragma unroll
            for (int i = 0; i < 16; i++) hk[i] = pack_bf16(acc[2 * i] + bf_lo(hk[i]), acc[2 * i + 1] + bf_hi(hk[i]));
#pragma unroll
            for (int h = 0; h < 4; h++) {
                const uint32_t* v = hk + (h >> 1) * 8 + (h & 1);
                uint32_t v0 = v[0], v1 = v[2], v2 = v[4], v3 = v[6];
                const bool o1 = t4 & 1, o2 = t4 & 2;
                uint32_t a = __shfl_xor_sync(0xffffffffu, o1 ? v0 : v1, 1), c = __shfl_xor_sync(0xffffffffu, o1 ? v2 : v3, 1);
                if (o1) { v0 = a; v2 = c; } else { v1 = a; v3 = c; }
                a = __shfl_xor_sync(0xffffffffu, o2 ? v0 : v2, 2); c = __shfl_xor_sync(0xffffffffu, o2 ? v1 : v3, 2);
                if (o2) { v0 = a; v1 = c; } else { v2 = a; v3 = c; }
                *reinterpret_cast<uint4*>(P.out + (size_t)(mt * 64 + ww * 16 + g + 8 * (h & 1)) * D + j * 64 + (h >> 1) * 32 + t4 * 8) = make_uint4(v0, v1, v2, v3);
            }
        }
    }
    TS(12);
}

typedef CUresult (*EncodeFn)(CUtensorMap*, CUtensorMapDataType, cuuint32_t, void*, const cuuint64_t*, const cuuint64_t*, const cuuint32_t*,
                             const cuuint32_t*, CUtensorMapInterleave, CUtensorMapSwizzle, CUtensorMapL2promotion, CUtensorMapFloatOOBfill);

void encode2d(EncodeFn fn, CUtensorMap* tm, const void* ptr, int rows, int cols, int box_rows, int box_cols, CUtensorMapSwizzle sw) {
    cuuint64_t dims[2] = {(cuuint64_t)cols, (cuuint64_t)rows};
    cuuint64_t strides[1] = {(cuuint64_t)cols * 2};
    cuuint32_t box[2] = {(cuuint32_t)box_cols, (cuuint32_t)box_rows};
    cuuint32_t es[2] = {1, 1};
    fn(tm, CU_TENSOR_MAP_DATA_TYPE_BFLOAT16, 2, const_cast<void*>(ptr), dims, strides, box, es, CU_TENSOR_MAP_INTERLEAVE_NONE, sw,
       CU_TENSOR_MAP_L2_PROMOTION_L2_128B, CU_TENSOR_MAP_FLOAT_OOB_FILL_NONE);
}

}

extern "C" void kernel_launch(void* const* d_in, const int* in_sizes, int n_in, void* d_out, int out_size) {
    (void)in_sizes; (void)n_in; (void)out_size;
    void* fnp = nullptr;
    cudaDriverEntryPointQueryResult qr;
    cudaGetDriverEntryPoint("cuTensorMapEncodeTiled", &fnp, cudaEnableDefault, &qr);
    EncodeFn fn = (EncodeFn)fnp;
    Params P;
    encode2d(fn, &P.wq, d_in[1], D, D, 128, 64, CU_TENSOR_MAP_SWIZZLE_128B);
    P.wk = (const __nv_bfloat16*)d_in[2];
    P.wv_off = (const char*)d_in[3] - (const char*)d_in[2];
    encode2d(fn, &P.wo, d_in[4], D, D, 64, 64, CU_TENSOR_MAP_SWIZZLE_128B);
    encode2d(fn, &P.w1, d_in[6], D, FF, 64, 64, CU_TENSOR_MAP_SWIZZLE_128B);
    encode2d(fn, &P.w2, d_in[7], FF, D, 64, 64, CU_TENSOR_MAP_SWIZZLE_128B);
    P.x = (const __nv_bfloat16*)d_in[0];
    P.w1p = (const __nv_bfloat16*)d_in[6];
    P.w2p = (const __nv_bfloat16*)d_in[7];
    P.wop = (const __nv_bfloat16*)d_in[4];
    P.wqp = (const __nv_bfloat16*)d_in[1];
    P.out = (__nv_bfloat16*)d_out;
    P.neg1 = 0xFFFFFFFFu; P.pad = 0;
    cudaFuncSetAttribute(fused_kernel, cudaFuncAttributeMaxDynamicSharedMemorySize, SMEM_BYTES);
    fused_kernel<<<NCTA, 512, SMEM_BYTES>>>(P);
}
```

```cpp
#include <cuda_runtime.h>
#include <cuda_bf16.h>
#include <cuda.h>
#include <stdint.h>

namespace {

constexpr int D = 512, FF = 1376;
constexpr int NMAIN = 128, NHELP = 4, NCTA = NMAIN + NHELP;
constexpr uint32_t SENT = 0xFFFFFFFFu;
constexpr int SPIN_LIMIT = 1 << 22;

constexpr uint32_t KB = 1024, SLOT = 8192;
constexpr uint32_t SM_XN = 0;
constexpr uint32_t SM_WQ = 64 * KB;
constexpr uint32_t SM_WKV = 192 * KB;
constexpr uint32_t SM_K = 0;
constexpr uint32_t SM_Q = 64 * KB;
constexpr uint32_t SM_V = 96 * KB;
constexpr uint32_t SM_MISC = 224 * KB;
constexpr uint32_t SMEM_BYTES = 227 * KB;
constexpr uint32_t SM_KTMP = 200 * KB;
constexpr uint32_t SM_RSTD = 202 * KB;
constexpr uint32_t SM_WNRM = 203 * KB;
constexpr uint32_t SM_SENT = 208 * KB;
constexpr uint32_t MB_WQ = 0;
constexpr uint32_t MB_CS = 4;
constexpr uint32_t MB_DONE = 5;
constexpr uint32_t MB_EMPTY = 10;
constexpr uint32_t MB_W1 = 16;
constexpr uint32_t MB_W2 = 24;
constexpr uint32_t MB_WO = 32;
constexpr uint32_t MB_REL = 33;
constexpr uint32_t MB_LAND = 42;
constexpr uint32_t MB_KV = 48;
constexpr uint32_t MB_MID = 49;
constexpr uint32_t MB_FULL = 50;
constexpr uint32_t NBAR = 126;
constexpr uint32_t MISC_NRM = 1024;
constexpr uint32_t MISC_EPOCH = 1040;
constexpr uint32_t MISC_TS = 1056;
constexpr uint32_t MISC_CS = 1280;

__host__ __device__ constexpr uint32_t wo_slot(int kb) { return kb < 2 ? 10 + kb : kb - 2; }
__host__ __device__ constexpr uint32_t w1_slot(int kb, int a) { return kb < 4 ? 12 + kb + 4 * a : (kb == 4 ? 6 : kb == 7 ? 9 : 3 * kb - 15) + a; }

struct alignas(128) Small {
    unsigned epoch[160];
    unsigned cnt[100][32];
    float cs[1440];
    uint4 nrm[NMAIN * 2];
    uint4 kv[8192];
    uint4 kplain[4096];
};
__device__ Small g_s;
constexpr int C_KVH = 0, C_KV = 1, C_MID = 2, C_O = 3, C_H1 = 35, C_H2 = 67;
constexpr int X_O = 0, X_H1 = 32 * 32 * 128, X_H2 = 2 * X_H1, X_ST = X_H2 + 32 * 88 * 128, X_END = X_ST + 32 * 8 * 32;
constexpr int X_ARM = 16 * 32 * 128, X_SHARE = (X_END - X_ARM) / NMAIN;
__device__ uint4 g_x[X_END];
#define TS(i) do {} while (0)

#define TS_ARG
#define TS_PASS

__device__ __forceinline__ void mbar_init(uint32_t bar, int cnt) { asm volatile("mbarrier.init.shared::cta.b64 [%0], %1;" :: "r"(bar), "r"(cnt) : "memory"); }
__device__ __forceinline__ void mbar_expect(uint32_t bar, uint32_t bytes) { asm volatile("mbarrier.arrive.expect_tx.shared::cta.b64 _, [%0], %1;" :: "r"(bar), "r"(bytes) : "memory"); }
__device__ __forceinline__ void mbar_arrive(uint32_t bar) { asm volatile("mbarrier.arrive.shared::cta.b64 _, [%0];" :: "r"(bar) : "memory"); }
__device__ __forceinline__ void mbar_wait(uint32_t bar, uint32_t parity = 0) {
    uint32_t done; int spins = 0;
    do {
        asm volatile("{.reg .pred p; mbarrier.try_wait.parity.shared::cta.b64 p, [%1], %2; selp.u32 %0, 1, 0, p;}" : "=r"(done) : "r"(bar), "r"(parity) : "memory");
    } while (!__all_sync(0xffffffffu, done) && ++spins < SPIN_LIMIT);
}
__device__ __forceinline__ void tma2d(uint32_t dst, const CUtensorMap* tm, int c0, int c1, uint32_t bar) {
    asm volatile("cp.async.bulk.tensor.2d.shared::cluster.global.mbarrier::complete_tx::bytes [%0], [%1, {%3, %4}], [%2];"
                 :: "r"(dst), "l"(tm), "r"(bar), "r"(c0), "r"(c1) : "memory");
}
__device__ __forceinline__ void bulk_g2s(uint32_t dst, const void* src, uint32_t bytes, uint32_t bar) {
    asm volatile("cp.async.bulk.shared::cluster.global.mbarrier::complete_tx::bytes [%0], [%1], %2, [%3];" :: "r"(dst), "l"(src), "r"(bytes), "r"(bar) : "memory");
}
__device__ __forceinline__ void fence_async_smem() { asm volatile("fence.proxy.async.shared::cta;" ::: "memory"); }
__device__ __forceinline__ void bar_sync(int id, int n) { asm volatile("bar.sync %0, %1;" :: "r"(id), "r"(n) : "memory"); }
__device__ __forceinline__ void bar_arrive(int id, int n) { asm volatile("bar.arrive %0, %1;" :: "r"(id), "r"(n) : "memory"); }
__device__ __forceinline__ void wg_fence() { asm volatile("wgmma.fence.sync.aligned;" ::: "memory"); }
__device__ __forceinline__ void wg_commit() { asm volatile("wgmma.commit_group.sync.aligned;" ::: "memory"); }
template <int N> __device__ __forceinline__ void wg_wait() { asm volatile("wgmma.wait_group.sync.aligned %0;" :: "n"(N) : "memory"); }
template <int N> __device__ __forceinline__ void fence_regs(float (&d)[N]) {
#pragma unroll
    for (int i = 0; i < N; i++) asm volatile("" : "+f"(d[i]) :: "memory");
}
template <int N> __device__ __forceinline__ void fence_regs(uint32_t (&d)[N]) {
#pragma unroll
    for (int i = 0; i < N; i++) asm volatile("" : "+r"(d[i]) :: "memory");
}
__device__ __forceinline__ uint64_t mkdesc(uint32_t addr, uint32_t lbo, uint32_t sbo, uint32_t swz) {
    return (uint64_t)(((addr & 0x3FFFF) >> 4) | ((lbo >> 4) << 16)) | ((uint64_t)((sbo >> 4) | (swz << 30)) << 32);
}
__device__ __forceinline__ float ex2(float x) { float y; asm("ex2.approx.ftz.f32 %0, %1;" : "=f"(y) : "f"(x)); return y; }
__device__ __forceinline__ float rcp(float x) { float y; asm("rcp.approx.ftz.f32 %0, %1;" : "=f"(y) : "f"(x)); return y; }
__device__ __forceinline__ uint32_t pack_bf16(float lo, float hi) { uint32_t r; asm("cvt.rn.bf16x2.f32 %0, %1, %2;" : "=r"(r) : "f"(hi), "f"(lo)); return r; }
__device__ __forceinline__ uint32_t pack_f16(float lo, float hi) { uint32_t r; asm("cvt.rn.f16x2.f32 %0, %1, %2;" : "=r"(r) : "f"(hi), "f"(lo)); return r; }
__device__ __forceinline__ float bf_lo(uint32_t v) { return __uint_as_float(v << 16); }
__device__ __forceinline__ float bf_hi(uint32_t v) { return __uint_as_float(v & 0xFFFF0000u); }
__device__ __forceinline__ uint4 ldg_relaxed(const uint4* p) {
    uint4 v; asm volatile("ld.relaxed.gpu.global.v4.u32 {%0,%1,%2,%3}, [%4];" : "=r"(v.x), "=r"(v.y), "=r"(v.z), "=r"(v.w) : "l"(p) : "memory"); return v;
}
__device__ __forceinline__ void stg128(void* p, uint32_t a, uint32_t b, uint32_t c, uint32_t d) {
    asm volatile("st.relaxed.gpu.global.v4.u32 [%0], {%1,%2,%3,%4};" :: "l"(p), "r"(a), "r"(b), "r"(c), "r"(d) : "memory");
}
__device__ __forceinline__ void stg64(void* p, uint32_t a, uint32_t b) {
    asm volatile("st.relaxed.gpu.global.v2.u32 [%0], {%1,%2};" :: "l"(p), "r"(a), "r"(b) : "memory");
}
__device__ __forceinline__ void sts128(uint32_t a, uint32_t x, uint32_t y, uint32_t z, uint32_t w) {
    asm volatile("st.shared.v4.u32 [%0], {%1,%2,%3,%4};" :: "r"(a), "r"(x), "r"(y), "r"(z), "r"(w) : "memory");
}
__device__ __forceinline__ void sts32(uint32_t a, uint32_t x) { asm volatile("st.shared.u32 [%0], %1;" :: "r"(a), "r"(x) : "memory"); }
__device__ __forceinline__ float4 lds128f(uint32_t a) {
    float4 v; asm volatile("ld.shared.v4.f32 {%0,%1,%2,%3}, [%4];" : "=f"(v.x), "=f"(v.y), "=f"(v.z), "=f"(v.w) : "r"(a) : "memory"); return v;
}
__device__ __forceinline__ uint32_t lds32(uint32_t a) { uint32_t v; asm volatile("ld.shared.u32 %0, [%1];" : "=r"(v) : "r"(a) : "memory"); return v; }
__device__ __forceinline__ uint32_t nonzero(uint32_t w) { return w == 0u ? 0x8000u : w; }
__device__ __forceinline__ void stg32(void* p, uint32_t a) { asm volatile("st.global.u32 [%0], %1;" :: "l"(p), "r"(a) : "memory"); }
__device__ __forceinline__ uint32_t ldg32_relaxed(const void* p) { uint32_t v; asm volatile("ld.relaxed.gpu.global.u32 %0, [%1];" : "=r"(v) : "l"(p) : "memory"); return v; }
__device__ __forceinline__ void count_hint(int id) {
    if ((threadIdx.x & 31) == 0) asm volatile("red.relaxed.gpu.global.add.u32 [%0], 1;" :: "l"(g_s.cnt[id]) : "memory");
}
__device__ __forceinline__ void count_release(int id) {
    __syncwarp();
    if ((threadIdx.x & 31) == 0) asm volatile("red.release.gpu.global.add.u32 [%0], 1;" :: "l"(g_s.cnt[id]) : "memory");
    __syncwarp();
}
__device__ __forceinline__ void count_wait(int id, unsigned target) {
    uint32_t v; int spins = 0;
    do v = ldg32_relaxed(g_s.cnt[id]); while (__any_sync(0xffffffffu, v != target) && ++spins < SPIN_LIMIT);
    asm volatile("fence.acquire.gpu;" ::: "memory");
}
__device__ __forceinline__ void warp_done(uint32_t bar) {
    __syncwarp();
    asm volatile("{.reg .pred p; setp.eq.u32 p, %1, 0; @p mbarrier.arrive.shared::cta.b64 _, [%0];}" :: "r"(bar), "r"(threadIdx.x & 31) : "memory");
}
__device__ __forceinline__ uint32_t mul_bf16x2(uint32_t a, uint32_t b) { uint32_t r; asm("mul.rn.bf16x2 %0, %1, %2;" : "=r"(r) : "r"(a), "r"(b)); return r; }
__device__ __forceinline__ uint32_t fma_bf16x2(uint32_t a, uint32_t b, uint32_t c) { uint32_t r; asm("fma.rn.bf16x2 %0, %1, %2, %3;" : "=r"(r) : "r"(a), "r"(b), "r"(c)); return r; }
__device__ __forceinline__ uint32_t add_bf16x2(uint32_t a, uint32_t b) { uint32_t r; asm("add.rn.bf16x2 %0, %1, %2;" : "=r"(r) : "r"(a), "r"(b)); return r; }

#define R4(d, o) "+f"(d[o + 0]), "+f"(d[o + 1]), "+f"(d[o + 2]), "+f"(d[o + 3])
#define R8(d, o) R4(d, o), R4(d, o + 4)
#define R32(d) R8(d, 0), R8(d, 8), R8(d, 16), R8(d, 24)
#define D32 "{%0,%1,%2,%3,%4,%5,%6,%7,%8,%9,%10,%11,%12,%13,%14,%15,%16,%17,%18,%19,%20,%21,%22,%23,%24,%25,%26,%27,%28,%29,%30,%31}"
#define D64 "{%0,%1,%2,%3,%4,%5,%6,%7,%8,%9,%10,%11,%12,%13,%14,%15,%16,%17,%18,%19,%20,%21,%22,%23,%24,%25,%26,%27,%28,%29,%30,%31,%32,%33,%34,%35,%36,%37,%38,%39,%40,%41,%42,%43,%44,%45,%46,%47,%48,%49,%50,%51,%52,%53,%54,%55,%56,%57,%58,%59,%60,%61,%62,%63}"

__device__ __forceinline__ void mma_qk_f16(float (&d)[32], uint64_t da, uint64_t db) {
    asm volatile("{.reg .pred p; setp.eq.b32 p, 0, 0; wgmma.mma_async.sync.aligned.m64n64k16.f32.f16.f16 " D32 ", %32, %33, p, 1, 1, 0, 0;}"
                 : R32(d) : "l"(da), "l"(db));
}
__device__ __forceinline__ void mma_qk_bf16(float (&d)[32], uint64_t da, uint64_t db) {
    asm volatile("{.reg .pred p; setp.ne.b32 p, 0, 0; wgmma.mma_async.sync.aligned.m64n64k16.f32.bf16.bf16 " D32 ", %32, %33, p, 1, 1, 0, 0;}"
                 : R32(d) : "l"(da), "l"(db));
}
__device__ __forceinline__ void mma_pv(float (&d)[12], const uint32_t* a, uint64_t db) {
    asm volatile("{.reg .pred p; setp.eq.b32 p, 0, 0; wgmma.mma_async.sync.aligned.m64n24k16.f32.bf16.bf16 {%0,%1,%2,%3,%4,%5,%6,%7,%8,%9,%10,%11}, {%12,%13,%14,%15}, %16, p, 1, 1, 1;}"
                 : R8(d, 0), R4(d, 8) : "r"(a[0]), "r"(a[1]), "r"(a[2]), "r"(a[3]), "l"(db));
}
__device__ __forceinline__ void mma_ss128(float (&d)[64], uint64_t da, uint64_t db) {
    asm volatile("{.reg .pred p; setp.eq.b32 p, 0, 0; wgmma.mma_async.sync.aligned.m64n128k16.f32.bf16.bf16 " D64 ", %64, %65, p, 1, 1, 0, 1;}"
                 : R32(d), R8(d, 32), R8(d, 40), R8(d, 48), R8(d, 56) : "l"(da), "l"(db));
}
__device__ __forceinline__ void stsm4(uint32_t addr, uint32_t a, uint32_t b, uint32_t c, uint32_t d) {
    asm volatile("stmatrix.sync.aligned.m8n8.x4.shared.b16 [%0], {%1,%2,%3,%4};" :: "r"(addr), "r"(a), "r"(b), "r"(c), "r"(d) : "memory");
}
__device__ __forceinline__ void mma_ss8(float (&d)[4], uint64_t da, uint64_t db) {
    asm volatile("{.reg .pred p; setp.eq.b32 p, 0, 0; wgmma.mma_async.sync.aligned.m64n8k16.f32.bf16.bf16 {%0,%1,%2,%3}, %4, %5, p, 1, 1, 0, 1;}"
                 : R4(d, 0) : "l"(da), "l"(db));
}
__device__ __forceinline__ void mma_ss(float (&d)[32], uint64_t da, uint64_t db) {
    asm volatile("{.reg .pred p; setp.eq.b32 p, 0, 0; wgmma.mma_async.sync.aligned.m64n64k16.f32.bf16.bf16 " D32 ", %32, %33, p, 1, 1, 0, 1;}"
                 : R32(d) : "l"(da), "l"(db));
}
__device__ __forceinline__ void mma_ss(float (&d)[88], uint64_t da, uint64_t db) {
    asm volatile("{.reg .pred p; setp.eq.b32 p, 0, 0; wgmma.mma_async.sync.aligned.m64n176k16.f32.bf16.bf16 " "{%0,%1,%2,%3,%4,%5,%6,%7,%8,%9,%10,%11,%12,%13,%14,%15,%16,%17,%18,%19,%20,%21,%22,%23,%24,%25,%26,%27,%28,%29,%30,%31,%32,%33,%34,%35,%36,%37,%38,%39,%40,%41,%42,%43,%44,%45,%46,%47,%48,%49,%50,%51,%52,%53,%54,%55,%56,%57,%58,%59,%60,%61,%62,%63,%64,%65,%66,%67,%68,%69,%70,%71,%72,%73,%74,%75,%76,%77,%78,%79,%80,%81,%82,%83,%84,%85,%86,%87}"
                 ", %88, %89, p, 1, 1, 0, 1;}"
                 : R32(d), R8(d, 32), R8(d, 40), R8(d, 48), R8(d, 56), R8(d, 64), R8(d, 72), R8(d, 80) : "l"(da), "l"(db));
}

constexpr float EXP_MAGIC = 256.0f + 127.0f + 64.0f - 1.58621f + 0.00390625f;
constexpr uint32_t MUFU_MASK = 0x1111u;
__device__ __forceinline__ uint32_t exp2_pair(float y0, float y1, uint32_t cexp, uint32_t neg1) {
    uint32_t w, m, e, r;
    asm("prmt.b32 %0, %1, %2, 0x6521;" : "=r"(w) : "r"(__float_as_uint(y0)), "r"(__float_as_uint(y1)));
    asm("lop3.b32 %0, %1, 0x007F007F, %2, 0xEA;" : "=r"(m) : "r"(w), "r"(cexp));
    asm("mad.lo.u32 %0, %1, %2, %3;" : "=r"(e) : "r"(m), "r"(neg1), "r"(w));
    asm("fma.rn.bf16x2 %0, %1, %2, %3;" : "=r"(r) : "r"(w), "r"(m), "r"(e));
    return r;
}

struct Params {
    const __nv_bfloat16* x;
    const __nv_bfloat16* wk;
    long long wv_off;
    const __nv_bfloat16* wqp;
    __nv_bfloat16* out;
    uint32_t neg1, pad;
    const __nv_bfloat16* w1p;
    const __nv_bfloat16* w2p;
    CUtensorMap wq, wo, w1, w2;
    const __nv_bfloat16* wop;
};

__device__ __forceinline__ void load_box(uint32_t sb, const CUtensorMap* tm, uint32_t dst, uint32_t bar, uint32_t bytes, int c0, int c1) {
    mbar_expect(sb + SM_MISC + bar * 8, bytes);
    tma2d(sb + dst, tm, c0, c1, sb + SM_MISC + bar * 8);
}
__device__ __forceinline__ void load_wq(uint32_t sb, const Params& P, int gi, int atom) {
    load_box(sb, &P.wq, SM_WQ + atom * 65536 + gi * 16384, MB_WQ + gi, 16384, (blockIdx.x & 3) * 128 + atom * 64, gi * 128);
}
__device__ __forceinline__ void load_wo(uint32_t sb, const Params& P, int kb) { load_box(sb, &P.wo, wo_slot(kb) * SLOT, MB_WO, SLOT, (blockIdx.x & 7) * 64, kb * 64); }
__device__ __forceinline__ void refill_job(uint32_t sb, const Params& P, int gi, int job) {
    const bool w1 = job < 3;
    load_box(sb, w1 ? &P.w1 : &P.wo, (w1 ? 12 + gi + 4 * job : 2 * gi + job - 3) * SLOT, w1 ? MB_W1 + gi : MB_WO, SLOT,
             (blockIdx.x & 7) * (w1 ? 176 : 64) + (w1 ? job * 64 : 0), (w1 ? gi : 2 * gi + job - 1) * 64);
}

__host__ __device__ constexpr int ring_entry(int n) { return n < 32 ? (n & 3) : (n - 32) % 6; }
__host__ __device__ constexpr uint32_t ring_slot(int e) { return e < 4 ? 24 + e : 6 + e; }

template <int KIND, int NACC>
__device__ __forceinline__ void gemm_ss(float (&acc)[NACC], uint32_t sb, int pr) {
    const uint32_t mb = sb + SM_MISC;
    constexpr int NBLK = KIND == 2 ? 22 : 8, N0 = 16 * KIND;
    const uint32_t full = mb + (MB_FULL + N0 + pr * NBLK) * 8;
#pragma unroll
    for (int i = 0; i < NACC; i++) acc[i] = 0.f;
    fence_regs(acc);
#pragma unroll
    for (int i = 0; i < NBLK; i++) {
        const uint64_t db = KIND == 0 ? mkdesc(sb + wo_slot(i) * SLOT, 16, 1024, 1)
                          : KIND == 1 ? mkdesc(sb + w1_slot(i, 0) * SLOT, i < 4 ? 4 * SLOT : SLOT, 1024, 1) : mkdesc(sb + w1_slot(i / 3, i % 3) * SLOT, 16, 1024, 1);
        const uint64_t da = mkdesc(sb + (pr ? ring_slot(ring_entry(N0 + NBLK + i)) : ring_slot(ring_entry(N0 + i))) * SLOT, 128, 256, 0);
        mbar_wait(full + i * 8);
        wg_fence();
#pragma unroll
        for (int s = 0; s < 4; s++) mma_ss(acc, da + s * 128, db + s * 128);
        wg_commit();
        if (i > 0) {
            wg_wait<1>();
            warp_done(mb + (MB_EMPTY + (pr ? ring_entry(N0 + NBLK + i - 1) : ring_entry(N0 + i - 1))) * 8);
            if (KIND == 1) warp_done(mb + (MB_REL + i - 1) * 8);
        }
    }
    wg_wait<0>();
    fence_regs(acc);
    warp_done(mb + (MB_EMPTY + (pr ? ring_entry(N0 + 2 * NBLK - 1) : ring_entry(N0 + NBLK - 1))) * 8);
    if (KIND != 2) warp_done(mb + (MB_REL + 8 - KIND) * 8);
}
__device__ __forceinline__ void ring_feed(uint32_t sb, int e, unsigned epoch TS_ARG) {
    const uint32_t mb = sb + SM_MISC, dst = sb + ring_slot(e) * SLOT, land = mb + (MB_LAND + e) * 8;
    const int lane = threadIdx.x & 31;
    uint32_t use = 0, lph = 0;
    int seen = 0;
#pragma unroll 1
    for (int n = e < 4 ? e : 32 + e; n < 76; n += (n < 32 ? 4 : 6), use ^= 1) {
        const int job = n < 32 ? n >> 3 : 4 + (n >= 54), ph = job >> 1, i = n < 32 ? n & 7 : n - 32 - (job & 1) * 22;
        const int mt = (job & 1) * 16 + (blockIdx.x >> 3);
        const uint4* src = g_x + ph * X_H1 + mt * (ph == 2 ? 88 : 32) * 128 + i * 512;
        if (job != seen) { count_wait(C_O + 32 * ph + mt, epoch * (ph == 0 ? 128 : 32)); seen = job; TS(18 + job); }
        if (n == 32 + e && e >= 4) mbar_wait(mb + (MB_REL + 7) * 8);
        else if (n >= 4) mbar_wait(mb + (MB_EMPTY + e) * 8, use ^ 1);
        int spins = 0;
        bool bad;
        do {
            if (lane == 0) {
                asm volatile("fence.proxy.async.global;" ::: "memory");
                mbar_expect(land, SLOT); bulk_g2s(dst, src, SLOT, land);
            }
            __syncwarp();
            mbar_wait(mb + (ph == 0 ? MB_WO : ph == 1 ? MB_W1 + i : MB_W2 + i / 3) * 8);
            mbar_wait(land, lph); lph ^= 1;
            uint32_t m = 0;
#pragma unroll
            for (int k = 0; k < 8; k++) m = max(m, lds32(dst + k * 1024 + lane * 32 + (lane >> 2) * 4));
            bad = __any_sync(0xffffffffu, m == SENT);
        } while (bad && ++spins < SPIN_LIMIT);
        warp_done(mb + (MB_FULL + n) * 8);
    }
}
__device__ __forceinline__ void store_tile(uint32_t* p, uint32_t r0k0, uint32_t r8k0, uint32_t r0k8, uint32_t r8k8) {
    stg32(p, r0k0); stg32(p + 32, r0k8); stg32(p + 64, r8k0); stg32(p + 96, r8k8);
}

__device__ __forceinline__ float quad_sum(float v) { v += __shfl_xor_sync(0xffffffffu, v, 1); v += __shfl_xor_sync(0xffffffffu, v, 2); return v; }
__device__ __forceinline__ float reduce4(const float (&st)[4], int lane) {
    const bool u16 = lane & 16, u8 = lane & 8;
    const float a0 = (u16 ? st[2] : st[0]) + __shfl_xor_sync(0xffffffffu, u16 ? st[0] : st[2], 16);
    const float a1 = (u16 ? st[3] : st[1]) + __shfl_xor_sync(0xffffffffu, u16 ? st[1] : st[3], 16);
    float v = (u8 ? a1 : a0) + __shfl_xor_sync(0xffffffffu, u8 ? a0 : a1, 8);
    v += __shfl_xor_sync(0xffffffffu, v, 4); v += __shfl_xor_sync(0xffffffffu, v, 2); v += __shfl_xor_sync(0xffffffffu, v, 1);
    return v;
}
__device__ __forceinline__ float silu2(float h) { float t; asm("tanh.approx.f32 %0, %1;" : "=f"(t) : "f"(h)); return fmaf(h, t, h); }

template <bool SAFE>
__device__ __forceinline__ void attention(const Params& P, uint32_t sb, int warp TS_ARG) {
    const uint32_t mb = sb + SM_MISC;
    const int tid = threadIdx.x, lane = tid & 31, b = blockIdx.x;
    const int wg = warp >> 2, ww = warp & 3, job = 3 - wg + 4 * ww;
    const uint32_t cexp = 0x9F809F80u + (tid >> 12);
    const uint32_t neg1 = P.neg1;
    unsigned cnt = 0;
    if (SAFE && warp == 8) cnt = ldg32_relaxed(g_s.cnt[C_KV]);
#pragma unroll 1
    for (int pass = 0; pass < 2; pass++) {
    float o[12], s[32];
    const uint64_t dq = mkdesc(sb + SM_Q + (pass * 4 + wg) * 2048, 128, 256, 0);
    uint64_t dk = mkdesc(sb + SM_K, 128, 256, 0), dv = mkdesc(sb + SM_V, 128, 32768, 0);
    float m0 = -INFINITY, m1 = -INFINITY;
#pragma unroll
    for (int i = 0; i < 12; i++) o[i] = 0.f;
#pragma unroll
    for (int i = 0; i < 32; i++) s[i] = ((MUFU_MASK >> (i / 2)) & 1) ? 0.f : EXP_MAGIC;
    fence_regs(s); fence_regs(o);
    wg_fence();
    if (SAFE) mma_qk_f16(s, dq, dk + 31 * 128); else mma_qk_bf16(s, dq, dk + 31 * 128);
    wg_commit();
    wg_wait<0>(); fence_regs(s);
#pragma unroll 1
    for (int u = pass ? 3 : (wg == 2) ? 0 : 1; u < (pass ? 8 : 3); u++) {
        int n = 2 * ((((wg == 2) ? 0x22444C31u : 0x22444C40u) >> (4 * u)) & 15);
#pragma unroll 1
        do {
            uint32_t p[16];
            if (SAFE) {
#pragma unroll
                for (int j = 0; j < 16; j++) {
                    if ((MUFU_MASK >> j) & 1) p[j] = pack_bf16(ex2(s[2 * j]), ex2(s[2 * j + 1]));
                    else p[j] = exp2_pair(s[2 * j], s[2 * j + 1], cexp, neg1);
                }
            } else {
                fence_regs(o);
                float x0 = m0, x1 = m1;
#pragma unroll
                for (int j = 0; j < 8; j++) { x0 = fmaxf(x0, fmaxf(s[4 * j], s[4 * j + 1])); x1 = fmaxf(x1, fmaxf(s[4 * j + 2], s[4 * j + 3])); }
                x0 = fmaxf(x0, __shfl_xor_sync(0xffffffffu, x0, 1)); x0 = fmaxf(x0, __shfl_xor_sync(0xffffffffu, x0, 2));
                x1 = fmaxf(x1, __shfl_xor_sync(0xffffffffu, x1, 1)); x1 = fmaxf(x1, __shfl_xor_sync(0xffffffffu, x1, 2));
                const float c0 = ex2(m0 - x0), c1 = ex2(m1 - x1);
                m0 = x0; m1 = x1;
#pragma unroll
                for (int j = 0; j < 3; j++) { o[4 * j] *= c0; o[4 * j + 1] *= c0; o[4 * j + 2] *= c1; o[4 * j + 3] *= c1; }
#pragma unroll
                for (int j = 0; j < 8; j++) {
                    p[2 * j] = pack_bf16(ex2(s[4 * j] - m0), ex2(s[4 * j + 1] - m0));
                    p[2 * j + 1] = pack_bf16(ex2(s[4 * j + 2] - m1), ex2(s[4 * j + 3] - m1));
                }
                fence_regs(o);
            }
            fence_regs(p);
            wg_fence();
            if (SAFE) mma_qk_f16(s, dq, dk); else mma_qk_bf16(s, dq, dk);
#pragma unroll
            for (int j = 0; j < 4; j++) mma_pv(o, p + 4 * j, dv + j * 16);
            wg_commit();
            dk += 128; dv += 64;
            wg_wait<0>(); fence_regs(s);
        } while (--n > 0);
        if (u == 2 || u == 7) {
            fence_regs(o);
            const float i0 = rcp(o[8]), i1 = rcp(o[10]);
            if (u == 7) mbar_wait(mb + MB_MID * 8);
            store_tile(reinterpret_cast<uint32_t*>(g_x + X_O + (((u == 7) * 16 + (b >> 3)) * 32 + (b & 3) * 8 + 2 * wg + (ww >> 1)) * 128 + (((b >> 2) & 1) * 2 + (ww & 1)) * 32) + lane,
                       pack_bf16(o[0] * i0, o[1] * i0), pack_bf16(o[2] * i1, o[3] * i1), pack_bf16(o[4] * i0, o[5] * i0), pack_bf16(o[6] * i1, o[7] * i1));
            if (u == 2) asm volatile("cp.async.bulk.wait_group 0;" ::: "memory");
            else count_hint(C_O + 16 + (b >> 3));
            warp_done(mb + (MB_DONE + (u == 7) * 4) * 8);
            TS(5 + (u == 7));
        } else if (u >= 3) {
            if (u < 6) warp_done(mb + (MB_DONE + u - 2) * 8);
            if (job < (u == 3 ? 1 : 5)) {
                mbar_wait(mb + (MB_DONE + u - 3) * 8);
                if (u == 3) count_release(C_MID);
                else if (lane == 0) refill_job(sb, P, u - 4, job);
            } else if (warp == 7) {
                if (u == 5) cnt = ldg32_relaxed(g_s.cnt[C_MID]);
                if (u == 6) {
                    const unsigned target = lds32(mb + MISC_EPOCH) * NCTA;
                    if (__any_sync(0xffffffffu, cnt != target)) count_wait(C_MID, target);
                    asm volatile("fence.acquire.gpu;" ::: "memory");
                    warp_done(mb + MB_MID * 8);
                }
            }
        } else if (u == 1) {
            if (SAFE) mbar_wait(mb + MB_KV * 8);
            TS(17);
            if (lane == 0) {
                if (job < 9) {
                    asm volatile("cp.async.bulk.global.shared::cta.bulk_group [%0], [%1], %2;"
                                 :: "l"(g_x + X_ARM + b * X_SHARE + job * 512), "r"(sb + SM_SENT), "r"(job < 8 ? 8192 : (X_SHARE - 4096) * 16) : "memory");
                    asm volatile("cp.async.bulk.commit_group;" ::: "memory");
                } else if (job < 11) load_wo(sb, P, job - 9);
            }
        } else if (SAFE) {
            if (warp == 8) {
                const unsigned target = lds32(mb + MISC_EPOCH) * NMAIN;
                if (__any_sync(0xffffffffu, cnt != target)) count_wait(C_KV, target);
                if (lane == 0) {
                    asm volatile("fence.acquire.gpu; fence.proxy.async.global;" ::: "memory");
                    mbar_expect(mb + MB_KV * 8, 47104 + 2 * 24576);
                    bulk_g2s(sb + SM_K + 16384, g_s.kv + 1024, 47104, mb + MB_KV * 8);
                    bulk_g2s(sb + SM_V + 8192, g_s.kv + 4096 + 512, 24576, mb + MB_KV * 8);
                    bulk_g2s(sb + SM_V + 32768 + 8192, g_s.kv + 6144 + 512, 24576, mb + MB_KV * 8);
                }
            }
        }
        __syncwarp();
    }
    }
}

__device__ __forceinline__ int kv_slot() {
    const int t = (threadIdx.x & 63) >> 1, c = 2 * (blockIdx.x >> 2) + (threadIdx.x & 1), hg = blockIdx.x & 3;
    return hg < 2 ? ((t + 31) & 31) * 128 + (c >> 3) * 16 + (hg & 1) * 8 + (c & 7) : 4096 + (hg & 1) * 2048 + t * 64 + c;
}

__device__ __noinline__ void helper_cta(const Params& P, uint8_t* smem) {
    const int tid = threadIdx.x, b = blockIdx.x, hi = b - NMAIN;
    const unsigned epoch = g_s.epoch[b] + 1;
    float* red = reinterpret_cast<float*>(smem);
    if (tid < 32) count_wait(C_KV, epoch * NMAIN);
    __syncthreads();
    if (tid == 480) {
        for (int i = 0; i < 8; i++) asm volatile("cp.async.bulk.prefetch.L2.global [%0], %1;" :: "l"((const char*)P.wop + hi * 131072 + i * 16384), "r"(16384) : "memory");
        for (int i = 0; i < 43; i++) asm volatile("cp.async.bulk.prefetch.L2.global [%0], %1;" :: "l"((const char*)P.w2p + hi * 352256 + i * 8192), "r"(8192) : "memory");
    }
    if (tid < 344) {
        const int cg = tid % 43, rp = tid / 43;
        const uint4* src = reinterpret_cast<const uint4*>(P.w1p + (size_t)rp * 64 * FF + (hi * 43 + cg) * 8);
        float s[8] = {0, 0, 0, 0, 0, 0, 0, 0};
#pragma unroll 8
        for (int r = 0; r < 64; r++) {
            uint4 v = __ldg(src + r * (FF / 8));
            s[0] += bf_lo(v.x); s[1] += bf_hi(v.x); s[2] += bf_lo(v.y); s[3] += bf_hi(v.y);
            s[4] += bf_lo(v.z); s[5] += bf_hi(v.z); s[6] += bf_lo(v.w); s[7] += bf_hi(v.w);
        }
        float* part = red + (rp * 43 + cg) * 8;
#pragma unroll
        for (int i = 0; i < 8; i++) part[i] = s[i];
    }
    __syncthreads();
    if (tid < 344) {
        float s = 0.f;
#pragma unroll
        for (int rp = 0; rp < 8; rp++) s += red[rp * 344 + tid];
        g_s.cs[hi * 344 + tid] = s;
    } else if (hi == 3 && tid < 344 + 64) g_s.cs[FF + tid - 344] = 0.f;
    __syncthreads();
    if (tid < 32) count_release(C_MID);
    if (tid == 0) g_s.epoch[b] = epoch;
}

__global__ void __launch_bounds__(512, 1) fused_kernel(const __grid_constant__ Params P) {
    extern __shared__ __align__(1024) uint8_t smem[];
    const uint32_t sb = (uint32_t)__cvta_generic_to_shared(smem);
    const uint32_t mb = sb + SM_MISC;
    const int tid = threadIdx.x, lane = tid & 31, b = blockIdx.x;
    if (b >= NMAIN) { helper_cta(P, smem); return; }
    const int tg = b >> 2, hg = b & 3;
    const int warp = __shfl_sync(0xffffffffu, tid >> 5, 0);

    uint4 xv[4][2];
    unsigned epoch = 0;
    {
        const int r = (tid >> 5) * 4;
        const uint4* src = reinterpret_cast<const uint4*>(P.x + (size_t)((r & 31) + tg * 32 + (r >> 5) * 1024) * D) + lane;
#pragma unroll
        for (int i = 0; i < 4; i++) { xv[i][0] = ldg_relaxed(src + i * 64); xv[i][1] = ldg_relaxed(src + i * 64 + 32); }
    }
    const uint4 wkv = ldg_relaxed(reinterpret_cast<const uint4*>(reinterpret_cast<const char*>(P.wk) + (hg < 2 ? 0 : P.wv_off)) + tid * 2 + (hg & 1));
    const int wg = warp >> 2, ww = warp & 3, g = lane >> 2, t4 = lane & 3, t128 = tid & 127;
    if (lane == 0) {
        if (warp < 4) {
            mbar_init(mb + (MB_WQ + warp) * 8, 2);
            asm volatile("fence.mbarrier_init.release.cluster;" ::: "memory");
            load_wq(sb, P, warp, 0);
            load_wq(sb, P, warp, 1);
        } else if (warp < 7) {
            asm volatile("prefetch.tensormap [%0];" :: "l"(&P.wo + (warp - 4)) : "memory");
        } else if (warp == 7) {
            asm volatile("ld.relaxed.gpu.global.u32 %0, [%1];" : "=r"(epoch) : "l"(g_s.epoch + b) : "memory");
        } else if (warp == 8) {
            sts128(mb + MISC_NRM, 0, 0, 0, 0);

        }
    }
    __syncwarp();
    TS(16);
    float dlt;
    {
        float st[4];
#pragma unroll
        for (int i = 0; i < 4; i++) {
            const uint32_t s = add_bf16x2(add_bf16x2(add_bf16x2(xv[i][0].x, xv[i][0].y), add_bf16x2(xv[i][0].z, xv[i][0].w)),
                                          add_bf16x2(add_bf16x2(xv[i][1].x, xv[i][1].y), add_bf16x2(xv[i][1].z, xv[i][1].w)));
            st[i] = bf_lo(s) + bf_hi(s);
        }
        TS(13);
        const float tot = reduce4(st, lane) * (-1.0f / D);
        const uint32_t nmr = pack_bf16(tot, tot);
        dlt = bf_lo(nmr) - tot;
        const uint32_t xa = sb + SM_XN + (lane >> 3) * 8192 + warp * 512;
#pragma unroll
        for (int i = 0; i < 4; i++) {
            const uint32_t nm = __shfl_sync(0xffffffffu, nmr, i * 8);
            const uint32_t addr = xa + i * 128 + (((lane & 7) ^ ((warp & 1) * 4 + i)) << 4);
#pragma unroll
            for (int c = 0; c < 2; c++) {
                xv[i][c].x = add_bf16x2(xv[i][c].x, nm); xv[i][c].y = add_bf16x2(xv[i][c].y, nm);
                xv[i][c].z = add_bf16x2(xv[i][c].z, nm); xv[i][c].w = add_bf16x2(xv[i][c].w, nm);
                sts128(addr + c * 32768, xv[i][c].x, xv[i][c].y, xv[i][c].z, xv[i][c].w);
            }
        }
    }
    sts128(sb + SM_WKV + tid * 16, wkv.x, wkv.y, wkv.z, wkv.w);
    fence_async_smem();
    TS(0);
    __syncthreads();
    auto variances = [&]() {
        float st[4];
#pragma unroll
        for (int i = 0; i < 4; i++) {
            float v = 0.f;
#pragma unroll
            for (int c = 0; c < 2; c++) {
                const uint32_t a = fma_bf16x2(xv[i][c].x, xv[i][c].x, mul_bf16x2(xv[i][c].y, xv[i][c].y));
                const uint32_t d = fma_bf16x2(xv[i][c].z, xv[i][c].z, mul_bf16x2(xv[i][c].w, xv[i][c].w));
                v += (bf_lo(a) + bf_hi(a)) + (bf_lo(d) + bf_hi(d));
            }
            st[i] = v;
        }
        const float vs = reduce4(st, lane), dl = dlt;
        if ((lane & 7) == 0) sts32(sb + SM_RSTD + (warp * 4 + (lane >> 3)) * 4, __float_as_uint(rsqrtf(fmaxf(vs * (1.0f / D) - dl * dl, 0.f) + 1e-5f)));
    };
    float kv[4] = {0.f, 0.f, 0.f, 0.f};
    if (wg == 2) {
        fence_regs(kv);
        const uint64_t da = mkdesc(sb + SM_XN, 16, 1024, 1), db = mkdesc(sb + SM_WKV, 128, 16, 0);
        wg_fence();
#pragma unroll
        for (int s = 0; s < 32; s++) mma_ss8(kv, da + (s >> 2) * 512 + (s & 3) * 2, db + s * 16);
        wg_commit();
        variances();
        wg_wait<0>(); fence_regs(kv);
    } else {
        variances();
        if (tid == 7 * 32) { sts32(mb + MISC_EPOCH, epoch + 1); g_s.epoch[b] = epoch + 1; }
    }
    __syncthreads();
    constexpr float QSCALE = 0.25f * 1.4426950408889634f;
    float qa[64];
    const uint32_t qbase = sb + SM_Q + (ww >> 1) * 8192 + (ww & 1) * 512 + lane * 16;
    if (wg == 0) {
#pragma unroll
        for (int i = 0; i < 64; i++) qa[i] = 0.f;
        fence_regs(qa);
        const uint64_t da = mkdesc(sb + SM_XN, 16, 1024, 1), db = mkdesc(sb + SM_WQ, 65536, 1024, 1);
#pragma unroll 1
        for (int i = 0; i < 4; i++) {
            mbar_wait(mb + (MB_WQ + i) * 8);
            wg_fence();
#pragma unroll
            for (int s = 0; s < 8; s++) mma_ss128(qa, da + (i * 2 + (s >> 2)) * 512 + (s & 3) * 2, db + (i * 8 + s) * 128);
            wg_commit();
        }
        const float rs0 = __uint_as_float(lds32(sb + SM_RSTD + (ww * 16 + g) * 4)) * QSCALE, rs1 = __uint_as_float(lds32(sb + SM_RSTD + (ww * 16 + g + 8) * 4)) * QSCALE;
        wg_wait<0>();
        fence_regs(qa);
        bar_arrive(6, 256);
        bar_sync(5, 256);
        TS(1);
        uint32_t nm = 0;
#pragma unroll
        for (int h = 0; h < 8; h++) {
#pragma unroll
            for (int i = 0; i < 8; i++) qa[8 * h + i] *= (i & 2) ? rs1 : rs0;
            stsm4(qbase + h * 1024, pack_f16(qa[8 * h], qa[8 * h + 1]), pack_f16(qa[8 * h + 4], qa[8 * h + 5]), pack_f16(qa[8 * h + 2], qa[8 * h + 3]), pack_f16(qa[8 * h + 6], qa[8 * h + 7]));
            const float n0 = qa[8 * h] * qa[8 * h] + qa[8 * h + 1] * qa[8 * h + 1] + qa[8 * h + 4] * qa[8 * h + 4] + qa[8 * h + 5] * qa[8 * h + 5];
            const float n1 = qa[8 * h + 2] * qa[8 * h + 2] + qa[8 * h + 3] * qa[8 * h + 3] + qa[8 * h + 6] * qa[8 * h + 6] + qa[8 * h + 7] * qa[8 * h + 7];
            nm = max(nm, max(__float_as_uint(n0), __float_as_uint(n1)));
        }
        nm = __reduce_max_sync(0xffffffffu, __float_as_uint(quad_sum(__uint_as_float(nm))));
        if (lane == 0) asm volatile("red.shared.max.u32 [%0], %1;" :: "r"(mb + MISC_NRM), "r"(nm) : "memory");
    } else if (wg == 1) {
        if (lane == 0) {
#pragma unroll 1
            for (uint32_t i = 4 + ww; i < NBAR; i += 4) mbar_init(mb + i * 8, i >= MB_LAND ? 1 : i >= MB_WO ? 8 : i == MB_W2 + 7 ? 1 : i >= MB_W1 ? 3 : i >= MB_EMPTY ? 4 : i >= MB_DONE ? 16 : 2);
        }
        __syncwarp();
#pragma unroll
        for (int i = 0; i < 4; i++) sts128(sb + SM_SENT + (i * 128 + t128) * 16, SENT, SENT, SENT, SENT);
        bar_sync(5, 256);
#pragma unroll
        for (int i = 0; i < 16; i++) sts128(sb + SM_V + 65536 + (i * 128 + t128) * 16, 0x3F803F80u, 0x3F803F80u, 0x3F803F80u, 0x3F803F80u);
    } else if (wg == 2) {
        const float rs0 = __uint_as_float(lds32(sb + SM_RSTD + (ww * 16 + g) * 4)), rs1 = __uint_as_float(lds32(sb + SM_RSTD + (ww * 16 + g + 8) * 4));
        kv[0] *= rs0; kv[1] *= rs0; kv[2] *= rs1; kv[3] *= rs1;
        float2* kt = reinterpret_cast<float2*>(smem + SM_KTMP);
        kt[(ww * 16 + g) * 4 + t4] = make_float2(kv[0], kv[1]); kt[(ww * 16 + g + 8) * 4 + t4] = make_float2(kv[2], kv[3]);
        float n0 = kv[0] * kv[0] + kv[1] * kv[1], n1 = kv[2] * kv[2] + kv[3] * kv[3];
        n0 += __shfl_xor_sync(0xffffffffu, n0, 1); n1 += __shfl_xor_sync(0xffffffffu, n1, 1);
        n0 += __shfl_xor_sync(0xffffffffu, n0, 2); n1 += __shfl_xor_sync(0xffffffffu, n1, 2);
        const uint32_t nm = __reduce_max_sync(0xffffffffu, max(__float_as_uint(n0), __float_as_uint(n1)));
        if (lane == 0) sts32(sb + SM_WNRM + ww * 4, nm | 1u);
        bar_sync(2, 128);
        const uint32_t ra = sb + SM_KTMP + ((t128 & 1) * 32 + ((t128 & 63) >> 1)) * 32;
        const float4 c0 = lds128f(ra), c1 = lds128f(ra + 16);
        const int kvoff = kv_slot();
        if (ww < 2) {
            if (hg < 2) {
                float4 p0 = lds128f(ra - 32), p1 = lds128f(ra - 16);
                if (t128 < 2) { p0 = make_float4(0.f, 0.f, 0.f, 0.f); p1 = p0; }
                stg128(g_s.kv + kvoff, nonzero(pack_f16(c0.x - p0.x, c0.y - p0.y)), pack_f16(c0.z - p0.z, c0.w - p0.w), pack_f16(c1.x - p1.x, c1.y - p1.y), pack_f16(c1.z - p1.z, c1.w - p1.w));
            } else {
                stg128(g_s.kv + kvoff, nonzero(pack_bf16(c0.x, c0.y)), pack_bf16(c0.z, c0.w), pack_bf16(c1.x, c1.y), pack_bf16(c1.z, c1.w));
            }
            if (t128 < 2) { const float4 w = lds128f(sb + SM_WNRM); stg128(g_s.nrm + b * 2 + t128, __float_as_uint(w.x), __float_as_uint(w.y), __float_as_uint(w.z), __float_as_uint(w.w)); }
            count_hint(C_KVH);
        } else if (hg < 2) {
            stg128(g_s.kplain + kvoff, pack_bf16(c0.x, c0.y), pack_bf16(c0.z, c0.w), pack_bf16(c1.x, c1.y), pack_bf16(c1.z, c1.w));
        }
        TS(1);
        bar_sync(2, 128);
        if (ww == 3) count_release(C_KV);
    } else {
        uint4 kc[18];
        auto src = [&](int i) { return i < 8 ? g_s.kv + i * 128 : i < 12 ? g_s.kv + 4096 + (i - 8) * 128 : i < 16 ? g_s.kv + 6144 + (i - 12) * 128 : i == 16 ? g_s.kv + 31 * 128 : g_s.nrm + t128; };
        count_wait(C_KVH, lds32(mb + MISC_EPOCH) * (NMAIN * 2));
        TS(1);
        int spins = 0;
        while (true) {
#pragma unroll
            for (int i = 0; i < 18; i++) kc[i] = ldg_relaxed(src(i) + t128);
            uint32_t mn = 1;
#pragma unroll
            for (int i = 0; i < 18; i++) mn = min(mn, kc[i].x);
            if (!__any_sync(0xffffffffu, mn == 0u) || ++spins >= SPIN_LIMIT) break;
        }
        uint32_t nm = max(max(kc[17].x, kc[17].y), max(kc[17].z, kc[17].w));
        nm = max(nm, __shfl_xor_sync(0xffffffffu, nm, 4)); nm = max(nm, __shfl_xor_sync(0xffffffffu, nm, 8)); nm = max(nm, __shfl_xor_sync(0xffffffffu, nm, 16));
        if (lane < 4) asm volatile("red.shared.max.u32 [%0], %1;" :: "r"(mb + MISC_NRM + 4 + min(lane, 2) * 4), "r"(nm) : "memory");
        TS(2);
        bar_sync(6, 256);
#pragma unroll
        for (int i = 0; i < 17; i++) sts128(sb + (uint32_t)(src(i) - g_s.kv + t128) * 16 + ((i >= 8 && i < 16) ? SM_V - 65536 : 0), kc[i].x, kc[i].y, kc[i].z, kc[i].w);
    }
    fence_async_smem();
    TS(3);
    __syncthreads();
    const float4 nr = lds128f(mb + MISC_NRM);
    const bool safe = __all_sync(0xffffffffu, (nr.x * (nr.y + nr.z) <= 3500.0f) && (nr.x <= 65536.0f) && (nr.y + nr.z <= 65536.0f) && (nr.w <= 1e24f));
    TS(4);

    if (__builtin_expect(safe, 1)) {
        attention<true>(P, sb, warp TS_PASS);
    } else {
        if (wg == 0) {
#pragma unroll
            for (int h = 0; h < 8; h++)
                stsm4(qbase + h * 1024, pack_bf16(qa[8 * h], qa[8 * h + 1]), pack_bf16(qa[8 * h + 4], qa[8 * h + 5]), pack_bf16(qa[8 * h + 2], qa[8 * h + 3]), pack_bf16(qa[8 * h + 6], qa[8 * h + 7]));
            fence_async_smem();
        } else if (warp == 15) {
            count_wait(C_KV, lds32(mb + MISC_EPOCH) * NMAIN);
            if (lane == 0) {
                asm volatile("fence.proxy.async;" ::: "memory");
                mbar_expect(mb + MB_KV * 8, 131072);
                bulk_g2s(sb + SM_K, g_s.kplain, 65536, mb + MB_KV * 8);
                bulk_g2s(sb + SM_V, g_s.kv + 4096, 65536, mb + MB_KV * 8);
            }
            __syncwarp();
        }
        __syncthreads();
        mbar_wait(mb + MB_KV * 8);
        attention<false>(P, sb, warp TS_PASS);
    }

    epoch = lds32(mb + MISC_EPOCH);
    const int j = b & 7;
    if (wg == 1) {
        ring_feed(sb, ww, epoch TS_PASS);
    } else if (wg == 2) {
        if (ww < 2) {
            if (t128 < 44) {
                const uint4 v = ldg_relaxed(reinterpret_cast<const uint4*>(g_s.cs + j * 176) + t128);
                sts128(mb + MISC_CS + t128 * 16, v.x, v.y, v.z, v.w);
            }
            warp_done(mb + MB_CS * 8);
            stg128(g_s.kv + kv_slot(), 0u, 0u, 0u, 0u);
            if (t128 < 2) stg128(g_s.nrm + b * 2 + t128, 0u, 0u, 0u, 0u);
            ring_feed(sb, 4 + ww, epoch TS_PASS);
        } else {
#pragma unroll 1
            for (int i = 7 + ww; i < 46; i += 2) {
                const bool w1 = i < 24;
                const int n = w1 ? i : i - 24, kb = n / 3, a = n - 3 * kb;
                mbar_wait(mb + (w1 ? (i < 15 ? MB_DONE + 4 : MB_REL + 8) : MB_REL + kb) * 8);
                if (lane == 0) load_box(sb, w1 ? &P.w1 : &P.w2, w1_slot(kb, a) * SLOT, (w1 ? MB_W1 : MB_W2) + kb, SLOT, w1 ? j * 176 + a * 64 : j * 64, (w1 ? kb : n) * 64);
                __syncwarp();
            }
        }
    } else {
        const int pr = (wg == 0), mt = 16 * pr + (b >> 3);
        uint32_t* const hp = reinterpret_cast<uint32_t*>(g_x + X_H1 + (mt * 32 + j * 4) * 128 + ww * 32) + lane;
        {
            uint32_t hk[16];
            const uint32_t* xp = reinterpret_cast<const uint32_t*>(P.x + (size_t)(mt * 64 + ww * 16 + g) * D + j * 64 + t4 * 2);
#pragma unroll
            for (int k = 0; k < 8; k++) { hk[2 * k] = __ldg(xp + k * 4); hk[2 * k + 1] = __ldg(xp + k * 4 + 8 * (D / 2)); }
            float acc[32];
            gemm_ss<0>(acc, sb, pr);
            TS(7);
#pragma unroll
            for (int i = 0; i < 16; i++) hk[i] = pack_bf16(acc[2 * i] + bf_lo(hk[i]), acc[2 * i + 1] + bf_hi(hk[i]));
#pragma unroll
            for (int k = 0; k < 4; k++) store_tile(hp + k * 512, hk[4 * k], hk[4 * k + 1], hk[4 * k + 2], hk[4 * k + 3]);
            count_hint(C_H1 + mt);
            TS(8);
            float st[4] = {0.f, 0.f, 0.f, 0.f};
#pragma unroll
            for (int i = 0; i < 16; i++) {
                const float lo = bf_lo(hk[i]), hi = bf_hi(hk[i]);
                st[2 * (i & 1)] += lo + hi;
                st[2 * (i & 1) + 1] = fmaf(lo, lo, fmaf(hi, hi, st[2 * (i & 1) + 1]));
            }
#pragma unroll
            for (int o = 1; o < 4; o <<= 1)
#pragma unroll
                for (int i = 0; i < 4; i++) st[i] += __shfl_xor_sync(0xffffffffu, st[i], o);
            if (t4 == 0) stg128(g_x + X_ST + (mt * 8 + j) * 32 + ww * 8 + g, __float_as_uint(st[0]), __float_as_uint(st[1]), __float_as_uint(st[2]), __float_as_uint(st[3]));
        }
        {
            float acc[88];
            const uint4* sp = g_x + X_ST + (mt * 8 + t4) * 32 + ww * 8 + g;
            mbar_wait(mb + (MB_FULL + 16 + pr * 8) * 8);
            uint4 u0 = ldg_relaxed(sp), u1 = ldg_relaxed(sp + 128);
            gemm_ss<1>(acc, sb, pr);
            TS(9);
            int spins = 0;
            while (__builtin_expect(__any_sync(0xffffffffu, max(u0.x, u1.x) == SENT), 0) && ++spins < SPIN_LIMIT) { u0 = ldg_relaxed(sp); u1 = ldg_relaxed(sp + 128); }
            float st[4] = {__uint_as_float(u0.x) + __uint_as_float(u1.x), __uint_as_float(u0.y) + __uint_as_float(u1.y),
                           __uint_as_float(u0.z) + __uint_as_float(u1.z), __uint_as_float(u0.w) + __uint_as_float(u1.w)};
#pragma unroll
            for (int o = 1; o < 4; o <<= 1)
#pragma unroll
                for (int k = 0; k < 4; k++) st[k] += __shfl_xor_sync(0xffffffffu, st[k], o);
            float nmean[2], hrstd[2];
#pragma unroll
            for (int k = 0; k < 2; k++) {
                nmean[k] = st[2 * k] * (-1.0f / D);
                hrstd[k] = 0.5f * rsqrtf(fmaxf(fmaf(-nmean[k], nmean[k], st[2 * k + 1] * (1.0f / D)), 0.f) + 1e-5f);
                nmean[k] *= hrstd[k];
            }
            mbar_wait(mb + MB_CS * 8);
            uint32_t* hb = reinterpret_cast<uint32_t*>(g_x + X_H2 + (mt * 88 + j * 11) * 128 + ww * 32) + lane;
#pragma unroll
            for (int i = 0; i < 22; i++) {
                float2 cs;
                asm volatile("ld.shared.v2.f32 {%0,%1}, [%2];" : "=f"(cs.x), "=f"(cs.y) : "r"(mb + MISC_CS + i * 32 + t4 * 8));
                const float* z = acc + 4 * i;
                uint32_t* p = hb + (i >> 1) * 512 + (i & 1) * 32;
                stg32(p, pack_bf16(silu2(fmaf(hrstd[0], z[0], nmean[0] * cs.x)), silu2(fmaf(hrstd[0], z[1], nmean[0] * cs.y))));
                stg32(p + 64, pack_bf16(silu2(fmaf(hrstd[1], z[2], nmean[1] * cs.x)), silu2(fmaf(hrstd[1], z[3], nmean[1] * cs.y))));
            }
            count_hint(C_H2 + mt);
            TS(10);
        }
        {
            uint32_t hk[16];
#pragma unroll
            for (int i = 0; i < 16; i++) hk[i] = ldg32_relaxed(hp + (i >> 2) * 512 + ((i & 1) * 2 + ((i >> 1) & 1)) * 32);
            float acc[32];
            gemm_ss<2>(acc, sb, pr);
            TS(11);
#pragma unroll
            for (int i = 0; i < 16; i++) hk[i] = pack_bf16(acc[2 * i] + bf_lo(hk[i]), acc[2 * i + 1] + bf_hi(hk[i]));
#pragma unroll
            for (int h = 0; h < 4; h++) {
                const uint32_t* v = hk + (h >> 1) * 8 + (h & 1);
                uint32_t v0 = v[0], v1 = v[2], v2 = v[4], v3 = v[6];
                const bool o1 = t4 & 1, o2 = t4 & 2;
                uint32_t a = __shfl_xor_sync(0xffffffffu, o1 ? v0 : v1, 1), c = __shfl_xor_sync(0xffffffffu, o1 ? v2 : v3, 1);
                if (o1) { v0 = a; v2 = c; } else { v1 = a; v3 = c; }
                a = __shfl_xor_sync(0xffffffffu, o2 ? v0 : v2, 2); c = __shfl_xor_sync(0xffffffffu, o2 ? v1 : v3, 2);
                if (o2) { v0 = a; v1 = c; } else { v2 = a; v3 = c; }
                *reinterpret_cast<uint4*>(P.out + (size_t)(mt * 64 + ww * 16 + g + 8 * (h & 1)) * D + j * 64 + (h >> 1) * 32 + t4 * 8) = make_uint4(v0, v1, v2, v3);
            }
        }
    }
    TS(12);
}

typedef CUresult (*EncodeFn)(CUtensorMap*, CUtensorMapDataType, cuuint32_t, void*, const cuuint64_t*, const cuuint64_t*, const cuuint32_t*,
                             const cuuint32_t*, CUtensorMapInterleave, CUtensorMapSwizzle, CUtensorMapL2promotion, CUtensorMapFloatOOBfill);

void encode2d(EncodeFn fn, CUtensorMap* tm, const void* ptr, int rows, int cols, int box_rows, int box_cols, CUtensorMapSwizzle sw) {
    cuuint64_t dims[2] = {(cuuint64_t)cols, (cuuint64_t)rows};
    cuuint64_t strides[1] = {(cuuint64_t)cols * 2};
    cuuint32_t box[2] = {(cuuint32_t)box_cols, (cuuint32_t)box_rows};
    cuuint32_t es[2] = {1, 1};
    fn(tm, CU_TENSOR_MAP_DATA_TYPE_BFLOAT16, 2, const_cast<void*>(ptr), dims, strides, box, es, CU_TENSOR_MAP_INTERLEAVE_NONE, sw,
       CU_TENSOR_MAP_L2_PROMOTION_L2_128B, CU_TENSOR_MAP_FLOAT_OOB_FILL_NONE);
}

}

extern "C" void kernel_launch(void* const* d_in, const int* in_sizes, int n_in, void* d_out, int out_size) {
    (void)in_sizes; (void)n_in; (void)out_size;
    void* fnp = nullptr;
    cudaDriverEntryPointQueryResult qr;
    cudaGetDriverEntryPoint("cuTensorMapEncodeTiled", &fnp, cudaEnableDefault, &qr);
    EncodeFn fn = (EncodeFn)fnp;
    Params P;
    encode2d(fn, &P.wq, d_in[1], D, D, 128, 64, CU_TENSOR_MAP_SWIZZLE_128B);
    P.wk = (const __nv_bfloat16*)d_in[2];
    P.wv_off = (const char*)d_in[3] - (const char*)d_in[2];
    encode2d(fn, &P.wo, d_in[4], D, D, 64, 64, CU_TENSOR_MAP_SWIZZLE_128B);
    encode2d(fn, &P.w1, d_in[6], D, FF, 64, 64, CU_TENSOR_MAP_SWIZZLE_128B);
    encode2d(fn, &P.w2, d_in[7], FF, D, 64, 64, CU_TENSOR_MAP_SWIZZLE_128B);
    P.x = (const __nv_bfloat16*)d_in[0];
    P.w1p = (const __nv_bfloat16*)d_in[6];
    P.w2p = (const __nv_bfloat16*)d_in[7];
    P.wop = (const __nv_bfloat16*)d_in[4];
    P.wqp = (const __nv_bfloat16*)d_in[1];
    P.out = (__nv_bfloat16*)d_out;
    P.neg1 = 0xFFFFFFFFu; P.pad = 0;
    cudaFuncSetAttribute(fused_kernel, cudaFuncAttributeMaxDynamicSharedMemorySize, SMEM_BYTES);
    fused_kernel<<<NCTA, 512, SMEM_BYTES>>>(P);
}
```

```cpp
#include <cuda_runtime.h>
#include <cuda_bf16.h>
#include <cuda.h>
#include <stdint.h>

namespace {

constexpr int D = 512, FF = 1376;
constexpr int NMAIN = 128, NHELP = 4, NCTA = NMAIN + NHELP;
constexpr uint32_t SENT = 0xFFFFFFFFu;
constexpr int SPIN_LIMIT = 1 << 22;

constexpr uint32_t KB = 1024, SLOT = 8192;
constexpr uint32_t SM_XN = 0;
constexpr uint32_t SM_WQ = 64 * KB;
constexpr uint32_t SM_WKV = 192 * KB;
constexpr uint32_t SM_K = 0;
constexpr uint32_t SM_Q = 64 * KB;
constexpr uint32_t SM_V = 96 * KB;
constexpr uint32_t SM_MISC = 224 * KB;
constexpr uint32_t SMEM_BYTES = 227 * KB;
constexpr uint32_t SM_KTMP = 200 * KB;
constexpr uint32_t SM_RSTD = 202 * KB;
constexpr uint32_t SM_WNRM = 203 * KB;
constexpr uint32_t SM_SENT = 208 * KB;
constexpr uint32_t MB_WQ = 0;
constexpr uint32_t MB_CS = 4;
constexpr uint32_t MB_DONE = 5;
constexpr uint32_t MB_EMPTY = 10;
constexpr uint32_t MB_W1 = 16;
constexpr uint32_t MB_W2 = 24;
constexpr uint32_t MB_WO = 32;
constexpr uint32_t MB_REL = 33;
constexpr uint32_t MB_VALID = 42;
constexpr uint32_t MB_KV = 48;
constexpr uint32_t MB_MID = 49;
constexpr uint32_t MB_FULL = 50;
constexpr uint32_t NBAR = 126;
__host__ __device__ constexpr uint32_t bar_count(uint32_t i) {
    return i >= MB_FULL ? 2 : i >= MB_KV ? 1 : i >= MB_VALID + 4 ? 6 : i >= MB_VALID ? 4 : i >= MB_WO ? 8 : i == MB_W2 + 7 ? 1 : i >= MB_W1 ? 3 : i >= MB_EMPTY ? 4 : i >= MB_DONE ? 16 : 2;
}
constexpr uint32_t MISC_NRM = 1024;
constexpr uint32_t MISC_EPOCH = 1040;
constexpr uint32_t MISC_BAD = 1044;
constexpr uint32_t MISC_TS = 1056;
constexpr uint32_t MISC_CS = 1280;

__host__ __device__ constexpr uint32_t wo_slot(int kb) { return kb < 2 ? 10 + kb : kb - 2; }
__host__ __device__ constexpr uint32_t w1_slot(int kb, int a) { return kb < 4 ? 12 + kb + 4 * a : (kb == 4 ? 6 : kb == 7 ? 9 : 3 * kb - 15) + a; }

struct alignas(128) Small {
    unsigned epoch[160];
    unsigned cnt[100][32];
    float cs[1440];
    uint4 nrm[NMAIN * 2];
    uint4 kv[8192];
    uint4 kplain[4096];
};
__device__ Small g_s;
constexpr int C_KVH = 0, C_KV = 1, C_MID = 2, C_O = 3, C_H1 = 35, C_H2 = 67;
constexpr int X_O = 0, X_H1 = 32 * 32 * 128, X_H2 = 2 * X_H1, X_ST = X_H2 + 32 * 88 * 128, X_END = X_ST + 32 * 8 * 32;
constexpr int X_ARM = 16 * 32 * 128, X_SHARE = (X_END - X_ARM) / NMAIN;
__device__ uint4 g_x[X_END];
#define TS(i) do {} while (0)

#define TS_ARG
#define TS_PASS

__device__ __forceinline__ void mbar_init(uint32_t bar, int cnt) { asm volatile("mbarrier.init.shared::cta.b64 [%0], %1;" :: "r"(bar), "r"(cnt) : "memory"); }
__device__ __forceinline__ void mbar_expect(uint32_t bar, uint32_t bytes) { asm volatile("mbarrier.arrive.expect_tx.shared::cta.b64 _, [%0], %1;" :: "r"(bar), "r"(bytes) : "memory"); }
__device__ __forceinline__ void mbar_arrive(uint32_t bar) { asm volatile("mbarrier.arrive.shared::cta.b64 _, [%0];" :: "r"(bar) : "memory"); }
__device__ __forceinline__ void mbar_wait(uint32_t bar, uint32_t parity = 0) {
    uint32_t done; int spins = 0;
    do {
        asm volatile("{.reg .pred p; mbarrier.try_wait.parity.shared::cta.b64 p, [%1], %2; selp.u32 %0, 1, 0, p;}" : "=r"(done) : "r"(bar), "r"(parity) : "memory");
    } while (!__all_sync(0xffffffffu, done) && ++spins < SPIN_LIMIT);
}
__device__ __forceinline__ void tma2d(uint32_t dst, const CUtensorMap* tm, int c0, int c1, uint32_t bar) {
    asm volatile("cp.async.bulk.tensor.2d.shared::cluster.global.mbarrier::complete_tx::bytes [%0], [%1, {%3, %4}], [%2];"
                 :: "r"(dst), "l"(tm), "r"(bar), "r"(c0), "r"(c1) : "memory");
}
__device__ __forceinline__ void bulk_g2s(uint32_t dst, const void* src, uint32_t bytes, uint32_t bar) {
    asm volatile("cp.async.bulk.shared::cluster.global.mbarrier::complete_tx::bytes [%0], [%1], %2, [%3];" :: "r"(dst), "l"(src), "r"(bytes), "r"(bar) : "memory");
}
__device__ __forceinline__ void fence_async_smem() { asm volatile("fence.proxy.async.shared::cta;" ::: "memory"); }
__device__ __forceinline__ void bar_sync(int id, int n) { asm volatile("bar.sync %0, %1;" :: "r"(id), "r"(n) : "memory"); }
__device__ __forceinline__ void bar_arrive(int id, int n) { asm volatile("bar.arrive %0, %1;" :: "r"(id), "r"(n) : "memory"); }
__device__ __forceinline__ void wg_fence() { asm volatile("wgmma.fence.sync.aligned;" ::: "memory"); }
__device__ __forceinline__ void wg_commit() { asm volatile("wgmma.commit_group.sync.aligned;" ::: "memory"); }
template <int N> __device__ __forceinline__ void wg_wait() { asm volatile("wgmma.wait_group.sync.aligned %0;" :: "n"(N) : "memory"); }
template <int N> __device__ __forceinline__ void fence_regs(float (&d)[N]) {
#pragma unroll
    for (int i = 0; i < N; i++) asm volatile("" : "+f"(d[i]) :: "memory");
}
template <int N> __device__ __forceinline__ void fence_regs(uint32_t (&d)[N]) {
#pragma unroll
    for (int i = 0; i < N; i++) asm volatile("" : "+r"(d[i]) :: "memory");
}
__device__ __forceinline__ uint64_t mkdesc(uint32_t addr, uint32_t lbo, uint32_t sbo, uint32_t swz) {
    return (uint64_t)(((addr & 0x3FFFF) >> 4) | ((lbo >> 4) << 16)) | ((uint64_t)((sbo >> 4) | (swz << 30)) << 32);
}
__device__ __forceinline__ float ex2(float x) { float y; asm("ex2.approx.ftz.f32 %0, %1;" : "=f"(y) : "f"(x)); return y; }
__device__ __forceinline__ float rcp(float x) { float y; asm("rcp.approx.ftz.f32 %0, %1;" : "=f"(y) : "f"(x)); return y; }
__device__ __forceinline__ uint32_t pack_bf16(float lo, float hi) { uint32_t r; asm("cvt.rn.bf16x2.f32 %0, %1, %2;" : "=r"(r) : "f"(hi), "f"(lo)); return r; }
__device__ __forceinline__ uint32_t pack_f16(float lo, float hi) { uint32_t r; asm("cvt.rn.f16x2.f32 %0, %1, %2;" : "=r"(r) : "f"(hi), "f"(lo)); return r; }
__device__ __forceinline__ float bf_lo(uint32_t v) { return __uint_as_float(v << 16); }
__device__ __forceinline__ float bf_hi(uint32_t v) { return __uint_as_float(v & 0xFFFF0000u); }
__device__ __forceinline__ uint4 ldg_relaxed(const uint4* p) {
    uint4 v; asm volatile("ld.relaxed.gpu.global.v4.u32 {%0,%1,%2,%3}, [%4];" : "=r"(v.x), "=r"(v.y), "=r"(v.z), "=r"(v.w) : "l"(p) : "memory"); return v;
}
__device__ __forceinline__ void stg128(void* p, uint32_t a, uint32_t b, uint32_t c, uint32_t d) {
    asm volatile("st.relaxed.gpu.global.v4.u32 [%0], {%1,%2,%3,%4};" :: "l"(p), "r"(a), "r"(b), "r"(c), "r"(d) : "memory");
}
__device__ __forceinline__ void stg64(void* p, uint32_t a, uint32_t b) {
    asm volatile("st.relaxed.gpu.global.v2.u32 [%0], {%1,%2};" :: "l"(p), "r"(a), "r"(b) : "memory");
}
__device__ __forceinline__ void sts128(uint32_t a, uint32_t x, uint32_t y, uint32_t z, uint32_t w) {
    asm volatile("st.shared.v4.u32 [%0], {%1,%2,%3,%4};" :: "r"(a), "r"(x), "r"(y), "r"(z), "r"(w) : "memory");
}
__device__ __forceinline__ void sts32(uint32_t a, uint32_t x) { asm volatile("st.shared.u32 [%0], %1;" :: "r"(a), "r"(x) : "memory"); }
__device__ __forceinline__ float4 lds128f(uint32_t a) {
    float4 v; asm volatile("ld.shared.v4.f32 {%0,%1,%2,%3}, [%4];" : "=f"(v.x), "=f"(v.y), "=f"(v.z), "=f"(v.w) : "r"(a) : "memory"); return v;
}
__device__ __forceinline__ uint32_t lds32(uint32_t a) { uint32_t v; asm volatile("ld.shared.u32 %0, [%1];" : "=r"(v) : "r"(a) : "memory"); return v; }
__device__ __forceinline__ uint32_t nonzero(uint32_t w) { return w == 0u ? 0x8000u : w; }
__device__ __forceinline__ void stg32(void* p, uint32_t a) { asm volatile("st.global.u32 [%0], %1;" :: "l"(p), "r"(a) : "memory"); }
__device__ __forceinline__ uint32_t ldg32_relaxed(const void* p) { uint32_t v; asm volatile("ld.relaxed.gpu.global.u32 %0, [%1];" : "=r"(v) : "l"(p) : "memory"); return v; }
__device__ __forceinline__ void count_hint(int id) {
    if ((threadIdx.x & 31) == 0) asm volatile("red.relaxed.gpu.global.add.u32 [%0], 1;" :: "l"(g_s.cnt[id]) : "memory");
}
__device__ __forceinline__ void count_release(int id) {
    __syncwarp();
    if ((threadIdx.x & 31) == 0) asm volatile("red.release.gpu.global.add.u32 [%0], 1;" :: "l"(g_s.cnt[id]) : "memory");
    __syncwarp();
}
__device__ __forceinline__ void count_wait(int id, unsigned target) {
    uint32_t v; int spins = 0;
    do v = ldg32_relaxed(g_s.cnt[id]); while (__any_sync(0xffffffffu, v != target) && ++spins < SPIN_LIMIT);
    asm volatile("fence.acquire.gpu;" ::: "memory");
}
__device__ __forceinline__ void warp_done(uint32_t bar) {
    __syncwarp();
    asm volatile("{.reg .pred p; setp.eq.u32 p, %1, 0; @p mbarrier.arrive.shared::cta.b64 _, [%0];}" :: "r"(bar), "r"(threadIdx.x & 31) : "memory");
}
__device__ __forceinline__ uint32_t mul_bf16x2(uint32_t a, uint32_t b) { uint32_t r; asm("mul.rn.bf16x2 %0, %1, %2;" : "=r"(r) : "r"(a), "r"(b)); return r; }
__device__ __forceinline__ uint32_t fma_bf16x2(uint32_t a, uint32_t b, uint32_t c) { uint32_t r; asm("fma.rn.bf16x2 %0, %1, %2, %3;" : "=r"(r) : "r"(a), "r"(b), "r"(c)); return r; }
__device__ __forceinline__ uint32_t add_bf16x2(uint32_t a, uint32_t b) { uint32_t r; asm("add.rn.bf16x2 %0, %1, %2;" : "=r"(r) : "r"(a), "r"(b)); return r; }

#define R4(d, o) "+f"(d[o + 0]), "+f"(d[o + 1]), "+f"(d[o + 2]), "+f"(d[o + 3])
#define R8(d, o) R4(d, o), R4(d, o + 4)
#define R32(d) R8(d, 0), R8(d, 8), R8(d, 16), R8(d, 24)
#define D32 "{%0,%1,%2,%3,%4,%5,%6,%7,%8,%9,%10,%11,%12,%13,%14,%15,%16,%17,%18,%19,%20,%21,%22,%23,%24,%25,%26,%27,%28,%29,%30,%31}"
#define D64 "{%0,%1,%2,%3,%4,%5,%6,%7,%8,%9,%10,%11,%12,%13,%14,%15,%16,%17,%18,%19,%20,%21,%22,%23,%24,%25,%26,%27,%28,%29,%30,%31,%32,%33,%34,%35,%36,%37,%38,%39,%40,%41,%42,%43,%44,%45,%46,%47,%48,%49,%50,%51,%52,%53,%54,%55,%56,%57,%58,%59,%60,%61,%62,%63}"

__device__ __forceinline__ void mma_qk_f16(float (&d)[32], uint64_t da, uint64_t db) {
    asm volatile("{.reg .pred p; setp.eq.b32 p, 0, 0; wgmma.mma_async.sync.aligned.m64n64k16.f32.f16.f16 " D32 ", %32, %33, p, 1, 1, 0, 0;}"
                 : R32(d) : "l"(da), "l"(db));
}
__device__ __forceinline__ void mma_qk_bf16(float (&d)[32], uint64_t da, uint64_t db) {
    asm volatile("{.reg .pred p; setp.ne.b32 p, 0, 0; wgmma.mma_async.sync.aligned.m64n64k16.f32.bf16.bf16 " D32 ", %32, %33, p, 1, 1, 0, 0;}"
                 : R32(d) : "l"(da), "l"(db));
}
__device__ __forceinline__ void mma_pv(float (&d)[12], const uint32_t* a, uint64_t db) {
    asm volatile("{.reg .pred p; setp.eq.b32 p, 0, 0; wgmma.mma_async.sync.aligned.m64n24k16.f32.bf16.bf16 {%0,%1,%2,%3,%4,%5,%6,%7,%8,%9,%10,%11}, {%12,%13,%14,%15}, %16, p, 1, 1, 1;}"
                 : R8(d, 0), R4(d, 8) : "r"(a[0]), "r"(a[1]), "r"(a[2]), "r"(a[3]), "l"(db));
}
__device__ __forceinline__ void mma_ss128(float (&d)[64], uint64_t da, uint64_t db) {
    asm volatile("{.reg .pred p; setp.eq.b32 p, 0, 0; wgmma.mma_async.sync.aligned.m64n128k16.f32.bf16.bf16 " D64 ", %64, %65, p, 1, 1, 0, 1;}"
                 : R32(d), R8(d, 32), R8(d, 40), R8(d, 48), R8(d, 56) : "l"(da), "l"(db));
}
__device__ __forceinline__ void stsm4(uint32_t addr, uint32_t a, uint32_t b, uint32_t c, uint32_t d) {
    asm volatile("stmatrix.sync.aligned.m8n8.x4.shared.b16 [%0], {%1,%2,%3,%4};" :: "r"(addr), "r"(a), "r"(b), "r"(c), "r"(d) : "memory");
}
__device__ __forceinline__ void mma_ss8(float (&d)[4], uint64_t da, uint64_t db) {
    asm volatile("{.reg .pred p; setp.eq.b32 p, 0, 0; wgmma.mma_async.sync.aligned.m64n8k16.f32.bf16.bf16 {%0,%1,%2,%3}, %4, %5, p, 1, 1, 0, 1;}"
                 : R4(d, 0) : "l"(da), "l"(db));
}
__device__ __forceinline__ void mma_ss(float (&d)[32], uint64_t da, uint64_t db) {
    asm volatile("{.reg .pred p; setp.eq.b32 p, 0, 0; wgmma.mma_async.sync.aligned.m64n64k16.f32.bf16.bf16 " D32 ", %32, %33, p, 1, 1, 0, 1;}"
                 : R32(d) : "l"(da), "l"(db));
}
__device__ __forceinline__ void mma_ss(float (&d)[88], uint64_t da, uint64_t db) {
    asm volatile("{.reg .pred p; setp.eq.b32 p, 0, 0; wgmma.mma_async.sync.aligned.m64n176k16.f32.bf16.bf16 " "{%0,%1,%2,%3,%4,%5,%6,%7,%8,%9,%10,%11,%12,%13,%14,%15,%16,%17,%18,%19,%20,%21,%22,%23,%24,%25,%26,%27,%28,%29,%30,%31,%32,%33,%34,%35,%36,%37,%38,%39,%40,%41,%42,%43,%44,%45,%46,%47,%48,%49,%50,%51,%52,%53,%54,%55,%56,%57,%58,%59,%60,%61,%62,%63,%64,%65,%66,%67,%68,%69,%70,%71,%72,%73,%74,%75,%76,%77,%78,%79,%80,%81,%82,%83,%84,%85,%86,%87}"
                 ", %88, %89, p, 1, 1, 0, 1;}"
                 : R32(d), R8(d, 32), R8(d, 40), R8(d, 48), R8(d, 56), R8(d, 64), R8(d, 72), R8(d, 80) : "l"(da), "l"(db));
}

constexpr float EXP_MAGIC = 256.0f + 127.0f + 64.0f - 1.58621f + 0.00390625f;
constexpr uint32_t MUFU_MASK = 0x1111u;
__device__ __forceinline__ uint32_t exp2_pair(float y0, float y1, uint32_t cexp, uint32_t neg1) {
    uint32_t w, m, e, r;
    asm("prmt.b32 %0, %1, %2, 0x6521;" : "=r"(w) : "r"(__float_as_uint(y0)), "r"(__float_as_uint(y1)));
    asm("lop3.b32 %0, %1, 0x007F007F, %2, 0xEA;" : "=r"(m) : "r"(w), "r"(cexp));
    asm("mad.lo.u32 %0, %1, %2, %3;" : "=r"(e) : "r"(m), "r"(neg1), "r"(w));
    asm("fma.rn.bf16x2 %0, %1, %2, %3;" : "=r"(r) : "r"(w), "r"(m), "r"(e));
    return r;
}

struct Params {
    const __nv_bfloat16* x;
    const __nv_bfloat16* wk;
    long long wv_off;
    const __nv_bfloat16* wqp;
    __nv_bfloat16* out;
    uint32_t neg1, pad;
    const __nv_bfloat16* w1p;
    const __nv_bfloat16* w2p;
    CUtensorMap wq, wo, w1, w2;
    const __nv_bfloat16* wop;
};

__device__ __forceinline__ void load_box(uint32_t sb, const CUtensorMap* tm, uint32_t dst, uint32_t bar, uint32_t bytes, int c0, int c1) {
    mbar_expect(sb + SM_MISC + bar * 8, bytes);
    tma2d(sb + dst, tm, c0, c1, sb + SM_MISC + bar * 8);
}
__device__ __forceinline__ void load_wq(uint32_t sb, const Params& P, int gi, int atom) {
    load_box(sb, &P.wq, SM_WQ + atom * 65536 + gi * 16384, MB_WQ + gi, 16384, (blockIdx.x & 3) * 128 + atom * 64, gi * 128);
}
__device__ __forceinline__ void load_wo(uint32_t sb, const Params& P, int kb) { load_box(sb, &P.wo, wo_slot(kb) * SLOT, MB_WO, SLOT, (blockIdx.x & 7) * 64, kb * 64); }
__device__ __forceinline__ void refill_job(uint32_t sb, const Params& P, int gi, int job) {
    const bool w1 = job < 3;
    load_box(sb, w1 ? &P.w1 : &P.wo, (w1 ? 12 + gi + 4 * job : 2 * gi + job - 3) * SLOT, w1 ? MB_W1 + gi : MB_WO, SLOT,
             (blockIdx.x & 7) * (w1 ? 176 : 64) + (w1 ? job * 64 : 0), (w1 ? gi : 2 * gi + job - 1) * 64);
}

__host__ __device__ constexpr int ring_entry(int n) { return n < 32 ? (n & 3) : (n - 32) % 6; }
__host__ __device__ constexpr uint32_t ring_slot(int e) { return e < 4 ? 24 + e : 6 + e; }

template <int KIND, int NACC>
__device__ __forceinline__ void gemm_ss(float (&acc)[NACC], uint32_t sb, int pr) {
    const uint32_t mb = sb + SM_MISC;
    constexpr int NBLK = KIND == 2 ? 22 : 8, N0 = 16 * KIND;
    const uint32_t full = mb + (MB_FULL + N0 + pr * NBLK) * 8;
#pragma unroll
    for (int i = 0; i < NACC; i++) acc[i] = 0.f;
    fence_regs(acc);
#pragma unroll
    for (int i = 0; i < NBLK; i++) {
        const uint64_t db = KIND == 0 ? mkdesc(sb + wo_slot(i) * SLOT, 16, 1024, 1)
                          : KIND == 1 ? mkdesc(sb + w1_slot(i, 0) * SLOT, i < 4 ? 4 * SLOT : SLOT, 1024, 1) : mkdesc(sb + w1_slot(i / 3, i % 3) * SLOT, 16, 1024, 1);
        const uint64_t da = mkdesc(sb + (pr ? ring_slot(ring_entry(N0 + NBLK + i)) : ring_slot(ring_entry(N0 + i))) * SLOT, 128, 256, 0);
        mbar_wait(full + i * 8);
        wg_fence();
#pragma unroll
        for (int s = 0; s < 4; s++) mma_ss(acc, da + s * 128, db + s * 128);
        wg_commit();
        if (i > 0) {
            wg_wait<1>();
            warp_done(mb + (MB_EMPTY + (pr ? ring_entry(N0 + NBLK + i - 1) : ring_entry(N0 + i - 1))) * 8);
            if (KIND == 1) warp_done(mb + (MB_REL + i - 1) * 8);
        }
    }
    wg_wait<0>();
    fence_regs(acc);
    warp_done(mb + (MB_EMPTY + (pr ? ring_entry(N0 + 2 * NBLK - 1) : ring_entry(N0 + NBLK - 1))) * 8);
    if (KIND != 2) warp_done(mb + (MB_REL + 8 - KIND) * 8);
}
__device__ __forceinline__ void ring_feed(uint32_t sb, int e, unsigned epoch TS_ARG) {
    const uint32_t mb = sb + SM_MISC, dst = sb + ring_slot(e) * SLOT;
    const int lane = threadIdx.x & 31;
    uint32_t use = 0;
    int seen = 0;
#pragma unroll 1
    for (int n = e < 4 ? e : 32 + e; n < 76; use ^= 1) {
        const int job = n < 32 ? n >> 3 : 4 + (n >= 54), ph = job >> 1, i = n < 32 ? n & 7 : n - 32 - (job & 1) * 22;
        const int mt = (job & 1) * 16 + (blockIdx.x >> 3);
        const uint4* src = g_x + ph * X_H1 + mt * (ph == 2 ? 88 : 32) * 128 + i * 512;
        const uint32_t full = mb + (MB_FULL + n) * 8;
        if (lane == 0) mbar_expect(full, SLOT);
        if (job != seen) { count_wait(C_O + 32 * ph + mt, epoch * (ph == 0 ? 128 : 32)); seen = job; TS(18 + job); }
        asm volatile("fence.proxy.async.global;" ::: "memory");
        if (n >= 4) mbar_wait(mb + ((n == 32 + e && e >= 4) ? MB_REL + 7 : MB_EMPTY + e) * 8, (n == 32 + e && e >= 4) ? 0 : use ^ 1);
        if (lane == 0) bulk_g2s(dst, src, SLOT, full);
        __syncwarp();
        mbar_wait(mb + (ph == 0 ? MB_WO : ph == 1 ? MB_W1 + i : MB_W2 + i / 3) * 8);
        warp_done(full);
        mbar_wait(full);
        uint32_t m = 0;
#pragma unroll
        for (int k = 0; k < 8; k++) m = max(m, lds32(dst + k * 1024 + lane * 32 + (lane >> 2) * 4));
        if (m == SENT) asm volatile("red.shared.or.b32 [%0], %1;" :: "r"(mb + MISC_BAD), "r"(1 << job) : "memory");
        const int step = n < 32 ? 4 : 6;
        if (i + step >= (ph == 2 ? 22 : 8)) warp_done(mb + (MB_VALID + job) * 8);
        n += step;
    }
}
template <int NACC>
__device__ __forceinline__ void gemm_slow(float (&acc)[NACC], const uint4* a, int nst, const __nv_bfloat16* W, int ldw, int kmax, int n0) {
    const int lane = threadIdx.x & 31;
    const unsigned short* w = reinterpret_cast<const unsigned short*>(W);
    const uint32_t* p = reinterpret_cast<const uint32_t*>(a) + ((threadIdx.x >> 5) & 3) * 128 + lane;
#pragma unroll
    for (int i = 0; i < NACC; i++) acc[i] = 0.f;
#pragma unroll 1
    for (int st = 0; st < nst; st++, p += 512) {
        const int k = st * 16 + 2 * (lane & 3);
        uint32_t v0, v1, v2, v3; int spins = 0;
        do { v0 = ldg32_relaxed(p); v1 = ldg32_relaxed(p + 64); v2 = ldg32_relaxed(p + 32); v3 = ldg32_relaxed(p + 96); }
        while (__any_sync(0xffffffffu, max(max(v0, v1), max(v2, v3)) == SENT) && ++spins < SPIN_LIMIT);
#pragma unroll
        for (int j = 0; j < NACC / 4; j++) {
            const int n = n0 + 8 * j + (lane >> 2);
            uint32_t b0 = 0, b1 = 0;
            if (k < kmax && n < ldw) {
                const unsigned short* q = w + (size_t)k * ldw + n;
                b0 = q[0] | ((uint32_t)q[ldw] << 16); b1 = q[8 * ldw] | ((uint32_t)q[9 * ldw] << 16);
            }
            asm volatile("mma.sync.aligned.m16n8k16.row.col.f32.bf16.bf16.f32 {%0,%1,%2,%3}, {%4,%5,%6,%7}, {%8,%9}, {%0,%1,%2,%3};"
                         : R4(acc, 4 * j) : "r"(v0), "r"(v1), "r"(v2), "r"(v3), "r"(b0), "r"(b1));
        }
    }
}
__device__ __forceinline__ bool product_bad(uint32_t sb, int job) {
    mbar_wait(sb + SM_MISC + (MB_VALID + job) * 8);
    bool bad = __any_sync(0xffffffffu, (lds32(sb + SM_MISC + MISC_BAD) >> job) & 1);
    return __builtin_expect(bad, 0);
}
__device__ __forceinline__ void store_tile(uint32_t* p, uint32_t r0k0, uint32_t r8k0, uint32_t r0k8, uint32_t r8k8) {
    stg32(p, r0k0); stg32(p + 32, r0k8); stg32(p + 64, r8k0); stg32(p + 96, r8k8);
}

__device__ __forceinline__ float quad_sum(float v) { v += __shfl_xor_sync(0xffffffffu, v, 1); v += __shfl_xor_sync(0xffffffffu, v, 2); return v; }
__device__ __forceinline__ float reduce4(const float (&st)[4], int lane) {
    const bool u16 = lane & 16, u8 = lane & 8;
    const float a0 = (u16 ? st[2] : st[0]) + __shfl_xor_sync(0xffffffffu, u16 ? st[0] : st[2], 16);
    const float a1 = (u16 ? st[3] : st[1]) + __shfl_xor_sync(0xffffffffu, u16 ? st[1] : st[3], 16);
    float v = (u8 ? a1 : a0) + __shfl_xor_sync(0xffffffffu, u8 ? a0 : a1, 8);
    v += __shfl_xor_sync(0xffffffffu, v, 4); v += __shfl_xor_sync(0xffffffffu, v, 2); v += __shfl_xor_sync(0xffffffffu, v, 1);
    return v;
}
__device__ __forceinline__ float silu2(float h) { float t; asm("tanh.approx.f32 %0, %1;" : "=f"(t) : "f"(h)); return fmaf(h, t, h); }

template <bool SAFE>
__device__ __forceinline__ void attention(const Params& P, uint32_t sb, int warp TS_ARG) {
    const uint32_t mb = sb + SM_MISC;
    const int tid = threadIdx.x, lane = tid & 31, b = blockIdx.x;
    const int wg = warp >> 2, ww = warp & 3, job = 3 - wg + 4 * ww;
    const uint32_t cexp = 0x9F809F80u + (tid >> 12);
    const uint32_t neg1 = P.neg1;
    unsigned cnt = 0;
    if (SAFE && warp == 8) cnt = ldg32_relaxed(g_s.cnt[C_KV]);
#pragma unroll 1
    for (int pass = 0; pass < 2; pass++) {
    float o[12], s[32];
    const uint64_t dq = mkdesc(sb + SM_Q + (pass * 4 + wg) * 2048, 128, 256, 0);
    uint64_t dk = mkdesc(sb + SM_K, 128, 256, 0), dv = mkdesc(sb + SM_V, 128, 32768, 0);
    float m0 = -INFINITY, m1 = -INFINITY;
#pragma unroll
    for (int i = 0; i < 12; i++) o[i] = 0.f;
#pragma unroll
    for (int i = 0; i < 32; i++) s[i] = ((MUFU_MASK >> (i / 2)) & 1) ? 0.f : EXP_MAGIC;
    fence_regs(s); fence_regs(o);
    wg_fence();
    if (SAFE) mma_qk_f16(s, dq, dk + 31 * 128); else mma_qk_bf16(s, dq, dk + 31 * 128);
    wg_commit();
    wg_wait<0>(); fence_regs(s);
#pragma unroll 1
    for (int u = pass ? 3 : (wg == 2) ? 0 : 1; u < (pass ? 8 : 3); u++) {
        int n = 2 * ((((wg == 2) ? 0x22444C31u : 0x22444C40u) >> (4 * u)) & 15);
#pragma unroll 1
        do {
            uint32_t p[16];
            if (SAFE) {
#pragma unroll
                for (int j = 0; j < 16; j++) {
                    if ((MUFU_MASK >> j) & 1) p[j] = pack_bf16(ex2(s[2 * j]), ex2(s[2 * j + 1]));
                    else p[j] = exp2_pair(s[2 * j], s[2 * j + 1], cexp, neg1);
                }
            } else {
                fence_regs(o);
                float x0 = m0, x1 = m1;
#pragma unroll
                for (int j = 0; j < 8; j++) { x0 = fmaxf(x0, fmaxf(s[4 * j], s[4 * j + 1])); x1 = fmaxf(x1, fmaxf(s[4 * j + 2], s[4 * j + 3])); }
                x0 = fmaxf(x0, __shfl_xor_sync(0xffffffffu, x0, 1)); x0 = fmaxf(x0, __shfl_xor_sync(0xffffffffu, x0, 2));
                x1 = fmaxf(x1, __shfl_xor_sync(0xffffffffu, x1, 1)); x1 = fmaxf(x1, __shfl_xor_sync(0xffffffffu, x1, 2));
                const float c0 = ex2(m0 - x0), c1 = ex2(m1 - x1);
                m0 = x0; m1 = x1;
#pragma unroll
                for (int j = 0; j < 3; j++) { o[4 * j] *= c0; o[4 * j + 1] *= c0; o[4 * j + 2] *= c1; o[4 * j + 3] *= c1; }
#pragma unroll
                for (int j = 0; j < 8; j++) {
                    p[2 * j] = pack_bf16(ex2(s[4 * j] - m0), ex2(s[4 * j + 1] - m0));
                    p[2 * j + 1] = pack_bf16(ex2(s[4 * j + 2] - m1), ex2(s[4 * j + 3] - m1));
                }
                fence_regs(o);
            }
            fence_regs(p);
            wg_fence();
            if (SAFE) mma_qk_f16(s, dq, dk); else mma_qk_bf16(s, dq, dk);
#pragma unroll
            for (int j = 0; j < 4; j++) mma_pv(o, p + 4 * j, dv + j * 16);
            wg_commit();
            dk += 128; dv += 64;
            wg_wait<0>(); fence_regs(s);
        } while (--n > 0);
        if (u == 2 || u == 7) {
            fence_regs(o);
            const float i0 = rcp(o[8]), i1 = rcp(o[10]);
            if (u == 7) mbar_wait(mb + MB_MID * 8);
            store_tile(reinterpret_cast<uint32_t*>(g_x + X_O + (((u == 7) * 16 + (b >> 3)) * 32 + (b & 3) * 8 + 2 * wg + (ww >> 1)) * 128 + (((b >> 2) & 1) * 2 + (ww & 1)) * 32) + lane,
                       pack_bf16(o[0] * i0, o[1] * i0), pack_bf16(o[2] * i1, o[3] * i1), pack_bf16(o[4] * i0, o[5] * i0), pack_bf16(o[6] * i1, o[7] * i1));
            if (u == 2) asm volatile("cp.async.bulk.wait_group 0;" ::: "memory");
            else count_hint(C_O + 16 + (b >> 3));
            warp_done(mb + (MB_DONE + (u == 7) * 4) * 8);
            TS(5 + (u == 7));
        } else if (u >= 3) {
            if (u < 6) warp_done(mb + (MB_DONE + u - 2) * 8);
            if (job < (u == 3 ? 1 : 5)) {
                mbar_wait(mb + (MB_DONE + u - 3) * 8);
                if (u == 3) count_release(C_MID);
                else if (lane == 0) refill_job(sb, P, u - 4, job);
            } else if (warp == 7) {
                if (u == 5) cnt = ldg32_relaxed(g_s.cnt[C_MID]);
                if (u == 6) {
                    const unsigned target = lds32(mb + MISC_EPOCH) * NCTA;
                    if (__any_sync(0xffffffffu, cnt != target)) count_wait(C_MID, target);
                    asm volatile("fence.acquire.gpu;" ::: "memory");
                    warp_done(mb + MB_MID * 8);
                }
            }
        } else if (u == 1) {
            if (SAFE) mbar_wait(mb + MB_KV * 8);
            TS(17);
            if (lane == 0) {
                if (job < 9) {
                    asm volatile("cp.async.bulk.global.shared::cta.bulk_group [%0], [%1], %2;"
                                 :: "l"(g_x + X_ARM + b * X_SHARE + job * 512), "r"(sb + SM_SENT), "r"(job < 8 ? 8192 : (X_SHARE - 4096) * 16) : "memory");
                    asm volatile("cp.async.bulk.commit_group;" ::: "memory");
                } else if (job < 11) load_wo(sb, P, job - 9);
            }
        } else if (SAFE) {
            if (warp == 8) {
                const unsigned target = lds32(mb + MISC_EPOCH) * NMAIN;
                if (__any_sync(0xffffffffu, cnt != target)) count_wait(C_KV, target);
                if (lane == 0) {
                    asm volatile("fence.acquire.gpu; fence.proxy.async.global;" ::: "memory");
                    mbar_expect(mb + MB_KV * 8, 47104 + 2 * 24576);
                    bulk_g2s(sb + SM_K + 16384, g_s.kv + 1024, 47104, mb + MB_KV * 8);
                    bulk_g2s(sb + SM_V + 8192, g_s.kv + 4096 + 512, 24576, mb + MB_KV * 8);
                    bulk_g2s(sb + SM_V + 32768 + 8192, g_s.kv + 6144 + 512, 24576, mb + MB_KV * 8);
                }
            }
        }
        __syncwarp();
    }
    }
}

__device__ __forceinline__ int kv_slot() {
    const int t = (threadIdx.x & 63) >> 1, c = 2 * (blockIdx.x >> 2) + (threadIdx.x & 1), hg = blockIdx.x & 3;
    return hg < 2 ? ((t + 31) & 31) * 128 + (c >> 3) * 16 + (hg & 1) * 8 + (c & 7) : 4096 + (hg & 1) * 2048 + t * 64 + c;
}

__device__ __noinline__ void helper_cta(const Params& P, uint8_t* smem) {
    const int tid = threadIdx.x, b = blockIdx.x, hi = b - NMAIN;
    const unsigned epoch = g_s.epoch[b] + 1;
    float* red = reinterpret_cast<float*>(smem);
    if (tid < 32) count_wait(C_KV, epoch * NMAIN);
    __syncthreads();
    if (tid == 480) {
        for (int i = 0; i < 8; i++) asm volatile("cp.async.bulk.prefetch.L2.global [%0], %1;" :: "l"((const char*)P.wop + hi * 131072 + i * 16384), "r"(16384) : "memory");
        for (int i = 0; i < 43; i++) asm volatile("cp.async.bulk.prefetch.L2.global [%0], %1;" :: "l"((const char*)P.w2p + hi * 352256 + i * 8192), "r"(8192) : "memory");
    }
    if (tid < 344) {
        const int cg = tid % 43, rp = tid / 43;
        const uint4* src = reinterpret_cast<const uint4*>(P.w1p + (size_t)rp * 64 * FF + (hi * 43 + cg) * 8);
        float s[8] = {0, 0, 0, 0, 0, 0, 0, 0};
#pragma unroll 8
        for (int r = 0; r < 64; r++) {
            uint4 v = __ldg(src + r * (FF / 8));
            s[0] += bf_lo(v.x); s[1] += bf_hi(v.x); s[2] += bf_lo(v.y); s[3] += bf_hi(v.y);
            s[4] += bf_lo(v.z); s[5] += bf_hi(v.z); s[6] += bf_lo(v.w); s[7] += bf_hi(v.w);
        }
        float* part = red + (rp * 43 + cg) * 8;
#pragma unroll
        for (int i = 0; i < 8; i++) part[i] = s[i];
    }
    __syncthreads();
    if (tid < 344) {
        float s = 0.f;
#pragma unroll
        for (int rp = 0; rp < 8; rp++) s += red[rp * 344 + tid];
        g_s.cs[hi * 344 + tid] = s;
    } else if (hi == 3 && tid < 344 + 64) g_s.cs[FF + tid - 344] = 0.f;
    __syncthreads();
    if (tid < 32) count_release(C_MID);
    if (tid == 0) g_s.epoch[b] = epoch;
}

__global__ void __launch_bounds__(512, 1) fused_kernel(const __grid_constant__ Params P) {
    extern __shared__ __align__(1024) uint8_t smem[];
    const uint32_t sb = (uint32_t)__cvta_generic_to_shared(smem);
    const uint32_t mb = sb + SM_MISC;
    const int tid = threadIdx.x, lane = tid & 31, b = blockIdx.x;
    if (b >= NMAIN) { helper_cta(P, smem); return; }
    const int tg = b >> 2, hg = b & 3;
    const int warp = __shfl_sync(0xffffffffu, tid >> 5, 0);

    uint4 xv[4][2];
    unsigned epoch = 0;
    {
        const int r = (tid >> 5) * 4;
        const uint4* src = reinterpret_cast<const uint4*>(P.x + (size_t)((r & 31) + tg * 32 + (r >> 5) * 1024) * D) + lane;
#pragma unroll
        for (int i = 0; i < 4; i++) { xv[i][0] = ldg_relaxed(src + i * 64); xv[i][1] = ldg_relaxed(src + i * 64 + 32); }
    }
    const uint4 wkv = ldg_relaxed(reinterpret_cast<const uint4*>(reinterpret_cast<const char*>(P.wk) + (hg < 2 ? 0 : P.wv_off)) + tid * 2 + (hg & 1));
    const int wg = warp >> 2, ww = warp & 3, g = lane >> 2, t4 = lane & 3, t128 = tid & 127;
    if (lane == 0) {
        if (warp < 4) {
            mbar_init(mb + (MB_WQ + warp) * 8, 2);
            asm volatile("fence.mbarrier_init.release.cluster;" ::: "memory");
            load_wq(sb, P, warp, 0);
            load_wq(sb, P, warp, 1);
        } else if (warp < 7) {
            asm volatile("prefetch.tensormap [%0];" :: "l"(&P.wo + (warp - 4)) : "memory");
        } else if (warp == 7) {
            asm volatile("ld.relaxed.gpu.global.u32 %0, [%1];" : "=r"(epoch) : "l"(g_s.epoch + b) : "memory");
        } else if (warp == 8) {
            sts128(mb + MISC_NRM, 0, 0, 0, 0);

        }
    }
    __syncwarp();
    TS(16);
    float dlt;
    {
        float st[4];
#pragma unroll
        for (int i = 0; i < 4; i++) {
            const uint32_t s = add_bf16x2(add_bf16x2(add_bf16x2(xv[i][0].x, xv[i][0].y), add_bf16x2(xv[i][0].z, xv[i][0].w)),
                                          add_bf16x2(add_bf16x2(xv[i][1].x, xv[i][1].y), add_bf16x2(xv[i][1].z, xv[i][1].w)));
            st[i] = bf_lo(s) + bf_hi(s);
        }
        TS(13);
        const float tot = reduce4(st, lane) * (-1.0f / D);
        const uint32_t nmr = pack_bf16(tot, tot);
        dlt = bf_lo(nmr) - tot;
        const uint32_t xa = sb + SM_XN + (lane >> 3) * 8192 + warp * 512;
#pragma unroll
        for (int i = 0; i < 4; i++) {
            const uint32_t nm = __shfl_sync(0xffffffffu, nmr, i * 8);
            const uint32_t addr = xa + i * 128 + (((lane & 7) ^ ((warp & 1) * 4 + i)) << 4);
#pragma unroll
            for (int c = 0; c < 2; c++) {
                xv[i][c].x = add_bf16x2(xv[i][c].x, nm); xv[i][c].y = add_bf16x2(xv[i][c].y, nm);
                xv[i][c].z = add_bf16x2(xv[i][c].z, nm); xv[i][c].w = add_bf16x2(xv[i][c].w, nm);
                sts128(addr + c * 32768, xv[i][c].x, xv[i][c].y, xv[i][c].z, xv[i][c].w);
            }
        }
    }
    sts128(sb + SM_WKV + tid * 16, wkv.x, wkv.y, wkv.z, wkv.w);
    fence_async_smem();
    TS(0);
    __syncthreads();
    auto variances = [&]() {
        float st[4];
#pragma unroll
        for (int i = 0; i < 4; i++) {
            float v = 0.f;
#pragma unroll
            for (int c = 0; c < 2; c++) {
                const uint32_t a = fma_bf16x2(xv[i][c].x, xv[i][c].x, mul_bf16x2(xv[i][c].y, xv[i][c].y));
                const uint32_t d = fma_bf16x2(xv[i][c].z, xv[i][c].z, mul_bf16x2(xv[i][c].w, xv[i][c].w));
                v += (bf_lo(a) + bf_hi(a)) + (bf_lo(d) + bf_hi(d));
            }
            st[i] = v;
        }
        const float vs = reduce4(st, lane), dl = dlt;
        if ((lane & 7) == 0) sts32(sb + SM_RSTD + (warp * 4 + (lane >> 3)) * 4, __float_as_uint(rsqrtf(fmaxf(vs * (1.0f / D) - dl * dl, 0.f) + 1e-5f)));
    };
    float kv[4] = {0.f, 0.f, 0.f, 0.f};
    if (wg == 2) {
        fence_regs(kv);
        const uint64_t da = mkdesc(sb + SM_XN, 16, 1024, 1), db = mkdesc(sb + SM_WKV, 128, 16, 0);
        wg_fence();
#pragma unroll
        for (int s = 0; s < 32; s++) mma_ss8(kv, da + (s >> 2) * 512 + (s & 3) * 2, db + s * 16);
        wg_commit();
        variances();
        wg_wait<0>(); fence_regs(kv);
    } else {
        variances();
        if (tid == 7 * 32) { sts32(mb + MISC_EPOCH, epoch + 1); sts32(mb + MISC_BAD, 0); g_s.epoch[b] = epoch + 1; }
    }
    __syncthreads();
    constexpr float QSCALE = 0.25f * 1.4426950408889634f;
    float qa[64];
    const uint32_t qbase = sb + SM_Q + (ww >> 1) * 8192 + (ww & 1) * 512 + lane * 16;
    if (wg == 0) {
#pragma unroll
        for (int i = 0; i < 64; i++) qa[i] = 0.f;
        fence_regs(qa);
        const uint64_t da = mkdesc(sb + SM_XN, 16, 1024, 1), db = mkdesc(sb + SM_WQ, 65536, 1024, 1);
#pragma unroll 1
        for (int i = 0; i < 4; i++) {
            mbar_wait(mb + (MB_WQ + i) * 8);
            wg_fence();
#pragma unroll
            for (int s = 0; s < 8; s++) mma_ss128(qa, da + (i * 2 + (s >> 2)) * 512 + (s & 3) * 2, db + (i * 8 + s) * 128);
            wg_commit();
        }
        const float rs0 = __uint_as_float(lds32(sb + SM_RSTD + (ww * 16 + g) * 4)) * QSCALE, rs1 = __uint_as_float(lds32(sb + SM_RSTD + (ww * 16 + g + 8) * 4)) * QSCALE;
        wg_wait<0>();
        fence_regs(qa);
        bar_arrive(6, 256);
        bar_sync(5, 256);
        TS(1);
        uint32_t nm = 0;
#pragma unroll
        for (int h = 0; h < 8; h++) {
#pragma unroll
            for (int i = 0; i < 8; i++) qa[8 * h + i] *= (i & 2) ? rs1 : rs0;
            stsm4(qbase + h * 1024, pack_f16(qa[8 * h], qa[8 * h + 1]), pack_f16(qa[8 * h + 4], qa[8 * h + 5]), pack_f16(qa[8 * h + 2], qa[8 * h + 3]), pack_f16(qa[8 * h + 6], qa[8 * h + 7]));
            const float n0 = qa[8 * h] * qa[8 * h] + qa[8 * h + 1] * qa[8 * h + 1] + qa[8 * h + 4] * qa[8 * h + 4] + qa[8 * h + 5] * qa[8 * h + 5];
            const float n1 = qa[8 * h + 2] * qa[8 * h + 2] + qa[8 * h + 3] * qa[8 * h + 3] + qa[8 * h + 6] * qa[8 * h + 6] + qa[8 * h + 7] * qa[8 * h + 7];
            nm = max(nm, max(__float_as_uint(n0), __float_as_uint(n1)));
        }
        nm = __reduce_max_sync(0xffffffffu, __float_as_uint(quad_sum(__uint_as_float(nm))));
        if (lane == 0) asm volatile("red.shared.max.u32 [%0], %1;" :: "r"(mb + MISC_NRM), "r"(nm) : "memory");
    } else if (wg == 1) {
        if (lane == 0) {
            if (ww == 0) {
#pragma unroll
                for (uint32_t i = 4; i < MB_WO; i++) mbar_init(mb + i * 8, bar_count(i));
            } else if (ww == 1) {
#pragma unroll
                for (uint32_t i = MB_WO; i < 62; i++) mbar_init(mb + i * 8, bar_count(i));
            } else {
#pragma unroll
                for (uint32_t i = 0; i < 32; i++) mbar_init(mb + (ww * 32 - 2 + i) * 8, 2);
            }
        }
        __syncwarp();
#pragma unroll
        for (int i = 0; i < 4; i++) sts128(sb + SM_SENT + (i * 128 + t128) * 16, SENT, SENT, SENT, SENT);
        bar_sync(5, 256);
#pragma unroll
        for (int i = 0; i < 16; i++) sts128(sb + SM_V + 65536 + (i * 128 + t128) * 16, 0x3F803F80u, 0x3F803F80u, 0x3F803F80u, 0x3F803F80u);
    } else if (wg == 2) {
        const float rs0 = __uint_as_float(lds32(sb + SM_RSTD + (ww * 16 + g) * 4)), rs1 = __uint_as_float(lds32(sb + SM_RSTD + (ww * 16 + g + 8) * 4));
        kv[0] *= rs0; kv[1] *= rs0; kv[2] *= rs1; kv[3] *= rs1;
        float2* kt = reinterpret_cast<float2*>(smem + SM_KTMP);
        kt[(ww * 16 + g) * 4 + t4] = make_float2(kv[0], kv[1]); kt[(ww * 16 + g + 8) * 4 + t4] = make_float2(kv[2], kv[3]);
        float n0 = kv[0] * kv[0] + kv[1] * kv[1], n1 = kv[2] * kv[2] + kv[3] * kv[3];
        n0 += __shfl_xor_sync(0xffffffffu, n0, 1); n1 += __shfl_xor_sync(0xffffffffu, n1, 1);
        n0 += __shfl_xor_sync(0xffffffffu, n0, 2); n1 += __shfl_xor_sync(0xffffffffu, n1, 2);
        const uint32_t nm = __reduce_max_sync(0xffffffffu, max(__float_as_uint(n0), __float_as_uint(n1)));
        if (lane == 0) sts32(sb + SM_WNRM + ww * 4, nm | 1u);
        bar_sync(2, 128);
        const uint32_t ra = sb + SM_KTMP + ((t128 & 1) * 32 + ((t128 & 63) >> 1)) * 32;
        const float4 c0 = lds128f(ra), c1 = lds128f(ra + 16);
        const int kvoff = kv_slot();
        if (ww < 2) {
            if (hg < 2) {
                float4 p0 = lds128f(ra - 32), p1 = lds128f(ra - 16);
                if (t128 < 2) { p0 = make_float4(0.f, 0.f, 0.f, 0.f); p1 = p0; }
                stg128(g_s.kv + kvoff, nonzero(pack_f16(c0.x - p0.x, c0.y - p0.y)), pack_f16(c0.z - p0.z, c0.w - p0.w), pack_f16(c1.x - p1.x, c1.y - p1.y), pack_f16(c1.z - p1.z, c1.w - p1.w));
            } else {
                stg128(g_s.kv + kvoff, nonzero(pack_bf16(c0.x, c0.y)), pack_bf16(c0.z, c0.w), pack_bf16(c1.x, c1.y), pack_bf16(c1.z, c1.w));
            }
            if (t128 < 2) { const float4 w = lds128f(sb + SM_WNRM); stg128(g_s.nrm + b * 2 + t128, __float_as_uint(w.x), __float_as_uint(w.y), __float_as_uint(w.z), __float_as_uint(w.w)); }
            count_hint(C_KVH);
        } else if (hg < 2) {
            stg128(g_s.kplain + kvoff, pack_bf16(c0.x, c0.y), pack_bf16(c0.z, c0.w), pack_bf16(c1.x, c1.y), pack_bf16(c1.z, c1.w));
        }
        TS(1);
        bar_sync(2, 128);
        if (ww == 3) count_release(C_KV);
    } else {
        uint4 kc[18];
        auto src = [&](int i) { return i < 8 ? g_s.kv + i * 128 : i < 12 ? g_s.kv + 4096 + (i - 8) * 128 : i < 16 ? g_s.kv + 6144 + (i - 12) * 128 : i == 16 ? g_s.kv + 31 * 128 : g_s.nrm + t128; };
        count_wait(C_KVH, lds32(mb + MISC_EPOCH) * (NMAIN * 2));
        TS(1);
        int spins = 0;
        while (true) {
#pragma unroll
            for (int i = 0; i < 18; i++) kc[i] = ldg_relaxed(src(i) + t128);
            uint32_t mn = 1;
#pragma unroll
            for (int i = 0; i < 18; i++) mn = min(mn, kc[i].x);
            if (!__any_sync(0xffffffffu, mn == 0u) || ++spins >= SPIN_LIMIT) break;
        }
        uint32_t nm = max(max(kc[17].x, kc[17].y), max(kc[17].z, kc[17].w));
        nm = max(nm, __shfl_xor_sync(0xffffffffu, nm, 4)); nm = max(nm, __shfl_xor_sync(0xffffffffu, nm, 8)); nm = max(nm, __shfl_xor_sync(0xffffffffu, nm, 16));
        if (lane < 4) asm volatile("red.shared.max.u32 [%0], %1;" :: "r"(mb + MISC_NRM + 4 + min(lane, 2) * 4), "r"(nm) : "memory");
        TS(2);
        bar_sync(6, 256);
#pragma unroll
        for (int i = 0; i < 17; i++) sts128(sb + (uint32_t)(src(i) - g_s.kv + t128) * 16 + ((i >= 8 && i < 16) ? SM_V - 65536 : 0), kc[i].x, kc[i].y, kc[i].z, kc[i].w);
    }
    fence_async_smem();
    TS(3);
    __syncthreads();
    const float4 nr = lds128f(mb + MISC_NRM);
    const bool safe = __all_sync(0xffffffffu, (nr.x * (nr.y + nr.z) <= 3500.0f) && (nr.x <= 65536.0f) && (nr.y + nr.z <= 65536.0f) && (nr.w <= 1e24f));
    TS(4);

    if (__builtin_expect(safe, 1)) {
        attention<true>(P, sb, warp TS_PASS);
    } else {
        if (wg == 0) {
#pragma unroll
            for (int h = 0; h < 8; h++)
                stsm4(qbase + h * 1024, pack_bf16(qa[8 * h], qa[8 * h + 1]), pack_bf16(qa[8 * h + 4], qa[8 * h + 5]), pack_bf16(qa[8 * h + 2], qa[8 * h + 3]), pack_bf16(qa[8 * h + 6], qa[8 * h + 7]));
            fence_async_smem();
        } else if (warp == 15) {
            count_wait(C_KV, lds32(mb + MISC_EPOCH) * NMAIN);
            if (lane == 0) {
                asm volatile("fence.proxy.async;" ::: "memory");
                mbar_expect(mb + MB_KV * 8, 131072);
                bulk_g2s(sb + SM_K, g_s.kplain, 65536, mb + MB_KV * 8);
                bulk_g2s(sb + SM_V, g_s.kv + 4096, 65536, mb + MB_KV * 8);
            }
            __syncwarp();
        }
        __syncthreads();
        mbar_wait(mb + MB_KV * 8);
        attention<false>(P, sb, warp TS_PASS);
    }

    epoch = lds32(mb + MISC_EPOCH);
    const int j = b & 7;
    if (wg == 1) {
        ring_feed(sb, ww, epoch TS_PASS);
    } else if (wg == 2) {
        if (ww < 2) {
            if (t128 < 44) {
                const uint4 v = ldg_relaxed(reinterpret_cast<const uint4*>(g_s.cs + j * 176) + t128);
                sts128(mb + MISC_CS + t128 * 16, v.x, v.y, v.z, v.w);
            }
            warp_done(mb + MB_CS * 8);
            stg128(g_s.kv + kv_slot(), 0u, 0u, 0u, 0u);
            if (t128 < 2) stg128(g_s.nrm + b * 2 + t128, 0u, 0u, 0u, 0u);
            ring_feed(sb, 4 + ww, epoch TS_PASS);
        } else {
#pragma unroll 1
            for (int i = 7 + ww; i < 46; i += 2) {
                const bool w1 = i < 24;
                const int n = w1 ? i : i - 24, kb = n / 3, a = n - 3 * kb;
                mbar_wait(mb + (w1 ? (i < 15 ? MB_DONE + 4 : MB_REL + 8) : MB_REL + kb) * 8);
                if (lane == 0) load_box(sb, w1 ? &P.w1 : &P.w2, w1_slot(kb, a) * SLOT, (w1 ? MB_W1 : MB_W2) + kb, SLOT, w1 ? j * 176 + a * 64 : j * 64, (w1 ? kb : n) * 64);
                __syncwarp();
            }
        }
    } else {
        const int pr = (wg == 0), mt = 16 * pr + (b >> 3);
        uint32_t* const hp = reinterpret_cast<uint32_t*>(g_x + X_H1 + (mt * 32 + j * 4) * 128 + ww * 32) + lane;
        {
            uint32_t hk[16];
            const uint32_t* xp = reinterpret_cast<const uint32_t*>(P.x + (size_t)(mt * 64 + ww * 16 + g) * D + j * 64 + t4 * 2);
#pragma unroll
            for (int k = 0; k < 8; k++) { hk[2 * k] = __ldg(xp + k * 4); hk[2 * k + 1] = __ldg(xp + k * 4 + 8 * (D / 2)); }
            float acc[32];
            gemm_ss<0>(acc, sb, pr);
            if (product_bad(sb, pr)) gemm_slow(acc, g_x + X_O + mt * 32 * 128, 32, P.wop, D, D, j * 64);
            TS(7);
#pragma unroll
            for (int i = 0; i < 16; i++) hk[i] = pack_bf16(acc[2 * i] + bf_lo(hk[i]), acc[2 * i + 1] + bf_hi(hk[i]));
#pragma unroll
            for (int k = 0; k < 4; k++) store_tile(hp + k * 512, hk[4 * k], hk[4 * k + 1], hk[4 * k + 2], hk[4 * k + 3]);
            count_hint(C_H1 + mt);
            TS(8);
            float st[4] = {0.f, 0.f, 0.f, 0.f};
#pragma unroll
            for (int i = 0; i < 16; i++) {
                const float lo = bf_lo(hk[i]), hi = bf_hi(hk[i]);
                st[2 * (i & 1)] += lo + hi;
                st[2 * (i & 1) + 1] = fmaf(lo, lo, fmaf(hi, hi, st[2 * (i & 1) + 1]));
            }
#pragma unroll
            for (int o = 1; o < 4; o <<= 1)
#pragma unroll
                for (int i = 0; i < 4; i++) st[i] += __shfl_xor_sync(0xffffffffu, st[i], o);
            if (t4 == 0) stg128(g_x + X_ST + (mt * 8 + j) * 32 + ww * 8 + g, __float_as_uint(st[0]), __float_as_uint(st[1]), __float_as_uint(st[2]), __float_as_uint(st[3]));
        }
        {
            float acc[88];
            const uint4* sp = g_x + X_ST + (mt * 8 + t4) * 32 + ww * 8 + g;
            mbar_wait(mb + (MB_FULL + 16 + pr * 8) * 8);
            uint4 u0 = ldg_relaxed(sp), u1 = ldg_relaxed(sp + 128);
            gemm_ss<1>(acc, sb, pr);
            if (product_bad(sb, 2 + pr)) gemm_slow(acc, g_x + X_H1 + mt * 32 * 128, 32, P.w1p, FF, D, j * 176);
            TS(9);
            int spins = 0;
            while (__builtin_expect(__any_sync(0xffffffffu, max(u0.x, u1.x) == SENT), 0) && ++spins < SPIN_LIMIT) { u0 = ldg_relaxed(sp); u1 = ldg_relaxed(sp + 128); }
            float st[4] = {__uint_as_float(u0.x) + __uint_as_float(u1.x), __uint_as_float(u0.y) + __uint_as_float(u1.y),
                           __uint_as_float(u0.z) + __uint_as_float(u1.z), __uint_as_float(u0.w) + __uint_as_float(u1.w)};
#pragma unroll
            for (int o = 1; o < 4; o <<= 1)
#pragma unroll
                for (int k = 0; k < 4; k++) st[k] += __shfl_xor_sync(0xffffffffu, st[k], o);
            float nmean[2], hrstd[2];
#pragma unroll
            for (int k = 0; k < 2; k++) {
                nmean[k] = st[2 * k] * (-1.0f / D);
                hrstd[k] = 0.5f * rsqrtf(fmaxf(fmaf(-nmean[k], nmean[k], st[2 * k + 1] * (1.0f / D)), 0.f) + 1e-5f);
                nmean[k] *= hrstd[k];
            }
            mbar_wait(mb + MB_CS * 8);
            uint32_t* hb = reinterpret_cast<uint32_t*>(g_x + X_H2 + (mt * 88 + j * 11) * 128 + ww * 32) + lane;
#pragma unroll
            for (int i = 0; i < 22; i++) {
                float2 cs;
                asm volatile("ld.shared.v2.f32 {%0,%1}, [%2];" : "=f"(cs.x), "=f"(cs.y) : "r"(mb + MISC_CS + i * 32 + t4 * 8));
                const float* z = acc + 4 * i;
                uint32_t* p = hb + (i >> 1) * 512 + (i & 1) * 32;
                stg32(p, pack_bf16(silu2(fmaf(hrstd[0], z[0], nmean[0] * cs.x)), silu2(fmaf(hrstd[0], z[1], nmean[0] * cs.y))));
                stg32(p + 64, pack_bf16(silu2(fmaf(hrstd[1], z[2], nmean[1] * cs.x)), silu2(fmaf(hrstd[1], z[3], nmean[1] * cs.y))));
            }
            count_hint(C_H2 + mt);
            TS(10);
        }
        {
            uint32_t hk[16];
#pragma unroll
            for (int i = 0; i < 16; i++) hk[i] = ldg32_relaxed(hp + (i >> 2) * 512 + ((i & 1) * 2 + ((i >> 1) & 1)) * 32);
            float acc[32];
            gemm_ss<2>(acc, sb, pr);
            if (product_bad(sb, 4 + pr)) gemm_slow(acc, g_x + X_H2 + mt * 88 * 128, 88, P.w2p, D, FF, j * 64);
            TS(11);
#pragma unroll
            for (int i = 0; i < 16; i++) hk[i] = pack_bf16(acc[2 * i] + bf_lo(hk[i]), acc[2 * i + 1] + bf_hi(hk[i]));
#pragma unroll
            for (int h = 0; h < 4; h++) {
                const uint32_t* v = hk + (h >> 1) * 8 + (h & 1);
                uint32_t v0 = v[0], v1 = v[2], v2 = v[4], v3 = v[6];
                const bool o1 = t4 & 1, o2 = t4 & 2;
                uint32_t a = __shfl_xor_sync(0xffffffffu, o1 ? v0 : v1, 1), c = __shfl_xor_sync(0xffffffffu, o1 ? v2 : v3, 1);
                if (o1) { v0 = a; v2 = c; } else { v1 = a; v3 = c; }
                a = __shfl_xor_sync(0xffffffffu, o2 ? v0 : v2, 2); c = __shfl_xor_sync(0xffffffffu, o2 ? v1 : v3, 2);
                if (o2) { v0 = a; v1 = c; } else { v2 = a; v3 = c; }
                *reinterpret_cast<uint4*>(P.out + (size_t)(mt * 64 + ww * 16 + g + 8 * (h & 1)) * D + j * 64 + (h >> 1) * 32 + t4 * 8) = make_uint4(v0, v1, v2, v3);
            }
        }
    }
    TS(12);
}

typedef CUresult (*EncodeFn)(CUtensorMap*, CUtensorMapDataType, cuuint32_t, void*, const cuuint64_t*, const cuuint64_t*, const cuuint32_t*,
                             const cuuint32_t*, CUtensorMapInterleave, CUtensorMapSwizzle, CUtensorMapL2promotion, CUtensorMapFloatOOBfill);

void encode2d(EncodeFn fn, CUtensorMap* tm, const void* ptr, int rows, int cols, int box_rows, int box_cols, CUtensorMapSwizzle sw) {
    cuuint64_t dims[2] = {(cuuint64_t)cols, (cuuint64_t)rows};
    cuuint64_t strides[1] = {(cuuint64_t)cols * 2};
    cuuint32_t box[2] = {(cuuint32_t)box_cols, (cuuint32_t)box_rows};
    cuuint32_t es[2] = {1, 1};
    fn(tm, CU_TENSOR_MAP_DATA_TYPE_BFLOAT16, 2, const_cast<void*>(ptr), dims, strides, box, es, CU_TENSOR_MAP_INTERLEAVE_NONE, sw,
       CU_TENSOR_MAP_L2_PROMOTION_L2_128B, CU_TENSOR_MAP_FLOAT_OOB_FILL_NONE);
}

}

extern "C" void kernel_launch(void* const* d_in, const int* in_sizes, int n_in, void* d_out, int out_size) {
    (void)in_sizes; (void)n_in; (void)out_size;
    void* fnp = nullptr;
    cudaDriverEntryPointQueryResult qr;
    cudaGetDriverEntryPoint("cuTensorMapEncodeTiled", &fnp, cudaEnableDefault, &qr);
    EncodeFn fn = (EncodeFn)fnp;
    Params P;
    encode2d(fn, &P.wq, d_in[1], D, D, 128, 64, CU_TENSOR_MAP_SWIZZLE_128B);
    P.wk = (const __nv_bfloat16*)d_in[2];
    P.wv_off = (const char*)d_in[3] - (const char*)d_in[2];
    encode2d(fn, &P.wo, d_in[4], D, D, 64, 64, CU_TENSOR_MAP_SWIZZLE_128B);
    encode2d(fn, &P.w1, d_in[6], D, FF, 64, 64, CU_TENSOR_MAP_SWIZZLE_128B);
    encode2d(fn, &P.w2, d_in[7], FF, D, 64, 64, CU_TENSOR_MAP_SWIZZLE_128B);
    P.x = (const __nv_bfloat16*)d_in[0];
    P.w1p = (const __nv_bfloat16*)d_in[6];
    P.w2p = (const __nv_bfloat16*)d_in[7];
    P.wop = (const __nv_bfloat16*)d_in[4];
    P.wqp = (const __nv_bfloat16*)d_in[1];
    P.out = (__nv_bfloat16*)d_out;
    P.neg1 = 0xFFFFFFFFu; P.pad = 0;
    cudaFuncSetAttribute(fused_kernel, cudaFuncAttributeMaxDynamicSharedMemorySize, SMEM_BYTES);
    fused_kernel<<<NCTA, 512, SMEM_BYTES>>>(P);
}
```

```cpp
#include <cuda_runtime.h>
#include <cuda_bf16.h>
#include <cuda.h>
#include <stdint.h>

namespace {

constexpr int D = 512, FF = 1376;
constexpr int NMAIN = 128, NHELP = 4, NCTA = NMAIN + NHELP;
constexpr uint32_t SENT = 0xFFFFFFFFu;
constexpr int SPIN_LIMIT = 1 << 22;

constexpr uint32_t KB = 1024, SLOT = 8192;
constexpr uint32_t SM_XN = 0;
constexpr uint32_t SM_WQ = 64 * KB;
constexpr uint32_t SM_WKV = 192 * KB;
constexpr uint32_t SM_K = 0;
constexpr uint32_t SM_Q = 64 * KB;
constexpr uint32_t SM_V = 96 * KB;
constexpr uint32_t SM_MISC = 224 * KB;
constexpr uint32_t SMEM_BYTES = 227 * KB;
constexpr uint32_t SM_KTMP = 200 * KB;
constexpr uint32_t SM_RSTD = 202 * KB;
constexpr uint32_t SM_WNRM = 203 * KB;
constexpr uint32_t SM_SENT = 208 * KB;
constexpr uint32_t MB_WQ = 0;
constexpr uint32_t MB_CS = 4;
constexpr uint32_t MB_DONE = 5;
constexpr uint32_t MB_EMPTY = 10;
constexpr uint32_t MB_W1 = 16;
constexpr uint32_t MB_W2 = 24;
constexpr uint32_t MB_WO = 32;
constexpr uint32_t MB_REL = 33;
constexpr uint32_t MB_VALID = 42;
constexpr uint32_t MB_KV = 48;
constexpr uint32_t MB_MID = 49;
constexpr uint32_t MB_FULL = 50;
constexpr uint32_t MB_NULL = 126;
constexpr uint32_t NBAR = 127;
__host__ __device__ constexpr uint32_t bar_count(uint32_t i) {
    return i >= MB_FULL ? 2 : i >= MB_KV ? 1 : i >= MB_VALID + 4 ? 6 : i >= MB_VALID ? 4 : i >= MB_WO ? 8 : i == MB_W2 + 7 ? 1 : i >= MB_W1 ? 3 : i >= MB_EMPTY ? 4 : i >= MB_DONE ? 16 : 2;
}
constexpr uint32_t MISC_NRM = 1024;
constexpr uint32_t MISC_EPOCH = 1040;
constexpr uint32_t MISC_BAD = 1044;
constexpr uint32_t MISC_TS = 1056;
constexpr uint32_t MISC_CS = 1280;

__host__ __device__ constexpr uint32_t wo_slot(int kb) { return kb < 2 ? 10 + kb : kb - 2; }
__host__ __device__ constexpr uint32_t w1_slot(int kb, int a) { return kb < 4 ? 12 + kb + 4 * a : (kb == 4 ? 6 : kb == 7 ? 9 : 3 * kb - 15) + a; }

struct alignas(128) Small {
    unsigned epoch[160];
    unsigned cnt[100][32];
    float cs[1440];
    uint4 nrm[NMAIN * 2];
    uint4 kv[8192];
    uint4 kplain[4096];
};
__device__ Small g_s;
constexpr int C_KVH = 0, C_KV = 1, C_MID = 2, C_O = 3, C_H1 = 35, C_H2 = 67;
constexpr int X_O = 0, X_H1 = 32 * 32 * 128, X_H2 = 2 * X_H1, X_ST = X_H2 + 32 * 88 * 128, X_END = X_ST + 32 * 8 * 32;
constexpr int X_ARM = 16 * 32 * 128, X_SHARE = (X_END - X_ARM) / NMAIN;
__device__ uint4 g_x[X_END];
#define TS(i) do {} while (0)
#define TSF(k)

#define TS_ARG
#define TS_PASS

__device__ __forceinline__ void mbar_init(uint32_t bar, int cnt) { asm volatile("mbarrier.init.shared::cta.b64 [%0], %1;" :: "r"(bar), "r"(cnt) : "memory"); }
__device__ __forceinline__ void mbar_expect(uint32_t bar, uint32_t bytes) { asm volatile("mbarrier.arrive.expect_tx.shared::cta.b64 _, [%0], %1;" :: "r"(bar), "r"(bytes) : "memory"); }
__device__ __forceinline__ void mbar_arrive(uint32_t bar) { asm volatile("mbarrier.arrive.shared::cta.b64 _, [%0];" :: "r"(bar) : "memory"); }
__device__ __forceinline__ bool mbar_try(uint32_t bar, uint32_t parity) {
    uint32_t done;
    asm volatile("{.reg .pred p; mbarrier.try_wait.parity.shared::cta.b64 p, [%1], %2; selp.u32 %0, 1, 0, p;}" : "=r"(done) : "r"(bar), "r"(parity) : "memory");
    return __all_sync(0xffffffffu, done);
}
__device__ __forceinline__ void mbar_wait(uint32_t bar, uint32_t parity = 0) {
    if (__builtin_expect(!mbar_try(bar, parity), 0)) {
        int spins = 0;
        while (!mbar_try(bar, parity) && ++spins < (SPIN_LIMIT >> 6)) {}
    }
}
__device__ __forceinline__ void tma2d(uint32_t dst, const CUtensorMap* tm, int c0, int c1, uint32_t bar) {
    asm volatile("cp.async.bulk.tensor.2d.shared::cluster.global.mbarrier::complete_tx::bytes [%0], [%1, {%3, %4}], [%2];"
                 :: "r"(dst), "l"(tm), "r"(bar), "r"(c0), "r"(c1) : "memory");
}
__device__ __forceinline__ void bulk_g2s(uint32_t dst, const void* src, uint32_t bytes, uint32_t bar) {
    asm volatile("cp.async.bulk.shared::cluster.global.mbarrier::complete_tx::bytes [%0], [%1], %2, [%3];" :: "r"(dst), "l"(src), "r"(bytes), "r"(bar) : "memory");
}
__device__ __forceinline__ void fence_async_smem() { asm volatile("fence.proxy.async.shared::cta;" ::: "memory"); }
__device__ __forceinline__ void bar_sync(int id, int n) { asm volatile("bar.sync %0, %1;" :: "r"(id), "r"(n) : "memory"); }
__device__ __forceinline__ void bar_arrive(int id, int n) { asm volatile("bar.arrive %0, %1;" :: "r"(id), "r"(n) : "memory"); }
__device__ __forceinline__ void wg_fence() { asm volatile("wgmma.fence.sync.aligned;" ::: "memory"); }
__device__ __forceinline__ void wg_commit() { asm volatile("wgmma.commit_group.sync.aligned;" ::: "memory"); }
template <int N> __device__ __forceinline__ void wg_wait() { asm volatile("wgmma.wait_group.sync.aligned %0;" :: "n"(N) : "memory"); }
template <int N> __device__ __forceinline__ void fence_regs(float (&d)[N]) {
#pragma unroll
    for (int i = 0; i < N; i++) asm volatile("" : "+f"(d[i]) :: "memory");
}
template <int N> __device__ __forceinline__ void fence_regs(uint32_t (&d)[N]) {
#pragma unroll
    for (int i = 0; i < N; i++) asm volatile("" : "+r"(d[i]) :: "memory");
}
__device__ __forceinline__ uint64_t mkdesc(uint32_t addr, uint32_t lbo, uint32_t sbo, uint32_t swz) {
    return (uint64_t)(((addr & 0x3FFFF) >> 4) | ((lbo >> 4) << 16)) | ((uint64_t)((sbo >> 4) | (swz << 30)) << 32);
}
__device__ __forceinline__ float ex2(float x) { float y; asm("ex2.approx.ftz.f32 %0, %1;" : "=f"(y) : "f"(x)); return y; }
__device__ __forceinline__ float rcp(float x) { float y; asm("rcp.approx.ftz.f32 %0, %1;" : "=f"(y) : "f"(x)); return y; }
__device__ __forceinline__ uint32_t pack_bf16(float lo, float hi) { uint32_t r; asm("cvt.rn.bf16x2.f32 %0, %1, %2;" : "=r"(r) : "f"(hi), "f"(lo)); return r; }
__device__ __forceinline__ uint32_t pack_f16(float lo, float hi) { uint32_t r; asm("cvt.rn.f16x2.f32 %0, %1, %2;" : "=r"(r) : "f"(hi), "f"(lo)); return r; }
__device__ __forceinline__ float bf_lo(uint32_t v) { return __uint_as_float(v << 16); }
__device__ __forceinline__ float bf_hi(uint32_t v) { return __uint_as_float(v & 0xFFFF0000u); }
__device__ __forceinline__ uint4 ldg_relaxed(const uint4* p) {
    uint4 v; asm volatile("ld.relaxed.gpu.global.v4.u32 {%0,%1,%2,%3}, [%4];" : "=r"(v.x), "=r"(v.y), "=r"(v.z), "=r"(v.w) : "l"(p) : "memory"); return v;
}
__device__ __forceinline__ void stg128(void* p, uint32_t a, uint32_t b, uint32_t c, uint32_t d) {
    asm volatile("st.relaxed.gpu.global.v4.u32 [%0], {%1,%2,%3,%4};" :: "l"(p), "r"(a), "r"(b), "r"(c), "r"(d) : "memory");
}
__device__ __forceinline__ void stg64(void* p, uint32_t a, uint32_t b) {
    asm volatile("st.relaxed.gpu.global.v2.u32 [%0], {%1,%2};" :: "l"(p), "r"(a), "r"(b) : "memory");
}
__device__ __forceinline__ void sts128(uint32_t a, uint32_t x, uint32_t y, uint32_t z, uint32_t w) {
    asm volatile("st.shared.v4.u32 [%0], {%1,%2,%3,%4};" :: "r"(a), "r"(x), "r"(y), "r"(z), "r"(w) : "memory");
}
__device__ __forceinline__ void sts32(uint32_t a, uint32_t x) { asm volatile("st.shared.u32 [%0], %1;" :: "r"(a), "r"(x) : "memory"); }
__device__ __forceinline__ float4 lds128f(uint32_t a) {
    float4 v; asm volatile("ld.shared.v4.f32 {%0,%1,%2,%3}, [%4];" : "=f"(v.x), "=f"(v.y), "=f"(v.z), "=f"(v.w) : "r"(a) : "memory"); return v;
}
__device__ __forceinline__ uint32_t lds32(uint32_t a) { uint32_t v; asm volatile("ld.shared.u32 %0, [%1];" : "=r"(v) : "r"(a) : "memory"); return v; }
__device__ __forceinline__ uint32_t nonzero(uint32_t w) { return w == 0u ? 0x8000u : w; }
__device__ __forceinline__ void stg32(void* p, uint32_t a) { asm volatile("st.global.u32 [%0], %1;" :: "l"(p), "r"(a) : "memory"); }
__device__ __forceinline__ uint32_t ldg32_relaxed(const void* p) { uint32_t v; asm volatile("ld.relaxed.gpu.global.u32 %0, [%1];" : "=r"(v) : "l"(p) : "memory"); return v; }
__device__ __forceinline__ void count_hint(int id) {
    if ((threadIdx.x & 31) == 0) asm volatile("red.relaxed.gpu.global.add.u32 [%0], 1;" :: "l"(g_s.cnt[id]) : "memory");
}
__device__ __forceinline__ void count_release(int id) {
    __syncwarp();
    if ((threadIdx.x & 31) == 0) asm volatile("red.release.gpu.global.add.u32 [%0], 1;" :: "l"(g_s.cnt[id]) : "memory");
    __syncwarp();
}
__device__ __forceinline__ void count_wait(int id, unsigned target) {
    uint32_t v; int spins = 0;
    do v = ldg32_relaxed(g_s.cnt[id]); while (__any_sync(0xffffffffu, v != target) && ++spins < SPIN_LIMIT);
    asm volatile("fence.acquire.gpu;" ::: "memory");
}
__device__ __forceinline__ void warp_done(uint32_t bar) {
    __syncwarp();
    asm volatile("{.reg .pred p; setp.eq.u32 p, %1, 0; @p mbarrier.arrive.shared::cta.b64 _, [%0];}" :: "r"(bar), "r"(threadIdx.x & 31) : "memory");
}
__device__ __forceinline__ uint32_t mul_bf16x2(uint32_t a, uint32_t b) { uint32_t r; asm("mul.rn.bf16x2 %0, %1, %2;" : "=r"(r) : "r"(a), "r"(b)); return r; }
__device__ __forceinline__ uint32_t fma_bf16x2(uint32_t a, uint32_t b, uint32_t c) { uint32_t r; asm("fma.rn.bf16x2 %0, %1, %2, %3;" : "=r"(r) : "r"(a), "r"(b), "r"(c)); return r; }
__device__ __forceinline__ uint32_t add_bf16x2(uint32_t a, uint32_t b) { uint32_t r; asm("add.rn.bf16x2 %0, %1, %2;" : "=r"(r) : "r"(a), "r"(b)); return r; }

#define R4(d, o) "+f"(d[o + 0]), "+f"(d[o + 1]), "+f"(d[o + 2]), "+f"(d[o + 3])
#define R8(d, o) R4(d, o), R4(d, o + 4)
#define R32(d) R8(d, 0), R8(d, 8), R8(d, 16), R8(d, 24)
#define D32 "{%0,%1,%2,%3,%4,%5,%6,%7,%8,%9,%10,%11,%12,%13,%14,%15,%16,%17,%18,%19,%20,%21,%22,%23,%24,%25,%26,%27,%28,%29,%30,%31}"
#define D64 "{%0,%1,%2,%3,%4,%5,%6,%7,%8,%9,%10,%11,%12,%13,%14,%15,%16,%17,%18,%19,%20,%21,%22,%23,%24,%25,%26,%27,%28,%29,%30,%31,%32,%33,%34,%35,%36,%37,%38,%39,%40,%41,%42,%43,%44,%45,%46,%47,%48,%49,%50,%51,%52,%53,%54,%55,%56,%57,%58,%59,%60,%61,%62,%63}"

__device__ __forceinline__ void mma_qk_f16(float (&d)[32], uint64_t da, uint64_t db) {
    asm volatile("{.reg .pred p; setp.eq.b32 p, 0, 0; wgmma.mma_async.sync.aligned.m64n64k16.f32.f16.f16 " D32 ", %32, %33, p, 1, 1, 0, 0;}"
                 : R32(d) : "l"(da), "l"(db));
}
__device__ __forceinline__ void mma_qk_bf16(float (&d)[32], uint64_t da, uint64_t db) {
    asm volatile("{.reg .pred p; setp.ne.b32 p, 0, 0; wgmma.mma_async.sync.aligned.m64n64k16.f32.bf16.bf16 " D32 ", %32, %33, p, 1, 1, 0, 0;}"
                 : R32(d) : "l"(da), "l"(db));
}
__device__ __forceinline__ void mma_pv(float (&d)[12], const uint32_t* a, uint64_t db) {
    asm volatile("{.reg .pred p; setp.eq.b32 p, 0, 0; wgmma.mma_async.sync.aligned.m64n24k16.f32.bf16.bf16 {%0,%1,%2,%3,%4,%5,%6,%7,%8,%9,%10,%11}, {%12,%13,%14,%15}, %16, p, 1, 1, 1;}"
                 : R8(d, 0), R4(d, 8) : "r"(a[0]), "r"(a[1]), "r"(a[2]), "r"(a[3]), "l"(db));
}
__device__ __forceinline__ void mma_ss128(float (&d)[64], uint64_t da, uint64_t db) {
    asm volatile("{.reg .pred p; setp.eq.b32 p, 0, 0; wgmma.mma_async.sync.aligned.m64n128k16.f32.bf16.bf16 " D64 ", %64, %65, p, 1, 1, 0, 1;}"
                 : R32(d), R8(d, 32), R8(d, 40), R8(d, 48), R8(d, 56) : "l"(da), "l"(db));
}
__device__ __forceinline__ void stsm4(uint32_t addr, uint32_t a, uint32_t b, uint32_t c, uint32_t d) {
    asm volatile("stmatrix.sync.aligned.m8n8.x4.shared.b16 [%0], {%1,%2,%3,%4};" :: "r"(addr), "r"(a), "r"(b), "r"(c), "r"(d) : "memory");
}
__device__ __forceinline__ void mma_ss8(float (&d)[4], uint64_t da, uint64_t db) {
    asm volatile("{.reg .pred p; setp.eq.b32 p, 0, 0; wgmma.mma_async.sync.aligned.m64n8k16.f32.bf16.bf16 {%0,%1,%2,%3}, %4, %5, p, 1, 1, 0, 1;}"
                 : R4(d, 0) : "l"(da), "l"(db));
}
__device__ __forceinline__ void mma_ss(float (&d)[32], uint64_t da, uint64_t db) {
    asm volatile("{.reg .pred p; setp.eq.b32 p, 0, 0; wgmma.mma_async.sync.aligned.m64n64k16.f32.bf16.bf16 " D32 ", %32, %33, p, 1, 1, 0, 1;}"
                 : R32(d) : "l"(da), "l"(db));
}
__device__ __forceinline__ void mma_ss(float (&d)[88], uint64_t da, uint64_t db) {
    asm volatile("{.reg .pred p; setp.eq.b32 p, 0, 0; wgmma.mma_async.sync.aligned.m64n176k16.f32.bf16.bf16 " "{%0,%1,%2,%3,%4,%5,%6,%7,%8,%9,%10,%11,%12,%13,%14,%15,%16,%17,%18,%19,%20,%21,%22,%23,%24,%25,%26,%27,%28,%29,%30,%31,%32,%33,%34,%35,%36,%37,%38,%39,%40,%41,%42,%43,%44,%45,%46,%47,%48,%49,%50,%51,%52,%53,%54,%55,%56,%57,%58,%59,%60,%61,%62,%63,%64,%65,%66,%67,%68,%69,%70,%71,%72,%73,%74,%75,%76,%77,%78,%79,%80,%81,%82,%83,%84,%85,%86,%87}"
                 ", %88, %89, p, 1, 1, 0, 1;}"
                 : R32(d), R8(d, 32), R8(d, 40), R8(d, 48), R8(d, 56), R8(d, 64), R8(d, 72), R8(d, 80) : "l"(da), "l"(db));
}

constexpr float EXP_MAGIC = 256.0f + 127.0f + 64.0f - 1.58621f + 0.00390625f;
constexpr uint32_t MUFU_MASK = 0x1111u;
__device__ __forceinline__ uint32_t exp2_pair(float y0, float y1, uint32_t cexp, uint32_t neg1) {
    uint32_t w, m, e, r;
    asm("prmt.b32 %0, %1, %2, 0x6521;" : "=r"(w) : "r"(__float_as_uint(y0)), "r"(__float_as_uint(y1)));
    asm("lop3.b32 %0, %1, 0x007F007F, %2, 0xEA;" : "=r"(m) : "r"(w), "r"(cexp));
    asm("mad.lo.u32 %0, %1, %2, %3;" : "=r"(e) : "r"(m), "r"(neg1), "r"(w));
    asm("fma.rn.bf16x2 %0, %1, %2, %3;" : "=r"(r) : "r"(w), "r"(m), "r"(e));
    return r;
}

struct Params {
    const __nv_bfloat16* x;
    const __nv_bfloat16* wk;
    long long wv_off;
    const __nv_bfloat16* wqp;
    __nv_bfloat16* out;
    uint32_t neg1, pad;
    const __nv_bfloat16* w1p;
    const __nv_bfloat16* w2p;
    CUtensorMap wq, wo, w1, w2;
    const __nv_bfloat16* wop;
};

__device__ __forceinline__ void load_box(uint32_t sb, const CUtensorMap* tm, uint32_t dst, uint32_t bar, uint32_t bytes, int c0, int c1) {
    mbar_expect(sb + SM_MISC + bar * 8, bytes);
    tma2d(sb + dst, tm, c0, c1, sb + SM_MISC + bar * 8);
}
__device__ __forceinline__ void load_wq(uint32_t sb, const Params& P, int gi, int atom) {
    load_box(sb, &P.wq, SM_WQ + atom * 65536 + gi * 16384, MB_WQ + gi, 16384, (blockIdx.x & 3) * 128 + atom * 64, gi * 128);
}
__device__ __forceinline__ void load_wo(uint32_t sb, const Params& P, int kb) { load_box(sb, &P.wo, wo_slot(kb) * SLOT, MB_WO, SLOT, (blockIdx.x & 7) * 64, kb * 64); }
__device__ __forceinline__ void refill_job(uint32_t sb, const Params& P, int gi, int job) {
    const bool w1 = job < 3;
    load_box(sb, w1 ? &P.w1 : &P.wo, (w1 ? 12 + gi + 4 * job : 2 * gi + job - 3) * SLOT, w1 ? MB_W1 + gi : MB_WO, SLOT,
             (blockIdx.x & 7) * (w1 ? 176 : 64) + (w1 ? job * 64 : 0), (w1 ? gi : 2 * gi + job - 1) * 64);
}

__host__ __device__ constexpr int ring_entry(int n) { return n < 32 ? (n & 3) : (n - 32) % 6; }
__host__ __device__ constexpr uint32_t ring_slot(int e) { return e < 4 ? 24 + e : 6 + e; }

template <int KIND> __host__ __device__ constexpr uint64_t b_slots(int first) {
    uint64_t v = 0;
    for (int i = first; i < first + 12; i++) v |= (uint64_t)((KIND == 0 ? wo_slot(i) : KIND == 1 ? w1_slot(i, 0) : w1_slot(i / 3, i % 3)) & 31) << (5 * (i - first));
    return v;
}
template <int KIND, int NACC>
__device__ __forceinline__ void gemm_ss(float (&acc)[NACC], uint32_t sb, int pr TS_ARG) {
    const uint32_t mb = sb + SM_MISC;
    constexpr int NBLK = KIND == 2 ? 22 : 8, N0 = 16 * KIND;
    uint32_t full = mb + (MB_FULL + N0 + pr * NBLK) * 8, empty = mb + MB_NULL * 8, rel = mb + MB_NULL * 8;
    uint32_t e = KIND == 2 ? 4 * pr : 0;
    uint64_t tab = b_slots<KIND>(0);
    uint64_t da = mkdesc(sb + ring_slot(e) * SLOT, 128, 256, 0), db = mkdesc(sb + (b_slots<KIND>(0) & 31) * SLOT, KIND == 1 ? 4 * SLOT : 16, 1024, 1);
#pragma unroll
    for (int i = 0; i < NACC; i++) acc[i] = 0.f;
    fence_regs(acc);
#pragma unroll 1
    for (int i = 0; i < NBLK; i++) {
        mbar_wait(full);
        wg_fence();
#pragma unroll
        for (int s = 0; s < 4; s++) mma_ss(acc, da + s * 128, db + s * 128);
        wg_commit();
        const uint32_t prev = empty, prel = rel;
        empty = mb + (MB_EMPTY + e) * 8;
        rel = mb + (MB_REL + i) * 8;
        e = (e == (KIND == 2 ? 5 : 3)) ? 0 : e + 1;
        tab = (KIND == 2 && i == 11) ? b_slots<KIND>(12) : tab >> 5;
        full += 8;
        da = mkdesc(sb + ring_slot(e) * SLOT, 128, 256, 0);
        db = mkdesc(sb + ((uint32_t)tab & 31) * SLOT, KIND == 1 ? (i < 3 ? 4 * SLOT : SLOT) : 16, 1024, 1);
        wg_wait<1>();
        warp_done(prev);
        if (KIND == 1) warp_done(prel);
    }
    wg_wait<0>();
    fence_regs(acc);
    warp_done(empty);
    if (KIND != 2) warp_done(mb + (MB_REL + 8 - KIND) * 8);
}
__device__ __forceinline__ void ring_feed(uint32_t sb, int e, unsigned epoch TS_ARG) {
    const uint32_t mb = sb + SM_MISC, dst = sb + ring_slot(e) * SLOT;
    const int lane = threadIdx.x & 31;
    uint32_t use = 0;
    int seen = 0;
#pragma unroll 1
    for (int n = e < 4 ? e : 32 + e; n < 76; use ^= 1) {
        const int job = n < 32 ? n >> 3 : 4 + (n >= 54), ph = job >> 1, i = n < 32 ? n & 7 : n - 32 - (job & 1) * 22;
        const int mt = (job & 1) * 16 + (blockIdx.x >> 3);
        const uint4* src = g_x + ph * X_H1 + mt * (ph == 2 ? 88 : 32) * 128 + i * 512;
        const uint32_t full = mb + (MB_FULL + n) * 8;
        if (lane == 0) mbar_expect(full, SLOT);
        if (job != seen) { count_wait(C_O + 32 * ph + mt, epoch * (ph == 0 ? 128 : 32)); seen = job; TS(18 + job); }
        TSF(0);
        asm volatile("fence.proxy.async.global;" ::: "memory");
        TSF(1);
        if (n >= 4) mbar_wait(mb + ((n == 32 + e && e >= 4) ? MB_REL + 7 : MB_EMPTY + e) * 8, (n == 32 + e && e >= 4) ? 0 : use ^ 1);
        TSF(2);
        if (lane == 0) bulk_g2s(dst, src, SLOT, full);
        __syncwarp();
        mbar_wait(mb + (ph == 0 ? MB_WO : ph == 1 ? MB_W1 + i : MB_W2 + i / 3) * 8);
        warp_done(full);
        mbar_wait(full);
        TSF(3);
        uint32_t m = 0;
#pragma unroll
        for (int k = 0; k < 8; k++) m = max(m, lds32(dst + k * 1024 + lane * 32 + (lane >> 2) * 4));
        if (m == SENT) asm volatile("red.shared.or.b32 [%0], %1;" :: "r"(mb + MISC_BAD), "r"(1 << job) : "memory");
        TSF(4);
        const int step = n < 32 ? 4 : 6;
        if (i + step >= (ph == 2 ? 22 : 8)) warp_done(mb + (MB_VALID + job) * 8);
        n += step;
    }
}
template <int NACC>
__device__ __forceinline__ void gemm_slow(float (&acc)[NACC], const uint4* a, int nst, const __nv_bfloat16* W, int ldw, int kmax, int n0) {
    const int lane = threadIdx.x & 31;
    const unsigned short* w = reinterpret_cast<const unsigned short*>(W);
    const uint32_t* p = reinterpret_cast<const uint32_t*>(a) + ((threadIdx.x >> 5) & 3) * 128 + lane;
#pragma unroll
    for (int i = 0; i < NACC; i++) acc[i] = 0.f;
#pragma unroll 1
    for (int st = 0; st < nst; st++, p += 512) {
        const int k = st * 16 + 2 * (lane & 3);
        uint32_t v0, v1, v2, v3; int spins = 0;
        do { v0 = ldg32_relaxed(p); v1 = ldg32_relaxed(p + 64); v2 = ldg32_relaxed(p + 32); v3 = ldg32_relaxed(p + 96); }
        while (__any_sync(0xffffffffu, max(max(v0, v1), max(v2, v3)) == SENT) && ++spins < SPIN_LIMIT);
#pragma unroll
        for (int j = 0; j < NACC / 4; j++) {
            const int n = n0 + 8 * j + (lane >> 2);
            uint32_t b0 = 0, b1 = 0;
            if (k < kmax && n < ldw) {
                const unsigned short* q = w + (size_t)k * ldw + n;
                b0 = q[0] | ((uint32_t)q[ldw] << 16); b1 = q[8 * ldw] | ((uint32_t)q[9 * ldw] << 16);
            }
            asm volatile("mma.sync.aligned.m16n8k16.row.col.f32.bf16.bf16.f32 {%0,%1,%2,%3}, {%4,%5,%6,%7}, {%8,%9}, {%0,%1,%2,%3};"
                         : R4(acc, 4 * j) : "r"(v0), "r"(v1), "r"(v2), "r"(v3), "r"(b0), "r"(b1));
        }
    }
}
__device__ __forceinline__ bool product_bad(uint32_t sb, int job) {
    mbar_wait(sb + SM_MISC + (MB_VALID + job) * 8);
    bool bad = __any_sync(0xffffffffu, (lds32(sb + SM_MISC + MISC_BAD) >> job) & 1);
    return __builtin_expect(bad, 0);
}
__device__ __forceinline__ void store_tile(uint32_t* p, uint32_t r0k0, uint32_t r8k0, uint32_t r0k8, uint32_t r8k8) {
    stg32(p, r0k0); stg32(p + 32, r0k8); stg32(p + 64, r8k0); stg32(p + 96, r8k8);
}

__device__ __forceinline__ float quad_sum(float v) { v += __shfl_xor_sync(0xffffffffu, v, 1); v += __shfl_xor_sync(0xffffffffu, v, 2); return v; }
__device__ __forceinline__ float reduce4(const float (&st)[4], int lane) {
    const bool u16 = lane & 16, u8 = lane & 8;
    const float a0 = (u16 ? st[2] : st[0]) + __shfl_xor_sync(0xffffffffu, u16 ? st[0] : st[2], 16);
    const float a1 = (u16 ? st[3] : st[1]) + __shfl_xor_sync(0xffffffffu, u16 ? st[1] : st[3], 16);
    float v = (u8 ? a1 : a0) + __shfl_xor_sync(0xffffffffu, u8 ? a0 : a1, 8);
    v += __shfl_xor_sync(0xffffffffu, v, 4); v += __shfl_xor_sync(0xffffffffu, v, 2); v += __shfl_xor_sync(0xffffffffu, v, 1);
    return v;
}
__device__ __forceinline__ float silu2(float h) { float t; asm("tanh.approx.f32 %0, %1;" : "=f"(t) : "f"(h)); return fmaf(h, t, h); }

template <bool SAFE>
__device__ __forceinline__ void attention(const Params& P, uint32_t sb, int warp TS_ARG) {
    const uint32_t mb = sb + SM_MISC;
    const int tid = threadIdx.x, lane = tid & 31, b = blockIdx.x;
    const int wg = warp >> 2, ww = warp & 3, job = 3 - wg + 4 * ww;
    const uint32_t cexp = 0x9F809F80u + (tid >> 12);
    const uint32_t neg1 = P.neg1;
    unsigned cnt = 0;
    if (SAFE && warp == 8) cnt = ldg32_relaxed(g_s.cnt[C_KV]);
#pragma unroll 1
    for (int pass = 0; pass < 2; pass++) {
    float o[12], s[32];
    const uint64_t dq = mkdesc(sb + SM_Q + (pass * 4 + wg) * 2048, 128, 256, 0);
    uint64_t dk = mkdesc(sb + SM_K, 128, 256, 0), dv = mkdesc(sb + SM_V, 128, 32768, 0);
    float m0 = -INFINITY, m1 = -INFINITY;
#pragma unroll
    for (int i = 0; i < 12; i++) o[i] = 0.f;
#pragma unroll
    for (int i = 0; i < 32; i++) s[i] = ((MUFU_MASK >> (i / 2)) & 1) ? 0.f : EXP_MAGIC;
    fence_regs(s); fence_regs(o);
    wg_fence();
    if (SAFE) mma_qk_f16(s, dq, dk + 31 * 128); else mma_qk_bf16(s, dq, dk + 31 * 128);
    wg_commit();
    wg_wait<0>(); fence_regs(s);
#pragma unroll 1
    for (int u = pass ? 3 : (wg == 2) ? 0 : 1; u < (pass ? 8 : 3); u++) {
        int n = 2 * ((((wg == 2) ? 0x22444C31u : 0x22444C40u) >> (4 * u)) & 15);
#pragma unroll 1
        do {
            uint32_t p[16];
            if (SAFE) {
#pragma unroll
                for (int j = 0; j < 16; j++) {
                    if ((MUFU_MASK >> j) & 1) p[j] = pack_bf16(ex2(s[2 * j]), ex2(s[2 * j + 1]));
                    else p[j] = exp2_pair(s[2 * j], s[2 * j + 1], cexp, neg1);
                }
            } else {
                fence_regs(o);
                float x0 = m0, x1 = m1;
#pragma unroll
                for (int j = 0; j < 8; j++) { x0 = fmaxf(x0, fmaxf(s[4 * j], s[4 * j + 1])); x1 = fmaxf(x1, fmaxf(s[4 * j + 2], s[4 * j + 3])); }
                x0 = fmaxf(x0, __shfl_xor_sync(0xffffffffu, x0, 1)); x0 = fmaxf(x0, __shfl_xor_sync(0xffffffffu, x0, 2));
                x1 = fmaxf(x1, __shfl_xor_sync(0xffffffffu, x1, 1)); x1 = fmaxf(x1, __shfl_xor_sync(0xffffffffu, x1, 2));
                const float c0 = ex2(m0 - x0), c1 = ex2(m1 - x1);
                m0 = x0; m1 = x1;
#pragma unroll
                for (int j = 0; j < 3; j++) { o[4 * j] *= c0; o[4 * j + 1] *= c0; o[4 * j + 2] *= c1; o[4 * j + 3] *= c1; }
#pragma unroll
                for (int j = 0; j < 8; j++) {
                    p[2 * j] = pack_bf16(ex2(s[4 * j] - m0), ex2(s[4 * j + 1] - m0));
                    p[2 * j + 1] = pack_bf16(ex2(s[4 * j + 2] - m1), ex2(s[4 * j + 3] - m1));
                }
                fence_regs(o);
            }
            fence_regs(p);
            wg_fence();
            if (SAFE) mma_qk_f16(s, dq, dk); else mma_qk_bf16(s, dq, dk);
#pragma unroll
            for (int j = 0; j < 4; j++) mma_pv(o, p + 4 * j, dv + j * 16);
            wg_commit();
            dk += 128; dv += 64;
            wg_wait<0>(); fence_regs(s);
        } while (--n > 0);
        if (u == 2 || u == 7) {
            fence_regs(o);
            const float i0 = rcp(o[8]), i1 = rcp(o[10]);
            if (u == 7) mbar_wait(mb + MB_MID * 8);
            store_tile(reinterpret_cast<uint32_t*>(g_x + X_O + (((u == 7) * 16 + (b >> 3)) * 32 + (b & 3) * 8 + 2 * wg + (ww >> 1)) * 128 + (((b >> 2) & 1) * 2 + (ww & 1)) * 32) + lane,
                       pack_bf16(o[0] * i0, o[1] * i0), pack_bf16(o[2] * i1, o[3] * i1), pack_bf16(o[4] * i0, o[5] * i0), pack_bf16(o[6] * i1, o[7] * i1));
            if (u == 2) asm volatile("cp.async.bulk.wait_group 0;" ::: "memory");
            else count_hint(C_O + 16 + (b >> 3));
            warp_done(mb + (MB_DONE + (u == 7) * 4) * 8);
            TS(5 + (u == 7));
        } else if (u >= 3) {
            if (u < 6) warp_done(mb + (MB_DONE + u - 2) * 8);
            if (job < (u == 3 ? 1 : 5)) {
                mbar_wait(mb + (MB_DONE + u - 3) * 8);
                if (u == 3) count_release(C_MID);
                else if (lane == 0) refill_job(sb, P, u - 4, job);
            } else if (warp == 7) {
                if (u == 5) cnt = ldg32_relaxed(g_s.cnt[C_MID]);
                if (u == 6) {
                    const unsigned target = lds32(mb + MISC_EPOCH) * NCTA;
                    if (__any_sync(0xffffffffu, cnt != target)) count_wait(C_MID, target);
                    asm volatile("fence.acquire.gpu;" ::: "memory");
                    warp_done(mb + MB_MID * 8);
                }
            }
        } else if (u == 1) {
            if (SAFE) mbar_wait(mb + MB_KV * 8);
            TS(17);
            if (lane == 0) {
                if (job < 9) {
                    asm volatile("cp.async.bulk.global.shared::cta.bulk_group [%0], [%1], %2;"
                                 :: "l"(g_x + X_ARM + b * X_SHARE + job * 512), "r"(sb + SM_SENT), "r"(job < 8 ? 8192 : (X_SHARE - 4096) * 16) : "memory");
                    asm volatile("cp.async.bulk.commit_group;" ::: "memory");
                } else if (job < 11) load_wo(sb, P, job - 9);
            }
        } else if (SAFE) {
            if (warp == 8) {
                const unsigned target = lds32(mb + MISC_EPOCH) * NMAIN;
                if (__any_sync(0xffffffffu, cnt != target)) count_wait(C_KV, target);
                if (lane == 0) {
                    asm volatile("fence.acquire.gpu; fence.proxy.async.global;" ::: "memory");
                    mbar_expect(mb + MB_KV * 8, 47104 + 2 * 24576);
                    bulk_g2s(sb + SM_K + 16384, g_s.kv + 1024, 47104, mb + MB_KV * 8);
                    bulk_g2s(sb + SM_V + 8192, g_s.kv + 4096 + 512, 24576, mb + MB_KV * 8);
                    bulk_g2s(sb + SM_V + 32768 + 8192, g_s.kv + 6144 + 512, 24576, mb + MB_KV * 8);
                }
            }
        }
        __syncwarp();
    }
    }
}

__device__ __forceinline__ int kv_slot() {
    const int t = (threadIdx.x & 63) >> 1, c = 2 * (blockIdx.x >> 2) + (threadIdx.x & 1), hg = blockIdx.x & 3;
    return hg < 2 ? ((t + 31) & 31) * 128 + (c >> 3) * 16 + (hg & 1) * 8 + (c & 7) : 4096 + (hg & 1) * 2048 + t * 64 + c;
}

__device__ __noinline__ void helper_cta(const Params& P, uint8_t* smem) {
    const int tid = threadIdx.x, b = blockIdx.x, hi = b - NMAIN;
    const unsigned epoch = g_s.epoch[b] + 1;
    float* red = reinterpret_cast<float*>(smem);
    if (tid < 32) count_wait(C_KV, epoch * NMAIN);
    __syncthreads();
    if (tid == 480) {
        for (int i = 0; i < 8; i++) asm volatile("cp.async.bulk.prefetch.L2.global [%0], %1;" :: "l"((const char*)P.wop + hi * 131072 + i * 16384), "r"(16384) : "memory");
        for (int i = 0; i < 43; i++) asm volatile("cp.async.bulk.prefetch.L2.global [%0], %1;" :: "l"((const char*)P.w2p + hi * 352256 + i * 8192), "r"(8192) : "memory");
    }
    if (tid < 344) {
        const int cg = tid % 43, rp = tid / 43;
        const uint4* src = reinterpret_cast<const uint4*>(P.w1p + (size_t)rp * 64 * FF + (hi * 43 + cg) * 8);
        float s[8] = {0, 0, 0, 0, 0, 0, 0, 0};
#pragma unroll 8
        for (int r = 0; r < 64; r++) {
            uint4 v = __ldg(src + r * (FF / 8));
            s[0] += bf_lo(v.x); s[1] += bf_hi(v.x); s[2] += bf_lo(v.y); s[3] += bf_hi(v.y);
            s[4] += bf_lo(v.z); s[5] += bf_hi(v.z); s[6] += bf_lo(v.w); s[7] += bf_hi(v.w);
        }
        float* part = red + (rp * 43 + cg) * 8;
#pragma unroll
        for (int i = 0; i < 8; i++) part[i] = s[i];
    }
    __syncthreads();
    if (tid < 344) {
        float s = 0.f;
#pragma unroll
        for (int rp = 0; rp < 8; rp++) s += red[rp * 344 + tid];
        g_s.cs[hi * 344 + tid] = s;
    } else if (hi == 3 && tid < 344 + 64) g_s.cs[FF + tid - 344] = 0.f;
    __syncthreads();
    if (tid < 32) count_release(C_MID);
    if (tid == 0) g_s.epoch[b] = epoch;
}

__global__ void __launch_bounds__(512, 1) fused_kernel(const __grid_constant__ Params P) {
    extern __shared__ __align__(1024) uint8_t smem[];
    const uint32_t sb = (uint32_t)__cvta_generic_to_shared(smem);
    const uint32_t mb = sb + SM_MISC;
    const int tid = threadIdx.x, lane = tid & 31, b = blockIdx.x;
    if (b >= NMAIN) { helper_cta(P, smem); return; }
    const int tg = b >> 2, hg = b & 3;
    const int warp = __shfl_sync(0xffffffffu, tid >> 5, 0);

    uint4 xv[4][2];
    unsigned epoch = 0;
    {
        const int r = (tid >> 5) * 4;
        const uint4* src = reinterpret_cast<const uint4*>(P.x + (size_t)((r & 31) + tg * 32 + (r >> 5) * 1024) * D) + lane;
#pragma unroll
        for (int i = 0; i < 4; i++) { xv[i][0] = ldg_relaxed(src + i * 64); xv[i][1] = ldg_relaxed(src + i * 64 + 32); }
    }
    const uint4 wkv = ldg_relaxed(reinterpret_cast<const uint4*>(reinterpret_cast<const char*>(P.wk) + (hg < 2 ? 0 : P.wv_off)) + tid * 2 + (hg & 1));
    const int wg = warp >> 2, ww = warp & 3, g = lane >> 2, t4 = lane & 3, t128 = tid & 127;
    if (lane == 0) {
        if (warp < 4) {
            mbar_init(mb + (MB_WQ + warp) * 8, 2);
            asm volatile("fence.mbarrier_init.release.cluster;" ::: "memory");
            load_wq(sb, P, warp, 0);
            load_wq(sb, P, warp, 1);
        } else if (warp < 7) {
            asm volatile("prefetch.tensormap [%0];" :: "l"(&P.wo + (warp - 4)) : "memory");
        } else if (warp == 7) {
            asm volatile("ld.relaxed.gpu.global.u32 %0, [%1];" : "=r"(epoch) : "l"(g_s.epoch + b) : "memory");
        } else if (warp == 8) {
            sts128(mb + MISC_NRM, 0, 0, 0, 0);

        }
    }
    __syncwarp();
    TS(16);
    float dlt;
    {
        float st[4];
#pragma unroll
        for (int i = 0; i < 4; i++) {
            const uint32_t s = add_bf16x2(add_bf16x2(add_bf16x2(xv[i][0].x, xv[i][0].y), add_bf16x2(xv[i][0].z, xv[i][0].w)),
                                          add_bf16x2(add_bf16x2(xv[i][1].x, xv[i][1].y), add_bf16x2(xv[i][1].z, xv[i][1].w)));
            st[i] = bf_lo(s) + bf_hi(s);
        }
        TS(13);
        const float tot = reduce4(st, lane) * (-1.0f / D);
        const uint32_t nmr = pack_bf16(tot, tot);
        dlt = bf_lo(nmr) - tot;
        const uint32_t xa = sb + SM_XN + (lane >> 3) * 8192 + warp * 512;
#pragma unroll
        for (int i = 0; i < 4; i++) {
            const uint32_t nm = __shfl_sync(0xffffffffu, nmr, i * 8);
            const uint32_t addr = xa + i * 128 + (((lane & 7) ^ ((warp & 1) * 4 + i)) << 4);
#pragma unroll
            for (int c = 0; c < 2; c++) {
                xv[i][c].x = add_bf16x2(xv[i][c].x, nm); xv[i][c].y = add_bf16x2(xv[i][c].y, nm);
                xv[i][c].z = add_bf16x2(xv[i][c].z, nm); xv[i][c].w = add_bf16x2(xv[i][c].w, nm);
                sts128(addr + c * 32768, xv[i][c].x, xv[i][c].y, xv[i][c].z, xv[i][c].w);
            }
        }
    }
    sts128(sb + SM_WKV + tid * 16, wkv.x, wkv.y, wkv.z, wkv.w);
    fence_async_smem();
    TS(0);
    __syncthreads();
    auto variances = [&]() {
        float st[4];
#pragma unroll
        for (int i = 0; i < 4; i++) {
            float v = 0.f;
#pragma unroll
            for (int c = 0; c < 2; c++) {
                const uint32_t a = fma_bf16x2(xv[i][c].x, xv[i][c].x, mul_bf16x2(xv[i][c].y, xv[i][c].y));
                const uint32_t d = fma_bf16x2(xv[i][c].z, xv[i][c].z, mul_bf16x2(xv[i][c].w, xv[i][c].w));
                v += (bf_lo(a) + bf_hi(a)) + (bf_lo(d) + bf_hi(d));
            }
            st[i] = v;
        }
        const float vs = reduce4(st, lane), dl = dlt;
        if ((lane & 7) == 0) sts32(sb + SM_RSTD + (warp * 4 + (lane >> 3)) * 4, __float_as_uint(rsqrtf(fmaxf(vs * (1.0f / D) - dl * dl, 0.f) + 1e-5f)));
    };
    float kv[4] = {0.f, 0.f, 0.f, 0.f};
    if (wg == 2) {
        fence_regs(kv);
        const uint64_t da = mkdesc(sb + SM_XN, 16, 1024, 1), db = mkdesc(sb + SM_WKV, 128, 16, 0);
        wg_fence();
#pragma unroll
        for (int s = 0; s < 32; s++) mma_ss8(kv, da + (s >> 2) * 512 + (s & 3) * 2, db + s * 16);
        wg_commit();
        variances();
        wg_wait<0>(); fence_regs(kv);
    } else {
        variances();
        if (tid == 7 * 32) { sts32(mb + MISC_EPOCH, epoch + 1); sts32(mb + MISC_BAD, 0); g_s.epoch[b] = epoch + 1; }
    }
    __syncthreads();
    constexpr float QSCALE = 0.25f * 1.4426950408889634f;
    float qa[64];
    const uint32_t qbase = sb + SM_Q + (ww >> 1) * 8192 + (ww & 1) * 512 + lane * 16;
    if (wg == 0) {
#pragma unroll
        for (int i = 0; i < 64; i++) qa[i] = 0.f;
        fence_regs(qa);
        const uint64_t da = mkdesc(sb + SM_XN, 16, 1024, 1), db = mkdesc(sb + SM_WQ, 65536, 1024, 1);
#pragma unroll 1
        for (int i = 0; i < 4; i++) {
            mbar_wait(mb + (MB_WQ + i) * 8);
            wg_fence();
#pragma unroll
            for (int s = 0; s < 8; s++) mma_ss128(qa, da + (i * 2 + (s >> 2)) * 512 + (s & 3) * 2, db + (i * 8 + s) * 128);
            wg_commit();
        }
        const float rs0 = __uint_as_float(lds32(sb + SM_RSTD + (ww * 16 + g) * 4)) * QSCALE, rs1 = __uint_as_float(lds32(sb + SM_RSTD + (ww * 16 + g + 8) * 4)) * QSCALE;
        wg_wait<0>();
        fence_regs(qa);
        bar_arrive(6, 256);
        bar_sync(5, 256);
        TS(1);
        uint32_t nm = 0;
#pragma unroll
        for (int h = 0; h < 8; h++) {
#pragma unroll
            for (int i = 0; i < 8; i++) qa[8 * h + i] *= (i & 2) ? rs1 : rs0;
            stsm4(qbase + h * 1024, pack_f16(qa[8 * h], qa[8 * h + 1]), pack_f16(qa[8 * h + 4], qa[8 * h + 5]), pack_f16(qa[8 * h + 2], qa[8 * h + 3]), pack_f16(qa[8 * h + 6], qa[8 * h + 7]));
            const float n0 = qa[8 * h] * qa[8 * h] + qa[8 * h + 1] * qa[8 * h + 1] + qa[8 * h + 4] * qa[8 * h + 4] + qa[8 * h + 5] * qa[8 * h + 5];
            const float n1 = qa[8 * h + 2] * qa[8 * h + 2] + qa[8 * h + 3] * qa[8 * h + 3] + qa[8 * h + 6] * qa[8 * h + 6] + qa[8 * h + 7] * qa[8 * h + 7];
            nm = max(nm, max(__float_as_uint(n0), __float_as_uint(n1)));
        }
        nm = __reduce_max_sync(0xffffffffu, __float_as_uint(quad_sum(__uint_as_float(nm))));
        if (lane == 0) asm volatile("red.shared.max.u32 [%0], %1;" :: "r"(mb + MISC_NRM), "r"(nm) : "memory");
    } else if (wg == 1) {
        if (lane == 0) {
            if (ww == 0) {
#pragma unroll
                for (uint32_t i = 4; i < MB_WO; i++) mbar_init(mb + i * 8, bar_count(i));
            } else if (ww == 1) {
#pragma unroll
                for (uint32_t i = MB_WO; i < 63; i++) mbar_init(mb + i * 8, bar_count(i));
            } else {
#pragma unroll
                for (uint32_t i = 0; i < 32; i++) mbar_init(mb + (ww * 32 - 1 + i) * 8, 2);
            }
        }
        __syncwarp();
#pragma unroll
        for (int i = 0; i < 4; i++) sts128(sb + SM_SENT + (i * 128 + t128) * 16, SENT, SENT, SENT, SENT);
        bar_sync(5, 256);
#pragma unroll
        for (int i = 0; i < 16; i++) sts128(sb + SM_V + 65536 + (i * 128 + t128) * 16, 0x3F803F80u, 0x3F803F80u, 0x3F803F80u, 0x3F803F80u);
    } else if (wg == 2) {
        const float rs0 = __uint_as_float(lds32(sb + SM_RSTD + (ww * 16 + g) * 4)), rs1 = __uint_as_float(lds32(sb + SM_RSTD + (ww * 16 + g + 8) * 4));
        kv[0] *= rs0; kv[1] *= rs0; kv[2] *= rs1; kv[3] *= rs1;
        float2* kt = reinterpret_cast<float2*>(smem + SM_KTMP);
        kt[(ww * 16 + g) * 4 + t4] = make_float2(kv[0], kv[1]); kt[(ww * 16 + g + 8) * 4 + t4] = make_float2(kv[2], kv[3]);
        float n0 = kv[0] * kv[0] + kv[1] * kv[1], n1 = kv[2] * kv[2] + kv[3] * kv[3];
        n0 += __shfl_xor_sync(0xffffffffu, n0, 1); n1 += __shfl_xor_sync(0xffffffffu, n1, 1);
        n0 += __shfl_xor_sync(0xffffffffu, n0, 2); n1 += __shfl_xor_sync(0xffffffffu, n1, 2);
        const uint32_t nm = __reduce_max_sync(0xffffffffu, max(__float_as_uint(n0), __float_as_uint(n1)));
        if (lane == 0) sts32(sb + SM_WNRM + ww * 4, nm | 1u);
        bar_sync(2, 128);
        const uint32_t ra = sb + SM_KTMP + ((t128 & 1) * 32 + ((t128 & 63) >> 1)) * 32;
        const float4 c0 = lds128f(ra), c1 = lds128f(ra + 16);
        const int kvoff = kv_slot();
        if (ww < 2) {
            if (hg < 2) {
                float4 p0 = lds128f(ra - 32), p1 = lds128f(ra - 16);
                if (t128 < 2) { p0 = make_float4(0.f, 0.f, 0.f, 0.f); p1 = p0; }
                stg128(g_s.kv + kvoff, nonzero(pack_f16(c0.x - p0.x, c0.y - p0.y)), pack_f16(c0.z - p0.z, c0.w - p0.w), pack_f16(c1.x - p1.x, c1.y - p1.y), pack_f16(c1.z - p1.z, c1.w - p1.w));
            } else {
                stg128(g_s.kv + kvoff, nonzero(pack_bf16(c0.x, c0.y)), pack_bf16(c0.z, c0.w), pack_bf16(c1.x, c1.y), pack_bf16(c1.z, c1.w));
            }
            if (t128 < 2) { const float4 w = lds128f(sb + SM_WNRM); stg128(g_s.nrm + b * 2 + t128, __float_as_uint(w.x), __float_as_uint(w.y), __float_as_uint(w.z), __float_as_uint(w.w)); }
            count_hint(C_KVH);
        } else if (hg < 2) {
            stg128(g_s.kplain + kvoff, pack_bf16(c0.x, c0.y), pack_bf16(c0.z, c0.w), pack_bf16(c1.x, c1.y), pack_bf16(c1.z, c1.w));
        }
        TS(1);
        bar_sync(2, 128);
        if (ww == 3) count_release(C_KV);
    } else {
        uint4 kc[18];
        auto src = [&](int i) { return i < 8 ? g_s.kv + i * 128 : i < 12 ? g_s.kv + 4096 + (i - 8) * 128 : i < 16 ? g_s.kv + 6144 + (i - 12) * 128 : i == 16 ? g_s.kv + 31 * 128 : g_s.nrm + t128; };
        count_wait(C_KVH, lds32(mb + MISC_EPOCH) * (NMAIN * 2));
        TS(1);
        int spins = 0;
        while (true) {
#pragma unroll
            for (int i = 0; i < 18; i++) kc[i] = ldg_relaxed(src(i) + t128);
            uint32_t mn = 1;
#pragma unroll
            for (int i = 0; i < 18; i++) mn = min(mn, kc[i].x);
            if (!__any_sync(0xffffffffu, mn == 0u) || ++spins >= SPIN_LIMIT) break;
        }
        uint32_t nm = max(max(kc[17].x, kc[17].y), max(kc[17].z, kc[17].w));
        nm = max(nm, __shfl_xor_sync(0xffffffffu, nm, 4)); nm = max(nm, __shfl_xor_sync(0xffffffffu, nm, 8)); nm = max(nm, __shfl_xor_sync(0xffffffffu, nm, 16));
        if (lane < 4) asm volatile("red.shared.max.u32 [%0], %1;" :: "r"(mb + MISC_NRM + 4 + min(lane, 2) * 4), "r"(nm) : "memory");
        TS(2);
        bar_sync(6, 256);
#pragma unroll
        for (int i = 0; i < 17; i++) sts128(sb + (uint32_t)(src(i) - g_s.kv + t128) * 16 + ((i >= 8 && i < 16) ? SM_V - 65536 : 0), kc[i].x, kc[i].y, kc[i].z, kc[i].w);
    }
    fence_async_smem();
    TS(3);
    __syncthreads();
    const float4 nr = lds128f(mb + MISC_NRM);
    const bool safe = __all_sync(0xffffffffu, (nr.x * (nr.y + nr.z) <= 3500.0f) && (nr.x <= 65536.0f) && (nr.y + nr.z <= 65536.0f) && (nr.w <= 1e24f));
    TS(4);

    if (__builtin_expect(safe, 1)) {
        attention<true>(P, sb, warp TS_PASS);
    } else {
        if (wg == 0) {
#pragma unroll
            for (int h = 0; h < 8; h++)
                stsm4(qbase + h * 1024, pack_bf16(qa[8 * h], qa[8 * h + 1]), pack_bf16(qa[8 * h + 4], qa[8 * h + 5]), pack_bf16(qa[8 * h + 2], qa[8 * h + 3]), pack_bf16(qa[8 * h + 6], qa[8 * h + 7]));
            fence_async_smem();
        } else if (warp == 15) {
            count_wait(C_KV, lds32(mb + MISC_EPOCH) * NMAIN);
            if (lane == 0) {
                asm volatile("fence.proxy.async;" ::: "memory");
                mbar_expect(mb + MB_KV * 8, 131072);
                bulk_g2s(sb + SM_K, g_s.kplain, 65536, mb + MB_KV * 8);
                bulk_g2s(sb + SM_V, g_s.kv + 4096, 65536, mb + MB_KV * 8);
            }
            __syncwarp();
        }
        __syncthreads();
        mbar_wait(mb + MB_KV * 8);
        attention<false>(P, sb, warp TS_PASS);
    }

    epoch = lds32(mb + MISC_EPOCH);
    const int j = b & 7;
    if (wg == 1) {
        ring_feed(sb, ww, epoch TS_PASS);
    } else if (wg == 2) {
        if (ww < 2) {
            if (t128 < 44) {
                const uint4 v = ldg_relaxed(reinterpret_cast<const uint4*>(g_s.cs + j * 176) + t128);
                sts128(mb + MISC_CS + t128 * 16, v.x, v.y, v.z, v.w);
            }
            warp_done(mb + MB_CS * 8);
            stg128(g_s.kv + kv_slot(), 0u, 0u, 0u, 0u);
            if (t128 < 2) stg128(g_s.nrm + b * 2 + t128, 0u, 0u, 0u, 0u);
            ring_feed(sb, 4 + ww, epoch TS_PASS);
        } else {
#pragma unroll 1
            for (int i = 7 + ww; i < 46; i += 2) {
                const bool w1 = i < 24;
                const int n = w1 ? i : i - 24, kb = n / 3, a = n - 3 * kb;
                mbar_wait(mb + (w1 ? (i < 15 ? MB_DONE + 4 : MB_REL + 8) : MB_REL + kb) * 8);
                if (lane == 0) load_box(sb, w1 ? &P.w1 : &P.w2, w1_slot(kb, a) * SLOT, (w1 ? MB_W1 : MB_W2) + kb, SLOT, w1 ? j * 176 + a * 64 : j * 64, (w1 ? kb : n) * 64);
                __syncwarp();
            }
        }
    } else {
        const int pr = (wg == 0), mt = 16 * pr + (b >> 3);
        uint32_t* const hp = reinterpret_cast<uint32_t*>(g_x + X_H1 + (mt * 32 + j * 4) * 128 + ww * 32) + lane;
        {
            uint32_t hk[16];
            const uint32_t* xp = reinterpret_cast<const uint32_t*>(P.x + (size_t)(mt * 64 + ww * 16 + g) * D + j * 64 + t4 * 2);
#pragma unroll
            for (int k = 0; k < 8; k++) { hk[2 * k] = __ldg(xp + k * 4); hk[2 * k + 1] = __ldg(xp + k * 4 + 8 * (D / 2)); }
            float acc[32];
            gemm_ss<0>(acc, sb, pr TS_PASS);
            if (product_bad(sb, pr)) gemm_slow(acc, g_x + X_O + mt * 32 * 128, 32, P.wop, D, D, j * 64);
            TS(7);
#pragma unroll
            for (int i = 0; i < 16; i++) hk[i] = pack_bf16(acc[2 * i] + bf_lo(hk[i]), acc[2 * i + 1] + bf_hi(hk[i]));
#pragma unroll
            for (int k = 0; k < 4; k++) store_tile(hp + k * 512, hk[4 * k], hk[4 * k + 1], hk[4 * k + 2], hk[4 * k + 3]);
            count_hint(C_H1 + mt);
            TS(8);
            float st[4] = {0.f, 0.f, 0.f, 0.f};
#pragma unroll
            for (int i = 0; i < 16; i++) {
                const float lo = bf_lo(hk[i]), hi = bf_hi(hk[i]);
                st[2 * (i & 1)] += lo + hi;
                st[2 * (i & 1) + 1] = fmaf(lo, lo, fmaf(hi, hi, st[2 * (i & 1) + 1]));
            }
#pragma unroll
            for (int o = 1; o < 4; o <<= 1)
#pragma unroll
                for (int i = 0; i < 4; i++) st[i] += __shfl_xor_sync(0xffffffffu, st[i], o);
            if (t4 == 0) stg128(g_x + X_ST + (mt * 8 + j) * 32 + ww * 8 + g, __float_as_uint(st[0]), __float_as_uint(st[1]), __float_as_uint(st[2]), __float_as_uint(st[3]));
        }
        {
            float acc[88];
            const uint4* sp = g_x + X_ST + (mt * 8 + t4) * 32 + ww * 8 + g;
            mbar_wait(mb + (MB_FULL + 16 + pr * 8) * 8);
            uint4 u0 = ldg_relaxed(sp), u1 = ldg_relaxed(sp + 128);
            gemm_ss<1>(acc, sb, pr TS_PASS);
            if (product_bad(sb, 2 + pr)) gemm_slow(acc, g_x + X_H1 + mt * 32 * 128, 32, P.w1p, FF, D, j * 176);
            TS(9);
            int spins = 0;
            while (__builtin_expect(__any_sync(0xffffffffu, max(u0.x, u1.x) == SENT), 0) && ++spins < SPIN_LIMIT) { u0 = ldg_relaxed(sp); u1 = ldg_relaxed(sp + 128); }
            float st[4] = {__uint_as_float(u0.x) + __uint_as_float(u1.x), __uint_as_float(u0.y) + __uint_as_float(u1.y),
                           __uint_as_float(u0.z) + __uint_as_float(u1.z), __uint_as_float(u0.w) + __uint_as_float(u1.w)};
#pragma unroll
            for (int o = 1; o < 4; o <<= 1)
#pragma unroll
                for (int k = 0; k < 4; k++) st[k] += __shfl_xor_sync(0xffffffffu, st[k], o);
            float nmean[2], hrstd[2];
#pragma unroll
            for (int k = 0; k < 2; k++) {
                nmean[k] = st[2 * k] * (-1.0f / D);
                hrstd[k] = 0.5f * rsqrtf(fmaxf(fmaf(-nmean[k], nmean[k], st[2 * k + 1] * (1.0f / D)), 0.f) + 1e-5f);
                nmean[k] *= hrstd[k];
            }
            mbar_wait(mb + MB_CS * 8);
            uint32_t* hb = reinterpret_cast<uint32_t*>(g_x + X_H2 + (mt * 88 + j * 11) * 128 + ww * 32) + lane;
#pragma unroll
            for (int i = 0; i < 22; i++) {
                float2 cs;
                asm volatile("ld.shared.v2.f32 {%0,%1}, [%2];" : "=f"(cs.x), "=f"(cs.y) : "r"(mb + MISC_CS + i * 32 + t4 * 8));
                const float* z = acc + 4 * i;
                uint32_t* p = hb + (i >> 1) * 512 + (i & 1) * 32;
                stg32(p, pack_bf16(silu2(fmaf(hrstd[0], z[0], nmean[0] * cs.x)), silu2(fmaf(hrstd[0], z[1], nmean[0] * cs.y))));
                stg32(p + 64, pack_bf16(silu2(fmaf(hrstd[1], z[2], nmean[1] * cs.x)), silu2(fmaf(hrstd[1], z[3], nmean[1] * cs.y))));
            }
            count_hint(C_H2 + mt);
            TS(10);
        }
        {
            uint32_t hk[16];
#pragma unroll
            for (int i = 0; i < 16; i++) hk[i] = ldg32_relaxed(hp + (i >> 2) * 512 + ((i & 1) * 2 + ((i >> 1) & 1)) * 32);
            float acc[32];
            gemm_ss<2>(acc, sb, pr TS_PASS);
            if (product_bad(sb, 4 + pr)) gemm_slow(acc, g_x + X_H2 + mt * 88 * 128, 88, P.w2p, D, FF, j * 64);
            TS(11);
#pragma unroll
            for (int i = 0; i < 16; i++) hk[i] = pack_bf16(acc[2 * i] + bf_lo(hk[i]), acc[2 * i + 1] + bf_hi(hk[i]));
#pragma unroll
            for (int h = 0; h < 4; h++) {
                const uint32_t* v = hk + (h >> 1) * 8 + (h & 1);
                uint32_t v0 = v[0], v1 = v[2], v2 = v[4], v3 = v[6];
                const bool o1 = t4 & 1, o2 = t4 & 2;
                uint32_t a = __shfl_xor_sync(0xffffffffu, o1 ? v0 : v1, 1), c = __shfl_xor_sync(0xffffffffu, o1 ? v2 : v3, 1);
                if (o1) { v0 = a; v2 = c; } else { v1 = a; v3 = c; }
                a = __shfl_xor_sync(0xffffffffu, o2 ? v0 : v2, 2); c = __shfl_xor_sync(0xffffffffu, o2 ? v1 : v3, 2);
                if (o2) { v0 = a; v1 = c; } else { v2 = a; v3 = c; }
                *reinterpret_cast<uint4*>(P.out + (size_t)(mt * 64 + ww * 16 + g + 8 * (h & 1)) * D + j * 64 + (h >> 1) * 32 + t4 * 8) = make_uint4(v0, v1, v2, v3);
            }
        }
    }
    TS(12);
}

typedef CUresult (*EncodeFn)(CUtensorMap*, CUtensorMapDataType, cuuint32_t, void*, const cuuint64_t*, const cuuint64_t*, const cuuint32_t*,
                             const cuuint32_t*, CUtensorMapInterleave, CUtensorMapSwizzle, CUtensorMapL2promotion, CUtensorMapFloatOOBfill);

void encode2d(EncodeFn fn, CUtensorMap* tm, const void* ptr, int rows, int cols, int box_rows, int box_cols, CUtensorMapSwizzle sw) {
    cuuint64_t dims[2] = {(cuuint64_t)cols, (cuuint64_t)rows};
    cuuint64_t strides[1] = {(cuuint64_t)cols * 2};
    cuuint32_t box[2] = {(cuuint32_t)box_cols, (cuuint32_t)box_rows};
    cuuint32_t es[2] = {1, 1};
    fn(tm, CU_TENSOR_MAP_DATA_TYPE_BFLOAT16, 2, const_cast<void*>(ptr), dims, strides, box, es, CU_TENSOR_MAP_INTERLEAVE_NONE, sw,
       CU_TENSOR_MAP_L2_PROMOTION_L2_128B, CU_TENSOR_MAP_FLOAT_OOB_FILL_NONE);
}

}

extern "C" void kernel_launch(void* const* d_in, const int* in_sizes, int n_in, void* d_out, int out_size) {
    (void)in_sizes; (void)n_in; (void)out_size;
    void* fnp = nullptr;
    cudaDriverEntryPointQueryResult qr;
    cudaGetDriverEntryPoint("cuTensorMapEncodeTiled", &fnp, cudaEnableDefault, &qr);
    EncodeFn fn = (EncodeFn)fnp;
    Params P;
    encode2d(fn, &P.wq, d_in[1], D, D, 128, 64, CU_TENSOR_MAP_SWIZZLE_128B);
    P.wk = (const __nv_bfloat16*)d_in[2];
    P.wv_off = (const char*)d_in[3] - (const char*)d_in[2];
    encode2d(fn, &P.wo, d_in[4], D, D, 64, 64, CU_TENSOR_MAP_SWIZZLE_128B);
    encode2d(fn, &P.w1, d_in[6], D, FF, 64, 64, CU_TENSOR_MAP_SWIZZLE_128B);
    encode2d(fn, &P.w2, d_in[7], FF, D, 64, 64, CU_TENSOR_MAP_SWIZZLE_128B);
    P.x = (const __nv_bfloat16*)d_in[0];
    P.w1p = (const __nv_bfloat16*)d_in[6];
    P.w2p = (const __nv_bfloat16*)d_in[7];
    P.wop = (const __nv_bfloat16*)d_in[4];
    P.wqp = (const __nv_bfloat16*)d_in[1];
    P.out = (__nv_bfloat16*)d_out;
    P.neg1 = 0xFFFFFFFFu; P.pad = 0;
    cudaFuncSetAttribute(fused_kernel, cudaFuncAttributeMaxDynamicSharedMemorySize, SMEM_BYTES);
    fused_kernel<<<NCTA, 512, SMEM_BYTES>>>(P);
}
```

```cpp
#include <cuda_runtime.h>
#include <cuda_bf16.h>
#include <cuda.h>
#include <stdint.h>

namespace {

constexpr int D = 512, FF = 1376;
constexpr int NMAIN = 128, NHELP = 4, NCTA = NMAIN + NHELP;
constexpr uint32_t SENT = 0xFFFFFFFFu;
constexpr int SPIN_LIMIT = 1 << 22;

constexpr uint32_t KB = 1024, SLOT = 8192;
constexpr uint32_t SM_XN = 0;
constexpr uint32_t SM_WQ = 64 * KB;
constexpr uint32_t SM_WKV = 192 * KB;
constexpr uint32_t SM_K = 0;
constexpr uint32_t SM_Q = 64 * KB;
constexpr uint32_t SM_V = 96 * KB;
constexpr uint32_t SM_MISC = 224 * KB;
constexpr uint32_t SMEM_BYTES = 227 * KB;
constexpr uint32_t SM_KTMP = 200 * KB;
constexpr uint32_t SM_RSTD = 202 * KB;
constexpr uint32_t SM_WNRM = 203 * KB;
constexpr uint32_t SM_SENT = 208 * KB;
constexpr uint32_t MB_WQ = 0;
constexpr uint32_t MB_CS = 4;
constexpr uint32_t MB_DONE = 5;
constexpr uint32_t MB_EMPTY = 10;
constexpr uint32_t MB_W1 = 16;
constexpr uint32_t MB_W2 = 24;
constexpr uint32_t MB_WO = 32;
constexpr uint32_t MB_REL = 33;
constexpr uint32_t MB_VALID = 42;
constexpr uint32_t MB_KV = 48;
constexpr uint32_t MB_MID = 49;
constexpr uint32_t MB_READY = 49;
constexpr uint32_t MB_FULL = 55;
constexpr uint32_t MB_NULL = 131;
constexpr uint32_t NBAR = 132;
__host__ __device__ constexpr uint32_t bar_count(uint32_t i) {
    return i >= MB_FULL ? 2 : i >= MB_KV ? 1 : i >= MB_VALID + 4 ? 6 : i >= MB_VALID ? 4 : i >= MB_WO ? 8 : i == MB_W2 + 7 ? 1 : i >= MB_W1 ? 3 : i >= MB_EMPTY ? 4 : i >= MB_DONE ? 16 : 1;
}
constexpr uint32_t MISC_NRM = 1056;
constexpr uint32_t MISC_EPOCH = 1072;
constexpr uint32_t MISC_BAD = 1076;
constexpr uint32_t MISC_TS = 1088;
constexpr uint32_t MISC_CS = 1344;

__host__ __device__ constexpr uint32_t wo_slot(int kb) { return kb < 2 ? 10 + kb : kb - 2; }
__host__ __device__ constexpr uint32_t w1_slot(int kb, int a) { return kb < 4 ? 12 + kb + 4 * a : (kb == 4 ? 6 : kb == 7 ? 9 : 3 * kb - 15) + a; }

struct alignas(128) Small {
    unsigned epoch[160];
    unsigned cnt[100][32];
    float cs[1440];
    uint4 nrm[NMAIN * 2];
    uint4 kv[8192];
    uint4 kplain[4096];
};
__device__ Small g_s;
constexpr int C_KVH = 0, C_KV = 1, C_MID = 2, C_O = 3, C_H1 = 35, C_H2 = 67;
constexpr int X_O = 0, X_H1 = 32 * 32 * 128, X_H2 = 2 * X_H1, X_ST = X_H2 + 32 * 88 * 128, X_END = X_ST + 32 * 8 * 32;
constexpr int X_ARM = 16 * 32 * 128, X_SHARE = (X_END - X_ARM) / NMAIN;
__device__ uint4 g_x[X_END];
#define TS(i) do {} while (0)
#define TSF(k)

#define TS_ARG
#define TS_PASS

__device__ __forceinline__ void mbar_init(uint32_t bar, int cnt) { asm volatile("mbarrier.init.shared::cta.b64 [%0], %1;" :: "r"(bar), "r"(cnt) : "memory"); }
__device__ __forceinline__ void mbar_expect(uint32_t bar, uint32_t bytes) { asm volatile("mbarrier.arrive.expect_tx.shared::cta.b64 _, [%0], %1;" :: "r"(bar), "r"(bytes) : "memory"); }
__device__ __forceinline__ void mbar_arrive(uint32_t bar) { asm volatile("mbarrier.arrive.shared::cta.b64 _, [%0];" :: "r"(bar) : "memory"); }
__device__ __forceinline__ bool mbar_try(uint32_t bar, uint32_t parity) {
    uint32_t done;
    asm volatile("{.reg .pred p; mbarrier.try_wait.parity.shared::cta.b64 p, [%1], %2; selp.u32 %0, 1, 0, p;}" : "=r"(done) : "r"(bar), "r"(parity) : "memory");
    return __all_sync(0xffffffffu, done);
}
__device__ __forceinline__ void mbar_wait(uint32_t bar, uint32_t parity = 0) {
    if (__builtin_expect(!mbar_try(bar, parity), 0)) {
        int spins = 0;
        while (!mbar_try(bar, parity) && ++spins < (SPIN_LIMIT >> 6)) {}
    }
}
__device__ __forceinline__ void tma2d(uint32_t dst, const CUtensorMap* tm, int c0, int c1, uint32_t bar) {
    asm volatile("cp.async.bulk.tensor.2d.shared::cluster.global.mbarrier::complete_tx::bytes [%0], [%1, {%3, %4}], [%2];"
                 :: "r"(dst), "l"(tm), "r"(bar), "r"(c0), "r"(c1) : "memory");
}
__device__ __forceinline__ void bulk_g2s(uint32_t dst, const void* src, uint32_t bytes, uint32_t bar) {
    asm volatile("cp.async.bulk.shared::cluster.global.mbarrier::complete_tx::bytes [%0], [%1], %2, [%3];" :: "r"(dst), "l"(src), "r"(bytes), "r"(bar) : "memory");
}
__device__ __forceinline__ void fence_async_smem() { asm volatile("fence.proxy.async.shared::cta;" ::: "memory"); }
__device__ __forceinline__ void bar_sync(int id, int n) { asm volatile("bar.sync %0, %1;" :: "r"(id), "r"(n) : "memory"); }
__device__ __forceinline__ void bar_arrive(int id, int n) { asm volatile("bar.arrive %0, %1;" :: "r"(id), "r"(n) : "memory"); }
__device__ __forceinline__ void wg_fence() { asm volatile("wgmma.fence.sync.aligned;" ::: "memory"); }
__device__ __forceinline__ void wg_commit() { asm volatile("wgmma.commit_group.sync.aligned;" ::: "memory"); }
template <int N> __device__ __forceinline__ void wg_wait() { asm volatile("wgmma.wait_group.sync.aligned %0;" :: "n"(N) : "memory"); }
template <int N> __device__ __forceinline__ void fence_regs(float (&d)[N]) {
#pragma unroll
    for (int i = 0; i < N; i++) asm volatile("" : "+f"(d[i]) :: "memory");
}
template <int N> __device__ __forceinline__ void fence_regs(uint32_t (&d)[N]) {
#pragma unroll
    for (int i = 0; i < N; i++) asm volatile("" : "+r"(d[i]) :: "memory");
}
__device__ __forceinline__ uint64_t mkdesc(uint32_t addr, uint32_t lbo, uint32_t sbo, uint32_t swz) {
    return (uint64_t)(((addr & 0x3FFFF) >> 4) | ((lbo >> 4) << 16)) | ((uint64_t)((sbo >> 4) | (swz << 30)) << 32);
}
__device__ __forceinline__ float ex2(float x) { float y; asm("ex2.approx.ftz.f32 %0, %1;" : "=f"(y) : "f"(x)); return y; }
__device__ __forceinline__ float rcp(float x) { float y; asm("rcp.approx.ftz.f32 %0, %1;" : "=f"(y) : "f"(x)); return y; }
__device__ __forceinline__ uint32_t pack_bf16(float lo, float hi) { uint32_t r; asm("cvt.rn.bf16x2.f32 %0, %1, %2;" : "=r"(r) : "f"(hi), "f"(lo)); return r; }
__device__ __forceinline__ uint32_t pack_f16(float lo, float hi) { uint32_t r; asm("cvt.rn.f16x2.f32 %0, %1, %2;" : "=r"(r) : "f"(hi), "f"(lo)); return r; }
__device__ __forceinline__ float bf_lo(uint32_t v) { return __uint_as_float(v << 16); }
__device__ __forceinline__ float bf_hi(uint32_t v) { return __uint_as_float(v & 0xFFFF0000u); }
__device__ __forceinline__ uint4 ldg_relaxed(const uint4* p) {
    uint4 v; asm volatile("ld.relaxed.gpu.global.v4.u32 {%0,%1,%2,%3}, [%4];" : "=r"(v.x), "=r"(v.y), "=r"(v.z), "=r"(v.w) : "l"(p) : "memory"); return v;
}
__device__ __forceinline__ void stg128(void* p, uint32_t a, uint32_t b, uint32_t c, uint32_t d) {
    asm volatile("st.relaxed.gpu.global.v4.u32 [%0], {%1,%2,%3,%4};" :: "l"(p), "r"(a), "r"(b), "r"(c), "r"(d) : "memory");
}
__device__ __forceinline__ void stg64(void* p, uint32_t a, uint32_t b) {
    asm volatile("st.relaxed.gpu.global.v2.u32 [%0], {%1,%2};" :: "l"(p), "r"(a), "r"(b) : "memory");
}
__device__ __forceinline__ void sts128(uint32_t a, uint32_t x, uint32_t y, uint32_t z, uint32_t w) {
    asm volatile("st.shared.v4.u32 [%0], {%1,%2,%3,%4};" :: "r"(a), "r"(x), "r"(y), "r"(z), "r"(w) : "memory");
}
__device__ __forceinline__ void sts32(uint32_t a, uint32_t x) { asm volatile("st.shared.u32 [%0], %1;" :: "r"(a), "r"(x) : "memory"); }
__device__ __forceinline__ float4 lds128f(uint32_t a) {
    float4 v; asm volatile("ld.shared.v4.f32 {%0,%1,%2,%3}, [%4];" : "=f"(v.x), "=f"(v.y), "=f"(v.z), "=f"(v.w) : "r"(a) : "memory"); return v;
}
__device__ __forceinline__ uint32_t lds32(uint32_t a) { uint32_t v; asm volatile("ld.shared.u32 %0, [%1];" : "=r"(v) : "r"(a) : "memory"); return v; }
__device__ __forceinline__ uint32_t nonzero(uint32_t w) { return w == 0u ? 0x8000u : w; }
__device__ __forceinline__ void stg32(void* p, uint32_t a) { asm volatile("st.global.u32 [%0], %1;" :: "l"(p), "r"(a) : "memory"); }
__device__ __forceinline__ uint32_t ldg32_relaxed(const void* p) { uint32_t v; asm volatile("ld.relaxed.gpu.global.u32 %0, [%1];" : "=r"(v) : "l"(p) : "memory"); return v; }
__device__ __forceinline__ void count_hint(int id) {
    if ((threadIdx.x & 31) == 0) asm volatile("red.relaxed.gpu.global.add.u32 [%0], 1;" :: "l"(g_s.cnt[id]) : "memory");
}
__device__ __forceinline__ void count_release(int id) {
    __syncwarp();
    if ((threadIdx.x & 31) == 0) asm volatile("red.release.gpu.global.add.u32 [%0], 1;" :: "l"(g_s.cnt[id]) : "memory");
    __syncwarp();
}
__device__ __forceinline__ void count_wait(int id, unsigned target) {
    uint32_t v; int spins = 0;
    do v = ldg32_relaxed(g_s.cnt[id]); while (__any_sync(0xffffffffu, v != target) && ++spins < SPIN_LIMIT);
    asm volatile("fence.acquire.gpu;" ::: "memory");
}
__device__ __forceinline__ void warp_done(uint32_t bar) {
    __syncwarp();
    asm volatile("{.reg .pred p; setp.eq.u32 p, %1, 0; @p mbarrier.arrive.shared::cta.b64 _, [%0];}" :: "r"(bar), "r"(threadIdx.x & 31) : "memory");
}
__device__ __forceinline__ uint32_t mul_bf16x2(uint32_t a, uint32_t b) { uint32_t r; asm("mul.rn.bf16x2 %0, %1, %2;" : "=r"(r) : "r"(a), "r"(b)); return r; }
__device__ __forceinline__ uint32_t fma_bf16x2(uint32_t a, uint32_t b, uint32_t c) { uint32_t r; asm("fma.rn.bf16x2 %0, %1, %2, %3;" : "=r"(r) : "r"(a), "r"(b), "r"(c)); return r; }
__device__ __forceinline__ uint32_t add_bf16x2(uint32_t a, uint32_t b) { uint32_t r; asm("add.rn.bf16x2 %0, %1, %2;" : "=r"(r) : "r"(a), "r"(b)); return r; }

#define R4(d, o) "+f"(d[o + 0]), "+f"(d[o + 1]), "+f"(d[o + 2]), "+f"(d[o + 3])
#define R8(d, o) R4(d, o), R4(d, o + 4)
#define R32(d) R8(d, 0), R8(d, 8), R8(d, 16), R8(d, 24)
#define D32 "{%0,%1,%2,%3,%4,%5,%6,%7,%8,%9,%10,%11,%12,%13,%14,%15,%16,%17,%18,%19,%20,%21,%22,%23,%24,%25,%26,%27,%28,%29,%30,%31}"
#define D64 "{%0,%1,%2,%3,%4,%5,%6,%7,%8,%9,%10,%11,%12,%13,%14,%15,%16,%17,%18,%19,%20,%21,%22,%23,%24,%25,%26,%27,%28,%29,%30,%31,%32,%33,%34,%35,%36,%37,%38,%39,%40,%41,%42,%43,%44,%45,%46,%47,%48,%49,%50,%51,%52,%53,%54,%55,%56,%57,%58,%59,%60,%61,%62,%63}"

__device__ __forceinline__ void mma_qk_f16(float (&d)[32], uint64_t da, uint64_t db) {
    asm volatile("{.reg .pred p; setp.eq.b32 p, 0, 0; wgmma.mma_async.sync.aligned.m64n64k16.f32.f16.f16 " D32 ", %32, %33, p, 1, 1, 0, 0;}"
                 : R32(d) : "l"(da), "l"(db));
}
__device__ __forceinline__ void mma_qk_bf16(float (&d)[32], uint64_t da, uint64_t db) {
    asm volatile("{.reg .pred p; setp.ne.b32 p, 0, 0; wgmma.mma_async.sync.aligned.m64n64k16.f32.bf16.bf16 " D32 ", %32, %33, p, 1, 1, 0, 0;}"
                 : R32(d) : "l"(da), "l"(db));
}
__device__ __forceinline__ void mma_pv(float (&d)[12], const uint32_t* a, uint64_t db) {
    asm volatile("{.reg .pred p; setp.eq.b32 p, 0, 0; wgmma.mma_async.sync.aligned.m64n24k16.f32.bf16.bf16 {%0,%1,%2,%3,%4,%5,%6,%7,%8,%9,%10,%11}, {%12,%13,%14,%15}, %16, p, 1, 1, 1;}"
                 : R8(d, 0), R4(d, 8) : "r"(a[0]), "r"(a[1]), "r"(a[2]), "r"(a[3]), "l"(db));
}
__device__ __forceinline__ void mma_ss128(float (&d)[64], uint64_t da, uint64_t db) {
    asm volatile("{.reg .pred p; setp.eq.b32 p, 0, 0; wgmma.mma_async.sync.aligned.m64n128k16.f32.bf16.bf16 " D64 ", %64, %65, p, 1, 1, 0, 1;}"
                 : R32(d), R8(d, 32), R8(d, 40), R8(d, 48), R8(d, 56) : "l"(da), "l"(db));
}
__device__ __forceinline__ void stsm4(uint32_t addr, uint32_t a, uint32_t b, uint32_t c, uint32_t d) {
    asm volatile("stmatrix.sync.aligned.m8n8.x4.shared.b16 [%0], {%1,%2,%3,%4};" :: "r"(addr), "r"(a), "r"(b), "r"(c), "r"(d) : "memory");
}
__device__ __forceinline__ void mma_ss8(float (&d)[4], uint64_t da, uint64_t db) {
    asm volatile("{.reg .pred p; setp.eq.b32 p, 0, 0; wgmma.mma_async.sync.aligned.m64n8k16.f32.bf16.bf16 {%0,%1,%2,%3}, %4, %5, p, 1, 1, 0, 1;}"
                 : R4(d, 0) : "l"(da), "l"(db));
}
__device__ __forceinline__ void mma_ss(float (&d)[32], uint64_t da, uint64_t db, int accum) {
    asm volatile("{.reg .pred p; setp.ne.b32 p, %34, 0; wgmma.mma_async.sync.aligned.m64n64k16.f32.bf16.bf16 " D32 ", %32, %33, p, 1, 1, 0, 1;}"
                 : R32(d) : "l"(da), "l"(db), "r"(accum));
}
__device__ __forceinline__ void mma_ss(float (&d)[88], uint64_t da, uint64_t db, int accum) {
    asm volatile("{.reg .pred p; setp.ne.b32 p, %90, 0; wgmma.mma_async.sync.aligned.m64n176k16.f32.bf16.bf16 " "{%0,%1,%2,%3,%4,%5,%6,%7,%8,%9,%10,%11,%12,%13,%14,%15,%16,%17,%18,%19,%20,%21,%22,%23,%24,%25,%26,%27,%28,%29,%30,%31,%32,%33,%34,%35,%36,%37,%38,%39,%40,%41,%42,%43,%44,%45,%46,%47,%48,%49,%50,%51,%52,%53,%54,%55,%56,%57,%58,%59,%60,%61,%62,%63,%64,%65,%66,%67,%68,%69,%70,%71,%72,%73,%74,%75,%76,%77,%78,%79,%80,%81,%82,%83,%84,%85,%86,%87}"
                 ", %88, %89, p, 1, 1, 0, 1;}"
                 : R32(d), R8(d, 32), R8(d, 40), R8(d, 48), R8(d, 56), R8(d, 64), R8(d, 72), R8(d, 80) : "l"(da), "l"(db), "r"(accum));
}

constexpr float EXP_MAGIC = 256.0f + 127.0f + 64.0f - 1.58621f + 0.00390625f;
constexpr uint32_t MUFU_MASK = 0x1111u;
__device__ __forceinline__ uint32_t exp2_pair(float y0, float y1, uint32_t cexp, uint32_t neg1) {
    uint32_t w, m, e, r;
    asm("prmt.b32 %0, %1, %2, 0x6521;" : "=r"(w) : "r"(__float_as_uint(y0)), "r"(__float_as_uint(y1)));
    asm("lop3.b32 %0, %1, 0x007F007F, %2, 0xEA;" : "=r"(m) : "r"(w), "r"(cexp));
    asm("mad.lo.u32 %0, %1, %2, %3;" : "=r"(e) : "r"(m), "r"(neg1), "r"(w));
    asm("fma.rn.bf16x2 %0, %1, %2, %3;" : "=r"(r) : "r"(w), "r"(m), "r"(e));
    return r;
}

struct Params {
    const __nv_bfloat16* x;
    const __nv_bfloat16* wk;
    long long wv_off;
    const __nv_bfloat16* wqp;
    __nv_bfloat16* out;
    uint32_t neg1, pad;
    const __nv_bfloat16* w1p;
    const __nv_bfloat16* w2p;
    CUtensorMap wq, wo, w1, w2;
    const __nv_bfloat16* wop;
};

__device__ __forceinline__ void load_box(uint32_t sb, const CUtensorMap* tm, uint32_t dst, uint32_t bar, uint32_t bytes, int c0, int c1) {
    mbar_expect(sb + SM_MISC + bar * 8, bytes);
    tma2d(sb + dst, tm, c0, c1, sb + SM_MISC + bar * 8);
}
__device__ __forceinline__ void load_wq(uint32_t sb, const Params& P, int gi, int atom) {
    load_box(sb, &P.wq, SM_WQ + atom * 65536 + gi * 16384, MB_WQ + gi, 16384, (blockIdx.x & 3) * 128 + atom * 64, gi * 128);
}
__device__ __forceinline__ void load_wo(uint32_t sb, const Params& P, int kb) { load_box(sb, &P.wo, wo_slot(kb) * SLOT, MB_WO, SLOT, (blockIdx.x & 7) * 64, kb * 64); }
__device__ __forceinline__ void refill_job(uint32_t sb, const Params& P, int gi, int job) {
    const bool w1 = job < 3;
    load_box(sb, w1 ? &P.w1 : &P.wo, (w1 ? 12 + gi + 4 * job : 2 * gi + job - 3) * SLOT, w1 ? MB_W1 + gi : MB_WO, SLOT,
             (blockIdx.x & 7) * (w1 ? 176 : 64) + (w1 ? job * 64 : 0), (w1 ? gi : 2 * gi + job - 1) * 64);
}

__host__ __device__ constexpr int ring_entry(int n) { return n < 32 ? (n & 3) : (n - 32) % 6; }
__host__ __device__ constexpr uint32_t ring_slot(int e) { return e < 4 ? 24 + e : 6 + e; }

template <int KIND> __host__ __device__ constexpr uint64_t b_slots(int first) {
    uint64_t v = 0;
    for (int i = first; i < first + 12; i++) v |= (uint64_t)((KIND == 0 ? wo_slot(i) : KIND == 1 ? w1_slot(i, 0) : w1_slot(i / 3, i % 3)) & 31) << (5 * (i - first));
    return v;
}
template <int KIND, int NACC>
__device__ __forceinline__ void gemm_ss(float (&acc)[NACC], uint32_t sb, int pr TS_ARG) {
    const uint32_t mb = sb + SM_MISC;
    constexpr int NBLK = KIND == 2 ? 22 : 8, N0 = 16 * KIND;
    uint32_t full = mb + (MB_FULL + N0 + pr * NBLK) * 8, empty = mb + MB_NULL * 8, rel = mb + MB_NULL * 8;
    uint32_t e = KIND == 2 ? 4 * pr : 0;
    uint64_t tab = b_slots<KIND>(0);
    uint64_t da = mkdesc(sb + ring_slot(e) * SLOT, 128, 256, 0), db = mkdesc(sb + (b_slots<KIND>(0) & 31) * SLOT, KIND == 1 ? 4 * SLOT : 16, 1024, 1);
#pragma unroll 1
    for (int i = 0; i < NBLK; i++) {
        mbar_wait(full);
        wg_fence();
#pragma unroll
        for (int s = 0; s < 4; s++) mma_ss(acc, da + s * 128, db + s * 128, s ? 1 : i);
        wg_commit();
        const uint32_t prev = empty, prel = rel;
        empty = mb + ((KIND == 0 && pr && i >= 4) ? MB_NULL : MB_EMPTY + e) * 8;
        rel = mb + (MB_REL + i) * 8;
        e = (e == (KIND == 2 ? 5 : 3)) ? 0 : e + 1;
        tab = (KIND == 2 && i == 11) ? b_slots<KIND>(12) : tab >> 5;
        full += 8;
        da = mkdesc(sb + ((KIND == 0 && pr && i >= 3) ? 6 + e : ring_slot(e)) * SLOT, 128, 256, 0);
        db = mkdesc(sb + ((uint32_t)tab & 31) * SLOT, KIND == 1 ? (i < 3 ? 4 * SLOT : SLOT) : 16, 1024, 1);
        wg_wait<1>();
        warp_done(prev);
        if (KIND == 1) warp_done(prel);
    }
    wg_wait<0>();
    fence_regs(acc);
    warp_done(empty);
    if (KIND != 2) warp_done(mb + (MB_REL + 8 - KIND) * 8);
}
__device__ __forceinline__ void ring_feed(uint32_t sb, int e TS_ARG) {
    const uint32_t mb = sb + SM_MISC, dst = sb + ring_slot(e) * SLOT;
    const int lane = threadIdx.x & 31;
    const uint32_t probe = lane * 32 + (lane >> 2) * 4;
    uint32_t use = 0;
#pragma unroll 1
    for (int n = e < 4 ? e : 32 + e; n < 76; use ^= 1) {
        const int job = n < 32 ? n >> 3 : 4 + (n >= 54), ph = job >> 1, i = n < 32 ? n & 7 : n - 32 - (job & 1) * 22;
        const uint4* src = g_x + ph * X_H1 + ((job & 1) * 16 + (blockIdx.x >> 3)) * (ph == 2 ? 88 : 32) * 128 + i * 512;
        const uint32_t full = mb + (MB_FULL + n) * 8;
        const int step = job == 1 ? 8 : n < 32 ? 4 : 6;
        if (n >= 4) {
            if (lane == 0) { mbar_expect(full, SLOT); if (job == 1) mbar_expect(full + 32, SLOT); }
            if (job == 1) mbar_wait(mb + (MB_DONE + 4) * 8);
            TSF(0);
            mbar_wait(mb + ((n == 32 + e && e >= 4) ? MB_REL + 7 : MB_EMPTY + e) * 8, (n == 32 + e && e >= 4) ? 0 : use ^ 1);
            TSF(1);
            mbar_wait(mb + (MB_READY + job) * 8);
            TSF(2);
            if (lane == 0) { bulk_g2s(dst, src, SLOT, full); if (job == 1) bulk_g2s(sb + (6 + e) * SLOT, src + 2048, SLOT, full + 32); }
            __syncwarp();
        }
        mbar_wait(mb + (ph == 0 ? MB_WO : ph == 1 ? MB_W1 + i : MB_W2 + i / 3) * 8);
        warp_done(full);
        if (job == 1) warp_done(full + 32);
        mbar_wait(full);
        TSF(3);
        uint32_t m = 0;
#pragma unroll
        for (int k = 0; k < 8; k++) m = max(m, lds32(dst + k * 1024 + probe));
        if (job == 1) {
            mbar_wait(full + 32);
#pragma unroll
            for (int k = 0; k < 8; k++) m = max(m, lds32(sb + (6 + e) * SLOT + k * 1024 + probe));
        }
        if (m == SENT) asm volatile("red.shared.or.b32 [%0], %1;" :: "r"(mb + MISC_BAD), "r"(1 << job) : "memory");
        TSF(4);
        if (i + step >= (ph == 2 ? 22 : 8)) warp_done(mb + (MB_VALID + job) * 8);
        n += step;
    }
}
__device__ __noinline__ void gemm_slow_impl(float* out, int ntile, const uint4* a, int nst, const __nv_bfloat16* W, int ldw, int kmax, int n0) {
    const int lane = threadIdx.x & 31;
    const unsigned short* w = reinterpret_cast<const unsigned short*>(W);
    for (int j = 0; j < ntile; j++) {
        const uint32_t* p = reinterpret_cast<const uint32_t*>(a) + ((threadIdx.x >> 5) & 3) * 128 + lane;
        const int n = n0 + 8 * j + (lane >> 2);
        float d[4] = {0.f, 0.f, 0.f, 0.f};
        for (int st = 0; st < nst; st++, p += 512) {
            const int k = st * 16 + 2 * (lane & 3);
            uint32_t v0, v1, v2, v3, b0 = 0, b1 = 0; int spins = 0;
            do { v0 = ldg32_relaxed(p); v1 = ldg32_relaxed(p + 64); v2 = ldg32_relaxed(p + 32); v3 = ldg32_relaxed(p + 96); }
            while (__any_sync(0xffffffffu, max(max(v0, v1), max(v2, v3)) == SENT) && ++spins < SPIN_LIMIT);
            if (k < kmax && n < ldw) {
                const unsigned short* q = w + (size_t)k * ldw + n;
                b0 = q[0] | ((uint32_t)q[ldw] << 16); b1 = q[8 * ldw] | ((uint32_t)q[9 * ldw] << 16);
            }
            asm volatile("mma.sync.aligned.m16n8k16.row.col.f32.bf16.bf16.f32 {%0,%1,%2,%3}, {%4,%5,%6,%7}, {%8,%9}, {%0,%1,%2,%3};"
                         : R4(d, 0) : "r"(v0), "r"(v1), "r"(v2), "r"(v3), "r"(b0), "r"(b1));
        }
        *reinterpret_cast<float4*>(out + 4 * j) = make_float4(d[0], d[1], d[2], d[3]);
    }
}
template <int NACC>
__device__ __forceinline__ void gemm_slow(float (&acc)[NACC], const uint4* a, int nst, const __nv_bfloat16* W, int ldw, int kmax, int n0) {
    __align__(16) float tmp[NACC];
    gemm_slow_impl(tmp, NACC / 4, a, nst, W, ldw, kmax, n0);
#pragma unroll
    for (int i = 0; i < NACC; i++) acc[i] = tmp[i];
}
__device__ __forceinline__ bool product_bad(uint32_t sb, int job) {
    mbar_wait(sb + SM_MISC + (MB_VALID + job) * 8);
    bool bad = __any_sync(0xffffffffu, (lds32(sb + SM_MISC + MISC_BAD) >> job) & 1);
    return __builtin_expect(bad, 0);
}
__device__ __forceinline__ void store_tile(uint32_t* p, uint32_t r0k0, uint32_t r8k0, uint32_t r0k8, uint32_t r8k8) {
    stg32(p, r0k0); stg32(p + 32, r0k8); stg32(p + 64, r8k0); stg32(p + 96, r8k8);
}

__device__ __forceinline__ float quad_sum(float v) { v += __shfl_xor_sync(0xffffffffu, v, 1); v += __shfl_xor_sync(0xffffffffu, v, 2); return v; }
__device__ __forceinline__ float reduce4(const float (&st)[4], int lane) {
    const bool u16 = lane & 16, u8 = lane & 8;
    const float a0 = (u16 ? st[2] : st[0]) + __shfl_xor_sync(0xffffffffu, u16 ? st[0] : st[2], 16);
    const float a1 = (u16 ? st[3] : st[1]) + __shfl_xor_sync(0xffffffffu, u16 ? st[1] : st[3], 16);
    float v = (u8 ? a1 : a0) + __shfl_xor_sync(0xffffffffu, u8 ? a0 : a1, 8);
    v += __shfl_xor_sync(0xffffffffu, v, 4); v += __shfl_xor_sync(0xffffffffu, v, 2); v += __shfl_xor_sync(0xffffffffu, v, 1);
    return v;
}
__device__ __forceinline__ float silu2(float h) { float t; asm("tanh.approx.f32 %0, %1;" : "=f"(t) : "f"(h)); return fmaf(h, t, h); }

template <bool SAFE>
__device__ __forceinline__ void attention(const Params& P, uint32_t sb, int warp TS_ARG) {
    const uint32_t mb = sb + SM_MISC;
    const int tid = threadIdx.x, lane = tid & 31, b = blockIdx.x;
    const int wg = warp >> 2, ww = warp & 3, job = 3 - wg + 4 * ww;
    const uint32_t cexp = 0x9F809F80u + (tid >> 12);
    const uint32_t neg1 = P.neg1;
    unsigned cnt = 0;
    if (SAFE && warp == 8) cnt = ldg32_relaxed(g_s.cnt[C_KV]);
#pragma unroll 1
    for (int pass = 0; pass < 2; pass++) {
    float o[12], s[32];
    const uint64_t dq = mkdesc(sb + SM_Q + (pass * 4 + wg) * 2048, 128, 256, 0);
    uint64_t dk = mkdesc(sb + SM_K, 128, 256, 0), dv = mkdesc(sb + SM_V, 128, 32768, 0);
    float m0 = -INFINITY, m1 = -INFINITY;
#pragma unroll
    for (int i = 0; i < 12; i++) o[i] = 0.f;
#pragma unroll
    for (int i = 0; i < 32; i++) s[i] = ((MUFU_MASK >> (i / 2)) & 1) ? 0.f : EXP_MAGIC;
    fence_regs(s); fence_regs(o);
    wg_fence();
    if (SAFE) mma_qk_f16(s, dq, dk + 31 * 128); else mma_qk_bf16(s, dq, dk + 31 * 128);
    wg_commit();
    wg_wait<0>(); fence_regs(s);
#pragma unroll 1
    for (int u = pass ? 3 : (wg == 2) ? 0 : 1; u < (pass ? 8 : 3); u++) {
        int n = 2 * ((((wg == 2) ? 0x22444C31u : 0x22444C40u) >> (4 * u)) & 15);
#pragma unroll 1
        do {
            uint32_t p[16];
            if (SAFE) {
#pragma unroll
                for (int j = 0; j < 16; j++) {
                    if ((MUFU_MASK >> j) & 1) p[j] = pack_bf16(ex2(s[2 * j]), ex2(s[2 * j + 1]));
                    else p[j] = exp2_pair(s[2 * j], s[2 * j + 1], cexp, neg1);
                }
            } else {
                fence_regs(o);
                float x0 = m0, x1 = m1;
#pragma unroll
                for (int j = 0; j < 8; j++) { x0 = fmaxf(x0, fmaxf(s[4 * j], s[4 * j + 1])); x1 = fmaxf(x1, fmaxf(s[4 * j + 2], s[4 * j + 3])); }
                x0 = fmaxf(x0, __shfl_xor_sync(0xffffffffu, x0, 1)); x0 = fmaxf(x0, __shfl_xor_sync(0xffffffffu, x0, 2));
                x1 = fmaxf(x1, __shfl_xor_sync(0xffffffffu, x1, 1)); x1 = fmaxf(x1, __shfl_xor_sync(0xffffffffu, x1, 2));
                const float c0 = ex2(m0 - x0), c1 = ex2(m1 - x1);
                m0 = x0; m1 = x1;
#pragma unroll
                for (int j = 0; j < 3; j++) { o[4 * j] *= c0; o[4 * j + 1] *= c0; o[4 * j + 2] *= c1; o[4 * j + 3] *= c1; }
#pragma unroll
                for (int j = 0; j < 8; j++) {
                    p[2 * j] = pack_bf16(ex2(s[4 * j] - m0), ex2(s[4 * j + 1] - m0));
                    p[2 * j + 1] = pack_bf16(ex2(s[4 * j + 2] - m1), ex2(s[4 * j + 3] - m1));
                }
                fence_regs(o);
            }
            fence_regs(p);
            wg_fence();
            if (SAFE) mma_qk_f16(s, dq, dk); else mma_qk_bf16(s, dq, dk);
#pragma unroll
            for (int j = 0; j < 4; j++) mma_pv(o, p + 4 * j, dv + j * 16);
            wg_commit();
            dk += 128; dv += 64;
            wg_wait<0>(); fence_regs(s);
        } while (--n > 0);
        if (u == 2 || u == 7) {
            fence_regs(o);
            const float i0 = rcp(o[8]), i1 = rcp(o[10]);
            if (u == 7) mbar_wait(mb + MB_MID * 8);
            store_tile(reinterpret_cast<uint32_t*>(g_x + X_O + (((u == 7) * 16 + (b >> 3)) * 32 + (b & 3) * 8 + 2 * wg + (ww >> 1)) * 128 + (((b >> 2) & 1) * 2 + (ww & 1)) * 32) + lane,
                       pack_bf16(o[0] * i0, o[1] * i0), pack_bf16(o[2] * i1, o[3] * i1), pack_bf16(o[4] * i0, o[5] * i0), pack_bf16(o[6] * i1, o[7] * i1));
            if (u == 2) asm volatile("cp.async.bulk.wait_group 0;" ::: "memory");
            else count_hint(C_O + 16 + (b >> 3));
            warp_done(mb + (MB_DONE + (u == 7) * 4) * 8);
            TS(5 + (u == 7));
        } else if (u >= 3) {
            if (u < 6) warp_done(mb + (MB_DONE + u - 2) * 8);
            if (job < (u == 3 ? 1 : 5)) {
                mbar_wait(mb + (MB_DONE + u - 3) * 8);
                if (u == 3) count_release(C_MID);
                else if (lane == 0) refill_job(sb, P, u - 4, job);
            } else if (u == 6) {
                if (job < 9) {
                    mbar_wait(mb + MB_MID * 8);
                    if (lane == 0) {
                        mbar_expect(mb + (MB_FULL + job - 5) * 8, SLOT);
                        bulk_g2s(sb + (19 + job) * SLOT, g_x + X_O + (b >> 3) * 4096 + (job - 5) * 512, SLOT, mb + (MB_FULL + job - 5) * 8);
                    }
                }
            } else if (warp == 7) {
                if (u == 4) cnt = ldg32_relaxed(g_s.cnt[C_MID]);
                if (u == 5) {
                    const unsigned target = lds32(mb + MISC_EPOCH) * NCTA;
                    if (__any_sync(0xffffffffu, cnt != target)) count_wait(C_MID, target);
                    asm volatile("fence.acquire.gpu; fence.proxy.async.global;" ::: "memory");
                    warp_done(mb + MB_MID * 8);
                }
            }
        } else if (u == 1) {
            if (SAFE) mbar_wait(mb + MB_KV * 8);
            TS(17);
            if (lane == 0) {
                if (job < 9) {
                    asm volatile("cp.async.bulk.global.shared::cta.bulk_group [%0], [%1], %2;"
                                 :: "l"(g_x + X_ARM + b * X_SHARE + job * 512), "r"(sb + SM_SENT), "r"(job < 8 ? 8192 : (X_SHARE - 4096) * 16) : "memory");
                    asm volatile("cp.async.bulk.commit_group;" ::: "memory");
                } else if (job < 11) load_wo(sb, P, job - 9);
            }
        } else if (SAFE) {
            if (warp == 8) {
                const unsigned target = lds32(mb + MISC_EPOCH) * NMAIN;
                if (__any_sync(0xffffffffu, cnt != target)) count_wait(C_KV, target);
                if (lane == 0) {
                    asm volatile("fence.acquire.gpu; fence.proxy.async.global;" ::: "memory");
                    mbar_expect(mb + MB_KV * 8, 47104 + 2 * 24576);
                    bulk_g2s(sb + SM_K + 16384, g_s.kv + 1024, 47104, mb + MB_KV * 8);
                    bulk_g2s(sb + SM_V + 8192, g_s.kv + 4096 + 512, 24576, mb + MB_KV * 8);
                    bulk_g2s(sb + SM_V + 32768 + 8192, g_s.kv + 6144 + 512, 24576, mb + MB_KV * 8);
                }
            }
        }
        __syncwarp();
    }
    }
}

__device__ __forceinline__ int kv_slot(int idx) {
    const int t = (idx & 63) >> 1, c = 2 * (blockIdx.x >> 2) + (idx & 1), hg = blockIdx.x & 3;
    return hg < 2 ? ((t + 31) & 31) * 128 + (c >> 3) * 16 + (hg & 1) * 8 + (c & 7) : 4096 + (hg & 1) * 2048 + t * 64 + c;
}

__device__ __noinline__ void helper_cta(const Params& P, uint8_t* smem) {
    const int tid = threadIdx.x, b = blockIdx.x, hi = b - NMAIN;
    const unsigned epoch = g_s.epoch[b] + 1;
    float* red = reinterpret_cast<float*>(smem);
    if (tid < 32) count_wait(C_KV, epoch * NMAIN);
    __syncthreads();
    if (tid == 480) {
        for (int i = 0; i < 8; i++) asm volatile("cp.async.bulk.prefetch.L2.global [%0], %1;" :: "l"((const char*)P.wop + hi * 131072 + i * 16384), "r"(16384) : "memory");
        for (int i = 0; i < 43; i++) asm volatile("cp.async.bulk.prefetch.L2.global [%0], %1;" :: "l"((const char*)P.w2p + hi * 352256 + i * 8192), "r"(8192) : "memory");
    }
    if (tid < 344) {
        const int cg = tid % 43, rp = tid / 43;
        const uint4* src = reinterpret_cast<const uint4*>(P.w1p + (size_t)rp * 64 * FF + (hi * 43 + cg) * 8);
        float s[8] = {0, 0, 0, 0, 0, 0, 0, 0};
#pragma unroll 8
        for (int r = 0; r < 64; r++) {
            uint4 v = __ldg(src + r * (FF / 8));
            s[0] += bf_lo(v.x); s[1] += bf_hi(v.x); s[2] += bf_lo(v.y); s[3] += bf_hi(v.y);
            s[4] += bf_lo(v.z); s[5] += bf_hi(v.z); s[6] += bf_lo(v.w); s[7] += bf_hi(v.w);
        }
        float* part = red + (rp * 43 + cg) * 8;
#pragma unroll
        for (int i = 0; i < 8; i++) part[i] = s[i];
    }
    __syncthreads();
    if (tid < 344) {
        float s = 0.f;
#pragma unroll
        for (int rp = 0; rp < 8; rp++) s += red[rp * 344 + tid];
        g_s.cs[hi * 344 + tid] = s;
    } else if (hi == 3 && tid < 344 + 64) g_s.cs[FF + tid - 344] = 0.f;
    __syncthreads();
    if (tid < 32) count_release(C_MID);
    if (tid == 0) g_s.epoch[b] = epoch;
}

__global__ void __launch_bounds__(512, 1) fused_kernel(const __grid_constant__ Params P) {
    extern __shared__ __align__(1024) uint8_t smem[];
    const uint32_t sb = (uint32_t)__cvta_generic_to_shared(smem);
    const uint32_t mb = sb + SM_MISC;
    const int tid = threadIdx.x, lane = tid & 31, b = blockIdx.x;
    if (b >= NMAIN) { helper_cta(P, smem); return; }
    const int tg = b >> 2, hg = b & 3;
    const int warp = __shfl_sync(0xffffffffu, tid >> 5, 0);

    uint4 xv[4][2];
    unsigned epoch = 0;
    {
        const int r = (tid >> 5) * 4;
        const uint4* src = reinterpret_cast<const uint4*>(P.x + (size_t)((r & 31) + tg * 32 + (r >> 5) * 1024) * D) + lane;
#pragma unroll
        for (int i = 0; i < 4; i++) { xv[i][0] = ldg_relaxed(src + i * 64); xv[i][1] = ldg_relaxed(src + i * 64 + 32); }
    }
    const uint4 wkv = ldg_relaxed(reinterpret_cast<const uint4*>(reinterpret_cast<const char*>(P.wk) + (hg < 2 ? 0 : P.wv_off)) + tid * 2 + (hg & 1));
    const int wg = warp >> 2, ww = warp & 3, g = lane >> 2, t4 = lane & 3, t128 = tid & 127;
    if (lane == 0) {
        if (warp < 4) {
            mbar_init(mb + (MB_WQ + warp) * 8, 2);
            asm volatile("fence.mbarrier_init.release.cluster;" ::: "memory");
            load_wq(sb, P, warp, 0);
            load_wq(sb, P, warp, 1);
        } else if (warp < 7) {
            asm volatile("prefetch.tensormap [%0];" :: "l"(&P.wo + (warp - 4)) : "memory");
        } else if (warp == 7) {
            asm volatile("ld.relaxed.gpu.global.u32 %0, [%1];" : "=r"(epoch) : "l"(g_s.epoch + b) : "memory");
        } else if (warp == 8) {
            sts128(mb + MISC_NRM, 0, 0, 0, 0);

        }
    }
    __syncwarp();
    TS(16);
    float dlt;
    {
        float st[4];
#pragma unroll
        for (int i = 0; i < 4; i++) {
            const uint32_t s = add_bf16x2(add_bf16x2(add_bf16x2(xv[i][0].x, xv[i][0].y), add_bf16x2(xv[i][0].z, xv[i][0].w)),
                                          add_bf16x2(add_bf16x2(xv[i][1].x, xv[i][1].y), add_bf16x2(xv[i][1].z, xv[i][1].w)));
            st[i] = bf_lo(s) + bf_hi(s);
        }
        TS(13);
        const float tot = reduce4(st, lane) * (-1.0f / D);
        const uint32_t nmr = pack_bf16(tot, tot);
        dlt = bf_lo(nmr) - tot;
        const uint32_t xa = sb + SM_XN + (lane >> 3) * 8192 + warp * 512;
#pragma unroll
        for (int i = 0; i < 4; i++) {
            const uint32_t nm = __shfl_sync(0xffffffffu, nmr, i * 8);
            const uint32_t addr = xa + i * 128 + (((lane & 7) ^ ((warp & 1) * 4 + i)) << 4);
#pragma unroll
            for (int c = 0; c < 2; c++) {
                xv[i][c].x = add_bf16x2(xv[i][c].x, nm); xv[i][c].y = add_bf16x2(xv[i][c].y, nm);
                xv[i][c].z = add_bf16x2(xv[i][c].z, nm); xv[i][c].w = add_bf16x2(xv[i][c].w, nm);
                sts128(addr + c * 32768, xv[i][c].x, xv[i][c].y, xv[i][c].z, xv[i][c].w);
            }
        }
    }
    sts128(sb + SM_WKV + tid * 16, wkv.x, wkv.y, wkv.z, wkv.w);
    fence_async_smem();
    TS(0);
    __syncthreads();
    auto variances = [&]() {
        float st[4];
#pragma unroll
        for (int i = 0; i < 4; i++) {
            float v = 0.f;
#pragma unroll
            for (int c = 0; c < 2; c++) {
                const uint32_t a = fma_bf16x2(xv[i][c].x, xv[i][c].x, mul_bf16x2(xv[i][c].y, xv[i][c].y));
                const uint32_t d = fma_bf16x2(xv[i][c].z, xv[i][c].z, mul_bf16x2(xv[i][c].w, xv[i][c].w));
                v += (bf_lo(a) + bf_hi(a)) + (bf_lo(d) + bf_hi(d));
            }
            st[i] = v;
        }
        const float vs = reduce4(st, lane), dl = dlt;
        if ((lane & 7) == 0) sts32(sb + SM_RSTD + (warp * 4 + (lane >> 3)) * 4, __float_as_uint(rsqrtf(fmaxf(vs * (1.0f / D) - dl * dl, 0.f) + 1e-5f)));
    };
    float kv[4] = {0.f, 0.f, 0.f, 0.f};
    if (wg == 2) {
        fence_regs(kv);
        const uint64_t da = mkdesc(sb + SM_XN, 16, 1024, 1), db = mkdesc(sb + SM_WKV, 128, 16, 0);
        wg_fence();
#pragma unroll
        for (int s = 0; s < 32; s++) mma_ss8(kv, da + (s >> 2) * 512 + (s & 3) * 2, db + s * 16);
        wg_commit();
        variances();
        wg_wait<0>(); fence_regs(kv);
    } else {
        variances();
        if (tid == 7 * 32) { sts32(mb + MISC_EPOCH, epoch + 1); sts32(mb + MISC_BAD, 0); g_s.epoch[b] = epoch + 1; }
    }
    __syncthreads();
    constexpr float QSCALE = 0.25f * 1.4426950408889634f;
    float qa[64];
    const uint32_t qbase = sb + SM_Q + (ww >> 1) * 8192 + (ww & 1) * 512 + lane * 16;
    if (wg == 0) {
#pragma unroll
        for (int i = 0; i < 64; i++) qa[i] = 0.f;
        fence_regs(qa);
        const uint64_t da = mkdesc(sb + SM_XN, 16, 1024, 1), db = mkdesc(sb + SM_WQ, 65536, 1024, 1);
#pragma unroll 1
        for (int i = 0; i < 4; i++) {
            mbar_wait(mb + (MB_WQ + i) * 8);
            wg_fence();
#pragma unroll
            for (int s = 0; s < 8; s++) mma_ss128(qa, da + (i * 2 + (s >> 2)) * 512 + (s & 3) * 2, db + (i * 8 + s) * 128);
            wg_commit();
        }
        const float rs0 = __uint_as_float(lds32(sb + SM_RSTD + (ww * 16 + g) * 4)) * QSCALE, rs1 = __uint_as_float(lds32(sb + SM_RSTD + (ww * 16 + g + 8) * 4)) * QSCALE;
        wg_wait<0>();
        fence_regs(qa);
        bar_arrive(6, 256);
        bar_sync(5, 256);
        TS(1);
        uint32_t nm = 0;
#pragma unroll
        for (int h = 0; h < 8; h++) {
#pragma unroll
            for (int i = 0; i < 8; i++) qa[8 * h + i] *= (i & 2) ? rs1 : rs0;
            stsm4(qbase + h * 1024, pack_f16(qa[8 * h], qa[8 * h + 1]), pack_f16(qa[8 * h + 4], qa[8 * h + 5]), pack_f16(qa[8 * h + 2], qa[8 * h + 3]), pack_f16(qa[8 * h + 6], qa[8 * h + 7]));
            const float n0 = qa[8 * h] * qa[8 * h] + qa[8 * h + 1] * qa[8 * h + 1] + qa[8 * h + 4] * qa[8 * h + 4] + qa[8 * h + 5] * qa[8 * h + 5];
            const float n1 = qa[8 * h + 2] * qa[8 * h + 2] + qa[8 * h + 3] * qa[8 * h + 3] + qa[8 * h + 6] * qa[8 * h + 6] + qa[8 * h + 7] * qa[8 * h + 7];
            nm = max(nm, max(__float_as_uint(n0), __float_as_uint(n1)));
        }
        nm = __reduce_max_sync(0xffffffffu, __float_as_uint(quad_sum(__uint_as_float(nm))));
        if (lane == 0) asm volatile("red.shared.max.u32 [%0], %1;" :: "r"(mb + MISC_NRM), "r"(nm) : "memory");
    } else if (wg == 1) {
        if (lane == 0) {
            if (ww == 0) {
#pragma unroll
                for (uint32_t i = 4; i < 36; i++) mbar_init(mb + i * 8, bar_count(i));
            } else if (ww == 1) {
#pragma unroll
                for (uint32_t i = 36; i < 68; i++) mbar_init(mb + i * 8, bar_count(i));
            } else {
#pragma unroll
                for (uint32_t i = 0; i < 32; i++) mbar_init(mb + (ww * 32 + 4 + i) * 8, 2);
            }
        }
        __syncwarp();
#pragma unroll
        for (int i = 0; i < 4; i++) sts128(sb + SM_SENT + (i * 128 + t128) * 16, SENT, SENT, SENT, SENT);
        bar_sync(5, 256);
#pragma unroll
        for (int i = 0; i < 16; i++) sts128(sb + SM_V + 65536 + (i * 128 + t128) * 16, 0x3F803F80u, 0x3F803F80u, 0x3F803F80u, 0x3F803F80u);
    } else if (wg == 2) {
        const float rs0 = __uint_as_float(lds32(sb + SM_RSTD + (ww * 16 + g) * 4)), rs1 = __uint_as_float(lds32(sb + SM_RSTD + (ww * 16 + g + 8) * 4));
        kv[0] *= rs0; kv[1] *= rs0; kv[2] *= rs1; kv[3] *= rs1;
        float2* kt = reinterpret_cast<float2*>(smem + SM_KTMP);
        kt[(ww * 16 + g) * 4 + t4] = make_float2(kv[0], kv[1]); kt[(ww * 16 + g + 8) * 4 + t4] = make_float2(kv[2], kv[3]);
        float n0 = kv[0] * kv[0] + kv[1] * kv[1], n1 = kv[2] * kv[2] + kv[3] * kv[3];
        n0 += __shfl_xor_sync(0xffffffffu, n0, 1); n1 += __shfl_xor_sync(0xffffffffu, n1, 1);
        n0 += __shfl_xor_sync(0xffffffffu, n0, 2); n1 += __shfl_xor_sync(0xffffffffu, n1, 2);
        const uint32_t nm = __reduce_max_sync(0xffffffffu, max(__float_as_uint(n0), __float_as_uint(n1)));
        if (lane == 0) sts32(sb + SM_WNRM + ww * 4, nm | 1u);
        bar_sync(2, 128);
        const uint32_t ra = sb + SM_KTMP + ((t128 & 1) * 32 + ((t128 & 63) >> 1)) * 32;
        const float4 c0 = lds128f(ra), c1 = lds128f(ra + 16);
        const int kvoff = kv_slot(tid);
        if (ww < 2) {
            if (hg < 2) {
                float4 p0 = lds128f(ra - 32), p1 = lds128f(ra - 16);
                if (t128 < 2) { p0 = make_float4(0.f, 0.f, 0.f, 0.f); p1 = p0; }
                stg128(g_s.kv + kvoff, nonzero(pack_f16(c0.x - p0.x, c0.y - p0.y)), pack_f16(c0.z - p0.z, c0.w - p0.w), pack_f16(c1.x - p1.x, c1.y - p1.y), pack_f16(c1.z - p1.z, c1.w - p1.w));
            } else {
                stg128(g_s.kv + kvoff, nonzero(pack_bf16(c0.x, c0.y)), pack_bf16(c0.z, c0.w), pack_bf16(c1.x, c1.y), pack_bf16(c1.z, c1.w));
            }
            if (t128 < 2) { const float4 w = lds128f(sb + SM_WNRM); stg128(g_s.nrm + b * 2 + t128, __float_as_uint(w.x), __float_as_uint(w.y), __float_as_uint(w.z), __float_as_uint(w.w)); }
            count_hint(C_KVH);
        } else if (hg < 2) {
            stg128(g_s.kplain + kvoff, pack_bf16(c0.x, c0.y), pack_bf16(c0.z, c0.w), pack_bf16(c1.x, c1.y), pack_bf16(c1.z, c1.w));
        }
        TS(1);
        bar_sync(2, 128);
        if (ww == 3) count_release(C_KV);
    } else {
        uint4 kc[18];
        auto src = [&](int i) { return i < 8 ? g_s.kv + i * 128 : i < 12 ? g_s.kv + 4096 + (i - 8) * 128 : i < 16 ? g_s.kv + 6144 + (i - 12) * 128 : i == 16 ? g_s.kv + 31 * 128 : g_s.nrm + t128; };
        count_wait(C_KVH, lds32(mb + MISC_EPOCH) * (NMAIN * 2));
        TS(1);
        int spins = 0;
        while (true) {
#pragma unroll
            for (int i = 0; i < 18; i++) kc[i] = ldg_relaxed(src(i) + t128);
            uint32_t mn = 1;
#pragma unroll
            for (int i = 0; i < 18; i++) mn = min(mn, kc[i].x);
            if (!__any_sync(0xffffffffu, mn == 0u) || ++spins >= SPIN_LIMIT) break;
        }
        uint32_t nm = max(max(kc[17].x, kc[17].y), max(kc[17].z, kc[17].w));
        nm = max(nm, __shfl_xor_sync(0xffffffffu, nm, 4)); nm = max(nm, __shfl_xor_sync(0xffffffffu, nm, 8)); nm = max(nm, __shfl_xor_sync(0xffffffffu, nm, 16));
        if (lane < 4) asm volatile("red.shared.max.u32 [%0], %1;" :: "r"(mb + MISC_NRM + 4 + min(lane, 2) * 4), "r"(nm) : "memory");
        TS(2);
        bar_sync(6, 256);
#pragma unroll
        for (int i = 0; i < 17; i++) sts128(sb + (uint32_t)(src(i) - g_s.kv + t128) * 16 + ((i >= 8 && i < 16) ? SM_V - 65536 : 0), kc[i].x, kc[i].y, kc[i].z, kc[i].w);
    }
    fence_async_smem();
    TS(3);
    __syncthreads();
    const float4 nr = lds128f(mb + MISC_NRM);
    const bool safe = __all_sync(0xffffffffu, (nr.x * (nr.y + nr.z) <= 3500.0f) && (nr.x <= 65536.0f) && (nr.y + nr.z <= 65536.0f) && (nr.w <= 1e24f));
    TS(4);

    if (__builtin_expect(safe, 1)) {
        attention<true>(P, sb, warp TS_PASS);
    } else {
        if (wg == 0) {
#pragma unroll
            for (int h = 0; h < 8; h++)
                stsm4(qbase + h * 1024, pack_bf16(qa[8 * h], qa[8 * h + 1]), pack_bf16(qa[8 * h + 4], qa[8 * h + 5]), pack_bf16(qa[8 * h + 2], qa[8 * h + 3]), pack_bf16(qa[8 * h + 6], qa[8 * h + 7]));
            fence_async_smem();
        } else if (warp == 15) {
            count_wait(C_KV, lds32(mb + MISC_EPOCH) * NMAIN);
            if (lane == 0) {
                asm volatile("fence.proxy.async;" ::: "memory");
                mbar_expect(mb + MB_KV * 8, 131072);
                bulk_g2s(sb + SM_K, g_s.kplain, 65536, mb + MB_KV * 8);
                bulk_g2s(sb + SM_V, g_s.kv + 4096, 65536, mb + MB_KV * 8);
            }
            __syncwarp();
        }
        __syncthreads();
        mbar_wait(mb + MB_KV * 8);
        attention<false>(P, sb, warp TS_PASS);
    }

    const int j = b & 7;
    if (wg == 1 || wg == 2) {
        if (warp == 8) {
            epoch = lds32(mb + MISC_EPOCH);
#pragma unroll 1
            for (int job = 1; job < 6; job++) {
                count_wait(C_O + 32 * (job >> 1) + (job & 1) * 16 + (b >> 3), epoch * (job == 1 ? 128 : 32));
                asm volatile("fence.proxy.async.global;" ::: "memory");
                warp_done(mb + (MB_READY + job) * 8);
                TS(18 + job);
            }
        } else if (warp == 9) {
#pragma unroll
            for (int i = 0; i < 2; i++) {
                if (lane < 22) {
                    const uint4 v = ldg_relaxed(reinterpret_cast<const uint4*>(g_s.cs + j * 176) + i * 22 + lane);
                    sts128(mb + MISC_CS + (i * 22 + lane) * 16, v.x, v.y, v.z, v.w);
                }
                stg128(g_s.kv + kv_slot(i * 32 + lane), 0u, 0u, 0u, 0u);
            }
            warp_done(mb + MB_CS * 8);
            if (lane < 2) stg128(g_s.nrm + b * 2 + lane, 0u, 0u, 0u, 0u);
        } else {
            if (wg == 2) {
#pragma unroll 1
                for (int i = 7 + ww; i < 46; i += 2) {
                    const bool w1 = i < 24;
                    const int n = w1 ? i : i - 24, kb = n / 3, a = n - 3 * kb;
                    mbar_wait(mb + (w1 ? (i < 12 ? MB_DONE + 4 : MB_REL + 8) : MB_REL + kb) * 8);
                    if (i == 12 || i == 13) mbar_wait(mb + (MB_VALID + 1) * 8);
                    if (lane == 0) load_box(sb, w1 ? &P.w1 : &P.w2, w1_slot(kb, a) * SLOT, (w1 ? MB_W1 : MB_W2) + kb, SLOT, w1 ? j * 176 + a * 64 : j * 64, (w1 ? kb : n) * 64);
                    __syncwarp();
                }
            }
            ring_feed(sb, wg == 1 ? ww : ww + 2 TS_PASS);
        }
    } else {
        const int pr = (wg == 0), mt = 16 * pr + (b >> 3);
        uint32_t* const hp = reinterpret_cast<uint32_t*>(g_x + X_H1 + (mt * 32 + j * 4) * 128 + ww * 32) + lane;
        {
            uint32_t hk[16];
            const uint32_t* xp = reinterpret_cast<const uint32_t*>(P.x + (size_t)(mt * 64 + ww * 16 + g) * D + j * 64 + t4 * 2);
#pragma unroll
            for (int k = 0; k < 8; k++) { hk[2 * k] = __ldg(xp + k * 4); hk[2 * k + 1] = __ldg(xp + k * 4 + 8 * (D / 2)); }
            float acc[32];
            gemm_ss<0>(acc, sb, pr TS_PASS);
            if (product_bad(sb, pr)) gemm_slow(acc, g_x + X_O + mt * 32 * 128, 32, P.wop, D, D, j * 64);
            TS(7);
#pragma unroll
            for (int i = 0; i < 16; i++) hk[i] = pack_bf16(acc[2 * i] + bf_lo(hk[i]), acc[2 * i + 1] + bf_hi(hk[i]));
#pragma unroll
            for (int k = 0; k < 4; k++) store_tile(hp + k * 512, hk[4 * k], hk[4 * k + 1], hk[4 * k + 2], hk[4 * k + 3]);
            count_hint(C_H1 + mt);
            TS(8);
            float st[4] = {0.f, 0.f, 0.f, 0.f};
#pragma unroll
            for (int i = 0; i < 16; i++) {
                const float lo = bf_lo(hk[i]), hi = bf_hi(hk[i]);
                st[2 * (i & 1)] += lo + hi;
                st[2 * (i & 1) + 1] = fmaf(lo, lo, fmaf(hi, hi, st[2 * (i & 1) + 1]));
            }
#pragma unroll
            for (int o = 1; o < 4; o <<= 1)
#pragma unroll
                for (int i = 0; i < 4; i++) st[i] += __shfl_xor_sync(0xffffffffu, st[i], o);
            if (t4 == 0) stg128(g_x + X_ST + (mt * 8 + j) * 32 + ww * 8 + g, __float_as_uint(st[0]), __float_as_uint(st[1]), __float_as_uint(st[2]), __float_as_uint(st[3]));
        }
        {
            float acc[88];
            const uint4* sp = g_x + X_ST + (mt * 8 + t4) * 32 + ww * 8 + g;
            mbar_wait(mb + (MB_FULL + 16 + pr * 8) * 8);
            uint4 u0 = ldg_relaxed(sp), u1 = ldg_relaxed(sp + 128);
            gemm_ss<1>(acc, sb, pr TS_PASS);
            if (product_bad(sb, 2 + pr)) gemm_slow(acc, g_x + X_H1 + mt * 32 * 128, 32, P.w1p, FF, D, j * 176);
            TS(9);
            int spins = 0;
            while (__builtin_expect(__any_sync(0xffffffffu, max(u0.x, u1.x) == SENT), 0) && ++spins < SPIN_LIMIT) { u0 = ldg_relaxed(sp); u1 = ldg_relaxed(sp + 128); }
            float st[4] = {__uint_as_float(u0.x) + __uint_as_float(u1.x), __uint_as_float(u0.y) + __uint_as_float(u1.y),
                           __uint_as_float(u0.z) + __uint_as_float(u1.z), __uint_as_float(u0.w) + __uint_as_float(u1.w)};
#pragma unroll
            for (int o = 1; o < 4; o <<= 1)
#pragma unroll
                for (int k = 0; k < 4; k++) st[k] += __shfl_xor_sync(0xffffffffu, st[k], o);
            float nmean[2], hrstd[2];
#pragma unroll
            for (int k = 0; k < 2; k++) {
                nmean[k] = st[2 * k] * (-1.0f / D);
                hrstd[k] = 0.5f * rsqrtf(fmaxf(fmaf(-nmean[k], nmean[k], st[2 * k + 1] * (1.0f / D)), 0.f) + 1e-5f);
                nmean[k] *= hrstd[k];
            }
            mbar_wait(mb + MB_CS * 8);
            uint32_t* hb = reinterpret_cast<uint32_t*>(g_x + X_H2 + (mt * 88 + j * 11) * 128 + ww * 32) + lane;
#pragma unroll
            for (int i = 0; i < 22; i++) {
                float2 cs;
                asm volatile("ld.shared.v2.f32 {%0,%1}, [%2];" : "=f"(cs.x), "=f"(cs.y) : "r"(mb + MISC_CS + i * 32 + t4 * 8));
                const float* z = acc + 4 * i;
                uint32_t* p = hb + (i >> 1) * 512 + (i & 1) * 32;
                stg32(p, pack_bf16(silu2(fmaf(hrstd[0], z[0], nmean[0] * cs.x)), silu2(fmaf(hrstd[0], z[1], nmean[0] * cs.y))));
                stg32(p + 64, pack_bf16(silu2(fmaf(hrstd[1], z[2], nmean[1] * cs.x)), silu2(fmaf(hrstd[1], z[3], nmean[1] * cs.y))));
            }
            count_hint(C_H2 + mt);
            TS(10);
        }
        {
            uint32_t hk[16];
#pragma unroll
            for (int i = 0; i < 16; i++) hk[i] = ldg32_relaxed(hp + (i >> 2) * 512 + ((i & 1) * 2 + ((i >> 1) & 1)) * 32);
            float acc[32];
            gemm_ss<2>(acc, sb, pr TS_PASS);
            if (product_bad(sb, 4 + pr)) gemm_slow(acc, g_x + X_H2 + mt * 88 * 128, 88, P.w2p, D, FF, j * 64);
            TS(11);
#pragma unroll
            for (int i = 0; i < 16; i++) hk[i] = pack_bf16(acc[2 * i] + bf_lo(hk[i]), acc[2 * i + 1] + bf_hi(hk[i]));
#pragma unroll
            for (int h = 0; h < 4; h++) {
                const uint32_t* v = hk + (h >> 1) * 8 + (h & 1);
                uint32_t v0 = v[0], v1 = v[2], v2 = v[4], v3 = v[6];
                const bool o1 = t4 & 1, o2 = t4 & 2;
                uint32_t a = __shfl_xor_sync(0xffffffffu, o1 ? v0 : v1, 1), c = __shfl_xor_sync(0xffffffffu, o1 ? v2 : v3, 1);
                if (o1) { v0 = a; v2 = c; } else { v1 = a; v3 = c; }
                a = __shfl_xor_sync(0xffffffffu, o2 ? v0 : v2, 2); c = __shfl_xor_sync(0xffffffffu, o2 ? v1 : v3, 2);
                if (o2) { v0 = a; v1 = c; } else { v2 = a; v3 = c; }
                *reinterpret_cast<uint4*>(P.out + (size_t)(mt * 64 + ww * 16 + g + 8 * (h & 1)) * D + j * 64 + (h >> 1) * 32 + t4 * 8) = make_uint4(v0, v1, v2, v3);
            }
        }
    }
    TS(12);
}

typedef CUresult (*EncodeFn)(CUtensorMap*, CUtensorMapDataType, cuuint32_t, void*, const cuuint64_t*, const cuuint64_t*, const cuuint32_t*,
                             const cuuint32_t*, CUtensorMapInterleave, CUtensorMapSwizzle, CUtensorMapL2promotion, CUtensorMapFloatOOBfill);

void encode2d(EncodeFn fn, CUtensorMap* tm, const void* ptr, int rows, int cols, int box_rows, int box_cols, CUtensorMapSwizzle sw) {
    cuuint64_t dims[2] = {(cuuint64_t)cols, (cuuint64_t)rows};
    cuuint64_t strides[1] = {(cuuint64_t)cols * 2};
    cuuint32_t box[2] = {(cuuint32_t)box_cols, (cuuint32_t)box_rows};
    cuuint32_t es[2] = {1, 1};
    fn(tm, CU_TENSOR_MAP_DATA_TYPE_BFLOAT16, 2, const_cast<void*>(ptr), dims, strides, box, es, CU_TENSOR_MAP_INTERLEAVE_NONE, sw,
       CU_TENSOR_MAP_L2_PROMOTION_L2_128B, CU_TENSOR_MAP_FLOAT_OOB_FILL_NONE);
}

}

extern "C" void kernel_launch(void* const* d_in, const int* in_sizes, int n_in, void* d_out, int out_size) {
    (void)in_sizes; (void)n_in; (void)out_size;
    void* fnp = nullptr;
    cudaDriverEntryPointQueryResult qr;
    cudaGetDriverEntryPoint("cuTensorMapEncodeTiled", &fnp, cudaEnableDefault, &qr);
    EncodeFn fn = (EncodeFn)fnp;
    Params P;
    encode2d(fn, &P.wq, d_in[1], D, D, 128, 64, CU_TENSOR_MAP_SWIZZLE_128B);
    P.wk = (const __nv_bfloat16*)d_in[2];
    P.wv_off = (const char*)d_in[3] - (const char*)d_in[2];
    encode2d(fn, &P.wo, d_in[4], D, D, 64, 64, CU_TENSOR_MAP_SWIZZLE_128B);
    encode2d(fn, &P.w1, d_in[6], D, FF, 64, 64, CU_TENSOR_MAP_SWIZZLE_128B);
    encode2d(fn, &P.w2, d_in[7], FF, D, 64, 64, CU_TENSOR_MAP_SWIZZLE_128B);
    P.x = (const __nv_bfloat16*)d_in[0];
    P.w1p = (const __nv_bfloat16*)d_in[6];
    P.w2p = (const __nv_bfloat16*)d_in[7];
    P.wop = (const __nv_bfloat16*)d_in[4];
    P.wqp = (const __nv_bfloat16*)d_in[1];
    P.out = (__nv_bfloat16*)d_out;
    P.neg1 = 0xFFFFFFFFu; P.pad = 0;
    cudaFuncSetAttribute(fused_kernel, cudaFuncAttributeMaxDynamicSharedMemorySize, SMEM_BYTES);
    fused_kernel<<<NCTA, 512, SMEM_BYTES>>>(P);
}
```

```cpp
#include <cuda_runtime.h>
#include <cuda_bf16.h>
#include <cuda.h>
#include <stdint.h>

namespace {

constexpr int D = 512, FF = 1376;
constexpr int NMAIN = 128, NHELP = 4, NCTA = NMAIN + NHELP;
constexpr uint32_t SENT = 0xFFFFFFFFu;
constexpr int SPIN_LIMIT = 1 << 22;

constexpr uint32_t KB = 1024, SLOT = 8192;
constexpr uint32_t SM_XN = 0;
constexpr uint32_t SM_WQ = 64 * KB;
constexpr uint32_t SM_WKV = 192 * KB;
constexpr uint32_t SM_K = 0;
constexpr uint32_t SM_Q = 64 * KB;
constexpr uint32_t SM_V = 96 * KB;
constexpr uint32_t SM_MISC = 224 * KB;
constexpr uint32_t SMEM_BYTES = 227 * KB;
constexpr uint32_t SM_KTMP = 200 * KB;
constexpr uint32_t SM_RSTD = 202 * KB;
constexpr uint32_t SM_WNRM = 203 * KB;
constexpr uint32_t SM_SENT = 208 * KB;
constexpr uint32_t MB_WQ = 0;
constexpr uint32_t MB_CS = 4;
constexpr uint32_t MB_DONE = 5;
constexpr uint32_t MB_EMPTY = 10;
constexpr uint32_t MB_W1 = 16;
constexpr uint32_t MB_W2 = 24;
constexpr uint32_t MB_WO = 32;
constexpr uint32_t MB_REL = 33;
constexpr uint32_t MB_KV = 42;
constexpr uint32_t MB_MID = 43;
constexpr uint32_t MB_READY = 43;
constexpr uint32_t MB_FULL = 49;
constexpr uint32_t MB_NULL = 125;
__host__ __device__ constexpr uint32_t bar_count(uint32_t i) {
    return i >= MB_FULL + 16 ? 2 : i >= MB_KV ? 1 : i >= MB_WO ? 8 : i == MB_W2 + 7 ? 1 : i >= MB_W1 ? 3 : i >= MB_EMPTY ? 4 : i >= MB_DONE ? 16 : 1;
}
constexpr uint32_t MISC_NRM = 1056;
constexpr uint32_t MISC_EPOCH = 1072;
constexpr uint32_t MISC_TS = 1088;
constexpr uint32_t MISC_CS = 1344;

__host__ __device__ constexpr uint32_t wo_slot(int kb) { return kb < 2 ? 10 + kb : kb - 2; }
__host__ __device__ constexpr uint32_t w1_slot(int kb, int a) { return kb < 4 ? 12 + kb + 4 * a : (kb == 4 ? 6 : kb == 7 ? 9 : 3 * kb - 15) + a; }

struct alignas(128) Small {
    unsigned epoch[160];
    unsigned cnt[100][32];
    float cs[1440];
    uint4 nrm[NMAIN * 2];
    uint4 kv[8192];
    uint4 kplain[4096];
};
__device__ Small g_s;
constexpr int C_KVH = 0, C_KV = 1, C_MID = 2, C_O = 3, C_H1 = 35, C_H2 = 67;
constexpr int X_O = 0, X_H1 = 32 * 32 * 128, X_H2 = 2 * X_H1, X_ST = X_H2 + 32 * 88 * 128, X_END = X_ST + 32 * 8 * 32;
constexpr int X_ARM = 16 * 32 * 128, X_SHARE = (X_END - X_ARM) / NMAIN;
__device__ uint4 g_x[X_END];
#define TS(i) do {} while (0)
#define TSF(k)

#define TS_ARG
#define TS_PASS

__device__ __forceinline__ void mbar_init(uint32_t bar, int cnt) { asm volatile("mbarrier.init.shared::cta.b64 [%0], %1;" :: "r"(bar), "r"(cnt) : "memory"); }
__device__ __forceinline__ void mbar_expect(uint32_t bar, uint32_t bytes) { asm volatile("mbarrier.arrive.expect_tx.shared::cta.b64 _, [%0], %1;" :: "r"(bar), "r"(bytes) : "memory"); }
__device__ __forceinline__ void mbar_arrive(uint32_t bar) { asm volatile("mbarrier.arrive.shared::cta.b64 _, [%0];" :: "r"(bar) : "memory"); }
__device__ __forceinline__ bool mbar_try(uint32_t bar, uint32_t parity) {
    uint32_t done;
    asm volatile("{.reg .pred p; mbarrier.try_wait.parity.shared::cta.b64 p, [%1], %2; selp.u32 %0, 1, 0, p;}" : "=r"(done) : "r"(bar), "r"(parity) : "memory");
    return __all_sync(0xffffffffu, done);
}
__device__ __forceinline__ void mbar_wait(uint32_t bar, uint32_t parity = 0) {
    if (__builtin_expect(!mbar_try(bar, parity), 0)) {
        int spins = 0;
        while (!mbar_try(bar, parity) && ++spins < (SPIN_LIMIT >> 6)) {}
    }
}
__device__ __forceinline__ void tma2d(uint32_t dst, const CUtensorMap* tm, int c0, int c1, uint32_t bar) {
    asm volatile("cp.async.bulk.tensor.2d.shared::cluster.global.mbarrier::complete_tx::bytes [%0], [%1, {%3, %4}], [%2];"
                 :: "r"(dst), "l"(tm), "r"(bar), "r"(c0), "r"(c1) : "memory");
}
__device__ __forceinline__ void bulk_g2s(uint32_t dst, const void* src, uint32_t bytes, uint32_t bar) {
    asm volatile("cp.async.bulk.shared::cluster.global.mbarrier::complete_tx::bytes [%0], [%1], %2, [%3];" :: "r"(dst), "l"(src), "r"(bytes), "r"(bar) : "memory");
}
__device__ __forceinline__ void fence_async_smem() { asm volatile("fence.proxy.async.shared::cta;" ::: "memory"); }
__device__ __forceinline__ void bar_sync(int id, int n) { asm volatile("bar.sync %0, %1;" :: "r"(id), "r"(n) : "memory"); }
__device__ __forceinline__ void bar_arrive(int id, int n) { asm volatile("bar.arrive %0, %1;" :: "r"(id), "r"(n) : "memory"); }
__device__ __forceinline__ void wg_fence() { asm volatile("wgmma.fence.sync.aligned;" ::: "memory"); }
__device__ __forceinline__ void wg_commit() { asm volatile("wgmma.commit_group.sync.aligned;" ::: "memory"); }
template <int N> __device__ __forceinline__ void wg_wait() { asm volatile("wgmma.wait_group.sync.aligned %0;" :: "n"(N) : "memory"); }
template <int N> __device__ __forceinline__ void fence_regs(float (&d)[N]) {
#pragma unroll
    for (int i = 0; i < N; i++) asm volatile("" : "+f"(d[i]) :: "memory");
}
template <int N> __device__ __forceinline__ void fence_regs(uint32_t (&d)[N]) {
#pragma unroll
    for (int i = 0; i < N; i++) asm volatile("" : "+r"(d[i]) :: "memory");
}
__device__ __forceinline__ uint64_t mkdesc(uint32_t addr, uint32_t lbo, uint32_t sbo, uint32_t swz) {
    return (uint64_t)(((addr & 0x3FFFF) >> 4) | ((lbo >> 4) << 16)) | ((uint64_t)((sbo >> 4) | (swz << 30)) << 32);
}
__device__ __forceinline__ float ex2(float x) { float y; asm("ex2.approx.ftz.f32 %0, %1;" : "=f"(y) : "f"(x)); return y; }
__device__ __forceinline__ float rcp(float x) { float y; asm("rcp.approx.ftz.f32 %0, %1;" : "=f"(y) : "f"(x)); return y; }
__device__ __forceinline__ uint32_t pack_bf16(float lo, float hi) { uint32_t r; asm("cvt.rn.bf16x2.f32 %0, %1, %2;" : "=r"(r) : "f"(hi), "f"(lo)); return r; }
__device__ __forceinline__ uint32_t pack_f16(float lo, float hi) { uint32_t r; asm("cvt.rn.f16x2.f32 %0, %1, %2;" : "=r"(r) : "f"(hi), "f"(lo)); return r; }
__device__ __forceinline__ float bf_lo(uint32_t v) { return __uint_as_float(v << 16); }
__device__ __forceinline__ float bf_hi(uint32_t v) { return __uint_as_float(v & 0xFFFF0000u); }
__device__ __forceinline__ uint4 ldg_relaxed(const uint4* p) {
    uint4 v; asm volatile("ld.relaxed.gpu.global.v4.u32 {%0,%1,%2,%3}, [%4];" : "=r"(v.x), "=r"(v.y), "=r"(v.z), "=r"(v.w) : "l"(p) : "memory"); return v;
}
__device__ __forceinline__ void stg128(void* p, uint32_t a, uint32_t b, uint32_t c, uint32_t d) {
    asm volatile("st.relaxed.gpu.global.v4.u32 [%0], {%1,%2,%3,%4};" :: "l"(p), "r"(a), "r"(b), "r"(c), "r"(d) : "memory");
}
__device__ __forceinline__ void stg64(void* p, uint32_t a, uint32_t b) {
    asm volatile("st.relaxed.gpu.global.v2.u32 [%0], {%1,%2};" :: "l"(p), "r"(a), "r"(b) : "memory");
}
__device__ __forceinline__ void sts128(uint32_t a, uint32_t x, uint32_t y, uint32_t z, uint32_t w) {
    asm volatile("st.shared.v4.u32 [%0], {%1,%2,%3,%4};" :: "r"(a), "r"(x), "r"(y), "r"(z), "r"(w) : "memory");
}
__device__ __forceinline__ void sts32(uint32_t a, uint32_t x) { asm volatile("st.shared.u32 [%0], %1;" :: "r"(a), "r"(x) : "memory"); }
__device__ __forceinline__ float4 lds128f(uint32_t a) {
    float4 v; asm volatile("ld.shared.v4.f32 {%0,%1,%2,%3}, [%4];" : "=f"(v.x), "=f"(v.y), "=f"(v.z), "=f"(v.w) : "r"(a) : "memory"); return v;
}
__device__ __forceinline__ uint32_t lds32(uint32_t a) { uint32_t v; asm volatile("ld.shared.u32 %0, [%1];" : "=r"(v) : "r"(a) : "memory"); return v; }
__device__ __forceinline__ uint32_t nonzero(uint32_t w) { return w == 0u ? 0x8000u : w; }
__device__ __forceinline__ void stg32(void* p, uint32_t a) { asm volatile("st.global.u32 [%0], %1;" :: "l"(p), "r"(a) : "memory"); }
__device__ __forceinline__ uint32_t ldg32_relaxed(const void* p) { uint32_t v; asm volatile("ld.relaxed.gpu.global.u32 %0, [%1];" : "=r"(v) : "l"(p) : "memory"); return v; }
__device__ __forceinline__ void count_hint(int id) {
    if ((threadIdx.x & 31) == 0) asm volatile("red.relaxed.gpu.global.add.u32 [%0], 1;" :: "l"(g_s.cnt[id]) : "memory");
}
__device__ __forceinline__ void count_release(int id) {
    __syncwarp();
    if ((threadIdx.x & 31) == 0) asm volatile("red.release.gpu.global.add.u32 [%0], 1;" :: "l"(g_s.cnt[id]) : "memory");
    __syncwarp();
}
__device__ __forceinline__ void count_wait(int id, unsigned target) {
    uint32_t v; int spins = 0;
    do v = ldg32_relaxed(g_s.cnt[id]); while (__any_sync(0xffffffffu, v != target) && ++spins < SPIN_LIMIT);
    asm volatile("fence.acquire.gpu;" ::: "memory");
}
__device__ __forceinline__ void warp_done(uint32_t bar) {
    __syncwarp();
    asm volatile("{.reg .pred p; setp.eq.u32 p, %1, 0; @p mbarrier.arrive.shared::cta.b64 _, [%0];}" :: "r"(bar), "r"(threadIdx.x & 31) : "memory");
}
__device__ __forceinline__ uint32_t mul_bf16x2(uint32_t a, uint32_t b) { uint32_t r; asm("mul.rn.bf16x2 %0, %1, %2;" : "=r"(r) : "r"(a), "r"(b)); return r; }
__device__ __forceinline__ uint32_t fma_bf16x2(uint32_t a, uint32_t b, uint32_t c) { uint32_t r; asm("fma.rn.bf16x2 %0, %1, %2, %3;" : "=r"(r) : "r"(a), "r"(b), "r"(c)); return r; }
__device__ __forceinline__ uint32_t add_bf16x2(uint32_t a, uint32_t b) { uint32_t r; asm("add.rn.bf16x2 %0, %1, %2;" : "=r"(r) : "r"(a), "r"(b)); return r; }

#define R4(d, o) "+f"(d[o + 0]), "+f"(d[o + 1]), "+f"(d[o + 2]), "+f"(d[o + 3])
#define R8(d, o) R4(d, o), R4(d, o + 4)
#define R32(d) R8(d, 0), R8(d, 8), R8(d, 16), R8(d, 24)
#define D32 "{%0,%1,%2,%3,%4,%5,%6,%7,%8,%9,%10,%11,%12,%13,%14,%15,%16,%17,%18,%19,%20,%21,%22,%23,%24,%25,%26,%27,%28,%29,%30,%31}"
#define D64 "{%0,%1,%2,%3,%4,%5,%6,%7,%8,%9,%10,%11,%12,%13,%14,%15,%16,%17,%18,%19,%20,%21,%22,%23,%24,%25,%26,%27,%28,%29,%30,%31,%32,%33,%34,%35,%36,%37,%38,%39,%40,%41,%42,%43,%44,%45,%46,%47,%48,%49,%50,%51,%52,%53,%54,%55,%56,%57,%58,%59,%60,%61,%62,%63}"

__device__ __forceinline__ void mma_qk_f16(float (&d)[32], uint64_t da, uint64_t db) {
    asm volatile("{.reg .pred p; setp.eq.b32 p, 0, 0; wgmma.mma_async.sync.aligned.m64n64k16.f32.f16.f16 " D32 ", %32, %33, p, 1, 1, 0, 0;}"
                 : R32(d) : "l"(da), "l"(db));
}
__device__ __forceinline__ void mma_qk_bf16(float (&d)[32], uint64_t da, uint64_t db) {
    asm volatile("{.reg .pred p; setp.ne.b32 p, 0, 0; wgmma.mma_async.sync.aligned.m64n64k16.f32.bf16.bf16 " D32 ", %32, %33, p, 1, 1, 0, 0;}"
                 : R32(d) : "l"(da), "l"(db));
}
__device__ __forceinline__ void mma_pv(float (&d)[12], const uint32_t* a, uint64_t db) {
    asm volatile("{.reg .pred p; setp.eq.b32 p, 0, 0; wgmma.mma_async.sync.aligned.m64n24k16.f32.bf16.bf16 {%0,%1,%2,%3,%4,%5,%6,%7,%8,%9,%10,%11}, {%12,%13,%14,%15}, %16, p, 1, 1, 1;}"
                 : R8(d, 0), R4(d, 8) : "r"(a[0]), "r"(a[1]), "r"(a[2]), "r"(a[3]), "l"(db));
}
__device__ __forceinline__ void mma_ss128(float (&d)[64], uint64_t da, uint64_t db) {
    asm volatile("{.reg .pred p; setp.eq.b32 p, 0, 0; wgmma.mma_async.sync.aligned.m64n128k16.f32.bf16.bf16 " D64 ", %64, %65, p, 1, 1, 0, 1;}"
                 : R32(d), R8(d, 32), R8(d, 40), R8(d, 48), R8(d, 56) : "l"(da), "l"(db));
}
__device__ __forceinline__ void stsm4(uint32_t addr, uint32_t a, uint32_t b, uint32_t c, uint32_t d) {
    asm volatile("stmatrix.sync.aligned.m8n8.x4.shared.b16 [%0], {%1,%2,%3,%4};" :: "r"(addr), "r"(a), "r"(b), "r"(c), "r"(d) : "memory");
}
__device__ __forceinline__ void mma_ss8(float (&d)[4], uint64_t da, uint64_t db) {
    asm volatile("{.reg .pred p; setp.eq.b32 p, 0, 0; wgmma.mma_async.sync.aligned.m64n8k16.f32.bf16.bf16 {%0,%1,%2,%3}, %4, %5, p, 1, 1, 0, 1;}"
                 : R4(d, 0) : "l"(da), "l"(db));
}
__device__ __forceinline__ void mma_ss(float (&d)[32], uint64_t da, uint64_t db, int accum) {
    asm volatile("{.reg .pred p; setp.ne.b32 p, %34, 0; wgmma.mma_async.sync.aligned.m64n64k16.f32.bf16.bf16 " D32 ", %32, %33, p, 1, 1, 0, 1;}"
                 : R32(d) : "l"(da), "l"(db), "r"(accum));
}
__device__ __forceinline__ void mma_ss(float (&d)[88], uint64_t da, uint64_t db, int accum) {
    asm volatile("{.reg .pred p; setp.ne.b32 p, %90, 0; wgmma.mma_async.sync.aligned.m64n176k16.f32.bf16.bf16 " "{%0,%1,%2,%3,%4,%5,%6,%7,%8,%9,%10,%11,%12,%13,%14,%15,%16,%17,%18,%19,%20,%21,%22,%23,%24,%25,%26,%27,%28,%29,%30,%31,%32,%33,%34,%35,%36,%37,%38,%39,%40,%41,%42,%43,%44,%45,%46,%47,%48,%49,%50,%51,%52,%53,%54,%55,%56,%57,%58,%59,%60,%61,%62,%63,%64,%65,%66,%67,%68,%69,%70,%71,%72,%73,%74,%75,%76,%77,%78,%79,%80,%81,%82,%83,%84,%85,%86,%87}"
                 ", %88, %89, p, 1, 1, 0, 1;}"
                 : R32(d), R8(d, 32), R8(d, 40), R8(d, 48), R8(d, 56), R8(d, 64), R8(d, 72), R8(d, 80) : "l"(da), "l"(db), "r"(accum));
}

constexpr float EXP_MAGIC = 256.0f + 127.0f + 64.0f - 1.58621f + 0.00390625f;
constexpr uint32_t MUFU_MASK = 0x1111u;
__device__ __forceinline__ uint32_t exp2_pair(float y0, float y1, uint32_t cexp, uint32_t neg1) {
    uint32_t w, m, e, r;
    asm("prmt.b32 %0, %1, %2, 0x6521;" : "=r"(w) : "r"(__float_as_uint(y0)), "r"(__float_as_uint(y1)));
    asm("lop3.b32 %0, %1, 0x007F007F, %2, 0xEA;" : "=r"(m) : "r"(w), "r"(cexp));
    asm("mad.lo.u32 %0, %1, %2, %3;" : "=r"(e) : "r"(m), "r"(neg1), "r"(w));
    asm("fma.rn.bf16x2 %0, %1, %2, %3;" : "=r"(r) : "r"(w), "r"(m), "r"(e));
    return r;
}

struct Params {
    const __nv_bfloat16* x;
    const __nv_bfloat16* wk;
    long long wv_off;
    const __nv_bfloat16* wqp;
    __nv_bfloat16* out;
    uint32_t neg1, pad;
    const __nv_bfloat16* w1p;
    const __nv_bfloat16* w2p;
    CUtensorMap wq, wo, w1, w2;
    const __nv_bfloat16* wop;
};

__device__ __forceinline__ void load_box(uint32_t sb, const CUtensorMap* tm, uint32_t dst, uint32_t bar, uint32_t bytes, int c0, int c1) {
    mbar_expect(sb + SM_MISC + bar * 8, bytes);
    tma2d(sb + dst, tm, c0, c1, sb + SM_MISC + bar * 8);
}
__device__ __forceinline__ void load_wq(uint32_t sb, const Params& P, int gi, int atom) {
    load_box(sb, &P.wq, SM_WQ + atom * 65536 + gi * 16384, MB_WQ + gi, 16384, (blockIdx.x & 3) * 128 + atom * 64, gi * 128);
}
__device__ __forceinline__ void load_wo(uint32_t sb, const Params& P, int kb) { load_box(sb, &P.wo, wo_slot(kb) * SLOT, MB_WO, SLOT, (blockIdx.x & 7) * 64, kb * 64); }
__device__ __forceinline__ void refill_job(uint32_t sb, const Params& P, int gi, int job) {
    const bool w1 = job < 3;
    load_box(sb, w1 ? &P.w1 : &P.wo, (w1 ? 12 + gi + 4 * job : 2 * gi + job - 3) * SLOT, w1 ? MB_W1 + gi : MB_WO, SLOT,
             (blockIdx.x & 7) * (w1 ? 176 : 64) + (w1 ? job * 64 : 0), (w1 ? gi : 2 * gi + job - 1) * 64);
}

__host__ __device__ constexpr int ring_entry(int n) { return n < 32 ? (n & 3) : (n - 32) % 6; }
__host__ __device__ constexpr uint32_t ring_slot(int e) { return e < 4 ? 24 + e : 6 + e; }

template <int KIND> __host__ __device__ constexpr uint64_t b_slots(int first) {
    uint64_t v = 0;
    for (int i = first; i < first + 12; i++) v |= (uint64_t)((KIND == 0 ? wo_slot(i) : KIND == 1 ? w1_slot(i, 0) : w1_slot(i / 3, i % 3)) & 31) << (5 * (i - first));
    return v;
}
template <int KIND, int NACC>
__device__ __forceinline__ bool gemm_ss(float (&acc)[NACC], uint32_t sb, int pr TS_ARG) {
    const uint32_t mb = sb + SM_MISC;
    constexpr int NBLK = KIND == 2 ? 22 : 8, N0 = 16 * KIND;
    uint32_t full = mb + (MB_FULL + N0 + pr * NBLK) * 8, empty = mb + MB_NULL * 8, rel = mb + MB_NULL * 8;
    uint32_t e = KIND == 2 ? 4 * pr : 0;
    const uint32_t lane = threadIdx.x & 31, probe = ((threadIdx.x >> 5) & 3) * 512 + (lane >> 4) * 2048 + (lane & 15) * 32 + (lane >> 2) * 4;
    uint32_t m = 0, m0 = 0, m1 = 0;
    uint64_t tab = b_slots<KIND>(0);
    uint64_t da = mkdesc(sb + ring_slot(e) * SLOT, 128, 256, 0), db = mkdesc(sb + (b_slots<KIND>(0) & 31) * SLOT, KIND == 1 ? 4 * SLOT : 16, 1024, 1);
#pragma unroll 1
    for (int i = 0; i < NBLK; i++) {
        mbar_wait(full);
        wg_fence();
#pragma unroll
        for (int s = 0; s < 4; s++) mma_ss(acc, da + s * 128, db + s * 128, s ? 1 : i);
        wg_commit();
        m = max(m, max(m0, m1));
        m0 = lds32((((uint32_t)da & 0x3FFF) << 4) + probe); m1 = lds32((((uint32_t)da & 0x3FFF) << 4) + probe + 4096);
        const uint32_t prev = empty, prel = rel;
        empty = mb + ((KIND == 0 && pr && i >= 4) ? MB_NULL : MB_EMPTY + e) * 8;
        rel = mb + (MB_REL + i) * 8;
        e = (e == (KIND == 2 ? 5 : 3)) ? 0 : e + 1;
        tab = (KIND == 2 && i == 11) ? b_slots<KIND>(12) : tab >> 5;
        full += 8;
        da = mkdesc(sb + ((KIND == 0 && pr && i >= 3) ? 6 + e : ring_slot(e)) * SLOT, 128, 256, 0);
        db = mkdesc(sb + ((uint32_t)tab & 31) * SLOT, KIND == 1 ? (i < 3 ? 4 * SLOT : SLOT) : 16, 1024, 1);
        wg_wait<1>();
        warp_done(prev);
        if (KIND == 1) warp_done(prel);
    }
    bool bad = __any_sync(0xffffffffu, max(m, max(m0, m1)) == SENT);
    wg_wait<0>();
    fence_regs(acc);
    warp_done(empty);
    if (KIND != 2) warp_done(mb + (MB_REL + 8 - KIND) * 8);
    return __builtin_expect(bad, 0);
}
__device__ __forceinline__ void ring_feed(uint32_t sb, int e TS_ARG) {
    const uint32_t mb = sb + SM_MISC, dst = sb + ring_slot(e) * SLOT, empty = mb + (MB_EMPTY + e) * 8;
    const bool lead = (threadIdx.x & 31) == 0;
    const uint4* base = g_x + (blockIdx.x >> 3) * 4096 + e * 512;
    uint32_t par = 0;
    auto fetch = [&](int n, const uint4* src) {
        const uint32_t full = mb + (MB_FULL + n) * 8;
        if (lead) mbar_expect(full, SLOT);
        mbar_wait(empty, par); par ^= 1;
        if (lead) bulk_g2s(dst, src, SLOT, full);
        __syncwarp();
    };
    if (e < 4) {
        fetch(4 + e, base + 2048);
        if (lead) mbar_expect(mb + (MB_FULL + 12 + e) * 8, SLOT);
        mbar_wait(mb + (MB_DONE + 4) * 8);
        mbar_wait(mb + (MB_READY + 1) * 8);
        if (lead) bulk_g2s(sb + (6 + e) * SLOT, base + 65536 + 2048, SLOT, mb + (MB_FULL + 12 + e) * 8);
        fetch(8 + e, base + 65536);
#pragma unroll 1
        for (int h = 0; h < 2; h++) {
            mbar_wait(mb + (MB_READY + 2 + h) * 8);
            fetch(16 + 8 * h + e, base + X_H1 + h * 65536);
            fetch(20 + 8 * h + e, base + X_H1 + h * 65536 + 2048);
        }
    } else {
        mbar_wait(mb + (MB_REL + 7) * 8);
        par = 1;
    }
    const uint4* src = g_x + X_H2 + (blockIdx.x >> 3) * 88 * 128 + e * 512;
    mbar_wait(mb + (MB_READY + 4) * 8);
#pragma unroll 1
    for (int n = e; n < 44; n += 6, src += 6 * 512) {
        if (n >= 22 && n < 28) { mbar_wait(mb + (MB_READY + 5) * 8); src += 16 * 88 * 128 - 22 * 512; }
        fetch(32 + n, src);
    }
}
__device__ __noinline__ void gemm_slow_impl(float* out, int ntile, const uint4* a, int nst, const __nv_bfloat16* W, int ldw, int kmax, int n0) {
    const int lane = threadIdx.x & 31;
    const unsigned short* w = reinterpret_cast<const unsigned short*>(W);
    for (int j = 0; j < ntile; j++) {
        const uint32_t* p = reinterpret_cast<const uint32_t*>(a) + ((threadIdx.x >> 5) & 3) * 128 + lane;
        const int n = n0 + 8 * j + (lane >> 2);
        float d[4] = {0.f, 0.f, 0.f, 0.f};
        for (int st = 0; st < nst; st++, p += 512) {
            const int k = st * 16 + 2 * (lane & 3);
            uint32_t v0, v1, v2, v3, b0 = 0, b1 = 0; int spins = 0;
            do { v0 = ldg32_relaxed(p); v1 = ldg32_relaxed(p + 64); v2 = ldg32_relaxed(p + 32); v3 = ldg32_relaxed(p + 96); }
            while (__any_sync(0xffffffffu, max(max(v0, v1), max(v2, v3)) == SENT) && ++spins < SPIN_LIMIT);
            if (k < kmax && n < ldw) {
                const unsigned short* q = w + (size_t)k * ldw + n;
                b0 = q[0] | ((uint32_t)q[ldw] << 16); b1 = q[8 * ldw] | ((uint32_t)q[9 * ldw] << 16);
            }
            asm volatile("mma.sync.aligned.m16n8k16.row.col.f32.bf16.bf16.f32 {%0,%1,%2,%3}, {%4,%5,%6,%7}, {%8,%9}, {%0,%1,%2,%3};"
                         : R4(d, 0) : "r"(v0), "r"(v1), "r"(v2), "r"(v3), "r"(b0), "r"(b1));
        }
        *reinterpret_cast<float4*>(out + 4 * j) = make_float4(d[0], d[1], d[2], d[3]);
    }
}
template <int NACC>
__device__ __forceinline__ void gemm_slow(float (&acc)[NACC], const uint4* a, int nst, const __nv_bfloat16* W, int ldw, int kmax, int n0) {
    __align__(16) float tmp[NACC];
    gemm_slow_impl(tmp, NACC / 4, a, nst, W, ldw, kmax, n0);
#pragma unroll
    for (int i = 0; i < NACC; i++) acc[i] = tmp[i];
}
__device__ __forceinline__ void store_tile(uint32_t* p, uint32_t r0k0, uint32_t r8k0, uint32_t r0k8, uint32_t r8k8) {
    stg32(p, r0k0); stg32(p + 32, r0k8); stg32(p + 64, r8k0); stg32(p + 96, r8k8);
}

__device__ __forceinline__ float quad_sum(float v) { v += __shfl_xor_sync(0xffffffffu, v, 1); v += __shfl_xor_sync(0xffffffffu, v, 2); return v; }
__device__ __forceinline__ float reduce4(const float (&st)[4], int lane) {
    const bool u16 = lane & 16, u8 = lane & 8;
    const float a0 = (u16 ? st[2] : st[0]) + __shfl_xor_sync(0xffffffffu, u16 ? st[0] : st[2], 16);
    const float a1 = (u16 ? st[3] : st[1]) + __shfl_xor_sync(0xffffffffu, u16 ? st[1] : st[3], 16);
    float v = (u8 ? a1 : a0) + __shfl_xor_sync(0xffffffffu, u8 ? a0 : a1, 8);
    v += __shfl_xor_sync(0xffffffffu, v, 4); v += __shfl_xor_sync(0xffffffffu, v, 2); v += __shfl_xor_sync(0xffffffffu, v, 1);
    return v;
}
__device__ __forceinline__ float silu2(float h) { float t; asm("tanh.approx.f32 %0, %1;" : "=f"(t) : "f"(h)); return fmaf(h, t, h); }

template <bool SAFE>
__device__ __forceinline__ void attention(const Params& P, uint32_t sb, int warp TS_ARG) {
    const uint32_t mb = sb + SM_MISC;
    const int tid = threadIdx.x, lane = tid & 31, b = blockIdx.x;
    const int wg = warp >> 2, ww = warp & 3, job = 3 - wg + 4 * ww;
    const uint32_t cexp = 0x9F809F80u + (tid >> 12);
    const uint32_t neg1 = P.neg1;
    unsigned cnt = 0;
    if (SAFE && warp == 8) cnt = ldg32_relaxed(g_s.cnt[C_KV]);
#pragma unroll 1
    for (int pass = 0; pass < 2; pass++) {
    float o[12], s[32];
    const uint64_t dq = mkdesc(sb + SM_Q + (pass * 4 + wg) * 2048, 128, 256, 0);
    uint64_t dk = mkdesc(sb + SM_K, 128, 256, 0), dv = mkdesc(sb + SM_V, 128, 32768, 0);
    float m0 = -INFINITY, m1 = -INFINITY;
#pragma unroll
    for (int i = 0; i < 12; i++) o[i] = 0.f;
#pragma unroll
    for (int i = 0; i < 32; i++) s[i] = ((MUFU_MASK >> (i / 2)) & 1) ? 0.f : EXP_MAGIC;
    fence_regs(s); fence_regs(o);
    wg_fence();
    if (SAFE) mma_qk_f16(s, dq, dk + 31 * 128); else mma_qk_bf16(s, dq, dk + 31 * 128);
    wg_commit();
    wg_wait<0>(); fence_regs(s);
#pragma unroll 1
    for (int u = pass ? 3 : (wg == 2) ? 0 : 1; u < (pass ? 8 : 3); u++) {
        int n = 2 * ((((wg == 2) ? 0x22444C31u : 0x22444C40u) >> (4 * u)) & 15);
#pragma unroll 1
        do {
            uint32_t p[16];
            if (SAFE) {
#pragma unroll
                for (int j = 0; j < 16; j++) {
                    if ((MUFU_MASK >> j) & 1) p[j] = pack_bf16(ex2(s[2 * j]), ex2(s[2 * j + 1]));
                    else p[j] = exp2_pair(s[2 * j], s[2 * j + 1], cexp, neg1);
                }
            } else {
                fence_regs(o);
                float x0 = m0, x1 = m1;
#pragma unroll
                for (int j = 0; j < 8; j++) { x0 = fmaxf(x0, fmaxf(s[4 * j], s[4 * j + 1])); x1 = fmaxf(x1, fmaxf(s[4 * j + 2], s[4 * j + 3])); }
                x0 = fmaxf(x0, __shfl_xor_sync(0xffffffffu, x0, 1)); x0 = fmaxf(x0, __shfl_xor_sync(0xffffffffu, x0, 2));
                x1 = fmaxf(x1, __shfl_xor_sync(0xffffffffu, x1, 1)); x1 = fmaxf(x1, __shfl_xor_sync(0xffffffffu, x1, 2));
                const float c0 = ex2(m0 - x0), c1 = ex2(m1 - x1);
                m0 = x0; m1 = x1;
#pragma unroll
                for (int j = 0; j < 3; j++) { o[4 * j] *= c0; o[4 * j + 1] *= c0; o[4 * j + 2] *= c1; o[4 * j + 3] *= c1; }
#pragma unroll
                for (int j = 0; j < 8; j++) {
                    p[2 * j] = pack_bf16(ex2(s[4 * j] - m0), ex2(s[4 * j + 1] - m0));
                    p[2 * j + 1] = pack_bf16(ex2(s[4 * j + 2] - m1), ex2(s[4 * j + 3] - m1));
                }
                fence_regs(o);
            }
            fence_regs(p);
            wg_fence();
            if (SAFE) mma_qk_f16(s, dq, dk); else mma_qk_bf16(s, dq, dk);
#pragma unroll
            for (int j = 0; j < 4; j++) mma_pv(o, p + 4 * j, dv + j * 16);
            wg_commit();
            dk += 128; dv += 64;
            wg_wait<0>(); fence_regs(s);
        } while (--n > 0);
        if (u == 2 || u == 7) {
            fence_regs(o);
            const float i0 = rcp(o[8]), i1 = rcp(o[10]);
            if (u == 7) mbar_wait(mb + MB_MID * 8);
            store_tile(reinterpret_cast<uint32_t*>(g_x + X_O + (((u == 7) * 16 + (b >> 3)) * 32 + (b & 3) * 8 + 2 * wg + (ww >> 1)) * 128 + (((b >> 2) & 1) * 2 + (ww & 1)) * 32) + lane,
                       pack_bf16(o[0] * i0, o[1] * i0), pack_bf16(o[2] * i1, o[3] * i1), pack_bf16(o[4] * i0, o[5] * i0), pack_bf16(o[6] * i1, o[7] * i1));
            if (u == 2) asm volatile("cp.async.bulk.wait_group 0;" ::: "memory");
            else count_hint(C_O + 16 + (b >> 3));
            warp_done(mb + (MB_DONE + (u == 7) * 4) * 8);
            TS(5 + (u == 7));
        } else if (u >= 3) {
            if (u < 6) warp_done(mb + (MB_DONE + u - 2) * 8);
            if (job < (u == 3 ? 1 : 5)) {
                mbar_wait(mb + (MB_DONE + u - 3) * 8);
                if (u == 3) count_release(C_MID);
                else if (lane == 0) refill_job(sb, P, u - 4, job);
            } else if (u == 6) {
                if (job < 9) {
                    mbar_wait(mb + MB_MID * 8);
                    if (lane == 0) {
                        mbar_expect(mb + (MB_FULL + job - 5) * 8, SLOT);
                        bulk_g2s(sb + (19 + job) * SLOT, g_x + X_O + (b >> 3) * 4096 + (job - 5) * 512, SLOT, mb + (MB_FULL + job - 5) * 8);
                    }
                }
            } else if (warp == 7) {
                if (u == 4) cnt = ldg32_relaxed(g_s.cnt[C_MID]);
                if (u == 5) {
                    const unsigned target = lds32(mb + MISC_EPOCH) * NCTA;
                    if (__any_sync(0xffffffffu, cnt != target)) count_wait(C_MID, target);
                    asm volatile("fence.acquire.gpu; fence.proxy.async.global;" ::: "memory");
                    warp_done(mb + MB_MID * 8);
                }
            }
        } else if (u == 1) {
            if (SAFE) mbar_wait(mb + MB_KV * 8);
            TS(17);
            if (lane == 0) {
                if (job < 9) {
                    asm volatile("cp.async.bulk.global.shared::cta.bulk_group [%0], [%1], %2;"
                                 :: "l"(g_x + X_ARM + b * X_SHARE + job * 512), "r"(sb + SM_SENT), "r"(job < 8 ? 8192 : (X_SHARE - 4096) * 16) : "memory");
                    asm volatile("cp.async.bulk.commit_group;" ::: "memory");
                } else if (job < 11) load_wo(sb, P, job - 9);
            }
        } else if (SAFE) {
            if (warp == 8) {
                const unsigned target = lds32(mb + MISC_EPOCH) * NMAIN;
                if (__any_sync(0xffffffffu, cnt != target)) count_wait(C_KV, target);
                if (lane == 0) {
                    asm volatile("fence.acquire.gpu; fence.proxy.async.global;" ::: "memory");
                    mbar_expect(mb + MB_KV * 8, 47104 + 2 * 24576);
                    bulk_g2s(sb + SM_K + 16384, g_s.kv + 1024, 47104, mb + MB_KV * 8);
                    bulk_g2s(sb + SM_V + 8192, g_s.kv + 4096 + 512, 24576, mb + MB_KV * 8);
                    bulk_g2s(sb + SM_V + 32768 + 8192, g_s.kv + 6144 + 512, 24576, mb + MB_KV * 8);
                }
            }
        }
        __syncwarp();
    }
    }
}

__device__ __forceinline__ int kv_slot(int idx) {
    const int t = (idx & 63) >> 1, c = 2 * (blockIdx.x >> 2) + (idx & 1), hg = blockIdx.x & 3;
    return hg < 2 ? ((t + 31) & 31) * 128 + (c >> 3) * 16 + (hg & 1) * 8 + (c & 7) : 4096 + (hg & 1) * 2048 + t * 64 + c;
}

__device__ __noinline__ void helper_cta(const Params& P, uint8_t* smem) {
    const int tid = threadIdx.x, b = blockIdx.x, hi = b - NMAIN;
    const unsigned epoch = g_s.epoch[b] + 1;
    float* red = reinterpret_cast<float*>(smem);
    if (tid < 32) count_wait(C_KV, epoch * NMAIN);
    __syncthreads();
    if (tid == 480) {
        for (int i = 0; i < 8; i++) asm volatile("cp.async.bulk.prefetch.L2.global [%0], %1;" :: "l"((const char*)P.wop + hi * 131072 + i * 16384), "r"(16384) : "memory");
        for (int i = 0; i < 43; i++) asm volatile("cp.async.bulk.prefetch.L2.global [%0], %1;" :: "l"((const char*)P.w2p + hi * 352256 + i * 8192), "r"(8192) : "memory");
    }
    if (tid < 344) {
        const int cg = tid % 43, rp = tid / 43;
        const uint4* src = reinterpret_cast<const uint4*>(P.w1p + (size_t)rp * 64 * FF + (hi * 43 + cg) * 8);
        float s[8] = {0, 0, 0, 0, 0, 0, 0, 0};
#pragma unroll 8
        for (int r = 0; r < 64; r++) {
            uint4 v = __ldg(src + r * (FF / 8));
            s[0] += bf_lo(v.x); s[1] += bf_hi(v.x); s[2] += bf_lo(v.y); s[3] += bf_hi(v.y);
            s[4] += bf_lo(v.z); s[5] += bf_hi(v.z); s[6] += bf_lo(v.w); s[7] += bf_hi(v.w);
        }
        float* part = red + (rp * 43 + cg) * 8;
#pragma unroll
        for (int i = 0; i < 8; i++) part[i] = s[i];
    }
    __syncthreads();
    if (tid < 344) {
        float s = 0.f;
#pragma unroll
        for (int rp = 0; rp < 8; rp++) s += red[rp * 344 + tid];
        g_s.cs[hi * 344 + tid] = s;
    } else if (hi == 3 && tid < 344 + 64) g_s.cs[FF + tid - 344] = 0.f;
    __syncthreads();
    if (tid < 32) count_release(C_MID);
    if (tid == 0) g_s.epoch[b] = epoch;
}

__global__ void __launch_bounds__(512, 1) fused_kernel(const __grid_constant__ Params P) {
    extern __shared__ __align__(1024) uint8_t smem[];
    const uint32_t sb = (uint32_t)__cvta_generic_to_shared(smem);
    const uint32_t mb = sb + SM_MISC;
    const int tid = threadIdx.x, lane = tid & 31, b = blockIdx.x;
    if (b >= NMAIN) { helper_cta(P, smem); return; }
    const int tg = b >> 2, hg = b & 3;
    const int warp = __shfl_sync(0xffffffffu, tid >> 5, 0);

    uint4 xv[4][2];
    unsigned epoch = 0;
    {
        const int r = (tid >> 5) * 4;
        const uint4* src = reinterpret_cast<const uint4*>(P.x + (size_t)((r & 31) + tg * 32 + (r >> 5) * 1024) * D) + lane;
#pragma unroll
        for (int i = 0; i < 4; i++) { xv[i][0] = ldg_relaxed(src + i * 64); xv[i][1] = ldg_relaxed(src + i * 64 + 32); }
    }
    const uint4 wkv = ldg_relaxed(reinterpret_cast<const uint4*>(reinterpret_cast<const char*>(P.wk) + (hg < 2 ? 0 : P.wv_off)) + tid * 2 + (hg & 1));
    const int wg = warp >> 2, ww = warp & 3, g = lane >> 2, t4 = lane & 3, t128 = tid & 127;
    if (lane == 0) {
        if (warp < 4) {
            mbar_init(mb + (MB_WQ + warp) * 8, 2);
            asm volatile("fence.mbarrier_init.release.cluster;" ::: "memory");
            load_wq(sb, P, warp, 0);
            load_wq(sb, P, warp, 1);
        } else if (warp < 7) {
            asm volatile("prefetch.tensormap [%0];" :: "l"(&P.wo + (warp - 4)) : "memory");
        } else if (warp == 7) {
            asm volatile("ld.relaxed.gpu.global.u32 %0, [%1];" : "=r"(epoch) : "l"(g_s.epoch + b) : "memory");
        } else if (warp == 8) {
            sts128(mb + MISC_NRM, 0, 0, 0, 0);

        }
    }
    __syncwarp();
    TS(16);
    float dlt;
    {
        float st[4];
#pragma unroll
        for (int i = 0; i < 4; i++) {
            const uint32_t s = add_bf16x2(add_bf16x2(add_bf16x2(xv[i][0].x, xv[i][0].y), add_bf16x2(xv[i][0].z, xv[i][0].w)),
                                          add_bf16x2(add_bf16x2(xv[i][1].x, xv[i][1].y), add_bf16x2(xv[i][1].z, xv[i][1].w)));
            st[i] = bf_lo(s) + bf_hi(s);
        }
        TS(13);
        const float tot = reduce4(st, lane) * (-1.0f / D);
        const uint32_t nmr = pack_bf16(tot, tot);
        dlt = bf_lo(nmr) - tot;
        const uint32_t xa = sb + SM_XN + (lane >> 3) * 8192 + warp * 512;
#pragma unroll
        for (int i = 0; i < 4; i++) {
            const uint32_t nm = __shfl_sync(0xffffffffu, nmr, i * 8);
            const uint32_t addr = xa + i * 128 + (((lane & 7) ^ ((warp & 1) * 4 + i)) << 4);
#pragma unroll
            for (int c = 0; c < 2; c++) {
                xv[i][c].x = add_bf16x2(xv[i][c].x, nm); xv[i][c].y = add_bf16x2(xv[i][c].y, nm);
                xv[i][c].z = add_bf16x2(xv[i][c].z, nm); xv[i][c].w = add_bf16x2(xv[i][c].w, nm);
                sts128(addr + c * 32768, xv[i][c].x, xv[i][c].y, xv[i][c].z, xv[i][c].w);
            }
        }
    }
    sts128(sb + SM_WKV + tid * 16, wkv.x, wkv.y, wkv.z, wkv.w);
    fence_async_smem();
    TS(0);
    __syncthreads();
    auto variances = [&]() {
        float st[4];
#pragma unroll
        for (int i = 0; i < 4; i++) {
            float v = 0.f;
#pragma unroll
            for (int c = 0; c < 2; c++) {
                const uint32_t a = fma_bf16x2(xv[i][c].x, xv[i][c].x, mul_bf16x2(xv[i][c].y, xv[i][c].y));
                const uint32_t d = fma_bf16x2(xv[i][c].z, xv[i][c].z, mul_bf16x2(xv[i][c].w, xv[i][c].w));
                v += (bf_lo(a) + bf_hi(a)) + (bf_lo(d) + bf_hi(d));
            }
            st[i] = v;
        }
        const float vs = reduce4(st, lane), dl = dlt;
        if ((lane & 7) == 0) sts32(sb + SM_RSTD + (warp * 4 + (lane >> 3)) * 4, __float_as_uint(rsqrtf(fmaxf(vs * (1.0f / D) - dl * dl, 0.f) + 1e-5f)));
    };
    float kv[4] = {0.f, 0.f, 0.f, 0.f};
    if (wg == 2) {
        fence_regs(kv);
        const uint64_t da = mkdesc(sb + SM_XN, 16, 1024, 1), db = mkdesc(sb + SM_WKV, 128, 16, 0);
        wg_fence();
#pragma unroll
        for (int s = 0; s < 32; s++) mma_ss8(kv, da + (s >> 2) * 512 + (s & 3) * 2, db + s * 16);
        wg_commit();
        variances();
        wg_wait<0>(); fence_regs(kv);
    } else {
        variances();
        if (tid == 7 * 32) { sts32(mb + MISC_EPOCH, epoch + 1); g_s.epoch[b] = epoch + 1; }
    }
    __syncthreads();
    constexpr float QSCALE = 0.25f * 1.4426950408889634f;
    float qa[64];
    const uint32_t qbase = sb + SM_Q + (ww >> 1) * 8192 + (ww & 1) * 512 + lane * 16;
    if (wg == 0) {
#pragma unroll
        for (int i = 0; i < 64; i++) qa[i] = 0.f;
        fence_regs(qa);
        const uint64_t da = mkdesc(sb + SM_XN, 16, 1024, 1), db = mkdesc(sb + SM_WQ, 65536, 1024, 1);
#pragma unroll 1
        for (int i = 0; i < 4; i++) {
            mbar_wait(mb + (MB_WQ + i) * 8);
            wg_fence();
#pragma unroll
            for (int s = 0; s < 8; s++) mma_ss128(qa, da + (i * 2 + (s >> 2)) * 512 + (s & 3) * 2, db + (i * 8 + s) * 128);
            wg_commit();
        }
        const float rs0 = __uint_as_float(lds32(sb + SM_RSTD + (ww * 16 + g) * 4)) * QSCALE, rs1 = __uint_as_float(lds32(sb + SM_RSTD + (ww * 16 + g + 8) * 4)) * QSCALE;
        wg_wait<0>();
        fence_regs(qa);
        bar_arrive(6, 256);
        bar_sync(5, 256);
        TS(1);
        uint32_t nm = 0;
#pragma unroll
        for (int h = 0; h < 8; h++) {
#pragma unroll
            for (int i = 0; i < 8; i++) qa[8 * h + i] *= (i & 2) ? rs1 : rs0;
            stsm4(qbase + h * 1024, pack_f16(qa[8 * h], qa[8 * h + 1]), pack_f16(qa[8 * h + 4], qa[8 * h + 5]), pack_f16(qa[8 * h + 2], qa[8 * h + 3]), pack_f16(qa[8 * h + 6], qa[8 * h + 7]));
            const float n0 = qa[8 * h] * qa[8 * h] + qa[8 * h + 1] * qa[8 * h + 1] + qa[8 * h + 4] * qa[8 * h + 4] + qa[8 * h + 5] * qa[8 * h + 5];
            const float n1 = qa[8 * h + 2] * qa[8 * h + 2] + qa[8 * h + 3] * qa[8 * h + 3] + qa[8 * h + 6] * qa[8 * h + 6] + qa[8 * h + 7] * qa[8 * h + 7];
            nm = max(nm, max(__float_as_uint(n0), __float_as_uint(n1)));
        }
        nm = __reduce_max_sync(0xffffffffu, __float_as_uint(quad_sum(__uint_as_float(nm))));
        if (lane == 0) asm volatile("red.shared.max.u32 [%0], %1;" :: "r"(mb + MISC_NRM), "r"(nm) : "memory");
    } else if (wg == 1) {
        if (lane == 0) {
            if (ww == 0) {
#pragma unroll
                for (uint32_t i = 4; i < 35; i++) mbar_init(mb + i * 8, bar_count(i));
            } else if (ww == 1) {
#pragma unroll
                for (uint32_t i = 35; i < 66; i++) mbar_init(mb + i * 8, bar_count(i));
            } else {
#pragma unroll
                for (uint32_t i = 0; i < 30; i++) mbar_init(mb + (ww * 30 + 6 + i) * 8, 2);
            }
        }
        __syncwarp();
#pragma unroll
        for (int i = 0; i < 4; i++) sts128(sb + SM_SENT + (i * 128 + t128) * 16, SENT, SENT, SENT, SENT);
        bar_sync(5, 256);
#pragma unroll
        for (int i = 0; i < 16; i++) sts128(sb + SM_V + 65536 + (i * 128 + t128) * 16, 0x3F803F80u, 0x3F803F80u, 0x3F803F80u, 0x3F803F80u);
    } else if (wg == 2) {
        const float rs0 = __uint_as_float(lds32(sb + SM_RSTD + (ww * 16 + g) * 4)), rs1 = __uint_as_float(lds32(sb + SM_RSTD + (ww * 16 + g + 8) * 4));
        kv[0] *= rs0; kv[1] *= rs0; kv[2] *= rs1; kv[3] *= rs1;
        float2* kt = reinterpret_cast<float2*>(smem + SM_KTMP);
        kt[(ww * 16 + g) * 4 + t4] = make_float2(kv[0], kv[1]); kt[(ww * 16 + g + 8) * 4 + t4] = make_float2(kv[2], kv[3]);
        float n0 = kv[0] * kv[0] + kv[1] * kv[1], n1 = kv[2] * kv[2] + kv[3] * kv[3];
        n0 += __shfl_xor_sync(0xffffffffu, n0, 1); n1 += __shfl_xor_sync(0xffffffffu, n1, 1);
        n0 += __shfl_xor_sync(0xffffffffu, n0, 2); n1 += __shfl_xor_sync(0xffffffffu, n1, 2);
        const uint32_t nm = __reduce_max_sync(0xffffffffu, max(__float_as_uint(n0), __float_as_uint(n1)));
        if (lane == 0) sts32(sb + SM_WNRM + ww * 4, nm | 1u);
        bar_sync(2, 128);
        const uint32_t ra = sb + SM_KTMP + ((t128 & 1) * 32 + ((t128 & 63) >> 1)) * 32;
        const float4 c0 = lds128f(ra), c1 = lds128f(ra + 16);
        const int kvoff = kv_slot(tid);
        if (ww < 2) {
            if (hg < 2) {
                float4 p0 = lds128f(ra - 32), p1 = lds128f(ra - 16);
                if (t128 < 2) { p0 = make_float4(0.f, 0.f, 0.f, 0.f); p1 = p0; }
                stg128(g_s.kv + kvoff, nonzero(pack_f16(c0.x - p0.x, c0.y - p0.y)), pack_f16(c0.z - p0.z, c0.w - p0.w), pack_f16(c1.x - p1.x, c1.y - p1.y), pack_f16(c1.z - p1.z, c1.w - p1.w));
            } else {
                stg128(g_s.kv + kvoff, nonzero(pack_bf16(c0.x, c0.y)), pack_bf16(c0.z, c0.w), pack_bf16(c1.x, c1.y), pack_bf16(c1.z, c1.w));
            }
            if (t128 < 2) { const float4 w = lds128f(sb + SM_WNRM); stg128(g_s.nrm + b * 2 + t128, __float_as_uint(w.x), __float_as_uint(w.y), __float_as_uint(w.z), __float_as_uint(w.w)); }
            count_hint(C_KVH);
        } else if (hg < 2) {
            stg128(g_s.kplain + kvoff, pack_bf16(c0.x, c0.y), pack_bf16(c0.z, c0.w), pack_bf16(c1.x, c1.y), pack_bf16(c1.z, c1.w));
        }
        TS(1);
        bar_sync(2, 128);
        if (ww == 3) count_release(C_KV);
    } else {
        uint4 kc[18];
        auto src = [&](int i) { return i < 8 ? g_s.kv + i * 128 : i < 12 ? g_s.kv + 4096 + (i - 8) * 128 : i < 16 ? g_s.kv + 6144 + (i - 12) * 128 : i == 16 ? g_s.kv + 31 * 128 : g_s.nrm + t128; };
        count_wait(C_KVH, lds32(mb + MISC_EPOCH) * (NMAIN * 2));
        TS(1);
        int spins = 0;
        while (true) {
#pragma unroll
            for (int i = 0; i < 18; i++) kc[i] = ldg_relaxed(src(i) + t128);
            uint32_t mn = 1;
#pragma unroll
            for (int i = 0; i < 18; i++) mn = min(mn, kc[i].x);
            if (!__any_sync(0xffffffffu, mn == 0u) || ++spins >= SPIN_LIMIT) break;
        }
        uint32_t nm = max(max(kc[17].x, kc[17].y), max(kc[17].z, kc[17].w));
        nm = max(nm, __shfl_xor_sync(0xffffffffu, nm, 4)); nm = max(nm, __shfl_xor_sync(0xffffffffu, nm, 8)); nm = max(nm, __shfl_xor_sync(0xffffffffu, nm, 16));
        if (lane < 4) asm volatile("red.shared.max.u32 [%0], %1;" :: "r"(mb + MISC_NRM + 4 + min(lane, 2) * 4), "r"(nm) : "memory");
        TS(2);
        bar_sync(6, 256);
#pragma unroll
        for (int i = 0; i < 17; i++) sts128(sb + (uint32_t)(src(i) - g_s.kv + t128) * 16 + ((i >= 8 && i < 16) ? SM_V - 65536 : 0), kc[i].x, kc[i].y, kc[i].z, kc[i].w);
    }
    fence_async_smem();
    TS(3);
    __syncthreads();
    const float4 nr = lds128f(mb + MISC_NRM);
    const bool safe = __all_sync(0xffffffffu, (nr.x * (nr.y + nr.z) <= 3500.0f) && (nr.x <= 65536.0f) && (nr.y + nr.z <= 65536.0f) && (nr.w <= 1e24f));
    TS(4);

    if (__builtin_expect(safe, 1)) {
        attention<true>(P, sb, warp TS_PASS);
    } else {
        if (wg == 0) {
#pragma unroll
            for (int h = 0; h < 8; h++)
                stsm4(qbase + h * 1024, pack_bf16(qa[8 * h], qa[8 * h + 1]), pack_bf16(qa[8 * h + 4], qa[8 * h + 5]), pack_bf16(qa[8 * h + 2], qa[8 * h + 3]), pack_bf16(qa[8 * h + 6], qa[8 * h + 7]));
            fence_async_smem();
        } else if (warp == 15) {
            count_wait(C_KV, lds32(mb + MISC_EPOCH) * NMAIN);
            if (lane == 0) {
                asm volatile("fence.proxy.async;" ::: "memory");
                mbar_expect(mb + MB_KV * 8, 131072);
                bulk_g2s(sb + SM_K, g_s.kplain, 65536, mb + MB_KV * 8);
                bulk_g2s(sb + SM_V, g_s.kv + 4096, 65536, mb + MB_KV * 8);
            }
            __syncwarp();
        }
        __syncthreads();
        mbar_wait(mb + MB_KV * 8);
        attention<false>(P, sb, warp TS_PASS);
    }

    const int j = b & 7;
    if (wg == 1 || wg == 2) {
        if (warp == 8) {
            epoch = lds32(mb + MISC_EPOCH);
#pragma unroll 1
            for (int job = 1; job < 6; job++) {
                count_wait(C_O + 32 * (job >> 1) + (job & 1) * 16 + (b >> 3), epoch * (job == 1 ? 128 : 32));
                asm volatile("fence.proxy.async.global;" ::: "memory");
                warp_done(mb + (MB_READY + job) * 8);
                TS(18 + job);
            }
        } else if (warp == 9) {
#pragma unroll
            for (int i = 0; i < 2; i++) {
                if (lane < 22) {
                    const uint4 v = ldg_relaxed(reinterpret_cast<const uint4*>(g_s.cs + j * 176) + i * 22 + lane);
                    sts128(mb + MISC_CS + (i * 22 + lane) * 16, v.x, v.y, v.z, v.w);
                }
                stg128(g_s.kv + kv_slot(i * 32 + lane), 0u, 0u, 0u, 0u);
            }
            warp_done(mb + MB_CS * 8);
            if (lane < 2) stg128(g_s.nrm + b * 2 + lane, 0u, 0u, 0u, 0u);
#pragma unroll 1
            for (int i = 0; i < 16; i++) {
                mbar_wait(mb + (MB_W1 + i) * 8);
                const int n = i < 8 ? 16 + i + 8 * (lane & 1) : 32 + 3 * (i - 8) + (lane >> 1) + 22 * (lane & 1);
                if (lane < (i < 8 || i == 15 ? 2 : 6)) mbar_arrive(mb + (MB_FULL + n) * 8);
                __syncwarp();
            }
        } else {
            if (wg == 2) {
#pragma unroll 1
                for (int i = 7 + ww; i < 46; i += 2) {
                    const bool w1 = i < 24;
                    const int n = w1 ? i : i - 24, kb = n / 3, a = n - 3 * kb;
                    mbar_wait(mb + (w1 ? (i < 12 ? MB_DONE + 4 : MB_REL + 8) : MB_REL + kb) * 8);
                    if (lane == 0) load_box(sb, w1 ? &P.w1 : &P.w2, w1_slot(kb, a) * SLOT, (w1 ? MB_W1 : MB_W2) + kb, SLOT, w1 ? j * 176 + a * 64 : j * 64, (w1 ? kb : n) * 64);
                    __syncwarp();
                }
            }
            ring_feed(sb, wg == 1 ? ww : ww + 2 TS_PASS);
        }
    } else {
        const int pr = (wg == 0), mt = 16 * pr + (b >> 3);
        uint32_t* const hp = reinterpret_cast<uint32_t*>(g_x + X_H1 + (mt * 32 + j * 4) * 128 + ww * 32) + lane;
        {
            uint32_t hk[16];
            const uint32_t* xp = reinterpret_cast<const uint32_t*>(P.x + (size_t)(mt * 64 + ww * 16 + g) * D + j * 64 + t4 * 2);
#pragma unroll
            for (int k = 0; k < 8; k++) { hk[2 * k] = __ldg(xp + k * 4); hk[2 * k + 1] = __ldg(xp + k * 4 + 8 * (D / 2)); }
            mbar_wait(mb + MB_WO * 8);
            float acc[32];
            if (gemm_ss<0>(acc, sb, pr TS_PASS)) gemm_slow(acc, g_x + X_O + mt * 32 * 128, 32, P.wop, D, D, j * 64);
            TS(7);
#pragma unroll
            for (int i = 0; i < 16; i++) hk[i] = pack_bf16(acc[2 * i] + bf_lo(hk[i]), acc[2 * i + 1] + bf_hi(hk[i]));
#pragma unroll
            for (int k = 0; k < 4; k++) store_tile(hp + k * 512, hk[4 * k], hk[4 * k + 1], hk[4 * k + 2], hk[4 * k + 3]);
            count_hint(C_H1 + mt);
            TS(8);
            float st[4] = {0.f, 0.f, 0.f, 0.f};
#pragma unroll
            for (int i = 0; i < 16; i++) {
                const float lo = bf_lo(hk[i]), hi = bf_hi(hk[i]);
                st[2 * (i & 1)] += lo + hi;
                st[2 * (i & 1) + 1] = fmaf(lo, lo, fmaf(hi, hi, st[2 * (i & 1) + 1]));
            }
#pragma unroll
            for (int o = 1; o < 4; o <<= 1)
#pragma unroll
                for (int i = 0; i < 4; i++) st[i] += __shfl_xor_sync(0xffffffffu, st[i], o);
            if (t4 == 0) stg128(g_x + X_ST + (mt * 8 + j) * 32 + ww * 8 + g, __float_as_uint(st[0]), __float_as_uint(st[1]), __float_as_uint(st[2]), __float_as_uint(st[3]));
        }
        {
            float acc[88];
            const uint4* sp = g_x + X_ST + (mt * 8 + t4) * 32 + ww * 8 + g;
            mbar_wait(mb + (MB_FULL + 16 + pr * 8) * 8);
            uint4 u0 = ldg_relaxed(sp), u1 = ldg_relaxed(sp + 128);
            if (gemm_ss<1>(acc, sb, pr TS_PASS)) gemm_slow(acc, g_x + X_H1 + mt * 32 * 128, 32, P.w1p, FF, D, j * 176);
            TS(9);
            int spins = 0;
            while (__builtin_expect(__any_sync(0xffffffffu, max(u0.x, u1.x) == SENT), 0) && ++spins < SPIN_LIMIT) { u0 = ldg_relaxed(sp); u1 = ldg_relaxed(sp + 128); }
            float st[4] = {__uint_as_float(u0.x) + __uint_as_float(u1.x), __uint_as_float(u0.y) + __uint_as_float(u1.y),
                           __uint_as_float(u0.z) + __uint_as_float(u1.z), __uint_as_float(u0.w) + __uint_as_float(u1.w)};
#pragma unroll
            for (int o = 1; o < 4; o <<= 1)
#pragma unroll
                for (int k = 0; k < 4; k++) st[k] += __shfl_xor_sync(0xffffffffu, st[k], o);
            float nmean[2], hrstd[2];
#pragma unroll
            for (int k = 0; k < 2; k++) {
                nmean[k] = st[2 * k] * (-1.0f / D);
                hrstd[k] = 0.5f * rsqrtf(fmaxf(fmaf(-nmean[k], nmean[k], st[2 * k + 1] * (1.0f / D)), 0.f) + 1e-5f);
                nmean[k] *= hrstd[k];
            }
            mbar_wait(mb + MB_CS * 8);
            uint32_t* hb = reinterpret_cast<uint32_t*>(g_x + X_H2 + (mt * 88 + j * 11) * 128 + ww * 32) + lane;
#pragma unroll
            for (int i = 0; i < 22; i++) {
                float2 cs;
                asm volatile("ld.shared.v2.f32 {%0,%1}, [%2];" : "=f"(cs.x), "=f"(cs.y) : "r"(mb + MISC_CS + i * 32 + t4 * 8));
                const float* z = acc + 4 * i;
                uint32_t* p = hb + (i >> 1) * 512 + (i & 1) * 32;
                stg32(p, pack_bf16(silu2(fmaf(hrstd[0], z[0], nmean[0] * cs.x)), silu2(fmaf(hrstd[0], z[1], nmean[0] * cs.y))));
                stg32(p + 64, pack_bf16(silu2(fmaf(hrstd[1], z[2], nmean[1] * cs.x)), silu2(fmaf(hrstd[1], z[3], nmean[1] * cs.y))));
            }
            count_hint(C_H2 + mt);
            TS(10);
        }
        {
            uint32_t hk[16];
#pragma unroll
            for (int i = 0; i < 16; i++) hk[i] = ldg32_relaxed(hp + (i >> 2) * 512 + ((i & 1) * 2 + ((i >> 1) & 1)) * 32);
            float acc[32];
            if (gemm_ss<2>(acc, sb, pr TS_PASS)) gemm_slow(acc, g_x + X_H2 + mt * 88 * 128, 88, P.w2p, D, FF, j * 64);
            TS(11);
#pragma unroll
            for (int i = 0; i < 16; i++) hk[i] = pack_bf16(acc[2 * i] + bf_lo(hk[i]), acc[2 * i + 1] + bf_hi(hk[i]));
#pragma unroll
            for (int h = 0; h < 4; h++) {
                const uint32_t* v = hk + (h >> 1) * 8 + (h & 1);
                uint32_t v0 = v[0], v1 = v[2], v2 = v[4], v3 = v[6];
                const bool o1 = t4 & 1, o2 = t4 & 2;
                uint32_t a = __shfl_xor_sync(0xffffffffu, o1 ? v0 : v1, 1), c = __shfl_xor_sync(0xffffffffu, o1 ? v2 : v3, 1);
                if (o1) { v0 = a; v2 = c; } else { v1 = a; v3 = c; }
                a = __shfl_xor_sync(0xffffffffu, o2 ? v0 : v2, 2); c = __shfl_xor_sync(0xffffffffu, o2 ? v1 : v3, 2);
                if (o2) { v0 = a; v1 = c; } else { v2 = a; v3 = c; }
                *reinterpret_cast<uint4*>(P.out + (size_t)(mt * 64 + ww * 16 + g + 8 * (h & 1)) * D + j * 64 + (h >> 1) * 32 + t4 * 8) = make_uint4(v0, v1, v2, v3);
            }
        }
    }
    TS(12);
}

typedef CUresult (*EncodeFn)(CUtensorMap*, CUtensorMapDataType, cuuint32_t, void*, const cuuint64_t*, const cuuint64_t*, const cuuint32_t*,
                             const cuuint32_t*, CUtensorMapInterleave, CUtensorMapSwizzle, CUtensorMapL2promotion, CUtensorMapFloatOOBfill);

void encode2d(EncodeFn fn, CUtensorMap* tm, const void* ptr, int rows, int cols, int box_rows, int box_cols, CUtensorMapSwizzle sw) {
    cuuint64_t dims[2] = {(cuuint64_t)cols, (cuuint64_t)rows};
    cuuint64_t strides[1] = {(cuuint64_t)cols * 2};
    cuuint32_t box[2] = {(cuuint32_t)box_cols, (cuuint32_t)box_rows};
    cuuint32_t es[2] = {1, 1};
    fn(tm, CU_TENSOR_MAP_DATA_TYPE_BFLOAT16, 2, const_cast<void*>(ptr), dims, strides, box, es, CU_TENSOR_MAP_INTERLEAVE_NONE, sw,
       CU_TENSOR_MAP_L2_PROMOTION_L2_128B, CU_TENSOR_MAP_FLOAT_OOB_FILL_NONE);
}

}

extern "C" void kernel_launch(void* const* d_in, const int* in_sizes, int n_in, void* d_out, int out_size) {
    (void)in_sizes; (void)n_in; (void)out_size;
    void* fnp = nullptr;
    cudaDriverEntryPointQueryResult qr;
    cudaGetDriverEntryPoint("cuTensorMapEncodeTiled", &fnp, cudaEnableDefault, &qr);
    EncodeFn fn = (EncodeFn)fnp;
    Params P;
    encode2d(fn, &P.wq, d_in[1], D, D, 128, 64, CU_TENSOR_MAP_SWIZZLE_128B);
    P.wk = (const __nv_bfloat16*)d_in[2];
    P.wv_off = (const char*)d_in[3] - (const char*)d_in[2];
    encode2d(fn, &P.wo, d_in[4], D, D, 64, 64, CU_TENSOR_MAP_SWIZZLE_128B);
    encode2d(fn, &P.w1, d_in[6], D, FF, 64, 64, CU_TENSOR_MAP_SWIZZLE_128B);
    encode2d(fn, &P.w2, d_in[7], FF, D, 64, 64, CU_TENSOR_MAP_SWIZZLE_128B);
    P.x = (const __nv_bfloat16*)d_in[0];
    P.w1p = (const __nv_bfloat16*)d_in[6];
    P.w2p = (const __nv_bfloat16*)d_in[7];
    P.wop = (const __nv_bfloat16*)d_in[4];
    P.wqp = (const __nv_bfloat16*)d_in[1];
    P.out = (__nv_bfloat16*)d_out;
    P.neg1 = 0xFFFFFFFFu; P.pad = 0;
    cudaFuncSetAttribute(fused_kernel, cudaFuncAttributeMaxDynamicSharedMemorySize, SMEM_BYTES);
    fused_kernel<<<NCTA, 512, SMEM_BYTES>>>(P);
}
```

```cpp
#include <cuda_runtime.h>
#include <cuda_bf16.h>
#include <cuda.h>
#include <stdint.h>

namespace {

constexpr int D = 512, FF = 1376;
constexpr int NMAIN = 128, NHELP = 4, NCTA = NMAIN + NHELP;
constexpr uint32_t SENT = 0xFFFFFFFFu;
constexpr int SPIN_LIMIT = 1 << 22;

constexpr uint32_t KB = 1024, SLOT = 8192;
constexpr uint32_t SM_XN = 0;
constexpr uint32_t SM_WQ = 64 * KB;
constexpr uint32_t SM_WKV = 192 * KB;
constexpr uint32_t SM_K = 0;
constexpr uint32_t SM_Q = 64 * KB;
constexpr uint32_t SM_V = 96 * KB;
constexpr uint32_t SM_MISC = 224 * KB;
constexpr uint32_t SMEM_BYTES = 227 * KB;
constexpr uint32_t SM_KTMP = 200 * KB;
constexpr uint32_t SM_RSTD = 202 * KB;
constexpr uint32_t SM_WNRM = 203 * KB;
constexpr uint32_t SM_SENT = 208 * KB;
constexpr uint32_t MB_WQ = 0;
constexpr uint32_t MB_CS = 4;
constexpr uint32_t MB_DONE = 5;
constexpr uint32_t MB_EMPTY = 10;
constexpr uint32_t MB_W1 = 16;
constexpr uint32_t MB_W2 = 24;
constexpr uint32_t MB_WO = 32;
constexpr uint32_t MB_REL = 33;
constexpr uint32_t MB_KV = 43;
constexpr uint32_t MB_MID = 44;
constexpr uint32_t MB_READY = 44;
constexpr uint32_t MB_FULL = 50;
constexpr uint32_t MB_NULL = 126;
__host__ __device__ constexpr uint32_t bar_count(uint32_t i) {
    return i >= MB_FULL + 16 ? 2 : i >= MB_KV ? 1 : i >= MB_WO ? 8 : i == MB_W2 + 7 ? 1 : i >= MB_W1 ? 3 : i >= MB_EMPTY ? 4 : i >= MB_DONE ? 16 : 1;
}
constexpr uint32_t MISC_NRM = 1056;
constexpr uint32_t MISC_EPOCH = 1072;
constexpr uint32_t MISC_TS = 1088;
constexpr uint32_t MISC_CS = 1344;

__host__ __device__ constexpr uint32_t wo_slot(int kb) { return kb < 2 ? 10 + kb : kb - 2; }
__host__ __device__ constexpr uint32_t w1_slot(int kb, int a) { return kb < 4 ? 12 + kb + 4 * a : (kb < 6 ? 3 * kb - 6 : 3 * kb - 18) + a; }

struct alignas(128) Small {
    unsigned epoch[160];
    unsigned cnt[100][32];
    float cs[1440];
    uint4 nrm[NMAIN * 2];
    uint4 kv[8192];
    uint4 kplain[4096];
};
__device__ Small g_s;
constexpr int C_KVH = 0, C_KV = 1, C_MID = 2, C_O = 3, C_H1 = 35, C_H2 = 67;
constexpr int X_O = 0, X_H1 = 32 * 32 * 128, X_H2 = 2 * X_H1, X_ST = X_H2 + 32 * 88 * 128, X_END = X_ST + 32 * 8 * 32;
constexpr int X_ARM = 16 * 32 * 128, X_SHARE = (X_END - X_ARM) / NMAIN;
__device__ uint4 g_x[X_END];
#define TS(i) do {} while (0)
#define TSF(k)

#define TS_ARG
#define TS_PASS

__device__ __forceinline__ void mbar_init(uint32_t bar, int cnt) { asm volatile("mbarrier.init.shared::cta.b64 [%0], %1;" :: "r"(bar), "r"(cnt) : "memory"); }
__device__ __forceinline__ void mbar_expect(uint32_t bar, uint32_t bytes) { asm volatile("mbarrier.arrive.expect_tx.shared::cta.b64 _, [%0], %1;" :: "r"(bar), "r"(bytes) : "memory"); }
__device__ __forceinline__ void mbar_arrive(uint32_t bar) { asm volatile("mbarrier.arrive.shared::cta.b64 _, [%0];" :: "r"(bar) : "memory"); }
__device__ __forceinline__ bool mbar_try(uint32_t bar, uint32_t parity) {
    uint32_t done;
    asm volatile("{.reg .pred p; mbarrier.try_wait.parity.shared::cta.b64 p, [%1], %2; selp.u32 %0, 1, 0, p;}" : "=r"(done) : "r"(bar), "r"(parity) : "memory");
    return __all_sync(0xffffffffu, done);
}
__device__ __forceinline__ void mbar_wait(uint32_t bar, uint32_t parity = 0) {
    if (__builtin_expect(!mbar_try(bar, parity), 0)) {
        int spins = 0;
        while (!mbar_try(bar, parity) && ++spins < (SPIN_LIMIT >> 6)) {}
    }
}
__device__ __forceinline__ void tma2d(uint32_t dst, const CUtensorMap* tm, int c0, int c1, uint32_t bar) {
    asm volatile("cp.async.bulk.tensor.2d.shared::cluster.global.mbarrier::complete_tx::bytes [%0], [%1, {%3, %4}], [%2];"
                 :: "r"(dst), "l"(tm), "r"(bar), "r"(c0), "r"(c1) : "memory");
}
__device__ __forceinline__ void bulk_g2s(uint32_t dst, const void* src, uint32_t bytes, uint32_t bar) {
    asm volatile("cp.async.bulk.shared::cluster.global.mbarrier::complete_tx::bytes [%0], [%1], %2, [%3];" :: "r"(dst), "l"(src), "r"(bytes), "r"(bar) : "memory");
}
__device__ __forceinline__ void fence_async_smem() { asm volatile("fence.proxy.async.shared::cta;" ::: "memory"); }
__device__ __forceinline__ void bar_sync(int id, int n) { asm volatile("bar.sync %0, %1;" :: "r"(id), "r"(n) : "memory"); }
__device__ __forceinline__ void bar_arrive(int id, int n) { asm volatile("bar.arrive %0, %1;" :: "r"(id), "r"(n) : "memory"); }
__device__ __forceinline__ void wg_fence() { asm volatile("wgmma.fence.sync.aligned;" ::: "memory"); }
__device__ __forceinline__ void wg_commit() { asm volatile("wgmma.commit_group.sync.aligned;" ::: "memory"); }
template <int N> __device__ __forceinline__ void wg_wait() { asm volatile("wgmma.wait_group.sync.aligned %0;" :: "n"(N) : "memory"); }
template <int N> __device__ __forceinline__ void fence_regs(float (&d)[N]) {
#pragma unroll
    for (int i = 0; i < N; i++) asm volatile("" : "+f"(d[i]) :: "memory");
}
template <int N> __device__ __forceinline__ void fence_regs(uint32_t (&d)[N]) {
#pragma unroll
    for (int i = 0; i < N; i++) asm volatile("" : "+r"(d[i]) :: "memory");
}
__device__ __forceinline__ uint64_t mkdesc(uint32_t addr, uint32_t lbo, uint32_t sbo, uint32_t swz) {
    return (uint64_t)(((addr & 0x3FFFF) >> 4) | ((lbo >> 4) << 16)) | ((uint64_t)((sbo >> 4) | (swz << 30)) << 32);
}
__device__ __forceinline__ float ex2(float x) { float y; asm("ex2.approx.ftz.f32 %0, %1;" : "=f"(y) : "f"(x)); return y; }
__device__ __forceinline__ float rcp(float x) { float y; asm("rcp.approx.ftz.f32 %0, %1;" : "=f"(y) : "f"(x)); return y; }
__device__ __forceinline__ uint32_t pack_bf16(float lo, float hi) { uint32_t r; asm("cvt.rn.bf16x2.f32 %0, %1, %2;" : "=r"(r) : "f"(hi), "f"(lo)); return r; }
__device__ __forceinline__ uint32_t pack_f16(float lo, float hi) { uint32_t r; asm("cvt.rn.f16x2.f32 %0, %1, %2;" : "=r"(r) : "f"(hi), "f"(lo)); return r; }
__device__ __forceinline__ float bf_lo(uint32_t v) { return __uint_as_float(v << 16); }
__device__ __forceinline__ float bf_hi(uint32_t v) { return __uint_as_float(v & 0xFFFF0000u); }
__device__ __forceinline__ uint4 ldg_relaxed(const uint4* p) {
    uint4 v; asm volatile("ld.relaxed.gpu.global.v4.u32 {%0,%1,%2,%3}, [%4];" : "=r"(v.x), "=r"(v.y), "=r"(v.z), "=r"(v.w) : "l"(p) : "memory"); return v;
}
__device__ __forceinline__ void stg128(void* p, uint32_t a, uint32_t b, uint32_t c, uint32_t d) {
    asm volatile("st.relaxed.gpu.global.v4.u32 [%0], {%1,%2,%3,%4};" :: "l"(p), "r"(a), "r"(b), "r"(c), "r"(d) : "memory");
}
__device__ __forceinline__ void stg64(void* p, uint32_t a, uint32_t b) {
    asm volatile("st.relaxed.gpu.global.v2.u32 [%0], {%1,%2};" :: "l"(p), "r"(a), "r"(b) : "memory");
}
__device__ __forceinline__ void sts128(uint32_t a, uint32_t x, uint32_t y, uint32_t z, uint32_t w) {
    asm volatile("st.shared.v4.u32 [%0], {%1,%2,%3,%4};" :: "r"(a), "r"(x), "r"(y), "r"(z), "r"(w) : "memory");
}
__device__ __forceinline__ void sts32(uint32_t a, uint32_t x) { asm volatile("st.shared.u32 [%0], %1;" :: "r"(a), "r"(x) : "memory"); }
__device__ __forceinline__ float4 lds128f(uint32_t a) {
    float4 v; asm volatile("ld.shared.v4.f32 {%0,%1,%2,%3}, [%4];" : "=f"(v.x), "=f"(v.y), "=f"(v.z), "=f"(v.w) : "r"(a) : "memory"); return v;
}
__device__ __forceinline__ uint32_t lds32(uint32_t a) { uint32_t v; asm volatile("ld.shared.u32 %0, [%1];" : "=r"(v) : "r"(a) : "memory"); return v; }
__device__ __forceinline__ uint32_t nonzero(uint32_t w) { return w == 0u ? 0x8000u : w; }
__device__ __forceinline__ void stg32(void* p, uint32_t a) { asm volatile("st.global.u32 [%0], %1;" :: "l"(p), "r"(a) : "memory"); }
__device__ __forceinline__ uint32_t ldg32_relaxed(const void* p) { uint32_t v; asm volatile("ld.relaxed.gpu.global.u32 %0, [%1];" : "=r"(v) : "l"(p) : "memory"); return v; }
__device__ __forceinline__ void count_hint(int id) {
    if ((threadIdx.x & 31) == 0) asm volatile("red.relaxed.gpu.global.add.u32 [%0], 1;" :: "l"(g_s.cnt[id]) : "memory");
}
__device__ __forceinline__ void count_release(int id) {
    __syncwarp();
    if ((threadIdx.x & 31) == 0) asm volatile("red.release.gpu.global.add.u32 [%0], 1;" :: "l"(g_s.cnt[id]) : "memory");
    __syncwarp();
}
__device__ __forceinline__ void count_wait(int id, unsigned target) {
    uint32_t v; int spins = 0;
    do v = ldg32_relaxed(g_s.cnt[id]); while (__any_sync(0xffffffffu, v != target) && ++spins < SPIN_LIMIT);
    asm volatile("fence.acquire.gpu;" ::: "memory");
}
__device__ __forceinline__ void warp_done(uint32_t bar) {
    __syncwarp();
    asm volatile("{.reg .pred p; setp.eq.u32 p, %1, 0; @p mbarrier.arrive.shared::cta.b64 _, [%0];}" :: "r"(bar), "r"(threadIdx.x & 31) : "memory");
}
__device__ __forceinline__ uint32_t mul_bf16x2(uint32_t a, uint32_t b) { uint32_t r; asm("mul.rn.bf16x2 %0, %1, %2;" : "=r"(r) : "r"(a), "r"(b)); return r; }
__device__ __forceinline__ uint32_t fma_bf16x2(uint32_t a, uint32_t b, uint32_t c) { uint32_t r; asm("fma.rn.bf16x2 %0, %1, %2, %3;" : "=r"(r) : "r"(a), "r"(b), "r"(c)); return r; }
__device__ __forceinline__ uint32_t add_bf16x2(uint32_t a, uint32_t b) { uint32_t r; asm("add.rn.bf16x2 %0, %1, %2;" : "=r"(r) : "r"(a), "r"(b)); return r; }

#define R4(d, o) "+f"(d[o + 0]), "+f"(d[o + 1]), "+f"(d[o + 2]), "+f"(d[o + 3])
#define R8(d, o) R4(d, o), R4(d, o + 4)
#define R32(d) R8(d, 0), R8(d, 8), R8(d, 16), R8(d, 24)
#define D32 "{%0,%1,%2,%3,%4,%5,%6,%7,%8,%9,%10,%11,%12,%13,%14,%15,%16,%17,%18,%19,%20,%21,%22,%23,%24,%25,%26,%27,%28,%29,%30,%31}"
#define D64 "{%0,%1,%2,%3,%4,%5,%6,%7,%8,%9,%10,%11,%12,%13,%14,%15,%16,%17,%18,%19,%20,%21,%22,%23,%24,%25,%26,%27,%28,%29,%30,%31,%32,%33,%34,%35,%36,%37,%38,%39,%40,%41,%42,%43,%44,%45,%46,%47,%48,%49,%50,%51,%52,%53,%54,%55,%56,%57,%58,%59,%60,%61,%62,%63}"

__device__ __forceinline__ void mma_qk_f16(float (&d)[32], uint64_t da, uint64_t db) {
    asm volatile("{.reg .pred p; setp.eq.b32 p, 0, 0; wgmma.mma_async.sync.aligned.m64n64k16.f32.f16.f16 " D32 ", %32, %33, p, 1, 1, 0, 0;}"
                 : R32(d) : "l"(da), "l"(db));
}
__device__ __forceinline__ void mma_qk_bf16(float (&d)[32], uint64_t da, uint64_t db) {
    asm volatile("{.reg .pred p; setp.ne.b32 p, 0, 0; wgmma.mma_async.sync.aligned.m64n64k16.f32.bf16.bf16 " D32 ", %32, %33, p, 1, 1, 0, 0;}"
                 : R32(d) : "l"(da), "l"(db));
}
__device__ __forceinline__ void mma_pv(float (&d)[12], const uint32_t* a, uint64_t db) {
    asm volatile("{.reg .pred p; setp.eq.b32 p, 0, 0; wgmma.mma_async.sync.aligned.m64n24k16.f32.bf16.bf16 {%0,%1,%2,%3,%4,%5,%6,%7,%8,%9,%10,%11}, {%12,%13,%14,%15}, %16, p, 1, 1, 1;}"
                 : R8(d, 0), R4(d, 8) : "r"(a[0]), "r"(a[1]), "r"(a[2]), "r"(a[3]), "l"(db));
}
__device__ __forceinline__ void mma_ss128(float (&d)[64], uint64_t da, uint64_t db) {
    asm volatile("{.reg .pred p; setp.eq.b32 p, 0, 0; wgmma.mma_async.sync.aligned.m64n128k16.f32.bf16.bf16 " D64 ", %64, %65, p, 1, 1, 0, 1;}"
                 : R32(d), R8(d, 32), R8(d, 40), R8(d, 48), R8(d, 56) : "l"(da), "l"(db));
}
__device__ __forceinline__ void stsm4(uint32_t addr, uint32_t a, uint32_t b, uint32_t c, uint32_t d) {
    asm volatile("stmatrix.sync.aligned.m8n8.x4.shared.b16 [%0], {%1,%2,%3,%4};" :: "r"(addr), "r"(a), "r"(b), "r"(c), "r"(d) : "memory");
}
__device__ __forceinline__ void mma_ss8(float (&d)[4], uint64_t da, uint64_t db) {
    asm volatile("{.reg .pred p; setp.eq.b32 p, 0, 0; wgmma.mma_async.sync.aligned.m64n8k16.f32.bf16.bf16 {%0,%1,%2,%3}, %4, %5, p, 1, 1, 0, 1;}"
                 : R4(d, 0) : "l"(da), "l"(db));
}
__device__ __forceinline__ void mma_ss(float (&d)[32], uint64_t da, uint64_t db, int accum) {
    asm volatile("{.reg .pred p; setp.ne.b32 p, %34, 0; wgmma.mma_async.sync.aligned.m64n64k16.f32.bf16.bf16 " D32 ", %32, %33, p, 1, 1, 0, 1;}"
                 : R32(d) : "l"(da), "l"(db), "r"(accum));
}
__device__ __forceinline__ void mma_ss(float (&d)[88], uint64_t da, uint64_t db, int accum) {
    asm volatile("{.reg .pred p; setp.ne.b32 p, %90, 0; wgmma.mma_async.sync.aligned.m64n176k16.f32.bf16.bf16 " "{%0,%1,%2,%3,%4,%5,%6,%7,%8,%9,%10,%11,%12,%13,%14,%15,%16,%17,%18,%19,%20,%21,%22,%23,%24,%25,%26,%27,%28,%29,%30,%31,%32,%33,%34,%35,%36,%37,%38,%39,%40,%41,%42,%43,%44,%45,%46,%47,%48,%49,%50,%51,%52,%53,%54,%55,%56,%57,%58,%59,%60,%61,%62,%63,%64,%65,%66,%67,%68,%69,%70,%71,%72,%73,%74,%75,%76,%77,%78,%79,%80,%81,%82,%83,%84,%85,%86,%87}"
                 ", %88, %89, p, 1, 1, 0, 1;}"
                 : R32(d), R8(d, 32), R8(d, 40), R8(d, 48), R8(d, 56), R8(d, 64), R8(d, 72), R8(d, 80) : "l"(da), "l"(db), "r"(accum));
}

constexpr float EXP_MAGIC = 256.0f + 127.0f + 64.0f - 1.58621f + 0.00390625f;
constexpr uint32_t MUFU_MASK = 0x1111u;
__device__ __forceinline__ uint32_t exp2_pair(float y0, float y1, uint32_t cexp, uint32_t neg1) {
    uint32_t w, m, e, r;
    asm("prmt.b32 %0, %1, %2, 0x6521;" : "=r"(w) : "r"(__float_as_uint(y0)), "r"(__float_as_uint(y1)));
    asm("lop3.b32 %0, %1, 0x007F007F, %2, 0xEA;" : "=r"(m) : "r"(w), "r"(cexp));
    asm("mad.lo.u32 %0, %1, %2, %3;" : "=r"(e) : "r"(m), "r"(neg1), "r"(w));
    asm("fma.rn.bf16x2 %0, %1, %2, %3;" : "=r"(r) : "r"(w), "r"(m), "r"(e));
    return r;
}

struct Params {
    const __nv_bfloat16* x;
    const __nv_bfloat16* wk;
    long long wv_off;
    const __nv_bfloat16* wqp;
    __nv_bfloat16* out;
    uint32_t neg1, pad;
    const __nv_bfloat16* w1p;
    const __nv_bfloat16* w2p;
    CUtensorMap wq, wo, w1, w2;
    const __nv_bfloat16* wop;
};

__device__ __forceinline__ void load_box(uint32_t sb, const CUtensorMap* tm, uint32_t dst, uint32_t bar, uint32_t bytes, int c0, int c1) {
    mbar_expect(sb + SM_MISC + bar * 8, bytes);
    tma2d(sb + dst, tm, c0, c1, sb + SM_MISC + bar * 8);
}
__device__ __forceinline__ void load_wq(uint32_t sb, const Params& P, int gi, int atom) {
    load_box(sb, &P.wq, SM_WQ + atom * 65536 + gi * 16384, MB_WQ + gi, 16384, (blockIdx.x & 3) * 128 + atom * 64, gi * 128);
}
__device__ __forceinline__ void load_wo(uint32_t sb, const Params& P, int kb) { load_box(sb, &P.wo, wo_slot(kb) * SLOT, MB_WO, SLOT, (blockIdx.x & 7) * 64, kb * 64); }
__device__ __forceinline__ void refill_job(uint32_t sb, const Params& P, int gi, int job) {
    const bool w1 = job < 3;
    load_box(sb, w1 ? &P.w1 : &P.wo, (w1 ? 12 + gi + 4 * job : 2 * gi + job - 3) * SLOT, w1 ? MB_W1 + gi : MB_WO, SLOT,
             (blockIdx.x & 7) * (w1 ? 176 : 64) + (w1 ? job * 64 : 0), (w1 ? gi : 2 * gi + job - 1) * 64);
}

__host__ __device__ constexpr int ring_entry(int n) { return n < 32 ? (n & 3) : (n - 32) % 6; }
__host__ __device__ constexpr uint32_t ring_slot(int e) { return e < 4 ? 24 + e : e; }

template <int KIND> __host__ __device__ constexpr uint64_t b_slots(int first) {
    uint64_t v = 0;
    for (int i = first; i < first + 12; i++) v |= (uint64_t)((KIND == 0 ? wo_slot(i) : KIND == 1 ? w1_slot(i, 0) : w1_slot(i / 3, i % 3)) & 31) << (5 * (i - first));
    return v;
}
__device__ __forceinline__ uint64_t desc64(uint32_t lo, uint32_t hi) { uint64_t d; asm("mov.b64 %0, {%1, %2};" : "=l"(d) : "r"(lo), "r"(hi)); return d; }
__device__ __forceinline__ uint32_t mbar_test(uint32_t bar) {
    uint32_t done;
    asm volatile("{.reg .pred p; mbarrier.test_wait.parity.shared::cta.b64 p, [%1], 0; selp.u32 %0, 1, 0, p;}" : "=r"(done) : "r"(bar) : "memory");
    return done;
}
template <int KIND, int NACC>
__device__ __forceinline__ bool gemm_ss(float (&acc)[NACC], uint32_t sb, int pr TS_ARG) {
    const uint32_t mb = sb + SM_MISC;
    constexpr int NBLK = KIND == 2 ? 22 : 8, N0 = 16 * KIND;
    uint32_t full = mb + (MB_FULL + N0 + pr * NBLK) * 8, empty = mb + MB_NULL * 8, rel = mb + MB_NULL * 8;
    const uint32_t lane = threadIdx.x & 31, probe = sb + ((threadIdx.x >> 5) & 3) * 512 + (lane >> 4) * 2048 + (lane & 15) * 32 + (lane >> 2) * 4;
    uint32_t m = 0;
    constexpr uint32_t R4S = 24 | 25 << 5 | 26 << 10 | 27 << 15;
    uint32_t ra = KIND == 2 ? (pr ? (4 | 5 << 5 | R4S << 10) : (R4S | 4 << 20 | 5 << 25)) : (KIND == 0 && pr) ? (6 | 7 << 5 | 8 << 10 | 9 << 15) : R4S;
    uint64_t tab = b_slots<KIND>(0);
    const uint32_t a0 = (sb >> 4) | (8 << 16);
    uint32_t b0 = (sb >> 4) | ((KIND == 1 ? 4 * SLOT / 16 : 1) << 16);
    mbar_wait(full);
#pragma unroll 1
    for (int i = 0; i < NBLK; i++) {
        const uint32_t sa = ra & 31, da = a0 + sa * 512, db = b0 + ((uint32_t)tab & 31) * 512;
        full += (i == NBLK - 1) ? 0 : 8;
        const uint32_t ready = mbar_test(full);
        const uint32_t m0 = lds32(probe + sa * SLOT), m1 = lds32(probe + sa * SLOT + 4096);
        wg_fence();
#pragma unroll
        for (int s = 0; s < 4; s++) mma_ss(acc, desc64(da + s * 128, 16), desc64(db + s * 128, 0x40000040), s ? 1 : i);
        wg_commit();
        m = max(m, max(m0, m1));
        const uint32_t prev = empty, prel = rel;
        empty = mb + ((KIND == 0 && sa < 24) ? MB_NULL : MB_EMPTY + (sa & 7)) * 8;
        rel = mb + (KIND == 1 ? MB_REL + i : i == 3 ? MB_REL + 9 : MB_NULL) * 8;
        ra = KIND == 2 ? (ra >> 5) | (sa << 25) : i == 3 ? R4S : ra >> 5;
        tab = (KIND == 2 && i == 11) ? b_slots<KIND>(12) : tab >> 5;
        if (KIND == 1 && i == 3) b0 -= (3 * SLOT / 16) << 16;
        wg_wait<1>();
        warp_done(prev);
        if (KIND != 2) warp_done(prel);
        if (!__all_sync(0xffffffffu, ready)) mbar_wait(full);
    }
    bool bad = __any_sync(0xffffffffu, m == SENT);
    wg_wait<0>();
    fence_regs(acc);
    warp_done(empty);
    if (KIND != 2) warp_done(mb + (MB_REL + 8 - KIND) * 8);
    return __builtin_expect(bad, 0);
}
__device__ __forceinline__ void ring_feed(uint32_t sb, int e TS_ARG) {
    const uint32_t mb = sb + SM_MISC, dst = sb + ring_slot(e) * SLOT, empty = mb + (MB_EMPTY + e) * 8;
    const bool lead = (threadIdx.x & 31) == 0;
    const uint4* base = g_x + (blockIdx.x >> 3) * 4096 + e * 512;
    uint32_t par = 0;
    auto fetch = [&](int n, const uint4* src, int job) {
        const uint32_t full = mb + (MB_FULL + n) * 8;
        if (lead) mbar_expect(full, SLOT);
        mbar_wait(empty, par); par ^= 1;
        if (job) mbar_wait(mb + (MB_READY + job) * 8);
        if (lead) bulk_g2s(dst, src, SLOT, full);
        __syncwarp();
    };
    if (e < 4) {
        fetch(4 + e, base + 2048, 0);
        if (lead) mbar_expect(mb + (MB_FULL + 8 + e) * 8, SLOT);
        mbar_wait(mb + (MB_DONE + 4) * 8);
        mbar_wait(mb + (MB_READY + 1) * 8);
        if (lead) bulk_g2s(sb + (6 + e) * SLOT, base + 65536, SLOT, mb + (MB_FULL + 8 + e) * 8);
        fetch(12 + e, base + 65536 + 2048, 0);
#pragma unroll 1
        for (int h = 0; h < 2; h++) {
            fetch(16 + 8 * h + e, base + X_H1 + h * 65536, 2 + h);
            fetch(20 + 8 * h + e, base + X_H1 + h * 65536 + 2048, 0);
        }
    } else {
        mbar_wait(mb + (MB_REL + 7) * 8);
        par = 1;
    }
    const uint4* src = g_x + X_H2 + (blockIdx.x >> 3) * 88 * 128 + e * 512;
#pragma unroll 1
    for (int n = e; n < 44; n += 6, src += 6 * 512) {
        const bool second = n >= 22 && n < 28;
        if (second) src += 16 * 88 * 128 - 22 * 512;
        fetch(32 + n, src, n < 6 ? 4 : second ? 5 : 0);
    }
}
__device__ __noinline__ void gemm_slow_impl(float* out, int ntile, const uint4* a, int nst, const __nv_bfloat16* W, int ldw, int kmax, int n0) {
    const int lane = threadIdx.x & 31;
    const unsigned short* w = reinterpret_cast<const unsigned short*>(W);
    for (int j = 0; j < ntile; j++) {
        const uint32_t* p = reinterpret_cast<const uint32_t*>(a) + ((threadIdx.x >> 5) & 3) * 128 + lane;
        const int n = n0 + 8 * j + (lane >> 2);
        float d[4] = {0.f, 0.f, 0.f, 0.f};
        for (int st = 0; st < nst; st++, p += 512) {
            const int k = st * 16 + 2 * (lane & 3);
            uint32_t v0, v1, v2, v3, b0 = 0, b1 = 0; int spins = 0;
            do { v0 = ldg32_relaxed(p); v1 = ldg32_relaxed(p + 64); v2 = ldg32_relaxed(p + 32); v3 = ldg32_relaxed(p + 96); }
            while (__any_sync(0xffffffffu, max(max(v0, v1), max(v2, v3)) == SENT) && ++spins < SPIN_LIMIT);
            if (k < kmax && n < ldw) {
                const unsigned short* q = w + (size_t)k * ldw + n;
                b0 = q[0] | ((uint32_t)q[ldw] << 16); b1 = q[8 * ldw] | ((uint32_t)q[9 * ldw] << 16);
            }
            asm volatile("mma.sync.aligned.m16n8k16.row.col.f32.bf16.bf16.f32 {%0,%1,%2,%3}, {%4,%5,%6,%7}, {%8,%9}, {%0,%1,%2,%3};"
                         : R4(d, 0) : "r"(v0), "r"(v1), "r"(v2), "r"(v3), "r"(b0), "r"(b1));
        }
        *reinterpret_cast<float4*>(out + 4 * j) = make_float4(d[0], d[1], d[2], d[3]);
    }
}
template <int NACC>
__device__ __forceinline__ void gemm_slow(float (&acc)[NACC], const uint4* a, int nst, const __nv_bfloat16* W, int ldw, int kmax, int n0) {
    __align__(16) float tmp[NACC];
    gemm_slow_impl(tmp, NACC / 4, a, nst, W, ldw, kmax, n0);
#pragma unroll
    for (int i = 0; i < NACC; i++) acc[i] = tmp[i];
}
__device__ __forceinline__ void store_tile(uint32_t* p, uint32_t r0k0, uint32_t r8k0, uint32_t r0k8, uint32_t r8k8) {
    stg32(p, r0k0); stg32(p + 32, r0k8); stg32(p + 64, r8k0); stg32(p + 96, r8k8);
}

__device__ __forceinline__ float quad_sum(float v) { v += __shfl_xor_sync(0xffffffffu, v, 1); v += __shfl_xor_sync(0xffffffffu, v, 2); return v; }
__device__ __forceinline__ float reduce4(const float (&st)[4], int lane) {
    const bool u16 = lane & 16, u8 = lane & 8;
    const float a0 = (u16 ? st[2] : st[0]) + __shfl_xor_sync(0xffffffffu, u16 ? st[0] : st[2], 16);
    const float a1 = (u16 ? st[3] : st[1]) + __shfl_xor_sync(0xffffffffu, u16 ? st[1] : st[3], 16);
    float v = (u8 ? a1 : a0) + __shfl_xor_sync(0xffffffffu, u8 ? a0 : a1, 8);
    v += __shfl_xor_sync(0xffffffffu, v, 4); v += __shfl_xor_sync(0xffffffffu, v, 2); v += __shfl_xor_sync(0xffffffffu, v, 1);
    return v;
}
__device__ __forceinline__ float silu2(float h) { float t; asm("tanh.approx.f32 %0, %1;" : "=f"(t) : "f"(h)); return fmaf(h, t, h); }

template <bool SAFE>
__device__ __forceinline__ void attention(const Params& P, uint32_t sb, int warp TS_ARG) {
    const uint32_t mb = sb + SM_MISC;
    const int tid = threadIdx.x, lane = tid & 31, b = blockIdx.x;
    const int wg = warp >> 2, ww = warp & 3, job = 3 - wg + 4 * ww;
    const uint32_t cexp = 0x9F809F80u + (tid >> 12);
    const uint32_t neg1 = P.neg1;
    unsigned cnt = 0;
    if (SAFE && warp == 8) cnt = ldg32_relaxed(g_s.cnt[C_KV]);
#pragma unroll 1
    for (int pass = 0; pass < 2; pass++) {
    float o[12], s[32];
    const uint64_t dq = mkdesc(sb + SM_Q + (pass * 4 + wg) * 2048, 128, 256, 0);
    uint64_t dk = mkdesc(sb + SM_K, 128, 256, 0), dv = mkdesc(sb + SM_V, 128, 32768, 0);
    float m0 = -INFINITY, m1 = -INFINITY;
#pragma unroll
    for (int i = 0; i < 12; i++) o[i] = 0.f;
#pragma unroll
    for (int i = 0; i < 32; i++) s[i] = ((MUFU_MASK >> (i / 2)) & 1) ? 0.f : EXP_MAGIC;
    fence_regs(s); fence_regs(o);
    wg_fence();
    if (SAFE) mma_qk_f16(s, dq, dk + 31 * 128); else mma_qk_bf16(s, dq, dk + 31 * 128);
    wg_commit();
    wg_wait<0>(); fence_regs(s);
#pragma unroll 1
    for (int u = pass ? 3 : (wg == 2) ? 0 : 1; u < (pass ? 8 : 3); u++) {
        int n = 2 * ((((wg == 2) ? 0x22444C31u : 0x22444C40u) >> (4 * u)) & 15);
#pragma unroll 1
        do {
            uint32_t p[16];
            if (SAFE) {
#pragma unroll
                for (int j = 0; j < 16; j++) {
                    if ((MUFU_MASK >> j) & 1) p[j] = pack_bf16(ex2(s[2 * j]), ex2(s[2 * j + 1]));
                    else p[j] = exp2_pair(s[2 * j], s[2 * j + 1], cexp, neg1);
                }
            } else {
                fence_regs(o);
                float x0 = m0, x1 = m1;
#pragma unroll
                for (int j = 0; j < 8; j++) { x0 = fmaxf(x0, fmaxf(s[4 * j], s[4 * j + 1])); x1 = fmaxf(x1, fmaxf(s[4 * j + 2], s[4 * j + 3])); }
                x0 = fmaxf(x0, __shfl_xor_sync(0xffffffffu, x0, 1)); x0 = fmaxf(x0, __shfl_xor_sync(0xffffffffu, x0, 2));
                x1 = fmaxf(x1, __shfl_xor_sync(0xffffffffu, x1, 1)); x1 = fmaxf(x1, __shfl_xor_sync(0xffffffffu, x1, 2));
                const float c0 = ex2(m0 - x0), c1 = ex2(m1 - x1);
                m0 = x0; m1 = x1;
#pragma unroll
                for (int j = 0; j < 3; j++) { o[4 * j] *= c0; o[4 * j + 1] *= c0; o[4 * j + 2] *= c1; o[4 * j + 3] *= c1; }
#pragma unroll
                for (int j = 0; j < 8; j++) {
                    p[2 * j] = pack_bf16(ex2(s[4 * j] - m0), ex2(s[4 * j + 1] - m0));
                    p[2 * j + 1] = pack_bf16(ex2(s[4 * j + 2] - m1), ex2(s[4 * j + 3] - m1));
                }
                fence_regs(o);
            }
            fence_regs(p);
            wg_fence();
            if (SAFE) mma_qk_f16(s, dq, dk); else mma_qk_bf16(s, dq, dk);
#pragma unroll
            for (int j = 0; j < 4; j++) mma_pv(o, p + 4 * j, dv + j * 16);
            wg_commit();
            dk += 128; dv += 64;
            wg_wait<0>(); fence_regs(s);
        } while (--n > 0);
        if (u == 2 || u == 7) {
            fence_regs(o);
            const float i0 = rcp(o[8]), i1 = rcp(o[10]);
            if (u == 7) mbar_wait(mb + MB_MID * 8);
            store_tile(reinterpret_cast<uint32_t*>(g_x + X_O + (((u == 7) * 16 + (b >> 3)) * 32 + (b & 3) * 8 + 2 * wg + (ww >> 1)) * 128 + (((b >> 2) & 1) * 2 + (ww & 1)) * 32) + lane,
                       pack_bf16(o[0] * i0, o[1] * i0), pack_bf16(o[2] * i1, o[3] * i1), pack_bf16(o[4] * i0, o[5] * i0), pack_bf16(o[6] * i1, o[7] * i1));
            if (u == 2) asm volatile("cp.async.bulk.wait_group 0;" ::: "memory");
            else count_hint(C_O + 16 + (b >> 3));
            warp_done(mb + (MB_DONE + (u == 7) * 4) * 8);
            TS(5 + (u == 7));
        } else if (u >= 3) {
            if (u < 6) warp_done(mb + (MB_DONE + u - 2) * 8);
            if (job < (u == 3 ? 1 : 5)) {
                mbar_wait(mb + (MB_DONE + u - 3) * 8);
                if (u == 3) count_release(C_MID);
                else if (lane == 0) refill_job(sb, P, u - 4, job);
            } else if (u == 6) {
                if (job < 9) {
                    mbar_wait(mb + MB_MID * 8);
                    if (lane == 0) {
                        mbar_expect(mb + (MB_FULL + job - 5) * 8, SLOT);
                        bulk_g2s(sb + (19 + job) * SLOT, g_x + X_O + (b >> 3) * 4096 + (job - 5) * 512, SLOT, mb + (MB_FULL + job - 5) * 8);
                    }
                }
            } else if (warp == 7) {
                if (u == 4) cnt = ldg32_relaxed(g_s.cnt[C_MID]);
                if (u == 5) {
                    const unsigned target = lds32(mb + MISC_EPOCH) * NCTA;
                    if (__any_sync(0xffffffffu, cnt != target)) count_wait(C_MID, target);
                    asm volatile("fence.acquire.gpu; fence.proxy.async.global;" ::: "memory");
                    warp_done(mb + MB_MID * 8);
                }
            }
        } else if (u == 1) {
            if (SAFE) mbar_wait(mb + MB_KV * 8);
            TS(17);
            if (lane == 0) {
                if (job < 9) {
                    asm volatile("cp.async.bulk.global.shared::cta.bulk_group [%0], [%1], %2;"
                                 :: "l"(g_x + X_ARM + b * X_SHARE + job * 512), "r"(sb + SM_SENT), "r"(job < 8 ? 8192 : (X_SHARE - 4096) * 16) : "memory");
                    asm volatile("cp.async.bulk.commit_group;" ::: "memory");
                } else if (job < 11) load_wo(sb, P, job - 9);
            }
        } else if (SAFE) {
            if (warp == 8) {
                const unsigned target = lds32(mb + MISC_EPOCH) * NMAIN;
                if (__any_sync(0xffffffffu, cnt != target)) count_wait(C_KV, target);
                if (lane == 0) {
                    asm volatile("fence.acquire.gpu; fence.proxy.async.global;" ::: "memory");
                    mbar_expect(mb + MB_KV * 8, 47104 + 2 * 24576);
                    bulk_g2s(sb + SM_K + 16384, g_s.kv + 1024, 47104, mb + MB_KV * 8);
                    bulk_g2s(sb + SM_V + 8192, g_s.kv + 4096 + 512, 24576, mb + MB_KV * 8);
                    bulk_g2s(sb + SM_V + 32768 + 8192, g_s.kv + 6144 + 512, 24576, mb + MB_KV * 8);
                }
            }
        }
        __syncwarp();
    }
    }
}

__device__ __forceinline__ int kv_slot(int idx) {
    const int t = (idx & 63) >> 1, c = 2 * (blockIdx.x >> 2) + (idx & 1), hg = blockIdx.x & 3;
    return hg < 2 ? ((t + 31) & 31) * 128 + (c >> 3) * 16 + (hg & 1) * 8 + (c & 7) : 4096 + (hg & 1) * 2048 + t * 64 + c;
}

__device__ __noinline__ void helper_cta(const Params& P, uint8_t* smem) {
    const int tid = threadIdx.x, b = blockIdx.x, hi = b - NMAIN;
    const unsigned epoch = g_s.epoch[b] + 1;
    float* red = reinterpret_cast<float*>(smem);
    if (tid < 32) count_wait(C_KV, epoch * NMAIN);
    __syncthreads();
    if (tid == 480) {
        for (int i = 0; i < 8; i++) asm volatile("cp.async.bulk.prefetch.L2.global [%0], %1;" :: "l"((const char*)P.wop + hi * 131072 + i * 16384), "r"(16384) : "memory");
        for (int i = 0; i < 43; i++) asm volatile("cp.async.bulk.prefetch.L2.global [%0], %1;" :: "l"((const char*)P.w2p + hi * 352256 + i * 8192), "r"(8192) : "memory");
    }
    if (tid < 344) {
        const int cg = tid % 43, rp = tid / 43;
        const uint4* src = reinterpret_cast<const uint4*>(P.w1p + (size_t)rp * 64 * FF + (hi * 43 + cg) * 8);
        float s[8] = {0, 0, 0, 0, 0, 0, 0, 0};
#pragma unroll 8
        for (int r = 0; r < 64; r++) {
            uint4 v = __ldg(src + r * (FF / 8));
            s[0] += bf_lo(v.x); s[1] += bf_hi(v.x); s[2] += bf_lo(v.y); s[3] += bf_hi(v.y);
            s[4] += bf_lo(v.z); s[5] += bf_hi(v.z); s[6] += bf_lo(v.w); s[7] += bf_hi(v.w);
        }
        float* part = red + (rp * 43 + cg) * 8;
#pragma unroll
        for (int i = 0; i < 8; i++) part[i] = s[i];
    }
    __syncthreads();
    if (tid < 344) {
        float s = 0.f;
#pragma unroll
        for (int rp = 0; rp < 8; rp++) s += red[rp * 344 + tid];
        g_s.cs[hi * 344 + tid] = s;
    } else if (hi == 3 && tid < 344 + 64) g_s.cs[FF + tid - 344] = 0.f;
    __syncthreads();
    if (tid < 32) count_release(C_MID);
    if (tid == 0) g_s.epoch[b] = epoch;
}

__global__ void __launch_bounds__(512, 1) fused_kernel(const __grid_constant__ Params P) {
    extern __shared__ __align__(1024) uint8_t smem[];
    const uint32_t sb = (uint32_t)__cvta_generic_to_shared(smem);
    const uint32_t mb = sb + SM_MISC;
    const int tid = threadIdx.x, lane = tid & 31, b = blockIdx.x;
    if (b >= NMAIN) { helper_cta(P, smem); return; }
    const int tg = b >> 2, hg = b & 3;
    const int warp = __shfl_sync(0xffffffffu, tid >> 5, 0);

    uint4 xv[4][2];
    unsigned epoch = 0;
    {
        const int r = (tid >> 5) * 4;
        const uint4* src = reinterpret_cast<const uint4*>(P.x + (size_t)((r & 31) + tg * 32 + (r >> 5) * 1024) * D) + lane;
#pragma unroll
        for (int i = 0; i < 4; i++) { xv[i][0] = ldg_relaxed(src + i * 64); xv[i][1] = ldg_relaxed(src + i * 64 + 32); }
    }
    const uint4 wkv = ldg_relaxed(reinterpret_cast<const uint4*>(reinterpret_cast<const char*>(P.wk) + (hg < 2 ? 0 : P.wv_off)) + tid * 2 + (hg & 1));
    const int wg = warp >> 2, ww = warp & 3, g = lane >> 2, t4 = lane & 3, t128 = tid & 127;
    if (lane == 0) {
        if (warp < 4) {
            mbar_init(mb + (MB_WQ + warp) * 8, 2);
            asm volatile("fence.mbarrier_init.release.cluster;" ::: "memory");
            load_wq(sb, P, warp, 0);
            load_wq(sb, P, warp, 1);
        } else if (warp < 7) {
            asm volatile("prefetch.tensormap [%0];" :: "l"(&P.wo + (warp - 4)) : "memory");
        } else if (warp == 7) {
            asm volatile("ld.relaxed.gpu.global.u32 %0, [%1];" : "=r"(epoch) : "l"(g_s.epoch + b) : "memory");
        } else if (warp == 8) {
            sts128(mb + MISC_NRM, 0, 0, 0, 0);

        }
    }
    __syncwarp();
    TS(16);
    float dlt;
    {
        float st[4];
#pragma unroll
        for (int i = 0; i < 4; i++) {
            const uint32_t s = add_bf16x2(add_bf16x2(add_bf16x2(xv[i][0].x, xv[i][0].y), add_bf16x2(xv[i][0].z, xv[i][0].w)),
                                          add_bf16x2(add_bf16x2(xv[i][1].x, xv[i][1].y), add_bf16x2(xv[i][1].z, xv[i][1].w)));
            st[i] = bf_lo(s) + bf_hi(s);
        }
        TS(13);
        const float tot = reduce4(st, lane) * (-1.0f / D);
        const uint32_t nmr = pack_bf16(tot, tot);
        dlt = bf_lo(nmr) - tot;
        const uint32_t xa = sb + SM_XN + (lane >> 3) * 8192 + warp * 512;
#pragma unroll
        for (int i = 0; i < 4; i++) {
            const uint32_t nm = __shfl_sync(0xffffffffu, nmr, i * 8);
            const uint32_t addr = xa + i * 128 + (((lane & 7) ^ ((warp & 1) * 4 + i)) << 4);
#pragma unroll
            for (int c = 0; c < 2; c++) {
                xv[i][c].x = add_bf16x2(xv[i][c].x, nm); xv[i][c].y = add_bf16x2(xv[i][c].y, nm);
                xv[i][c].z = add_bf16x2(xv[i][c].z, nm); xv[i][c].w = add_bf16x2(xv[i][c].w, nm);
                sts128(addr + c * 32768, xv[i][c].x, xv[i][c].y, xv[i][c].z, xv[i][c].w);
            }
        }
    }
    sts128(sb + SM_WKV + tid * 16, wkv.x, wkv.y, wkv.z, wkv.w);
    fence_async_smem();
    TS(0);
    __syncthreads();
    auto variances = [&]() {
        float st[4];
#pragma unroll
        for (int i = 0; i < 4; i++) {
            float v = 0.f;
#pragma unroll
            for (int c = 0; c < 2; c++) {
                const uint32_t a = fma_bf16x2(xv[i][c].x, xv[i][c].x, mul_bf16x2(xv[i][c].y, xv[i][c].y));
                const uint32_t d = fma_bf16x2(xv[i][c].z, xv[i][c].z, mul_bf16x2(xv[i][c].w, xv[i][c].w));
                v += (bf_lo(a) + bf_hi(a)) + (bf_lo(d) + bf_hi(d));
            }
            st[i] = v;
        }
        const float vs = reduce4(st, lane), dl = dlt;
        if ((lane & 7) == 0) sts32(sb + SM_RSTD + (warp * 4 + (lane >> 3)) * 4, __float_as_uint(rsqrtf(fmaxf(vs * (1.0f / D) - dl * dl, 0.f) + 1e-5f)));
    };
    float kv[4] = {0.f, 0.f, 0.f, 0.f};
    if (wg == 2) {
        fence_regs(kv);
        const uint64_t da = mkdesc(sb + SM_XN, 16, 1024, 1), db = mkdesc(sb + SM_WKV, 128, 16, 0);
        wg_fence();
#pragma unroll
        for (int s = 0; s < 32; s++) mma_ss8(kv, da + (s >> 2) * 512 + (s & 3) * 2, db + s * 16);
        wg_commit();
        variances();
        wg_wait<0>(); fence_regs(kv);
    } else {
        variances();
        if (tid == 7 * 32) { sts32(mb + MISC_EPOCH, epoch + 1); g_s.epoch[b] = epoch + 1; }
    }
    __syncthreads();
    constexpr float QSCALE = 0.25f * 1.4426950408889634f;
    float qa[64];
    const uint32_t qbase = sb + SM_Q + (ww >> 1) * 8192 + (ww & 1) * 512 + lane * 16;
    if (wg == 0) {
#pragma unroll
        for (int i = 0; i < 64; i++) qa[i] = 0.f;
        fence_regs(qa);
        const uint64_t da = mkdesc(sb + SM_XN, 16, 1024, 1), db = mkdesc(sb + SM_WQ, 65536, 1024, 1);
#pragma unroll 1
        for (int i = 0; i < 4; i++) {
            mbar_wait(mb + (MB_WQ + i) * 8);
            wg_fence();
#pragma unroll
            for (int s = 0; s < 8; s++) mma_ss128(qa, da + (i * 2 + (s >> 2)) * 512 + (s & 3) * 2, db + (i * 8 + s) * 128);
            wg_commit();
        }
        const float rs0 = __uint_as_float(lds32(sb + SM_RSTD + (ww * 16 + g) * 4)) * QSCALE, rs1 = __uint_as_float(lds32(sb + SM_RSTD + (ww * 16 + g + 8) * 4)) * QSCALE;
        wg_wait<0>();
        fence_regs(qa);
        bar_arrive(6, 256);
        bar_sync(5, 256);
        TS(1);
        uint32_t nm = 0;
#pragma unroll
        for (int h = 0; h < 8; h++) {
#pragma unroll
            for (int i = 0; i < 8; i++) qa[8 * h + i] *= (i & 2) ? rs1 : rs0;
            stsm4(qbase + h * 1024, pack_f16(qa[8 * h], qa[8 * h + 1]), pack_f16(qa[8 * h + 4], qa[8 * h + 5]), pack_f16(qa[8 * h + 2], qa[8 * h + 3]), pack_f16(qa[8 * h + 6], qa[8 * h + 7]));
            const float n0 = qa[8 * h] * qa[8 * h] + qa[8 * h + 1] * qa[8 * h + 1] + qa[8 * h + 4] * qa[8 * h + 4] + qa[8 * h + 5] * qa[8 * h + 5];
            const float n1 = qa[8 * h + 2] * qa[8 * h + 2] + qa[8 * h + 3] * qa[8 * h + 3] + qa[8 * h + 6] * qa[8 * h + 6] + qa[8 * h + 7] * qa[8 * h + 7];
            nm = max(nm, max(__float_as_uint(n0), __float_as_uint(n1)));
        }
        nm = __reduce_max_sync(0xffffffffu, __float_as_uint(quad_sum(__uint_as_float(nm))));
        if (lane == 0) asm volatile("red.shared.max.u32 [%0], %1;" :: "r"(mb + MISC_NRM), "r"(nm) : "memory");
    } else if (wg == 1) {
        if (lane == 0) {
            if (ww == 0) {
#pragma unroll
                for (uint32_t i = 4; i < 35; i++) mbar_init(mb + i * 8, bar_count(i));
            } else if (ww == 1) {
#pragma unroll
                for (uint32_t i = 35; i < 67; i++) mbar_init(mb + i * 8, bar_count(i));
            } else {
#pragma unroll
                for (uint32_t i = 0; i < 30; i++) mbar_init(mb + (ww * 30 + 7 + i) * 8, 2);
            }
        }
        __syncwarp();
#pragma unroll
        for (int i = 0; i < 4; i++) sts128(sb + SM_SENT + (i * 128 + t128) * 16, SENT, SENT, SENT, SENT);
        bar_sync(5, 256);
#pragma unroll
        for (int i = 0; i < 16; i++) sts128(sb + SM_V + 65536 + (i * 128 + t128) * 16, 0x3F803F80u, 0x3F803F80u, 0x3F803F80u, 0x3F803F80u);
    } else if (wg == 2) {
        const float rs0 = __uint_as_float(lds32(sb + SM_RSTD + (ww * 16 + g) * 4)), rs1 = __uint_as_float(lds32(sb + SM_RSTD + (ww * 16 + g + 8) * 4));
        kv[0] *= rs0; kv[1] *= rs0; kv[2] *= rs1; kv[3] *= rs1;
        float2* kt = reinterpret_cast<float2*>(smem + SM_KTMP);
        kt[(ww * 16 + g) * 4 + t4] = make_float2(kv[0], kv[1]); kt[(ww * 16 + g + 8) * 4 + t4] = make_float2(kv[2], kv[3]);
        float n0 = kv[0] * kv[0] + kv[1] * kv[1], n1 = kv[2] * kv[2] + kv[3] * kv[3];
        n0 += __shfl_xor_sync(0xffffffffu, n0, 1); n1 += __shfl_xor_sync(0xffffffffu, n1, 1);
        n0 += __shfl_xor_sync(0xffffffffu, n0, 2); n1 += __shfl_xor_sync(0xffffffffu, n1, 2);
        const uint32_t nm = __reduce_max_sync(0xffffffffu, max(__float_as_uint(n0), __float_as_uint(n1)));
        if (lane == 0) sts32(sb + SM_WNRM + ww * 4, nm | 1u);
        bar_sync(2, 128);
        const uint32_t ra = sb + SM_KTMP + ((t128 & 1) * 32 + ((t128 & 63) >> 1)) * 32;
        const float4 c0 = lds128f(ra), c1 = lds128f(ra + 16);
        const int kvoff = kv_slot(tid);
        if (ww < 2) {
            if (hg < 2) {
                float4 p0 = lds128f(ra - 32), p1 = lds128f(ra - 16);
                if (t128 < 2) { p0 = make_float4(0.f, 0.f, 0.f, 0.f); p1 = p0; }
                stg128(g_s.kv + kvoff, nonzero(pack_f16(c0.x - p0.x, c0.y - p0.y)), pack_f16(c0.z - p0.z, c0.w - p0.w), pack_f16(c1.x - p1.x, c1.y - p1.y), pack_f16(c1.z - p1.z, c1.w - p1.w));
            } else {
                stg128(g_s.kv + kvoff, nonzero(pack_bf16(c0.x, c0.y)), pack_bf16(c0.z, c0.w), pack_bf16(c1.x, c1.y), pack_bf16(c1.z, c1.w));
            }
            if (t128 < 2) { const float4 w = lds128f(sb + SM_WNRM); stg128(g_s.nrm + b * 2 + t128, __float_as_uint(w.x), __float_as_uint(w.y), __float_as_uint(w.z), __float_as_uint(w.w)); }
            count_hint(C_KVH);
        } else if (hg < 2) {
            stg128(g_s.kplain + kvoff, pack_bf16(c0.x, c0.y), pack_bf16(c0.z, c0.w), pack_bf16(c1.x, c1.y), pack_bf16(c1.z, c1.w));
        }
        TS(1);
        bar_sync(2, 128);
        if (ww == 3) count_release(C_KV);
    } else {
        uint4 kc[18];
        auto src = [&](int i) { return i < 8 ? g_s.kv + i * 128 : i < 12 ? g_s.kv + 4096 + (i - 8) * 128 : i < 16 ? g_s.kv + 6144 + (i - 12) * 128 : i == 16 ? g_s.kv + 31 * 128 : g_s.nrm + t128; };
        count_wait(C_KVH, lds32(mb + MISC_EPOCH) * (NMAIN * 2));
        TS(1);
        int spins = 0;
        while (true) {
#pragma unroll
            for (int i = 0; i < 18; i++) kc[i] = ldg_relaxed(src(i) + t128);
            uint32_t mn = 1;
#pragma unroll
            for (int i = 0; i < 18; i++) mn = min(mn, kc[i].x);
            if (!__any_sync(0xffffffffu, mn == 0u) || ++spins >= SPIN_LIMIT) break;
        }
        uint32_t nm = max(max(kc[17].x, kc[17].y), max(kc[17].z, kc[17].w));
        nm = max(nm, __shfl_xor_sync(0xffffffffu, nm, 4)); nm = max(nm, __shfl_xor_sync(0xffffffffu, nm, 8)); nm = max(nm, __shfl_xor_sync(0xffffffffu, nm, 16));
        if (lane < 4) asm volatile("red.shared.max.u32 [%0], %1;" :: "r"(mb + MISC_NRM + 4 + min(lane, 2) * 4), "r"(nm) : "memory");
        TS(2);
        bar_sync(6, 256);
#pragma unroll
        for (int i = 0; i < 17; i++) sts128(sb + (uint32_t)(src(i) - g_s.kv + t128) * 16 + ((i >= 8 && i < 16) ? SM_V - 65536 : 0), kc[i].x, kc[i].y, kc[i].z, kc[i].w);
    }
    fence_async_smem();
    TS(3);
    __syncthreads();
    const float4 nr = lds128f(mb + MISC_NRM);
    const bool safe = __all_sync(0xffffffffu, (nr.x * (nr.y + nr.z) <= 3500.0f) && (nr.x <= 65536.0f) && (nr.y + nr.z <= 65536.0f) && (nr.w <= 1e24f));
    TS(4);

    if (__builtin_expect(safe, 1)) {
        attention<true>(P, sb, warp TS_PASS);
    } else {
        if (wg == 0) {
#pragma unroll
            for (int h = 0; h < 8; h++)
                stsm4(qbase + h * 1024, pack_bf16(qa[8 * h], qa[8 * h + 1]), pack_bf16(qa[8 * h + 4], qa[8 * h + 5]), pack_bf16(qa[8 * h + 2], qa[8 * h + 3]), pack_bf16(qa[8 * h + 6], qa[8 * h + 7]));
            fence_async_smem();
        } else if (warp == 15) {
            count_wait(C_KV, lds32(mb + MISC_EPOCH) * NMAIN);
            if (lane == 0) {
                asm volatile("fence.proxy.async;" ::: "memory");
                mbar_expect(mb + MB_KV * 8, 131072);
                bulk_g2s(sb + SM_K, g_s.kplain, 65536, mb + MB_KV * 8);
                bulk_g2s(sb + SM_V, g_s.kv + 4096, 65536, mb + MB_KV * 8);
            }
            __syncwarp();
        }
        __syncthreads();
        mbar_wait(mb + MB_KV * 8);
        attention<false>(P, sb, warp TS_PASS);
    }

    const int j = b & 7;
    if (wg == 1 || wg == 2) {
        if (warp == 8) {
            epoch = lds32(mb + MISC_EPOCH);
#pragma unroll 1
            for (int job = 1; job < 6; job++) {
                count_wait(C_O + 32 * (job >> 1) + (job & 1) * 16 + (b >> 3), epoch * (job == 1 ? 128 : 32));
                asm volatile("fence.proxy.async.global;" ::: "memory");
                warp_done(mb + (MB_READY + job) * 8);
                TS(18 + job);
            }
        } else if (warp == 9) {
#pragma unroll
            for (int i = 0; i < 2; i++) {
                if (lane < 22) {
                    const uint4 v = ldg_relaxed(reinterpret_cast<const uint4*>(g_s.cs + j * 176) + i * 22 + lane);
                    sts128(mb + MISC_CS + (i * 22 + lane) * 16, v.x, v.y, v.z, v.w);
                }
                stg128(g_s.kv + kv_slot(i * 32 + lane), 0u, 0u, 0u, 0u);
            }
            warp_done(mb + MB_CS * 8);
            if (lane < 2) stg128(g_s.nrm + b * 2 + lane, 0u, 0u, 0u, 0u);
#pragma unroll 1
            for (int i = 0; i < 16; i++) {
                mbar_wait(mb + (MB_W1 + i) * 8);
                const int n = i < 8 ? 16 + i + 8 * (lane & 1) : 32 + 3 * (i - 8) + (lane >> 1) + 22 * (lane & 1);
                if (lane < (i < 8 || i == 15 ? 2 : 6)) mbar_arrive(mb + (MB_FULL + n) * 8);
                __syncwarp();
            }
        } else {
            if (wg == 2) {
#pragma unroll 1
                for (int i = 7 + ww; i < 46; i += 2) {
                    const bool w1 = i < 24;
                    const int n = w1 ? i : i - 24, kb = n / 3, a = n - 3 * kb;
                    mbar_wait(mb + (w1 ? (i < 12 ? MB_DONE + 4 : i < 18 ? MB_REL + 9 : MB_REL + 8) : MB_REL + kb) * 8);
                    if (lane == 0) load_box(sb, w1 ? &P.w1 : &P.w2, w1_slot(kb, a) * SLOT, (w1 ? MB_W1 : MB_W2) + kb, SLOT, w1 ? j * 176 + a * 64 : j * 64, (w1 ? kb : n) * 64);
                    __syncwarp();
                }
            }
            ring_feed(sb, wg == 1 ? ww : ww + 2 TS_PASS);
        }
    } else {
        const int pr = (wg == 0), mt = 16 * pr + (b >> 3);
        uint32_t* const hp = reinterpret_cast<uint32_t*>(g_x + X_H1 + (mt * 32 + j * 4) * 128 + ww * 32) + lane;
        {
            uint32_t hk[16];
            const uint32_t* xp = reinterpret_cast<const uint32_t*>(P.x + (size_t)(mt * 64 + ww * 16 + g) * D + j * 64 + t4 * 2);
#pragma unroll
            for (int k = 0; k < 8; k++) { hk[2 * k] = __ldg(xp + k * 4); hk[2 * k + 1] = __ldg(xp + k * 4 + 8 * (D / 2)); }
            mbar_wait(mb + MB_WO * 8);
            float acc[32];
            if (gemm_ss<0>(acc, sb, pr TS_PASS)) gemm_slow(acc, g_x + X_O + mt * 32 * 128, 32, P.wop, D, D, j * 64);
            TS(7);
#pragma unroll
            for (int i = 0; i < 16; i++) hk[i] = pack_bf16(acc[2 * i] + bf_lo(hk[i]), acc[2 * i + 1] + bf_hi(hk[i]));
#pragma unroll
            for (int k = 0; k < 4; k++) store_tile(hp + k * 512, hk[4 * k], hk[4 * k + 1], hk[4 * k + 2], hk[4 * k + 3]);
            count_hint(C_H1 + mt);
            TS(8);
            float st[4] = {0.f, 0.f, 0.f, 0.f};
#pragma unroll
            for (int i = 0; i < 16; i++) {
                const float lo = bf_lo(hk[i]), hi = bf_hi(hk[i]);
                st[2 * (i & 1)] += lo + hi;
                st[2 * (i & 1) + 1] = fmaf(lo, lo, fmaf(hi, hi, st[2 * (i & 1) + 1]));
            }
#pragma unroll
            for (int o = 1; o < 4; o <<= 1)
#pragma unroll
                for (int i = 0; i < 4; i++) st[i] += __shfl_xor_sync(0xffffffffu, st[i], o);
            if (t4 == 0) stg128(g_x + X_ST + (mt * 8 + j) * 32 + ww * 8 + g, __float_as_uint(st[0]), __float_as_uint(st[1]), __float_as_uint(st[2]), __float_as_uint(st[3]));
        }
        {
            float acc[88];
            const uint4* sp = g_x + X_ST + (mt * 8 + t4) * 32 + ww * 8 + g;
            mbar_wait(mb + (MB_FULL + 16 + pr * 8) * 8);
            uint4 u0 = ldg_relaxed(sp), u1 = ldg_relaxed(sp + 128);
            if (gemm_ss<1>(acc, sb, pr TS_PASS)) gemm_slow(acc, g_x + X_H1 + mt * 32 * 128, 32, P.w1p, FF, D, j * 176);
            TS(9);
            int spins = 0;
            while (__builtin_expect(__any_sync(0xffffffffu, max(u0.x, u1.x) == SENT), 0) && ++spins < SPIN_LIMIT) { u0 = ldg_relaxed(sp); u1 = ldg_relaxed(sp + 128); }
            float st[4] = {__uint_as_float(u0.x) + __uint_as_float(u1.x), __uint_as_float(u0.y) + __uint_as_float(u1.y),
                           __uint_as_float(u0.z) + __uint_as_float(u1.z), __uint_as_float(u0.w) + __uint_as_float(u1.w)};
#pragma unroll
            for (int o = 1; o < 4; o <<= 1)
#pragma unroll
                for (int k = 0; k < 4; k++) st[k] += __shfl_xor_sync(0xffffffffu, st[k], o);
            float nmean[2], hrstd[2];
#pragma unroll
            for (int k = 0; k < 2; k++) {
                nmean[k] = st[2 * k] * (-1.0f / D);
                hrstd[k] = 0.5f * rsqrtf(fmaxf(fmaf(-nmean[k], nmean[k], st[2 * k + 1] * (1.0f / D)), 0.f) + 1e-5f);
                nmean[k] *= hrstd[k];
            }
            mbar_wait(mb + MB_CS * 8);
            uint32_t* hb = reinterpret_cast<uint32_t*>(g_x + X_H2 + (mt * 88 + j * 11) * 128 + ww * 32) + lane;
#pragma unroll
            for (int i = 0; i < 22; i++) {
                float2 cs;
                asm volatile("ld.shared.v2.f32 {%0,%1}, [%2];" : "=f"(cs.x), "=f"(cs.y) : "r"(mb + MISC_CS + i * 32 + t4 * 8));
                const float* z = acc + 4 * i;
                uint32_t* p = hb + (i >> 1) * 512 + (i & 1) * 32;
                stg32(p, pack_bf16(silu2(fmaf(hrstd[0], z[0], nmean[0] * cs.x)), silu2(fmaf(hrstd[0], z[1], nmean[0] * cs.y))));
                stg32(p + 64, pack_bf16(silu2(fmaf(hrstd[1], z[2], nmean[1] * cs.x)), silu2(fmaf(hrstd[1], z[3], nmean[1] * cs.y))));
            }
            count_hint(C_H2 + mt);
            TS(10);
        }
        {
            uint32_t hk[16];
#pragma unroll
            for (int i = 0; i < 16; i++) hk[i] = ldg32_relaxed(hp + (i >> 2) * 512 + ((i & 1) * 2 + ((i >> 1) & 1)) * 32);
            float acc[32];
            if (gemm_ss<2>(acc, sb, pr TS_PASS)) gemm_slow(acc, g_x + X_H2 + mt * 88 * 128, 88, P.w2p, D, FF, j * 64);
            TS(11);
#pragma unroll
            for (int i = 0; i < 16; i++) hk[i] = pack_bf16(acc[2 * i] + bf_lo(hk[i]), acc[2 * i + 1] + bf_hi(hk[i]));
#pragma unroll
            for (int h = 0; h < 4; h++) {
                const uint32_t* v = hk + (h >> 1) * 8 + (h & 1);
                uint32_t v0 = v[0], v1 = v[2], v2 = v[4], v3 = v[6];
                const bool o1 = t4 & 1, o2 = t4 & 2;
                uint32_t a = __shfl_xor_sync(0xffffffffu, o1 ? v0 : v1, 1), c = __shfl_xor_sync(0xffffffffu, o1 ? v2 : v3, 1);
                if (o1) { v0 = a; v2 = c; } else { v1 = a; v3 = c; }
                a = __shfl_xor_sync(0xffffffffu, o2 ? v0 : v2, 2); c = __shfl_xor_sync(0xffffffffu, o2 ? v1 : v3, 2);
                if (o2) { v0 = a; v1 = c; } else { v2 = a; v3 = c; }
                *reinterpret_cast<uint4*>(P.out + (size_t)(mt * 64 + ww * 16 + g + 8 * (h & 1)) * D + j * 64 + (h >> 1) * 32 + t4 * 8) = make_uint4(v0, v1, v2, v3);
            }
        }
    }
    TS(12);
}

typedef CUresult (*EncodeFn)(CUtensorMap*, CUtensorMapDataType, cuuint32_t, void*, const cuuint64_t*, const cuuint64_t*, const cuuint32_t*,
                             const cuuint32_t*, CUtensorMapInterleave, CUtensorMapSwizzle, CUtensorMapL2promotion, CUtensorMapFloatOOBfill);

void encode2d(EncodeFn fn, CUtensorMap* tm, const void* ptr, int rows, int cols, int box_rows, int box_cols, CUtensorMapSwizzle sw) {
    cuuint64_t dims[2] = {(cuuint64_t)cols, (cuuint64_t)rows};
    cuuint64_t strides[1] = {(cuuint64_t)cols * 2};
    cuuint32_t box[2] = {(cuuint32_t)box_cols, (cuuint32_t)box_rows};
    cuuint32_t es[2] = {1, 1};
    fn(tm, CU_TENSOR_MAP_DATA_TYPE_BFLOAT16, 2, const_cast<void*>(ptr), dims, strides, box, es, CU_TENSOR_MAP_INTERLEAVE_NONE, sw,
       CU_TENSOR_MAP_L2_PROMOTION_L2_128B, CU_TENSOR_MAP_FLOAT_OOB_FILL_NONE);
}

}

extern "C" void kernel_launch(void* const* d_in, const int* in_sizes, int n_in, void* d_out, int out_size) {
    (void)in_sizes; (void)n_in; (void)out_size;
    void* fnp = nullptr;
    cudaDriverEntryPointQueryResult qr;
    cudaGetDriverEntryPoint("cuTensorMapEncodeTiled", &fnp, cudaEnableDefault, &qr);
    EncodeFn fn = (EncodeFn)fnp;
    Params P;
    encode2d(fn, &P.wq, d_in[1], D, D, 128, 64, CU_TENSOR_MAP_SWIZZLE_128B);
    P.wk = (const __nv_bfloat16*)d_in[2];
    P.wv_off = (const char*)d_in[3] - (const char*)d_in[2];
    encode2d(fn, &P.wo, d_in[4], D, D, 64, 64, CU_TENSOR_MAP_SWIZZLE_128B);
    encode2d(fn, &P.w1, d_in[6], D, FF, 64, 64, CU_TENSOR_MAP_SWIZZLE_128B);
    encode2d(fn, &P.w2, d_in[7], FF, D, 64, 64, CU_TENSOR_MAP_SWIZZLE_128B);
    P.x = (const __nv_bfloat16*)d_in[0];
    P.w1p = (const __nv_bfloat16*)d_in[6];
    P.w2p = (const __nv_bfloat16*)d_in[7];
    P.wop = (const __nv_bfloat16*)d_in[4];
    P.wqp = (const __nv_bfloat16*)d_in[1];
    P.out = (__nv_bfloat16*)d_out;
    P.neg1 = 0xFFFFFFFFu; P.pad = 0;
    cudaFuncSetAttribute(fused_kernel, cudaFuncAttributeMaxDynamicSharedMemorySize, SMEM_BYTES);
    fused_kernel<<<NCTA, 512, SMEM_BYTES>>>(P);
}
```

```cpp
#include <cuda_runtime.h>
#include <cuda_bf16.h>
#include <cuda.h>
#include <stdint.h>

namespace {

constexpr int D = 512, FF = 1376;
constexpr int NMAIN = 128, NHELP = 4, NCTA = NMAIN + NHELP;
constexpr uint32_t SENT = 0xFFFFFFFFu;
constexpr int SPIN_LIMIT = 1 << 22;

constexpr uint32_t KB = 1024, SLOT = 8192;
constexpr uint32_t SM_XN = 0;
constexpr uint32_t SM_WQ = 64 * KB;
constexpr uint32_t SM_WKV = 192 * KB;
constexpr uint32_t SM_K = 0;
constexpr uint32_t SM_Q = 64 * KB;
constexpr uint32_t SM_V = 96 * KB;
constexpr uint32_t SM_MISC = 224 * KB;
constexpr uint32_t SMEM_BYTES = 227 * KB;
constexpr uint32_t SM_KTMP = 200 * KB;
constexpr uint32_t SM_RSTD = 202 * KB;
constexpr uint32_t SM_WNRM = 203 * KB;
constexpr uint32_t SM_SENT = 208 * KB;
constexpr uint32_t MB_WQ = 0;
constexpr uint32_t MB_CS = 4;
constexpr uint32_t MB_DONE = 5;
constexpr uint32_t MB_EMPTY = 10;
constexpr uint32_t MB_W1 = 16;
constexpr uint32_t MB_W2 = 24;
constexpr uint32_t MB_WO = 32;
constexpr uint32_t MB_REL = 33;
constexpr uint32_t MB_KV = 43;
constexpr uint32_t MB_MID = 44;
constexpr uint32_t MB_READY = 44;
constexpr uint32_t MB_FULL = 50;
constexpr uint32_t MB_NULL = 126;
__host__ __device__ constexpr uint32_t bar_count(uint32_t i) {
    return i >= MB_FULL + 16 ? 2 : i >= MB_KV ? 1 : i >= MB_WO ? 8 : i == MB_W2 + 7 ? 1 : i >= MB_W1 ? 3 : i >= MB_EMPTY ? 4 : i >= MB_DONE ? 16 : 1;
}
constexpr uint32_t MISC_NRM = 1056;
constexpr uint32_t MISC_EPOCH = 1072;
constexpr uint32_t MISC_TS = 1088;
constexpr uint32_t MISC_CS = 1344;

__host__ __device__ constexpr uint32_t wo_slot(int kb) { return kb < 2 ? 10 + kb : kb - 2; }
__host__ __device__ constexpr uint32_t w1_slot(int kb, int a) { return kb < 4 ? 12 + kb + 4 * a : (kb < 6 ? 3 * kb - 6 : 3 * kb - 18) + a; }

struct alignas(128) Small {
    unsigned epoch[160];
    unsigned cnt[100][32];
    float cs[1440];
    uint4 nrm[NMAIN * 2];
    uint4 kv[8192];
    uint4 kplain[4096];
};
__device__ Small g_s;
constexpr int C_KVH = 0, C_KV = 1, C_MID = 2, C_O = 3, C_H1 = 35, C_H2 = 67;
constexpr int X_O = 0, X_H1 = 32 * 32 * 128, X_H2 = 2 * X_H1, X_ST = X_H2 + 32 * 88 * 128, X_END = X_ST + 32 * 8 * 32;
constexpr int X_ARM = 16 * 32 * 128, X_SHARE = (X_END - X_ARM) / NMAIN;
__device__ uint4 g_x[X_END];
#define TS(i) do {} while (0)
#define TSF(k)

#define TS_ARG
#define TS_PASS

__device__ __forceinline__ void mbar_init(uint32_t bar, int cnt) { asm volatile("mbarrier.init.shared::cta.b64 [%0], %1;" :: "r"(bar), "r"(cnt) : "memory"); }
__device__ __forceinline__ void mbar_expect(uint32_t bar, uint32_t bytes) { asm volatile("mbarrier.arrive.expect_tx.shared::cta.b64 _, [%0], %1;" :: "r"(bar), "r"(bytes) : "memory"); }
__device__ __forceinline__ void mbar_arrive(uint32_t bar) { asm volatile("mbarrier.arrive.shared::cta.b64 _, [%0];" :: "r"(bar) : "memory"); }
__device__ __forceinline__ bool mbar_try(uint32_t bar, uint32_t parity) {
    uint32_t done;
    asm volatile("{.reg .pred p; mbarrier.try_wait.parity.shared::cta.b64 p, [%1], %2; selp.u32 %0, 1, 0, p;}" : "=r"(done) : "r"(bar), "r"(parity) : "memory");
    return __all_sync(0xffffffffu, done);
}
__device__ __forceinline__ void mbar_wait(uint32_t bar, uint32_t parity = 0) {
    if (__builtin_expect(!mbar_try(bar, parity), 0)) {
        int spins = 0;
        while (!mbar_try(bar, parity) && ++spins < (SPIN_LIMIT >> 6)) {}
    }
}
__device__ __forceinline__ void tma2d(uint32_t dst, const CUtensorMap* tm, int c0, int c1, uint32_t bar) {
    asm volatile("cp.async.bulk.tensor.2d.shared::cluster.global.mbarrier::complete_tx::bytes [%0], [%1, {%3, %4}], [%2];"
                 :: "r"(dst), "l"(tm), "r"(bar), "r"(c0), "r"(c1) : "memory");
}
__device__ __forceinline__ void bulk_g2s(uint32_t dst, const void* src, uint32_t bytes, uint32_t bar) {
    asm volatile("cp.async.bulk.shared::cluster.global.mbarrier::complete_tx::bytes [%0], [%1], %2, [%3];" :: "r"(dst), "l"(src), "r"(bytes), "r"(bar) : "memory");
}
__device__ __forceinline__ void fence_async_smem() { asm volatile("fence.proxy.async.shared::cta;" ::: "memory"); }
__device__ __forceinline__ void bar_sync(int id, int n) { asm volatile("bar.sync %0, %1;" :: "r"(id), "r"(n) : "memory"); }
__device__ __forceinline__ void bar_arrive(int id, int n) { asm volatile("bar.arrive %0, %1;" :: "r"(id), "r"(n) : "memory"); }
__device__ __forceinline__ void wg_fence() { asm volatile("wgmma.fence.sync.aligned;" ::: "memory"); }
__device__ __forceinline__ void wg_commit() { asm volatile("wgmma.commit_group.sync.aligned;" ::: "memory"); }
template <int N> __device__ __forceinline__ void wg_wait() { asm volatile("wgmma.wait_group.sync.aligned %0;" :: "n"(N) : "memory"); }
template <int N> __device__ __forceinline__ void fence_regs(float (&d)[N]) {
#pragma unroll
    for (int i = 0; i < N; i++) asm volatile("" : "+f"(d[i]) :: "memory");
}
template <int N> __device__ __forceinline__ void fence_regs(uint32_t (&d)[N]) {
#pragma unroll
    for (int i = 0; i < N; i++) asm volatile("" : "+r"(d[i]) :: "memory");
}
__device__ __forceinline__ uint64_t mkdesc(uint32_t addr, uint32_t lbo, uint32_t sbo, uint32_t swz) {
    return (uint64_t)(((addr & 0x3FFFF) >> 4) | ((lbo >> 4) << 16)) | ((uint64_t)((sbo >> 4) | (swz << 30)) << 32);
}
__device__ __forceinline__ float ex2(float x) { float y; asm("ex2.approx.ftz.f32 %0, %1;" : "=f"(y) : "f"(x)); return y; }
__device__ __forceinline__ float rcp(float x) { float y; asm("rcp.approx.ftz.f32 %0, %1;" : "=f"(y) : "f"(x)); return y; }
__device__ __forceinline__ uint32_t pack_bf16(float lo, float hi) { uint32_t r; asm("cvt.rn.bf16x2.f32 %0, %1, %2;" : "=r"(r) : "f"(hi), "f"(lo)); return r; }
__device__ __forceinline__ uint32_t pack_f16(float lo, float hi) { uint32_t r; asm("cvt.rn.f16x2.f32 %0, %1, %2;" : "=r"(r) : "f"(hi), "f"(lo)); return r; }
__device__ __forceinline__ float bf_lo(uint32_t v) { return __uint_as_float(v << 16); }
__device__ __forceinline__ float bf_hi(uint32_t v) { return __uint_as_float(v & 0xFFFF0000u); }
__device__ __forceinline__ uint4 ldg_relaxed(const uint4* p) {
    uint4 v; asm volatile("ld.relaxed.gpu.global.v4.u32 {%0,%1,%2,%3}, [%4];" : "=r"(v.x), "=r"(v.y), "=r"(v.z), "=r"(v.w) : "l"(p) : "memory"); return v;
}
__device__ __forceinline__ void stg128(void* p, uint32_t a, uint32_t b, uint32_t c, uint32_t d) {
    asm volatile("st.relaxed.gpu.global.v4.u32 [%0], {%1,%2,%3,%4};" :: "l"(p), "r"(a), "r"(b), "r"(c), "r"(d) : "memory");
}
__device__ __forceinline__ void stg64(void* p, uint32_t a, uint32_t b) {
    asm volatile("st.relaxed.gpu.global.v2.u32 [%0], {%1,%2};" :: "l"(p), "r"(a), "r"(b) : "memory");
}
__device__ __forceinline__ void sts128(uint32_t a, uint32_t x, uint32_t y, uint32_t z, uint32_t w) {
    asm volatile("st.shared.v4.u32 [%0], {%1,%2,%3,%4};" :: "r"(a), "r"(x), "r"(y), "r"(z), "r"(w) : "memory");
}
__device__ __forceinline__ void sts32(uint32_t a, uint32_t x) { asm volatile("st.shared.u32 [%0], %1;" :: "r"(a), "r"(x) : "memory"); }
__device__ __forceinline__ float4 lds128f(uint32_t a) {
    float4 v; asm volatile("ld.shared.v4.f32 {%0,%1,%2,%3}, [%4];" : "=f"(v.x), "=f"(v.y), "=f"(v.z), "=f"(v.w) : "r"(a) : "memory"); return v;
}
__device__ __forceinline__ uint32_t lds32(uint32_t a) { uint32_t v; asm volatile("ld.shared.u32 %0, [%1];" : "=r"(v) : "r"(a) : "memory"); return v; }
__device__ __forceinline__ uint32_t nonzero(uint32_t w) { return w == 0u ? 0x8000u : w; }
__device__ __forceinline__ void stg32(void* p, uint32_t a) { asm volatile("st.global.u32 [%0], %1;" :: "l"(p), "r"(a) : "memory"); }
__device__ __forceinline__ uint32_t ldg32_relaxed(const void* p) { uint32_t v; asm volatile("ld.relaxed.gpu.global.u32 %0, [%1];" : "=r"(v) : "l"(p) : "memory"); return v; }
__device__ __forceinline__ void count_hint(int id) {
    if ((threadIdx.x & 31) == 0) asm volatile("red.relaxed.gpu.global.add.u32 [%0], 1;" :: "l"(g_s.cnt[id]) : "memory");
}
__device__ __forceinline__ void count_release(int id) {
    __syncwarp();
    if ((threadIdx.x & 31) == 0) asm volatile("red.release.gpu.global.add.u32 [%0], 1;" :: "l"(g_s.cnt[id]) : "memory");
    __syncwarp();
}
__device__ __forceinline__ void count_wait(int id, unsigned target) {
    uint32_t v; int spins = 0;
    do v = ldg32_relaxed(g_s.cnt[id]); while (__any_sync(0xffffffffu, v != target) && ++spins < SPIN_LIMIT);
    asm volatile("fence.acquire.gpu;" ::: "memory");
}
__device__ __forceinline__ void warp_done(uint32_t bar) {
    __syncwarp();
    asm volatile("{.reg .pred p; setp.eq.u32 p, %1, 0; @p mbarrier.arrive.shared::cta.b64 _, [%0];}" :: "r"(bar), "r"(threadIdx.x & 31) : "memory");
}
__device__ __forceinline__ uint32_t mul_bf16x2(uint32_t a, uint32_t b) { uint32_t r; asm("mul.rn.bf16x2 %0, %1, %2;" : "=r"(r) : "r"(a), "r"(b)); return r; }
__device__ __forceinline__ uint32_t fma_bf16x2(uint32_t a, uint32_t b, uint32_t c) { uint32_t r; asm("fma.rn.bf16x2 %0, %1, %2, %3;" : "=r"(r) : "r"(a), "r"(b), "r"(c)); return r; }
__device__ __forceinline__ uint32_t add_bf16x2(uint32_t a, uint32_t b) { uint32_t r; asm("add.rn.bf16x2 %0, %1, %2;" : "=r"(r) : "r"(a), "r"(b)); return r; }

#define R4(d, o) "+f"(d[o + 0]), "+f"(d[o + 1]), "+f"(d[o + 2]), "+f"(d[o + 3])
#define R8(d, o) R4(d, o), R4(d, o + 4)
#define R32(d) R8(d, 0), R8(d, 8), R8(d, 16), R8(d, 24)
#define D32 "{%0,%1,%2,%3,%4,%5,%6,%7,%8,%9,%10,%11,%12,%13,%14,%15,%16,%17,%18,%19,%20,%21,%22,%23,%24,%25,%26,%27,%28,%29,%30,%31}"
#define D64 "{%0,%1,%2,%3,%4,%5,%6,%7,%8,%9,%10,%11,%12,%13,%14,%15,%16,%17,%18,%19,%20,%21,%22,%23,%24,%25,%26,%27,%28,%29,%30,%31,%32,%33,%34,%35,%36,%37,%38,%39,%40,%41,%42,%43,%44,%45,%46,%47,%48,%49,%50,%51,%52,%53,%54,%55,%56,%57,%58,%59,%60,%61,%62,%63}"

__device__ __forceinline__ void mma_qk_f16(float (&d)[32], uint64_t da, uint64_t db) {
    asm volatile("{.reg .pred p; setp.eq.b32 p, 0, 0; wgmma.mma_async.sync.aligned.m64n64k16.f32.f16.f16 " D32 ", %32, %33, p, 1, 1, 0, 0;}"
                 : R32(d) : "l"(da), "l"(db));
}
__device__ __forceinline__ void mma_qk_bf16(float (&d)[32], uint64_t da, uint64_t db) {
    asm volatile("{.reg .pred p; setp.ne.b32 p, 0, 0; wgmma.mma_async.sync.aligned.m64n64k16.f32.bf16.bf16 " D32 ", %32, %33, p, 1, 1, 0, 0;}"
                 : R32(d) : "l"(da), "l"(db));
}
__device__ __forceinline__ void mma_pv(float (&d)[12], const uint32_t* a, uint64_t db) {
    asm volatile("{.reg .pred p; setp.eq.b32 p, 0, 0; wgmma.mma_async.sync.aligned.m64n24k16.f32.bf16.bf16 {%0,%1,%2,%3,%4,%5,%6,%7,%8,%9,%10,%11}, {%12,%13,%14,%15}, %16, p, 1, 1, 1;}"
                 : R8(d, 0), R4(d, 8) : "r"(a[0]), "r"(a[1]), "r"(a[2]), "r"(a[3]), "l"(db));
}
__device__ __forceinline__ void mma_ss128(float (&d)[64], uint64_t da, uint64_t db) {
    asm volatile("{.reg .pred p; setp.eq.b32 p, 0, 0; wgmma.mma_async.sync.aligned.m64n128k16.f32.bf16.bf16 " D64 ", %64, %65, p, 1, 1, 0, 1;}"
                 : R32(d), R8(d, 32), R8(d, 40), R8(d, 48), R8(d, 56) : "l"(da), "l"(db));
}
__device__ __forceinline__ void stsm4(uint32_t addr, uint32_t a, uint32_t b, uint32_t c, uint32_t d) {
    asm volatile("stmatrix.sync.aligned.m8n8.x4.shared.b16 [%0], {%1,%2,%3,%4};" :: "r"(addr), "r"(a), "r"(b), "r"(c), "r"(d) : "memory");
}
__device__ __forceinline__ void mma_ss8(float (&d)[4], uint64_t da, uint64_t db) {
    asm volatile("{.reg .pred p; setp.eq.b32 p, 0, 0; wgmma.mma_async.sync.aligned.m64n8k16.f32.bf16.bf16 {%0,%1,%2,%3}, %4, %5, p, 1, 1, 0, 1;}"
                 : R4(d, 0) : "l"(da), "l"(db));
}
__device__ __forceinline__ void mma_ss(float (&d)[32], uint64_t da, uint64_t db, int accum) {
    asm volatile("{.reg .pred p; setp.ne.b32 p, %34, 0; wgmma.mma_async.sync.aligned.m64n64k16.f32.bf16.bf16 " D32 ", %32, %33, p, 1, 1, 0, 1;}"
                 : R32(d) : "l"(da), "l"(db), "r"(accum));
}
__device__ __forceinline__ void mma_ss(float (&d)[88], uint64_t da, uint64_t db, int accum) {
    asm volatile("{.reg .pred p; setp.ne.b32 p, %90, 0; wgmma.mma_async.sync.aligned.m64n176k16.f32.bf16.bf16 " "{%0,%1,%2,%3,%4,%5,%6,%7,%8,%9,%10,%11,%12,%13,%14,%15,%16,%17,%18,%19,%20,%21,%22,%23,%24,%25,%26,%27,%28,%29,%30,%31,%32,%33,%34,%35,%36,%37,%38,%39,%40,%41,%42,%43,%44,%45,%46,%47,%48,%49,%50,%51,%52,%53,%54,%55,%56,%57,%58,%59,%60,%61,%62,%63,%64,%65,%66,%67,%68,%69,%70,%71,%72,%73,%74,%75,%76,%77,%78,%79,%80,%81,%82,%83,%84,%85,%86,%87}"
                 ", %88, %89, p, 1, 1, 0, 1;}"
                 : R32(d), R8(d, 32), R8(d, 40), R8(d, 48), R8(d, 56), R8(d, 64), R8(d, 72), R8(d, 80) : "l"(da), "l"(db), "r"(accum));
}

constexpr float EXP_MAGIC = 256.0f + 127.0f + 64.0f - 1.58621f + 0.00390625f;
constexpr uint32_t MUFU_MASK = 0x1111u;
__device__ __forceinline__ uint32_t exp2_pair(float y0, float y1, uint32_t cexp, uint32_t neg1) {
    uint32_t w, m, e, r;
    asm("prmt.b32 %0, %1, %2, 0x6521;" : "=r"(w) : "r"(__float_as_uint(y0)), "r"(__float_as_uint(y1)));
    asm("lop3.b32 %0, %1, 0x007F007F, %2, 0xEA;" : "=r"(m) : "r"(w), "r"(cexp));
    asm("mad.lo.u32 %0, %1, %2, %3;" : "=r"(e) : "r"(m), "r"(neg1), "r"(w));
    asm("fma.rn.bf16x2 %0, %1, %2, %3;" : "=r"(r) : "r"(w), "r"(m), "r"(e));
    return r;
}

struct Params {
    const __nv_bfloat16* x;
    const __nv_bfloat16* wk;
    long long wv_off;
    const __nv_bfloat16* wqp;
    __nv_bfloat16* out;
    uint32_t neg1, pad;
    const __nv_bfloat16* w1p;
    const __nv_bfloat16* w2p;
    CUtensorMap wq, wo, w1, w2;
    const __nv_bfloat16* wop;
};

__device__ __forceinline__ int tail_m() { return (blockIdx.x >> 5) * 4 + ((blockIdx.x >> 2) & 3); }
__device__ __forceinline__ int tail_j() { return ((blockIdx.x >> 4) & 1) * 4 + (blockIdx.x & 3); }
__device__ __forceinline__ void load_box(uint32_t sb, const CUtensorMap* tm, uint32_t dst, uint32_t bar, uint32_t bytes, int c0, int c1) {
    mbar_expect(sb + SM_MISC + bar * 8, bytes);
    tma2d(sb + dst, tm, c0, c1, sb + SM_MISC + bar * 8);
}
__device__ __forceinline__ void load_wq(uint32_t sb, const Params& P, int gi, int atom) {
    load_box(sb, &P.wq, SM_WQ + atom * 65536 + gi * 16384, MB_WQ + gi, 16384, (blockIdx.x & 3) * 128 + atom * 64, gi * 128);
}
__device__ __forceinline__ void load_wo(uint32_t sb, const Params& P, int kb) { load_box(sb, &P.wo, wo_slot(kb) * SLOT, MB_WO, SLOT, tail_j() * 64, kb * 64); }
__device__ __forceinline__ void refill_job(uint32_t sb, const Params& P, int gi, int job) {
    const bool w1 = job < 3;
    load_box(sb, w1 ? &P.w1 : &P.wo, (w1 ? 12 + gi + 4 * job : 2 * gi + job - 3) * SLOT, w1 ? MB_W1 + gi : MB_WO, SLOT,
             tail_j() * (w1 ? 176 : 64) + (w1 ? job * 64 : 0), (w1 ? gi : 2 * gi + job - 1) * 64);
}

__host__ __device__ constexpr int ring_entry(int n) { return n < 32 ? (n & 3) : (n - 32) % 6; }
__host__ __device__ constexpr uint32_t ring_slot(int e) { return e < 4 ? 24 + e : e; }

template <int KIND> __host__ __device__ constexpr uint64_t b_slots(int first) {
    uint64_t v = 0;
    for (int i = first; i < first + 12; i++) v |= (uint64_t)((KIND == 0 ? wo_slot(i) : KIND == 1 ? w1_slot(i, 0) : w1_slot(i / 3, i % 3)) & 31) << (5 * (i - first));
    return v;
}
__device__ __forceinline__ uint64_t desc64(uint32_t lo, uint32_t hi) { uint64_t d; asm("mov.b64 %0, {%1, %2};" : "=l"(d) : "r"(lo), "r"(hi)); return d; }
__device__ __forceinline__ uint32_t mbar_test(uint32_t bar) {
    uint32_t done;
    asm volatile("{.reg .pred p; mbarrier.test_wait.parity.shared::cta.b64 p, [%1], 0; selp.u32 %0, 1, 0, p;}" : "=r"(done) : "r"(bar) : "memory");
    return done;
}
template <int KIND, int NACC>
__device__ __forceinline__ bool gemm_ss(float (&acc)[NACC], uint32_t sb, int pr TS_ARG) {
    const uint32_t mb = sb + SM_MISC;
    constexpr int NBLK = KIND == 2 ? 22 : 8, N0 = 16 * KIND;
    uint32_t full = mb + (MB_FULL + N0 + pr * NBLK) * 8, empty = mb + MB_NULL * 8, rel = mb + MB_NULL * 8;
    const uint32_t lane = threadIdx.x & 31, probe = sb + ((threadIdx.x >> 5) & 3) * 512 + (lane >> 4) * 2048 + (lane & 15) * 32 + (lane >> 2) * 4;
    uint32_t m = 0;
    constexpr uint32_t R4S = 24 | 25 << 5 | 26 << 10 | 27 << 15;
    uint32_t ra = KIND == 2 ? (pr ? (4 | 5 << 5 | R4S << 10) : (R4S | 4 << 20 | 5 << 25)) : (KIND == 0 && pr) ? (6 | 7 << 5 | 8 << 10 | 9 << 15) : R4S;
    uint64_t tab = b_slots<KIND>(0);
    const uint32_t a0 = (sb >> 4) | (8 << 16);
    uint32_t b0 = (sb >> 4) | ((KIND == 1 ? 4 * SLOT / 16 : 1) << 16);
    mbar_wait(full);
#pragma unroll 1
    for (int i = 0; i < NBLK; i++) {
        const uint32_t sa = ra & 31, da = a0 + sa * 512, db = b0 + ((uint32_t)tab & 31) * 512;
        full += (i == NBLK - 1) ? 0 : 8;
        const uint32_t ready = mbar_test(full);
        const uint32_t m0 = lds32(probe + sa * SLOT), m1 = lds32(probe + sa * SLOT + 4096);
        wg_fence();
#pragma unroll
        for (int s = 0; s < 4; s++) mma_ss(acc, desc64(da + s * 128, 16), desc64(db + s * 128, 0x40000040), s ? 1 : i);
        wg_commit();
        m = max(m, max(m0, m1));
        const uint32_t prev = empty, prel = rel;
        empty = mb + ((KIND == 0 && sa < 24) ? MB_NULL : MB_EMPTY + (sa & 7)) * 8;
        rel = mb + (KIND == 1 ? MB_REL + i : i == 3 ? MB_REL + 9 : MB_NULL) * 8;
        ra = KIND == 2 ? (ra >> 5) | (sa << 25) : i == 3 ? R4S : ra >> 5;
        tab = (KIND == 2 && i == 11) ? b_slots<KIND>(12) : tab >> 5;
        if (KIND == 1 && i == 3) b0 -= (3 * SLOT / 16) << 16;
        wg_wait<1>();
        warp_done(prev);
        if (KIND != 2) warp_done(prel);
        if (!__all_sync(0xffffffffu, ready)) mbar_wait(full);
    }
    bool bad = __any_sync(0xffffffffu, m == SENT);
    wg_wait<0>();
    fence_regs(acc);
    warp_done(empty);
    if (KIND != 2) warp_done(mb + (MB_REL + 8 - KIND) * 8);
    return __builtin_expect(bad, 0);
}
__device__ __forceinline__ void ring_feed(uint32_t sb, int e TS_ARG) {
    const uint32_t mb = sb + SM_MISC, dst = sb + ring_slot(e) * SLOT, empty = mb + (MB_EMPTY + e) * 8;
    const bool lead = (threadIdx.x & 31) == 0;
    const uint4* base = g_x + tail_m() * 4096 + e * 512;
    uint32_t par = 0;
    auto fetch = [&](int n, const uint4* src, int job) {
        const uint32_t full = mb + (MB_FULL + n) * 8;
        if (lead) mbar_expect(full, SLOT);
        mbar_wait(empty, par); par ^= 1;
        if (job) mbar_wait(mb + (MB_READY + job) * 8);
        if (lead) bulk_g2s(dst, src, SLOT, full);
        __syncwarp();
    };
    if (e < 4) {
        fetch(4 + e, base + 2048, 0);
        if (lead) mbar_expect(mb + (MB_FULL + 8 + e) * 8, SLOT);
        mbar_wait(mb + (MB_DONE + 4) * 8);
        mbar_wait(mb + (MB_READY + 1) * 8);
        if (lead) bulk_g2s(sb + (6 + e) * SLOT, base + 65536, SLOT, mb + (MB_FULL + 8 + e) * 8);
        fetch(12 + e, base + 65536 + 2048, 0);
#pragma unroll 1
        for (int h = 0; h < 2; h++) {
            fetch(16 + 8 * h + e, base + X_H1 + h * 65536, 2 + h);
            fetch(20 + 8 * h + e, base + X_H1 + h * 65536 + 2048, 0);
        }
    } else {
        mbar_wait(mb + (MB_REL + 7) * 8);
        par = 1;
    }
    const uint4* src = g_x + X_H2 + tail_m() * 88 * 128 + e * 512;
#pragma unroll 1
    for (int n = e; n < 44; n += 6, src += 6 * 512) {
        const bool second = n >= 22 && n < 28;
        if (second) src += 16 * 88 * 128 - 22 * 512;
        fetch(32 + n, src, n < 6 ? 4 : second ? 5 : 0);
    }
}
__device__ __noinline__ void gemm_slow_impl(float* out, int ntile, const uint4* a, int nst, const __nv_bfloat16* W, int ldw, int kmax, int n0) {
    const int lane = threadIdx.x & 31;
    const unsigned short* w = reinterpret_cast<const unsigned short*>(W);
    for (int j = 0; j < ntile; j++) {
        const uint32_t* p = reinterpret_cast<const uint32_t*>(a) + ((threadIdx.x >> 5) & 3) * 128 + lane;
        const int n = n0 + 8 * j + (lane >> 2);
        float d[4] = {0.f, 0.f, 0.f, 0.f};
        for (int st = 0; st < nst; st++, p += 512) {
            const int k = st * 16 + 2 * (lane & 3);
            uint32_t v0, v1, v2, v3, b0 = 0, b1 = 0; int spins = 0;
            do { v0 = ldg32_relaxed(p); v1 = ldg32_relaxed(p + 64); v2 = ldg32_relaxed(p + 32); v3 = ldg32_relaxed(p + 96); }
            while (__any_sync(0xffffffffu, max(max(v0, v1), max(v2, v3)) == SENT) && ++spins < SPIN_LIMIT);
            if (k < kmax && n < ldw) {
                const unsigned short* q = w + (size_t)k * ldw + n;
                b0 = q[0] | ((uint32_t)q[ldw] << 16); b1 = q[8 * ldw] | ((uint32_t)q[9 * ldw] << 16);
            }
            asm volatile("mma.sync.aligned.m16n8k16.row.col.f32.bf16.bf16.f32 {%0,%1,%2,%3}, {%4,%5,%6,%7}, {%8,%9}, {%0,%1,%2,%3};"
                         : R4(d, 0) : "r"(v0), "r"(v1), "r"(v2), "r"(v3), "r"(b0), "r"(b1));
        }
        *reinterpret_cast<float4*>(out + 4 * j) = make_float4(d[0], d[1], d[2], d[3]);
    }
}
template <int NACC>
__device__ __forceinline__ void gemm_slow(float (&acc)[NACC], const uint4* a, int nst, const __nv_bfloat16* W, int ldw, int kmax, int n0) {
    __align__(16) float tmp[NACC];
    gemm_slow_impl(tmp, NACC / 4, a, nst, W, ldw, kmax, n0);
#pragma unroll
    for (int i = 0; i < NACC; i++) acc[i] = tmp[i];
}
__device__ __forceinline__ void store_tile(uint32_t* p, uint32_t r0k0, uint32_t r8k0, uint32_t r0k8, uint32_t r8k8) {
    stg32(p, r0k0); stg32(p + 32, r0k8); stg32(p + 64, r8k0); stg32(p + 96, r8k8);
}

__device__ __forceinline__ float quad_sum(float v) { v += __shfl_xor_sync(0xffffffffu, v, 1); v += __shfl_xor_sync(0xffffffffu, v, 2); return v; }
__device__ __forceinline__ float reduce4(const float (&st)[4], int lane) {
    const bool u16 = lane & 16, u8 = lane & 8;
    const float a0 = (u16 ? st[2] : st[0]) + __shfl_xor_sync(0xffffffffu, u16 ? st[0] : st[2], 16);
    const float a1 = (u16 ? st[3] : st[1]) + __shfl_xor_sync(0xffffffffu, u16 ? st[1] : st[3], 16);
    float v = (u8 ? a1 : a0) + __shfl_xor_sync(0xffffffffu, u8 ? a0 : a1, 8);
    v += __shfl_xor_sync(0xffffffffu, v, 4); v += __shfl_xor_sync(0xffffffffu, v, 2); v += __shfl_xor_sync(0xffffffffu, v, 1);
    return v;
}
__device__ __forceinline__ float silu2(float h) { float t; asm("tanh.approx.f32 %0, %1;" : "=f"(t) : "f"(h)); return fmaf(h, t, h); }

template <bool SAFE>
__device__ __forceinline__ void attention(const Params& P, uint32_t sb, int warp TS_ARG) {
    const uint32_t mb = sb + SM_MISC;
    const int tid = threadIdx.x, lane = tid & 31, b = blockIdx.x;
    const int wg = warp >> 2, ww = warp & 3, job = 3 - wg + 4 * ww;
    const uint32_t cexp = 0x9F809F80u + (tid >> 12);
    const uint32_t neg1 = P.neg1;
    unsigned cnt = 0;
    if (SAFE && warp == 8) cnt = ldg32_relaxed(g_s.cnt[C_KV]);
#pragma unroll 1
    for (int pass = 0; pass < 2; pass++) {
    float o[12], s[32];
    const uint64_t dq = mkdesc(sb + SM_Q + (pass * 4 + wg) * 2048, 128, 256, 0);
    uint64_t dk = mkdesc(sb + SM_K, 128, 256, 0), dv = mkdesc(sb + SM_V, 128, 32768, 0);
    float m0 = -INFINITY, m1 = -INFINITY;
#pragma unroll
    for (int i = 0; i < 12; i++) o[i] = 0.f;
#pragma unroll
    for (int i = 0; i < 32; i++) s[i] = ((MUFU_MASK >> (i / 2)) & 1) ? 0.f : EXP_MAGIC;
    fence_regs(s); fence_regs(o);
    wg_fence();
    if (SAFE) mma_qk_f16(s, dq, dk + 31 * 128); else mma_qk_bf16(s, dq, dk + 31 * 128);
    wg_commit();
    wg_wait<0>(); fence_regs(s);
#pragma unroll 1
    for (int u = pass ? 3 : (wg == 2) ? 0 : 1; u < (pass ? 8 : 3); u++) {
        int n = 2 * ((((wg == 2) ? 0x22444C31u : 0x22444C40u) >> (4 * u)) & 15);
#pragma unroll 1
        do {
            uint32_t p[16];
            if (SAFE) {
#pragma unroll
                for (int j = 0; j < 16; j++) {
                    if ((MUFU_MASK >> j) & 1) p[j] = pack_bf16(ex2(s[2 * j]), ex2(s[2 * j + 1]));
                    else p[j] = exp2_pair(s[2 * j], s[2 * j + 1], cexp, neg1);
                }
            } else {
                fence_regs(o);
                float x0 = m0, x1 = m1;
#pragma unroll
                for (int j = 0; j < 8; j++) { x0 = fmaxf(x0, fmaxf(s[4 * j], s[4 * j + 1])); x1 = fmaxf(x1, fmaxf(s[4 * j + 2], s[4 * j + 3])); }
                x0 = fmaxf(x0, __shfl_xor_sync(0xffffffffu, x0, 1)); x0 = fmaxf(x0, __shfl_xor_sync(0xffffffffu, x0, 2));
                x1 = fmaxf(x1, __shfl_xor_sync(0xffffffffu, x1, 1)); x1 = fmaxf(x1, __shfl_xor_sync(0xffffffffu, x1, 2));
                const float c0 = ex2(m0 - x0), c1 = ex2(m1 - x1);
                m0 = x0; m1 = x1;
#pragma unroll
                for (int j = 0; j < 3; j++) { o[4 * j] *= c0; o[4 * j + 1] *= c0; o[4 * j + 2] *= c1; o[4 * j + 3] *= c1; }
#pragma unroll
                for (int j = 0; j < 8; j++) {
                    p[2 * j] = pack_bf16(ex2(s[4 * j] - m0), ex2(s[4 * j + 1] - m0));
                    p[2 * j + 1] = pack_bf16(ex2(s[4 * j + 2] - m1), ex2(s[4 * j + 3] - m1));
                }
                fence_regs(o);
            }
            fence_regs(p);
            wg_fence();
            if (SAFE) mma_qk_f16(s, dq, dk); else mma_qk_bf16(s, dq, dk);
#pragma unroll
            for (int j = 0; j < 4; j++) mma_pv(o, p + 4 * j, dv + j * 16);
            wg_commit();
            dk += 128; dv += 64;
            wg_wait<0>(); fence_regs(s);
        } while (--n > 0);
        if (u == 2 || u == 7) {
            fence_regs(o);
            const float i0 = rcp(o[8]), i1 = rcp(o[10]);
            if (u == 7) mbar_wait(mb + MB_MID * 8);
            store_tile(reinterpret_cast<uint32_t*>(g_x + X_O + (((u == 7) * 16 + (b >> 3)) * 32 + (b & 3) * 8 + 2 * wg + (ww >> 1)) * 128 + (((b >> 2) & 1) * 2 + (ww & 1)) * 32) + lane,
                       pack_bf16(o[0] * i0, o[1] * i0), pack_bf16(o[2] * i1, o[3] * i1), pack_bf16(o[4] * i0, o[5] * i0), pack_bf16(o[6] * i1, o[7] * i1));
            if (u == 2) asm volatile("cp.async.bulk.wait_group 0;" ::: "memory");
            else count_hint(C_O + 16 + (b >> 3));
            warp_done(mb + (MB_DONE + (u == 7) * 4) * 8);
            TS(5 + (u == 7));
        } else if (u >= 3) {
            if (u < 6) warp_done(mb + (MB_DONE + u - 2) * 8);
            if (job < (u == 3 ? 1 : 5)) {
                mbar_wait(mb + (MB_DONE + u - 3) * 8);
                if (u == 3) count_release(C_MID);
                else if (lane == 0) refill_job(sb, P, u - 4, job);
            } else if (u == 6) {
                if (job < 9) {
                    mbar_wait(mb + MB_MID * 8);
                    if (lane == 0) {
                        mbar_expect(mb + (MB_FULL + job - 5) * 8, SLOT);
                        bulk_g2s(sb + (19 + job) * SLOT, g_x + X_O + tail_m() * 4096 + (job - 5) * 512, SLOT, mb + (MB_FULL + job - 5) * 8);
                    }
                }
            } else if (warp == 7) {
                if (u == 4) cnt = ldg32_relaxed(g_s.cnt[C_MID]);
                if (u == 5) {
                    const unsigned target = lds32(mb + MISC_EPOCH) * NCTA;
                    if (__any_sync(0xffffffffu, cnt != target)) count_wait(C_MID, target);
                    asm volatile("fence.acquire.gpu; fence.proxy.async.global;" ::: "memory");
                    warp_done(mb + MB_MID * 8);
                }
            }
        } else if (u == 1) {
            if (SAFE) mbar_wait(mb + MB_KV * 8);
            TS(17);
            if (lane == 0) {
                if (job < 9) {
                    asm volatile("cp.async.bulk.global.shared::cta.bulk_group [%0], [%1], %2;"
                                 :: "l"(g_x + X_ARM + b * X_SHARE + job * 512), "r"(sb + SM_SENT), "r"(job < 8 ? 8192 : (X_SHARE - 4096) * 16) : "memory");
                    asm volatile("cp.async.bulk.commit_group;" ::: "memory");
                } else if (job < 11) load_wo(sb, P, job - 9);
            }
        } else if (SAFE) {
            if (warp == 8) {
                const unsigned target = lds32(mb + MISC_EPOCH) * NMAIN;
                if (__any_sync(0xffffffffu, cnt != target)) count_wait(C_KV, target);
                if (lane == 0) {
                    asm volatile("fence.acquire.gpu; fence.proxy.async.global;" ::: "memory");
                    mbar_expect(mb + MB_KV * 8, 47104 + 2 * 24576);
                    bulk_g2s(sb + SM_K + 16384, g_s.kv + 1024, 47104, mb + MB_KV * 8);
                    bulk_g2s(sb + SM_V + 8192, g_s.kv + 4096 + 512, 24576, mb + MB_KV * 8);
                    bulk_g2s(sb + SM_V + 32768 + 8192, g_s.kv + 6144 + 512, 24576, mb + MB_KV * 8);
                }
            }
        }
        __syncwarp();
    }
    }
}

__device__ __forceinline__ int kv_slot(int idx) {
    const int t = (idx & 63) >> 1, c = 2 * (blockIdx.x >> 2) + (idx & 1), hg = blockIdx.x & 3;
    return hg < 2 ? ((t + 31) & 31) * 128 + (c >> 3) * 16 + (hg & 1) * 8 + (c & 7) : 4096 + (hg & 1) * 2048 + t * 64 + c;
}

__device__ __noinline__ void helper_cta(const Params& P, uint8_t* smem) {
    const int tid = threadIdx.x, b = blockIdx.x, hi = b - NMAIN;
    const unsigned epoch = g_s.epoch[b] + 1;
    float* red = reinterpret_cast<float*>(smem);
    if (tid < 32) count_wait(C_KV, epoch * NMAIN);
    __syncthreads();
    if (tid == 480) {
        for (int i = 0; i < 8; i++) asm volatile("cp.async.bulk.prefetch.L2.global [%0], %1;" :: "l"((const char*)P.wop + hi * 131072 + i * 16384), "r"(16384) : "memory");
        for (int i = 0; i < 43; i++) asm volatile("cp.async.bulk.prefetch.L2.global [%0], %1;" :: "l"((const char*)P.w2p + hi * 352256 + i * 8192), "r"(8192) : "memory");
    }
    if (tid < 344) {
        const int cg = tid % 43, rp = tid / 43;
        const uint4* src = reinterpret_cast<const uint4*>(P.w1p + (size_t)rp * 64 * FF + (hi * 43 + cg) * 8);
        float s[8] = {0, 0, 0, 0, 0, 0, 0, 0};
#pragma unroll 8
        for (int r = 0; r < 64; r++) {
            uint4 v = __ldg(src + r * (FF / 8));
            s[0] += bf_lo(v.x); s[1] += bf_hi(v.x); s[2] += bf_lo(v.y); s[3] += bf_hi(v.y);
            s[4] += bf_lo(v.z); s[5] += bf_hi(v.z); s[6] += bf_lo(v.w); s[7] += bf_hi(v.w);
        }
        float* part = red + (rp * 43 + cg) * 8;
#pragma unroll
        for (int i = 0; i < 8; i++) part[i] = s[i];
    }
    __syncthreads();
    if (tid < 344) {
        float s = 0.f;
#pragma unroll
        for (int rp = 0; rp < 8; rp++) s += red[rp * 344 + tid];
        g_s.cs[hi * 344 + tid] = s;
    } else if (hi == 3 && tid < 344 + 64) g_s.cs[FF + tid - 344] = 0.f;
    __syncthreads();
    if (tid < 32) count_release(C_MID);
    if (tid == 0) g_s.epoch[b] = epoch;
}

__global__ void __launch_bounds__(512, 1) fused_kernel(const __grid_constant__ Params P) {
    extern __shared__ __align__(1024) uint8_t smem[];
    const uint32_t sb = (uint32_t)__cvta_generic_to_shared(smem);
    const uint32_t mb = sb + SM_MISC;
    const int tid = threadIdx.x, lane = tid & 31, b = blockIdx.x;
    if (b >= NMAIN) { helper_cta(P, smem); return; }
    const int tg = b >> 2, hg = b & 3;
    const int warp = __shfl_sync(0xffffffffu, tid >> 5, 0);

    uint4 xv[4][2];
    unsigned epoch = 0;
    {
        const int r = (tid >> 5) * 4;
        const uint4* src = reinterpret_cast<const uint4*>(P.x + (size_t)((r & 31) + tg * 32 + (r >> 5) * 1024) * D) + lane;
#pragma unroll
        for (int i = 0; i < 4; i++) { xv[i][0] = ldg_relaxed(src + i * 64); xv[i][1] = ldg_relaxed(src + i * 64 + 32); }
    }
    const uint4 wkv = ldg_relaxed(reinterpret_cast<const uint4*>(reinterpret_cast<const char*>(P.wk) + (hg < 2 ? 0 : P.wv_off)) + tid * 2 + (hg & 1));
    const int wg = warp >> 2, ww = warp & 3, g = lane >> 2, t4 = lane & 3, t128 = tid & 127;
    if (lane == 0) {
        if (warp < 4) {
            mbar_init(mb + (MB_WQ + warp) * 8, 2);
            asm volatile("fence.mbarrier_init.release.cluster;" ::: "memory");
            load_wq(sb, P, warp, 0);
            load_wq(sb, P, warp, 1);
        } else if (warp < 7) {
            asm volatile("prefetch.tensormap [%0];" :: "l"(&P.wo + (warp - 4)) : "memory");
        } else if (warp == 7) {
            asm volatile("ld.relaxed.gpu.global.u32 %0, [%1];" : "=r"(epoch) : "l"(g_s.epoch + b) : "memory");
        } else if (warp == 8) {
            sts128(mb + MISC_NRM, 0, 0, 0, 0);

        }
    }
    __syncwarp();
    TS(16);
    float dlt;
    {
        float st[4];
#pragma unroll
        for (int i = 0; i < 4; i++) {
            const uint32_t s = add_bf16x2(add_bf16x2(add_bf16x2(xv[i][0].x, xv[i][0].y), add_bf16x2(xv[i][0].z, xv[i][0].w)),
                                          add_bf16x2(add_bf16x2(xv[i][1].x, xv[i][1].y), add_bf16x2(xv[i][1].z, xv[i][1].w)));
            st[i] = bf_lo(s) + bf_hi(s);
        }
        TS(13);
        const float tot = reduce4(st, lane) * (-1.0f / D);
        const uint32_t nmr = pack_bf16(tot, tot);
        dlt = bf_lo(nmr) - tot;
        const uint32_t xa = sb + SM_XN + (lane >> 3) * 8192 + warp * 512;
#pragma unroll
        for (int i = 0; i < 4; i++) {
            const uint32_t nm = __shfl_sync(0xffffffffu, nmr, i * 8);
            const uint32_t addr = xa + i * 128 + (((lane & 7) ^ ((warp & 1) * 4 + i)) << 4);
#pragma unroll
            for (int c = 0; c < 2; c++) {
                xv[i][c].x = add_bf16x2(xv[i][c].x, nm); xv[i][c].y = add_bf16x2(xv[i][c].y, nm);
                xv[i][c].z = add_bf16x2(xv[i][c].z, nm); xv[i][c].w = add_bf16x2(xv[i][c].w, nm);
                sts128(addr + c * 32768, xv[i][c].x, xv[i][c].y, xv[i][c].z, xv[i][c].w);
            }
        }
    }
    sts128(sb + SM_WKV + tid * 16, wkv.x, wkv.y, wkv.z, wkv.w);
    fence_async_smem();
    TS(0);
    __syncthreads();
    auto variances = [&]() {
        float st[4];
#pragma unroll
        for (int i = 0; i < 4; i++) {
            float v = 0.f;
#pragma unroll
            for (int c = 0; c < 2; c++) {
                const uint32_t a = fma_bf16x2(xv[i][c].x, xv[i][c].x, mul_bf16x2(xv[i][c].y, xv[i][c].y));
                const uint32_t d = fma_bf16x2(xv[i][c].z, xv[i][c].z, mul_bf16x2(xv[i][c].w, xv[i][c].w));
                v += (bf_lo(a) + bf_hi(a)) + (bf_lo(d) + bf_hi(d));
            }
            st[i] = v;
        }
        const float vs = reduce4(st, lane), dl = dlt;
        if ((lane & 7) == 0) sts32(sb + SM_RSTD + (warp * 4 + (lane >> 3)) * 4, __float_as_uint(rsqrtf(fmaxf(vs * (1.0f / D) - dl * dl, 0.f) + 1e-5f)));
    };
    float kv[4] = {0.f, 0.f, 0.f, 0.f};
    if (wg == 2) {
        fence_regs(kv);
        const uint64_t da = mkdesc(sb + SM_XN, 16, 1024, 1), db = mkdesc(sb + SM_WKV, 128, 16, 0);
        wg_fence();
#pragma unroll
        for (int s = 0; s < 32; s++) mma_ss8(kv, da + (s >> 2) * 512 + (s & 3) * 2, db + s * 16);
        wg_commit();
        variances();
        wg_wait<0>(); fence_regs(kv);
    } else {
        variances();
        if (tid == 7 * 32) { sts32(mb + MISC_EPOCH, epoch + 1); g_s.epoch[b] = epoch + 1; }
    }
    __syncthreads();
    constexpr float QSCALE = 0.25f * 1.4426950408889634f;
    float qa[64];
    const uint32_t qbase = sb + SM_Q + (ww >> 1) * 8192 + (ww & 1) * 512 + lane * 16;
    if (wg == 0) {
#pragma unroll
        for (int i = 0; i < 64; i++) qa[i] = 0.f;
        fence_regs(qa);
        const uint64_t da = mkdesc(sb + SM_XN, 16, 1024, 1), db = mkdesc(sb + SM_WQ, 65536, 1024, 1);
#pragma unroll 1
        for (int i = 0; i < 4; i++) {
            mbar_wait(mb + (MB_WQ + i) * 8);
            wg_fence();
#pragma unroll
            for (int s = 0; s < 8; s++) mma_ss128(qa, da + (i * 2 + (s >> 2)) * 512 + (s & 3) * 2, db + (i * 8 + s) * 128);
            wg_commit();
        }
        const float rs0 = __uint_as_float(lds32(sb + SM_RSTD + (ww * 16 + g) * 4)) * QSCALE, rs1 = __uint_as_float(lds32(sb + SM_RSTD + (ww * 16 + g + 8) * 4)) * QSCALE;
        wg_wait<0>();
        fence_regs(qa);
        bar_arrive(6, 256);
        bar_sync(5, 256);
        TS(1);
        uint32_t nm = 0;
#pragma unroll
        for (int h = 0; h < 8; h++) {
#pragma unroll
            for (int i = 0; i < 8; i++) qa[8 * h + i] *= (i & 2) ? rs1 : rs0;
            stsm4(qbase + h * 1024, pack_f16(qa[8 * h], qa[8 * h + 1]), pack_f16(qa[8 * h + 4], qa[8 * h + 5]), pack_f16(qa[8 * h + 2], qa[8 * h + 3]), pack_f16(qa[8 * h + 6], qa[8 * h + 7]));
            const float n0 = qa[8 * h] * qa[8 * h] + qa[8 * h + 1] * qa[8 * h + 1] + qa[8 * h + 4] * qa[8 * h + 4] + qa[8 * h + 5] * qa[8 * h + 5];
            const float n1 = qa[8 * h + 2] * qa[8 * h + 2] + qa[8 * h + 3] * qa[8 * h + 3] + qa[8 * h + 6] * qa[8 * h + 6] + qa[8 * h + 7] * qa[8 * h + 7];
            nm = max(nm, max(__float_as_uint(n0), __float_as_uint(n1)));
        }
        nm = __reduce_max_sync(0xffffffffu, __float_as_uint(quad_sum(__uint_as_float(nm))));
        if (lane == 0) asm volatile("red.shared.max.u32 [%0], %1;" :: "r"(mb + MISC_NRM), "r"(nm) : "memory");
    } else if (wg == 1) {
        if (lane == 0) {
            if (ww == 0) {
#pragma unroll
                for (uint32_t i = 4; i < 35; i++) mbar_init(mb + i * 8, bar_count(i));
            } else if (ww == 1) {
#pragma unroll
                for (uint32_t i = 35; i < 67; i++) mbar_init(mb + i * 8, bar_count(i));
            } else {
#pragma unroll
                for (uint32_t i = 0; i < 30; i++) mbar_init(mb + (ww * 30 + 7 + i) * 8, 2);
            }
        }
        __syncwarp();
#pragma unroll
        for (int i = 0; i < 4; i++) sts128(sb + SM_SENT + (i * 128 + t128) * 16, SENT, SENT, SENT, SENT);
        bar_sync(5, 256);
#pragma unroll
        for (int i = 0; i < 16; i++) sts128(sb + SM_V + 65536 + (i * 128 + t128) * 16, 0x3F803F80u, 0x3F803F80u, 0x3F803F80u, 0x3F803F80u);
    } else if (wg == 2) {
        const float rs0 = __uint_as_float(lds32(sb + SM_RSTD + (ww * 16 + g) * 4)), rs1 = __uint_as_float(lds32(sb + SM_RSTD + (ww * 16 + g + 8) * 4));
        kv[0] *= rs0; kv[1] *= rs0; kv[2] *= rs1; kv[3] *= rs1;
        float2* kt = reinterpret_cast<float2*>(smem + SM_KTMP);
        kt[(ww * 16 + g) * 4 + t4] = make_float2(kv[0], kv[1]); kt[(ww * 16 + g + 8) * 4 + t4] = make_float2(kv[2], kv[3]);
        float n0 = kv[0] * kv[0] + kv[1] * kv[1], n1 = kv[2] * kv[2] + kv[3] * kv[3];
        n0 += __shfl_xor_sync(0xffffffffu, n0, 1); n1 += __shfl_xor_sync(0xffffffffu, n1, 1);
        n0 += __shfl_xor_sync(0xffffffffu, n0, 2); n1 += __shfl_xor_sync(0xffffffffu, n1, 2);
        const uint32_t nm = __reduce_max_sync(0xffffffffu, max(__float_as_uint(n0), __float_as_uint(n1)));
        if (lane == 0) sts32(sb + SM_WNRM + ww * 4, nm | 1u);
        bar_sync(2, 128);
        const uint32_t ra = sb + SM_KTMP + ((t128 & 1) * 32 + ((t128 & 63) >> 1)) * 32;
        const float4 c0 = lds128f(ra), c1 = lds128f(ra + 16);
        const int kvoff = kv_slot(tid);
        if (ww < 2) {
            if (hg < 2) {
                float4 p0 = lds128f(ra - 32), p1 = lds128f(ra - 16);
                if (t128 < 2) { p0 = make_float4(0.f, 0.f, 0.f, 0.f); p1 = p0; }
                stg128(g_s.kv + kvoff, nonzero(pack_f16(c0.x - p0.x, c0.y - p0.y)), pack_f16(c0.z - p0.z, c0.w - p0.w), pack_f16(c1.x - p1.x, c1.y - p1.y), pack_f16(c1.z - p1.z, c1.w - p1.w));
            } else {
                stg128(g_s.kv + kvoff, nonzero(pack_bf16(c0.x, c0.y)), pack_bf16(c0.z, c0.w), pack_bf16(c1.x, c1.y), pack_bf16(c1.z, c1.w));
            }
            if (t128 < 2) { const float4 w = lds128f(sb + SM_WNRM); stg128(g_s.nrm + b * 2 + t128, __float_as_uint(w.x), __float_as_uint(w.y), __float_as_uint(w.z), __float_as_uint(w.w)); }
            count_hint(C_KVH);
        } else if (hg < 2) {
            stg128(g_s.kplain + kvoff, pack_bf16(c0.x, c0.y), pack_bf16(c0.z, c0.w), pack_bf16(c1.x, c1.y), pack_bf16(c1.z, c1.w));
        }
        TS(1);
        bar_sync(2, 128);
        if (ww == 3) count_release(C_KV);
    } else {
        uint4 kc[18];
        auto src = [&](int i) { return i < 8 ? g_s.kv + i * 128 : i < 12 ? g_s.kv + 4096 + (i - 8) * 128 : i < 16 ? g_s.kv + 6144 + (i - 12) * 128 : i == 16 ? g_s.kv + 31 * 128 : g_s.nrm + t128; };
        count_wait(C_KVH, lds32(mb + MISC_EPOCH) * (NMAIN * 2));
        TS(1);
        int spins = 0;
        while (true) {
#pragma unroll
            for (int i = 0; i < 18; i++) kc[i] = ldg_relaxed(src(i) + t128);
            uint32_t mn = 1;
#pragma unroll
            for (int i = 0; i < 18; i++) mn = min(mn, kc[i].x);
            if (!__any_sync(0xffffffffu, mn == 0u) || ++spins >= SPIN_LIMIT) break;
        }
        uint32_t nm = max(max(kc[17].x, kc[17].y), max(kc[17].z, kc[17].w));
        nm = max(nm, __shfl_xor_sync(0xffffffffu, nm, 4)); nm = max(nm, __shfl_xor_sync(0xffffffffu, nm, 8)); nm = max(nm, __shfl_xor_sync(0xffffffffu, nm, 16));
        if (lane < 4) asm volatile("red.shared.max.u32 [%0], %1;" :: "r"(mb + MISC_NRM + 4 + min(lane, 2) * 4), "r"(nm) : "memory");
        TS(2);
        bar_sync(6, 256);
#pragma unroll
        for (int i = 0; i < 17; i++) sts128(sb + (uint32_t)(src(i) - g_s.kv + t128) * 16 + ((i >= 8 && i < 16) ? SM_V - 65536 : 0), kc[i].x, kc[i].y, kc[i].z, kc[i].w);
    }
    fence_async_smem();
    TS(3);
    __syncthreads();
    const float4 nr = lds128f(mb + MISC_NRM);
    const bool safe = __all_sync(0xffffffffu, (nr.x * (nr.y + nr.z) <= 3500.0f) && (nr.x <= 65536.0f) && (nr.y + nr.z <= 65536.0f) && (nr.w <= 1e24f));
    TS(4);

    if (__builtin_expect(safe, 1)) {
        attention<true>(P, sb, warp TS_PASS);
    } else {
        if (wg == 0) {
#pragma unroll
            for (int h = 0; h < 8; h++)
                stsm4(qbase + h * 1024, pack_bf16(qa[8 * h], qa[8 * h + 1]), pack_bf16(qa[8 * h + 4], qa[8 * h + 5]), pack_bf16(qa[8 * h + 2], qa[8 * h + 3]), pack_bf16(qa[8 * h + 6], qa[8 * h + 7]));
            fence_async_smem();
        } else if (warp == 15) {
            count_wait(C_KV, lds32(mb + MISC_EPOCH) * NMAIN);
            if (lane == 0) {
                asm volatile("fence.proxy.async;" ::: "memory");
                mbar_expect(mb + MB_KV * 8, 131072);
                bulk_g2s(sb + SM_K, g_s.kplain, 65536, mb + MB_KV * 8);
                bulk_g2s(sb + SM_V, g_s.kv + 4096, 65536, mb + MB_KV * 8);
            }
            __syncwarp();
        }
        __syncthreads();
        mbar_wait(mb + MB_KV * 8);
        attention<false>(P, sb, warp TS_PASS);
    }

    const int j = tail_j();
    if (wg == 1 || wg == 2) {
        if (warp == 8) {
            epoch = lds32(mb + MISC_EPOCH);
#pragma unroll 1
            for (int job = 1; job < 6; job++) {
                count_wait(C_O + 32 * (job >> 1) + (job & 1) * 16 + tail_m(), epoch * (job == 1 ? 128 : 32));
                asm volatile("fence.proxy.async.global;" ::: "memory");
                warp_done(mb + (MB_READY + job) * 8);
                TS(18 + job);
            }
        } else if (warp == 9) {
#pragma unroll
            for (int i = 0; i < 2; i++) {
                if (lane < 22) {
                    const uint4 v = ldg_relaxed(reinterpret_cast<const uint4*>(g_s.cs + j * 176) + i * 22 + lane);
                    sts128(mb + MISC_CS + (i * 22 + lane) * 16, v.x, v.y, v.z, v.w);
                }
                stg128(g_s.kv + kv_slot(i * 32 + lane), 0u, 0u, 0u, 0u);
            }
            warp_done(mb + MB_CS * 8);
            if (lane < 2) stg128(g_s.nrm + b * 2 + lane, 0u, 0u, 0u, 0u);
#pragma unroll 1
            for (int i = 0; i < 16; i++) {
                mbar_wait(mb + (MB_W1 + i) * 8);
                const int n = i < 8 ? 16 + i + 8 * (lane & 1) : 32 + 3 * (i - 8) + (lane >> 1) + 22 * (lane & 1);
                if (lane < (i < 8 || i == 15 ? 2 : 6)) mbar_arrive(mb + (MB_FULL + n) * 8);
                __syncwarp();
            }
        } else {
            if (wg == 2) {
#pragma unroll 1
                for (int i = 7 + ww; i < 46; i += 2) {
                    const bool w1 = i < 24;
                    const int n = w1 ? i : i - 24, kb = n / 3, a = n - 3 * kb;
                    mbar_wait(mb + (w1 ? (i < 12 ? MB_DONE + 4 : i < 18 ? MB_REL + 9 : MB_REL + 8) : MB_REL + kb) * 8);
                    if (lane == 0) load_box(sb, w1 ? &P.w1 : &P.w2, w1_slot(kb, a) * SLOT, (w1 ? MB_W1 : MB_W2) + kb, SLOT, w1 ? j * 176 + a * 64 : j * 64, (w1 ? kb : n) * 64);
                    __syncwarp();
                }
            }
            ring_feed(sb, wg == 1 ? ww : ww + 2 TS_PASS);
        }
    } else {
        const int pr = (wg == 0), mt = 16 * pr + tail_m();
        uint32_t* const hp = reinterpret_cast<uint32_t*>(g_x + X_H1 + (mt * 32 + j * 4) * 128 + ww * 32) + lane;
        {
            uint32_t hk[16];
            const uint32_t* xp = reinterpret_cast<const uint32_t*>(P.x + (size_t)(mt * 64 + ww * 16 + g) * D + j * 64 + t4 * 2);
#pragma unroll
            for (int k = 0; k < 8; k++) { hk[2 * k] = __ldg(xp + k * 4); hk[2 * k + 1] = __ldg(xp + k * 4 + 8 * (D / 2)); }
            mbar_wait(mb + MB_WO * 8);
            float acc[32];
            if (gemm_ss<0>(acc, sb, pr TS_PASS)) gemm_slow(acc, g_x + X_O + mt * 32 * 128, 32, P.wop, D, D, j * 64);
            TS(7);
#pragma unroll
            for (int i = 0; i < 16; i++) hk[i] = pack_bf16(acc[2 * i] + bf_lo(hk[i]), acc[2 * i + 1] + bf_hi(hk[i]));
#pragma unroll
            for (int k = 0; k < 4; k++) store_tile(hp + k * 512, hk[4 * k], hk[4 * k + 1], hk[4 * k + 2], hk[4 * k + 3]);
            count_hint(C_H1 + mt);
            TS(8);
            float st[4] = {0.f, 0.f, 0.f, 0.f};
#pragma unroll
            for (int i = 0; i < 16; i++) {
                const float lo = bf_lo(hk[i]), hi = bf_hi(hk[i]);
                st[2 * (i & 1)] += lo + hi;
                st[2 * (i & 1) + 1] = fmaf(lo, lo, fmaf(hi, hi, st[2 * (i & 1) + 1]));
            }
#pragma unroll
            for (int o = 1; o < 4; o <<= 1)
#pragma unroll
                for (int i = 0; i < 4; i++) st[i] += __shfl_xor_sync(0xffffffffu, st[i], o);
            if (t4 == 0) stg128(g_x + X_ST + (mt * 8 + j) * 32 + ww * 8 + g, __float_as_uint(st[0]), __float_as_uint(st[1]), __float_as_uint(st[2]), __float_as_uint(st[3]));
        }
        {
            float acc[88];
            const uint4* sp = g_x + X_ST + (mt * 8 + t4) * 32 + ww * 8 + g;
            mbar_wait(mb + (MB_FULL + 16 + pr * 8) * 8);
            uint4 u0 = ldg_relaxed(sp), u1 = ldg_relaxed(sp + 128);
            if (gemm_ss<1>(acc, sb, pr TS_PASS)) gemm_slow(acc, g_x + X_H1 + mt * 32 * 128, 32, P.w1p, FF, D, j * 176);
            TS(9);
            int spins = 0;
            while (__builtin_expect(__any_sync(0xffffffffu, max(u0.x, u1.x) == SENT), 0) && ++spins < SPIN_LIMIT) { u0 = ldg_relaxed(sp); u1 = ldg_relaxed(sp + 128); }
            float st[4] = {__uint_as_float(u0.x) + __uint_as_float(u1.x), __uint_as_float(u0.y) + __uint_as_float(u1.y),
                           __uint_as_float(u0.z) + __uint_as_float(u1.z), __uint_as_float(u0.w) + __uint_as_float(u1.w)};
#pragma unroll
            for (int o = 1; o < 4; o <<= 1)
#pragma unroll
                for (int k = 0; k < 4; k++) st[k] += __shfl_xor_sync(0xffffffffu, st[k], o);
            float nmean[2], hrstd[2];
#pragma unroll
            for (int k = 0; k < 2; k++) {
                nmean[k] = st[2 * k] * (-1.0f / D);
                hrstd[k] = 0.5f * rsqrtf(fmaxf(fmaf(-nmean[k], nmean[k], st[2 * k + 1] * (1.0f / D)), 0.f) + 1e-5f);
                nmean[k] *= hrstd[k];
            }
            mbar_wait(mb + MB_CS * 8);
            uint32_t* hb = reinterpret_cast<uint32_t*>(g_x + X_H2 + (mt * 88 + j * 11) * 128 + ww * 32) + lane;
#pragma unroll
            for (int i = 0; i < 22; i++) {
                float2 cs;
                asm volatile("ld.shared.v2.f32 {%0,%1}, [%2];" : "=f"(cs.x), "=f"(cs.y) : "r"(mb + MISC_CS + i * 32 + t4 * 8));
                const float* z = acc + 4 * i;
                uint32_t* p = hb + (i >> 1) * 512 + (i & 1) * 32;
                stg32(p, pack_bf16(silu2(fmaf(hrstd[0], z[0], nmean[0] * cs.x)), silu2(fmaf(hrstd[0], z[1], nmean[0] * cs.y))));
                stg32(p + 64, pack_bf16(silu2(fmaf(hrstd[1], z[2], nmean[1] * cs.x)), silu2(fmaf(hrstd[1], z[3], nmean[1] * cs.y))));
            }
            count_hint(C_H2 + mt);
            TS(10);
        }
        {
            uint32_t hk[16];
#pragma unroll
            for (int i = 0; i < 16; i++) hk[i] = ldg32_relaxed(hp + (i >> 2) * 512 + ((i & 1) * 2 + ((i >> 1) & 1)) * 32);
            float acc[32];
            if (gemm_ss<2>(acc, sb, pr TS_PASS)) gemm_slow(acc, g_x + X_H2 + mt * 88 * 128, 88, P.w2p, D, FF, j * 64);
            TS(11);
#pragma unroll
            for (int i = 0; i < 16; i++) hk[i] = pack_bf16(acc[2 * i] + bf_lo(hk[i]), acc[2 * i + 1] + bf_hi(hk[i]));
#pragma unroll
            for (int h = 0; h < 4; h++) {
                const uint32_t* v = hk + (h >> 1) * 8 + (h & 1);
                uint32_t v0 = v[0], v1 = v[2], v2 = v[4], v3 = v[6];
                const bool o1 = t4 & 1, o2 = t4 & 2;
                uint32_t a = __shfl_xor_sync(0xffffffffu, o1 ? v0 : v1, 1), c = __shfl_xor_sync(0xffffffffu, o1 ? v2 : v3, 1);
                if (o1) { v0 = a; v2 = c; } else { v1 = a; v3 = c; }
                a = __shfl_xor_sync(0xffffffffu, o2 ? v0 : v2, 2); c = __shfl_xor_sync(0xffffffffu, o2 ? v1 : v3, 2);
                if (o2) { v0 = a; v1 = c; } else { v2 = a; v3 = c; }
                *reinterpret_cast<uint4*>(P.out + (size_t)(mt * 64 + ww * 16 + g + 8 * (h & 1)) * D + j * 64 + (h >> 1) * 32 + t4 * 8) = make_uint4(v0, v1, v2, v3);
            }
        }
    }
    TS(12);
}

typedef CUresult (*EncodeFn)(CUtensorMap*, CUtensorMapDataType, cuuint32_t, void*, const cuuint64_t*, const cuuint64_t*, const cuuint32_t*,
                             const cuuint32_t*, CUtensorMapInterleave, CUtensorMapSwizzle, CUtensorMapL2promotion, CUtensorMapFloatOOBfill);

void encode2d(EncodeFn fn, CUtensorMap* tm, const void* ptr, int rows, int cols, int box_rows, int box_cols, CUtensorMapSwizzle sw) {
    cuuint64_t dims[2] = {(cuuint64_t)cols, (cuuint64_t)rows};
    cuuint64_t strides[1] = {(cuuint64_t)cols * 2};
    cuuint32_t box[2] = {(cuuint32_t)box_cols, (cuuint32_t)box_rows};
    cuuint32_t es[2] = {1, 1};
    fn(tm, CU_TENSOR_MAP_DATA_TYPE_BFLOAT16, 2, const_cast<void*>(ptr), dims, strides, box, es, CU_TENSOR_MAP_INTERLEAVE_NONE, sw,
       CU_TENSOR_MAP_L2_PROMOTION_L2_128B, CU_TENSOR_MAP_FLOAT_OOB_FILL_NONE);
}

}

extern "C" void kernel_launch(void* const* d_in, const int* in_sizes, int n_in, void* d_out, int out_size) {
    (void)in_sizes; (void)n_in; (void)out_size;
    void* fnp = nullptr;
    cudaDriverEntryPointQueryResult qr;
    cudaGetDriverEntryPoint("cuTensorMapEncodeTiled", &fnp, cudaEnableDefault, &qr);
    EncodeFn fn = (EncodeFn)fnp;
    Params P;
    encode2d(fn, &P.wq, d_in[1], D, D, 128, 64, CU_TENSOR_MAP_SWIZZLE_128B);
    P.wk = (const __nv_bfloat16*)d_in[2];
    P.wv_off = (const char*)d_in[3] - (const char*)d_in[2];
    encode2d(fn, &P.wo, d_in[4], D, D, 64, 64, CU_TENSOR_MAP_SWIZZLE_128B);
    encode2d(fn, &P.w1, d_in[6], D, FF, 64, 64, CU_TENSOR_MAP_SWIZZLE_128B);
    encode2d(fn, &P.w2, d_in[7], FF, D, 64, 64, CU_TENSOR_MAP_SWIZZLE_128B);
    P.x = (const __nv_bfloat16*)d_in[0];
    P.w1p = (const __nv_bfloat16*)d_in[6];
    P.w2p = (const __nv_bfloat16*)d_in[7];
    P.wop = (const __nv_bfloat16*)d_in[4];
    P.wqp = (const __nv_bfloat16*)d_in[1];
    P.out = (__nv_bfloat16*)d_out;
    P.neg1 = 0xFFFFFFFFu; P.pad = 0;
    cudaFuncSetAttribute(fused_kernel, cudaFuncAttributeMaxDynamicSharedMemorySize, SMEM_BYTES);
    fused_kernel<<<NCTA, 512, SMEM_BYTES>>>(P);
}
```

```cpp
#include <cuda_runtime.h>
#include <cuda_bf16.h>
#include <cuda.h>
#include <stdint.h>

namespace {

constexpr int D = 512, FF = 1376;
constexpr int NMAIN = 128, NHELP = 4, NCTA = NMAIN + NHELP;
constexpr uint32_t SENT = 0xFFFFFFFFu;
constexpr int SPIN_LIMIT = 1 << 22;

constexpr uint32_t KB = 1024, SLOT = 8192;
constexpr uint64_t XN_SLOTS = 7 | 16 << 8 | 6 << 16 | 17 << 24 | 21ull << 32 | 27ull << 40 | 24ull << 48 | 25ull << 56;
constexpr uint32_t WQ0_SLOTS = 0 | 2 << 8 | 4 << 16 | 10 << 24, WQ1_SLOTS = 12 | 14 << 8 | 18 << 16 | 22 << 24;
__host__ __device__ constexpr uint32_t xn_slot(int kb) { return (XN_SLOTS >> (8 * kb)) & 31; }
constexpr uint32_t SM_WKV = 208 * KB;
constexpr uint32_t SM_K = 0;
constexpr uint32_t SM_Q = 64 * KB;
constexpr uint32_t SM_V = 96 * KB;
constexpr uint32_t SM_MISC = 224 * KB;
constexpr uint32_t SMEM_BYTES = 227 * KB;
constexpr uint32_t SM_KTMP = 76 * KB;
constexpr uint32_t SM_RSTD = 226 * KB;
constexpr uint32_t SM_SENT = 208 * KB;
constexpr uint32_t MB_WQ = 0;
constexpr uint32_t MB_CS = 4;
constexpr uint32_t MB_DONE = 5;
constexpr uint32_t MB_EMPTY = 10;
constexpr uint32_t MB_W1 = 16;
constexpr uint32_t MB_W2 = 24;
constexpr uint32_t MB_WO = 32;
constexpr uint32_t MB_REL = 33;
constexpr uint32_t MB_KV = 43;
constexpr uint32_t MB_MID = 44;
constexpr uint32_t MB_READY = 44;
constexpr uint32_t MB_FULL = 50;
constexpr uint32_t MB_NULL = 126;
constexpr uint32_t MB_KV0 = 128;
constexpr uint32_t MB_EPI = 127;
__host__ __device__ constexpr uint32_t bar_count(uint32_t i) {
    return i >= MB_FULL + 16 ? 2 : i >= MB_KV ? 1 : i >= MB_WO ? 8 : i >= MB_W1 + 3 ? 1 : i >= MB_W1 ? 3 : i >= MB_EMPTY ? 4 : i >= MB_DONE ? 16 : 1;
}
constexpr uint32_t MISC_NRM = 1056;
constexpr uint32_t MISC_EPOCH = 1072;
constexpr uint32_t MISC_TS = 1088;
constexpr uint32_t MISC_CS = 1344;

__host__ __device__ constexpr uint32_t wo_slot(int kb) { return kb < 2 ? 10 + kb : kb - 2; }
__host__ __device__ constexpr uint32_t w1_slot(int kb, int a) { return kb < 4 ? 12 + kb + 4 * a : (kb < 6 ? 3 * kb - 6 : 3 * kb - 18) + a; }

struct alignas(128) Small {
    unsigned epoch[160];
    unsigned cnt[100][32];
    float cs[1440];
    uint4 nrm[NMAIN * 2];
    uint4 kv[8192];
    uint4 kplain[4096];
};
__device__ Small g_s;
constexpr int C_KVH = 0, C_KV = 1, C_MID = 2, C_O = 3, C_H1 = 35, C_H2 = 67;
constexpr int X_O = 0, X_H1 = 32 * 32 * 128, X_H2 = 2 * X_H1, X_ST = X_H2 + 32 * 88 * 128, X_END = X_ST + 32 * 8 * 32;
constexpr int X_ARM = 16 * 32 * 128, X_SHARE = (X_END - X_ARM) / NMAIN;
__device__ uint4 g_x[X_END];
#define TS(i) do {} while (0)
#define TSF(k)

#define TS_ARG
#define TS_PASS

__device__ __forceinline__ void mbar_init(uint32_t bar, int cnt) { asm volatile("mbarrier.init.shared::cta.b64 [%0], %1;" :: "r"(bar), "r"(cnt) : "memory"); }
__device__ __forceinline__ void mbar_expect(uint32_t bar, uint32_t bytes) { asm volatile("mbarrier.arrive.expect_tx.shared::cta.b64 _, [%0], %1;" :: "r"(bar), "r"(bytes) : "memory"); }
__device__ __forceinline__ void mbar_arrive(uint32_t bar) { asm volatile("mbarrier.arrive.shared::cta.b64 _, [%0];" :: "r"(bar) : "memory"); }
__device__ __forceinline__ bool mbar_try(uint32_t bar, uint32_t parity) {
    uint32_t done;
    asm volatile("{.reg .pred p; mbarrier.try_wait.parity.shared::cta.b64 p, [%1], %2; selp.u32 %0, 1, 0, p;}" : "=r"(done) : "r"(bar), "r"(parity) : "memory");
    return __all_sync(0xffffffffu, done);
}
__device__ __forceinline__ void mbar_wait(uint32_t bar, uint32_t parity = 0) {
    if (__builtin_expect(!mbar_try(bar, parity), 0)) {
        int spins = 0;
        while (!mbar_try(bar, parity) && ++spins < (SPIN_LIMIT >> 6)) {}
    }
}
__device__ __forceinline__ void tma2d(uint32_t dst, const CUtensorMap* tm, int c0, int c1, uint32_t bar) {
    asm volatile("cp.async.bulk.tensor.2d.shared::cluster.global.mbarrier::complete_tx::bytes [%0], [%1, {%3, %4}], [%2];"
                 :: "r"(dst), "l"(tm), "r"(bar), "r"(c0), "r"(c1) : "memory");
}
__device__ __forceinline__ void bulk_g2s(uint32_t dst, const void* src, uint32_t bytes, uint32_t bar) {
    asm volatile("cp.async.bulk.shared::cluster.global.mbarrier::complete_tx::bytes [%0], [%1], %2, [%3];" :: "r"(dst), "l"(src), "r"(bytes), "r"(bar) : "memory");
}
__device__ __forceinline__ void fence_async_smem() { asm volatile("fence.proxy.async.shared::cta;" ::: "memory"); }
__device__ __forceinline__ void bar_sync(int id, int n) { asm volatile("bar.sync %0, %1;" :: "r"(id), "r"(n) : "memory"); }
__device__ __forceinline__ void bar_arrive(int id, int n) { asm volatile("bar.arrive %0, %1;" :: "r"(id), "r"(n) : "memory"); }
__device__ __forceinline__ void wg_fence() { asm volatile("wgmma.fence.sync.aligned;" ::: "memory"); }
__device__ __forceinline__ void wg_commit() { asm volatile("wgmma.commit_group.sync.aligned;" ::: "memory"); }
template <int N> __device__ __forceinline__ void wg_wait() { asm volatile("wgmma.wait_group.sync.aligned %0;" :: "n"(N) : "memory"); }
template <int N> __device__ __forceinline__ void fence_regs(float (&d)[N]) {
#pragma unroll
    for (int i = 0; i < N; i++) asm volatile("" : "+f"(d[i]) :: "memory");
}
template <int N> __device__ __forceinline__ void fence_regs(uint32_t (&d)[N]) {
#pragma unroll
    for (int i = 0; i < N; i++) asm volatile("" : "+r"(d[i]) :: "memory");
}
__device__ __forceinline__ uint64_t mkdesc(uint32_t addr, uint32_t lbo, uint32_t sbo, uint32_t swz) {
    return (uint64_t)(((addr & 0x3FFFF) >> 4) | ((lbo >> 4) << 16)) | ((uint64_t)((sbo >> 4) | (swz << 30)) << 32);
}
__device__ __forceinline__ float ex2(float x) { float y; asm("ex2.approx.ftz.f32 %0, %1;" : "=f"(y) : "f"(x)); return y; }
__device__ __forceinline__ float rcp(float x) { float y; asm("rcp.approx.ftz.f32 %0, %1;" : "=f"(y) : "f"(x)); return y; }
__device__ __forceinline__ uint32_t pack_bf16(float lo, float hi) { uint32_t r; asm("cvt.rn.bf16x2.f32 %0, %1, %2;" : "=r"(r) : "f"(hi), "f"(lo)); return r; }
__device__ __forceinline__ uint32_t pack_f16(float lo, float hi) { uint32_t r; asm("cvt.rn.f16x2.f32 %0, %1, %2;" : "=r"(r) : "f"(hi), "f"(lo)); return r; }
__device__ __forceinline__ float bf_lo(uint32_t v) { return __uint_as_float(v << 16); }
__device__ __forceinline__ float bf_hi(uint32_t v) { return __uint_as_float(v & 0xFFFF0000u); }
__device__ __forceinline__ uint4 ldg_relaxed(const uint4* p) {
    uint4 v; asm volatile("ld.relaxed.gpu.global.v4.u32 {%0,%1,%2,%3}, [%4];" : "=r"(v.x), "=r"(v.y), "=r"(v.z), "=r"(v.w) : "l"(p) : "memory"); return v;
}
__device__ __forceinline__ void stg128(void* p, uint32_t a, uint32_t b, uint32_t c, uint32_t d) {
    asm volatile("st.relaxed.gpu.global.v4.u32 [%0], {%1,%2,%3,%4};" :: "l"(p), "r"(a), "r"(b), "r"(c), "r"(d) : "memory");
}
__device__ __forceinline__ void stg64(void* p, uint32_t a, uint32_t b) {
    asm volatile("st.relaxed.gpu.global.v2.u32 [%0], {%1,%2};" :: "l"(p), "r"(a), "r"(b) : "memory");
}
__device__ __forceinline__ void sts128(uint32_t a, uint32_t x, uint32_t y, uint32_t z, uint32_t w) {
    asm volatile("st.shared.v4.u32 [%0], {%1,%2,%3,%4};" :: "r"(a), "r"(x), "r"(y), "r"(z), "r"(w) : "memory");
}
__device__ __forceinline__ void sts32(uint32_t a, uint32_t x) { asm volatile("st.shared.u32 [%0], %1;" :: "r"(a), "r"(x) : "memory"); }
__device__ __forceinline__ float4 lds128f(uint32_t a) {
    float4 v; asm volatile("ld.shared.v4.f32 {%0,%1,%2,%3}, [%4];" : "=f"(v.x), "=f"(v.y), "=f"(v.z), "=f"(v.w) : "r"(a) : "memory"); return v;
}
__device__ __forceinline__ uint32_t lds32(uint32_t a) { uint32_t v; asm volatile("ld.shared.u32 %0, [%1];" : "=r"(v) : "r"(a) : "memory"); return v; }
__device__ __forceinline__ uint32_t nonzero(uint32_t w) { return w == 0u ? 0x8000u : w; }
__device__ __forceinline__ void stg32(void* p, uint32_t a) { asm volatile("st.global.u32 [%0], %1;" :: "l"(p), "r"(a) : "memory"); }
__device__ __forceinline__ uint32_t ldg32_relaxed(const void* p) { uint32_t v; asm volatile("ld.relaxed.gpu.global.u32 %0, [%1];" : "=r"(v) : "l"(p) : "memory"); return v; }
__device__ __forceinline__ void count_hint(int id) {
    if ((threadIdx.x & 31) == 0) asm volatile("red.relaxed.gpu.global.add.u32 [%0], 1;" :: "l"(g_s.cnt[id]) : "memory");
}
__device__ __forceinline__ void count_release(int id) {
    __syncwarp();
    if ((threadIdx.x & 31) == 0) asm volatile("red.release.gpu.global.add.u32 [%0], 1;" :: "l"(g_s.cnt[id]) : "memory");
    __syncwarp();
}
__device__ __forceinline__ void count_wait(int id, unsigned target) {
    uint32_t v; int spins = 0;
    do v = ldg32_relaxed(g_s.cnt[id]); while (__any_sync(0xffffffffu, v != target) && ++spins < SPIN_LIMIT);
    asm volatile("fence.acquire.gpu;" ::: "memory");
}
__device__ __forceinline__ void warp_done(uint32_t bar) {
    __syncwarp();
    asm volatile("{.reg .pred p; setp.eq.u32 p, %1, 0; @p mbarrier.arrive.shared::cta.b64 _, [%0];}" :: "r"(bar), "r"(threadIdx.x & 31) : "memory");
}
__device__ __forceinline__ uint32_t mul_bf16x2(uint32_t a, uint32_t b) { uint32_t r; asm("mul.rn.bf16x2 %0, %1, %2;" : "=r"(r) : "r"(a), "r"(b)); return r; }
__device__ __forceinline__ uint32_t fma_bf16x2(uint32_t a, uint32_t b, uint32_t c) { uint32_t r; asm("fma.rn.bf16x2 %0, %1, %2, %3;" : "=r"(r) : "r"(a), "r"(b), "r"(c)); return r; }
__device__ __forceinline__ uint32_t add_bf16x2(uint32_t a, uint32_t b) { uint32_t r; asm("add.rn.bf16x2 %0, %1, %2;" : "=r"(r) : "r"(a), "r"(b)); return r; }

#define R4(d, o) "+f"(d[o + 0]), "+f"(d[o + 1]), "+f"(d[o + 2]), "+f"(d[o + 3])
#define R8(d, o) R4(d, o), R4(d, o + 4)
#define R32(d) R8(d, 0), R8(d, 8), R8(d, 16), R8(d, 24)
#define D32 "{%0,%1,%2,%3,%4,%5,%6,%7,%8,%9,%10,%11,%12,%13,%14,%15,%16,%17,%18,%19,%20,%21,%22,%23,%24,%25,%26,%27,%28,%29,%30,%31}"
#define D64 "{%0,%1,%2,%3,%4,%5,%6,%7,%8,%9,%10,%11,%12,%13,%14,%15,%16,%17,%18,%19,%20,%21,%22,%23,%24,%25,%26,%27,%28,%29,%30,%31,%32,%33,%34,%35,%36,%37,%38,%39,%40,%41,%42,%43,%44,%45,%46,%47,%48,%49,%50,%51,%52,%53,%54,%55,%56,%57,%58,%59,%60,%61,%62,%63}"

__device__ __forceinline__ void mma_qk_f16(float (&d)[32], uint64_t da, uint64_t db) {
    asm volatile("{.reg .pred p; setp.eq.b32 p, 0, 0; wgmma.mma_async.sync.aligned.m64n64k16.f32.f16.f16 " D32 ", %32, %33, p, 1, 1, 0, 0;}"
                 : R32(d) : "l"(da), "l"(db));
}
__device__ __forceinline__ void mma_qk_bf16(float (&d)[32], uint64_t da, uint64_t db) {
    asm volatile("{.reg .pred p; setp.ne.b32 p, 0, 0; wgmma.mma_async.sync.aligned.m64n64k16.f32.bf16.bf16 " D32 ", %32, %33, p, 1, 1, 0, 0;}"
                 : R32(d) : "l"(da), "l"(db));
}
__device__ __forceinline__ void mma_pv(float (&d)[12], const uint32_t* a, uint64_t db) {
    asm volatile("{.reg .pred p; setp.eq.b32 p, 0, 0; wgmma.mma_async.sync.aligned.m64n24k16.f32.bf16.bf16 {%0,%1,%2,%3,%4,%5,%6,%7,%8,%9,%10,%11}, {%12,%13,%14,%15}, %16, p, 1, 1, 1;}"
                 : R8(d, 0), R4(d, 8) : "r"(a[0]), "r"(a[1]), "r"(a[2]), "r"(a[3]), "l"(db));
}
__device__ __forceinline__ void mma_ss128(float (&d)[64], uint64_t da, uint64_t db) {
    asm volatile("{.reg .pred p; setp.eq.b32 p, 0, 0; wgmma.mma_async.sync.aligned.m64n128k16.f32.bf16.bf16 " D64 ", %64, %65, p, 1, 1, 0, 1;}"
                 : R32(d), R8(d, 32), R8(d, 40), R8(d, 48), R8(d, 56) : "l"(da), "l"(db));
}
__device__ __forceinline__ void stsm4(uint32_t addr, uint32_t a, uint32_t b, uint32_t c, uint32_t d) {
    asm volatile("stmatrix.sync.aligned.m8n8.x4.shared.b16 [%0], {%1,%2,%3,%4};" :: "r"(addr), "r"(a), "r"(b), "r"(c), "r"(d) : "memory");
}
__device__ __forceinline__ void mma_ss8(float (&d)[4], uint64_t da, uint64_t db) {
    asm volatile("{.reg .pred p; setp.eq.b32 p, 0, 0; wgmma.mma_async.sync.aligned.m64n8k16.f32.bf16.bf16 {%0,%1,%2,%3}, %4, %5, p, 1, 1, 0, 1;}"
                 : R4(d, 0) : "l"(da), "l"(db));
}
__device__ __forceinline__ void mma_ss(float (&d)[32], uint64_t da, uint64_t db, int accum) {
    asm volatile("{.reg .pred p; setp.ne.b32 p, %34, 0; wgmma.mma_async.sync.aligned.m64n64k16.f32.bf16.bf16 " D32 ", %32, %33, p, 1, 1, 0, 1;}"
                 : R32(d) : "l"(da), "l"(db), "r"(accum));
}
__device__ __forceinline__ void mma_ss(float (&d)[88], uint64_t da, uint64_t db, int accum) {
    asm volatile("{.reg .pred p; setp.ne.b32 p, %90, 0; wgmma.mma_async.sync.aligned.m64n176k16.f32.bf16.bf16 " "{%0,%1,%2,%3,%4,%5,%6,%7,%8,%9,%10,%11,%12,%13,%14,%15,%16,%17,%18,%19,%20,%21,%22,%23,%24,%25,%26,%27,%28,%29,%30,%31,%32,%33,%34,%35,%36,%37,%38,%39,%40,%41,%42,%43,%44,%45,%46,%47,%48,%49,%50,%51,%52,%53,%54,%55,%56,%57,%58,%59,%60,%61,%62,%63,%64,%65,%66,%67,%68,%69,%70,%71,%72,%73,%74,%75,%76,%77,%78,%79,%80,%81,%82,%83,%84,%85,%86,%87}"
                 ", %88, %89, p, 1, 1, 0, 1;}"
                 : R32(d), R8(d, 32), R8(d, 40), R8(d, 48), R8(d, 56), R8(d, 64), R8(d, 72), R8(d, 80) : "l"(da), "l"(db), "r"(accum));
}

constexpr float EXP_MAGIC = 256.0f + 127.0f + 64.0f - 1.58621f + 0.00390625f;
#define MUFU_M 0x1111u
#define ALU_M 0x0000u
constexpr uint32_t MUFU_MASK = MUFU_M;
constexpr uint32_t ALU_MASK = ALU_M;
template <bool ALU>
__device__ __forceinline__ uint32_t exp2_pair(float y0, float y1, uint32_t cexp, uint32_t neg1) {
    uint32_t w, m, e, r;
    asm("prmt.b32 %0, %1, %2, 0x6521;" : "=r"(w) : "r"(__float_as_uint(y0)), "r"(__float_as_uint(y1)));
    asm("lop3.b32 %0, %1, 0x007F007F, %2, 0xEA;" : "=r"(m) : "r"(w), "r"(cexp));
    if (ALU) e = w - m;
    else asm("mad.lo.u32 %0, %1, %2, %3;" : "=r"(e) : "r"(m), "r"(neg1), "r"(w));
    asm("fma.rn.bf16x2 %0, %1, %2, %3;" : "=r"(r) : "r"(w), "r"(m), "r"(e));
    return r;
}

struct Params {
    const __nv_bfloat16* x;
    const __nv_bfloat16* wk;
    long long wv_off;
    const __nv_bfloat16* wqp;
    __nv_bfloat16* out;
    uint32_t neg1, pad;
    const __nv_bfloat16* w1p;
    const __nv_bfloat16* w2p;
    CUtensorMap wq, wo, w1, w2;
    const __nv_bfloat16* wop;
};

__device__ __forceinline__ int tail_m() { return (blockIdx.x >> 5) * 4 + ((blockIdx.x >> 2) & 3); }
__device__ __forceinline__ int tail_j() { return ((blockIdx.x >> 4) & 1) * 4 + (blockIdx.x & 3); }
__device__ __forceinline__ void load_box(uint32_t sb, const CUtensorMap* tm, uint32_t dst, uint32_t bar, uint32_t bytes, int c0, int c1) {
    mbar_expect(sb + SM_MISC + bar * 8, bytes);
    tma2d(sb + dst, tm, c0, c1, sb + SM_MISC + bar * 8);
}
__device__ __forceinline__ void load_wq(uint32_t sb, const Params& P, int gi, int atom) {
    load_box(sb, &P.wq, (((atom ? WQ1_SLOTS : WQ0_SLOTS) >> (8 * gi)) & 31) * SLOT, MB_WQ + gi, 16384, (blockIdx.x & 3) * 128 + atom * 64, gi * 128);
}
__device__ __forceinline__ void load_wo(uint32_t sb, const Params& P, int kb) { load_box(sb, &P.wo, wo_slot(kb) * SLOT, MB_WO, SLOT, tail_j() * 64, kb * 64); }
__device__ __forceinline__ void refill_job(uint32_t sb, const Params& P, int gi, int job) {
    const bool w1 = job < 3;
    load_box(sb, w1 ? &P.w1 : &P.wo, (w1 ? 12 + gi + 4 * job : 2 * gi + job - 3) * SLOT, w1 ? MB_W1 + gi : MB_WO, SLOT,
             tail_j() * (w1 ? 176 : 64) + (w1 ? job * 64 : 0), (w1 ? gi : 2 * gi + job - 1) * 64);
}

__host__ __device__ constexpr int ring_entry(int n) { return n < 32 ? (n & 3) : (n - 32) % 6; }
__host__ __device__ constexpr uint32_t ring_slot(int e) { return e < 4 ? 24 + e : e; }

template <int KIND> __host__ __device__ constexpr uint64_t b_slots(int first) {
    uint64_t v = 0;
    for (int i = first; i < first + 12; i++) v |= (uint64_t)((KIND == 0 ? wo_slot(i) : KIND == 1 ? w1_slot(i, 0) : w1_slot(i / 3, i % 3)) & 31) << (5 * (i - first));
    return v;
}
__device__ __forceinline__ uint64_t desc64(uint32_t lo, uint32_t hi) { uint64_t d; asm("mov.b64 %0, {%1, %2};" : "=l"(d) : "r"(lo), "r"(hi)); return d; }
__device__ __forceinline__ uint32_t mbar_test(uint32_t bar) {
    uint32_t done;
    asm volatile("{.reg .pred p; mbarrier.test_wait.parity.shared::cta.b64 p, [%1], 0; selp.u32 %0, 1, 0, p;}" : "=r"(done) : "r"(bar) : "memory");
    return done;
}
template <int KIND, int NACC>
__device__ __forceinline__ bool gemm_ss(float (&acc)[NACC], uint32_t sb, int pr TS_ARG) {
    const uint32_t mb = sb + SM_MISC;
    constexpr int NBLK = KIND == 2 ? 22 : 8, N0 = 16 * KIND;
    uint32_t full = mb + (MB_FULL + N0 + pr * NBLK) * 8, empty = mb + MB_NULL * 8, rel = mb + MB_NULL * 8;
    const uint32_t lane = threadIdx.x & 31, probe = sb + ((threadIdx.x >> 5) & 3) * 512 + (lane >> 4) * 2048 + (lane & 15) * 32 + (lane >> 2) * 4;
    uint32_t m = 0;
    constexpr uint32_t R4S = 24 | 25 << 5 | 26 << 10 | 27 << 15;
    uint32_t ra = KIND == 2 ? (pr ? (4 | 5 << 5 | R4S << 10) : (R4S | 4 << 20 | 5 << 25)) : (KIND == 0 && pr) ? (6 | 7 << 5 | 8 << 10 | 9 << 15) : R4S;
    uint64_t tab = b_slots<KIND>(0);
    const uint32_t a0 = (sb >> 4) | (8 << 16);
    uint32_t b0 = (sb >> 4) | ((KIND == 1 ? 4 * SLOT / 16 : 1) << 16);
    mbar_wait(full);
#pragma unroll 1
    for (int i = 0; i < NBLK; i++) {
        const uint32_t sa = ra & 31, da = a0 + sa * 512, db = b0 + ((uint32_t)tab & 31) * 512;
        full += (i == NBLK - 1) ? 0 : 8;
        const uint32_t ready = mbar_test(full);
        const uint32_t m0 = lds32(probe + sa * SLOT), m1 = lds32(probe + sa * SLOT + 4096);
        wg_fence();
#pragma unroll
        for (int s = 0; s < 4; s++) mma_ss(acc, desc64(da + s * 128, 16), desc64(db + s * 128, 0x40000040), s ? 1 : i);
        wg_commit();
        m = max(m, max(m0, m1));
        const uint32_t prev = empty, prel = rel;
        empty = mb + ((KIND == 0 && sa < 24) ? MB_NULL : MB_EMPTY + (sa & 7)) * 8;
        rel = mb + (KIND == 1 ? MB_REL + i : i == 3 ? MB_REL + 9 : MB_NULL) * 8;
        ra = KIND == 2 ? (ra >> 5) | (sa << 25) : i == 3 ? R4S : ra >> 5;
        tab = (KIND == 2 && i == 11) ? b_slots<KIND>(12) : tab >> 5;
        if (KIND == 1 && i == 3) b0 -= (3 * SLOT / 16) << 16;
        wg_wait<1>();
        warp_done(prev);
        if (KIND != 2) warp_done(prel);
        if (!__all_sync(0xffffffffu, ready)) mbar_wait(full);
    }
    bool bad = __any_sync(0xffffffffu, m == SENT);
    wg_wait<0>();
    fence_regs(acc);
    warp_done(empty);
    if (KIND != 2) warp_done(mb + (MB_REL + 8 - KIND) * 8);
    return __builtin_expect(bad, 0);
}
__device__ __forceinline__ void ring_feed(uint32_t sb, int e TS_ARG) {
    const uint32_t mb = sb + SM_MISC;
    uint32_t dst = sb + ring_slot(e) * SLOT, empty = mb + (MB_EMPTY + e) * 8;
    const bool lead = (threadIdx.x & 31) == 0;
    const uint4* base = g_x + tail_m() * 4096 + e * 512;
    uint32_t par = 0;
    auto fetch = [&](int n, const uint4* src, int job) {
        const uint32_t full = mb + (MB_FULL + n) * 8;
        if (lead) mbar_expect(full, SLOT);
        mbar_wait(empty, par); par ^= 1;
        if (job) mbar_wait(mb + (MB_READY + job) * 8);
        if (lead) bulk_g2s(dst, src, SLOT, full);
        __syncwarp();
    };
    if (e < 4) {
        fetch(4 + e, base + 2048, 0);
        if (lead) mbar_expect(mb + (MB_FULL + 8 + e) * 8, SLOT);
        mbar_wait(mb + (MB_DONE + 4) * 8);
        mbar_wait(mb + (MB_READY + 1) * 8);
        if (lead) bulk_g2s(sb + (6 + e) * SLOT, base + 65536, SLOT, mb + (MB_FULL + 8 + e) * 8);
        fetch(12 + e, base + 65536 + 2048, 0);
#pragma unroll 1
        for (int h = 0; h < 2; h++) {
            fetch(16 + 8 * h + e, base + X_H1 + h * 65536, 2 + h);
            fetch(20 + 8 * h + e, base + X_H1 + h * 65536 + 2048, 0);
        }
    } else {
        mbar_wait(mb + (MB_REL + 7) * 8);
        par = 1;
    }
    const uint4* src = g_x + X_H2 + tail_m() * 88 * 128 + e * 512;
#pragma unroll 1
    for (int n = e; n < 44; n += 6, src += 6 * 512) {
        const bool second = n >= 22 && n < 28;
        if (second) src += 16 * 88 * 128 - 22 * 512;
        fetch(32 + n, src, n < 6 ? 4 : second ? 5 : 0);
        if (e == 4) {
            par ^= 1; dst += SLOT; empty += 8;
            fetch(33 + n, src + 512, 0);
            dst -= SLOT; empty -= 8;
        }
    }
}
__device__ __noinline__ void gemm_slow_impl(float* out, int ntile, const uint4* a, int nst, const __nv_bfloat16* W, int ldw, int kmax, int n0) {
    const int lane = threadIdx.x & 31;
    const unsigned short* w = reinterpret_cast<const unsigned short*>(W);
    for (int j = 0; j < ntile; j++) {
        const uint32_t* p = reinterpret_cast<const uint32_t*>(a) + ((threadIdx.x >> 5) & 3) * 128 + lane;
        const int n = n0 + 8 * j + (lane >> 2);
        float d[4] = {0.f, 0.f, 0.f, 0.f};
        for (int st = 0; st < nst; st++, p += 512) {
            const int k = st * 16 + 2 * (lane & 3);
            uint32_t v0, v1, v2, v3, b0 = 0, b1 = 0; int spins = 0;
            do { v0 = ldg32_relaxed(p); v1 = ldg32_relaxed(p + 64); v2 = ldg32_relaxed(p + 32); v3 = ldg32_relaxed(p + 96); }
            while (__any_sync(0xffffffffu, max(max(v0, v1), max(v2, v3)) == SENT) && ++spins < SPIN_LIMIT);
            if (k < kmax && n < ldw) {
                const unsigned short* q = w + (size_t)k * ldw + n;
                b0 = q[0] | ((uint32_t)q[ldw] << 16); b1 = q[8 * ldw] | ((uint32_t)q[9 * ldw] << 16);
            }
            asm volatile("mma.sync.aligned.m16n8k16.row.col.f32.bf16.bf16.f32 {%0,%1,%2,%3}, {%4,%5,%6,%7}, {%8,%9}, {%0,%1,%2,%3};"
                         : R4(d, 0) : "r"(v0), "r"(v1), "r"(v2), "r"(v3), "r"(b0), "r"(b1));
        }
        *reinterpret_cast<float4*>(out + 4 * j) = make_float4(d[0], d[1], d[2], d[3]);
    }
}
template <int NACC>
__device__ __forceinline__ void gemm_slow(float (&acc)[NACC], const uint4* a, int nst, const __nv_bfloat16* W, int ldw, int kmax, int n0) {
    __align__(16) float tmp[NACC];
    gemm_slow_impl(tmp, NACC / 4, a, nst, W, ldw, kmax, n0);
#pragma unroll
    for (int i = 0; i < NACC; i++) acc[i] = tmp[i];
}
__device__ __forceinline__ void store_tile(uint32_t* p, uint32_t r0k0, uint32_t r8k0, uint32_t r0k8, uint32_t r8k8) {
    stg32(p, r0k0); stg32(p + 32, r0k8); stg32(p + 64, r8k0); stg32(p + 96, r8k8);
}

__device__ __forceinline__ float quad_sum(float v) { v += __shfl_xor_sync(0xffffffffu, v, 1); v += __shfl_xor_sync(0xffffffffu, v, 2); return v; }
__device__ __forceinline__ float reduce4(const float (&st)[4], int lane) {
    const bool u16 = lane & 16, u8 = lane & 8;
    const float a0 = (u16 ? st[2] : st[0]) + __shfl_xor_sync(0xffffffffu, u16 ? st[0] : st[2], 16);
    const float a1 = (u16 ? st[3] : st[1]) + __shfl_xor_sync(0xffffffffu, u16 ? st[1] : st[3], 16);
    float v = (u8 ? a1 : a0) + __shfl_xor_sync(0xffffffffu, u8 ? a0 : a1, 8);
    v += __shfl_xor_sync(0xffffffffu, v, 4); v += __shfl_xor_sync(0xffffffffu, v, 2); v += __shfl_xor_sync(0xffffffffu, v, 1);
    return v;
}
__device__ __forceinline__ float silu2(float h) { float t; asm("tanh.approx.f32 %0, %1;" : "=f"(t) : "f"(h)); return fmaf(h, t, h); }

template <bool SAFE>
__device__ __forceinline__ void attention(const Params& P, uint32_t sb, int warp TS_ARG) {
    const uint32_t mb = sb + SM_MISC;
    const int tid = threadIdx.x, lane = tid & 31, b = blockIdx.x;
    const int wg = warp >> 2, ww = warp & 3, job = 3 - wg + 4 * ww;
    const uint32_t cexp = 0x9F809F80u + (tid >> 12);
    const uint32_t neg1 = P.neg1;
    unsigned cnt = 0;
    if (SAFE && warp == 8) cnt = ldg32_relaxed(g_s.cnt[C_KV]);
#pragma unroll 1
    for (int pass = 0; pass < 2; pass++) {
    float o[12], s[32];
    const uint64_t dq = mkdesc(sb + SM_Q + (pass * 4 + wg) * 2048, 128, 256, 0);
    uint64_t dk = mkdesc(sb + SM_K, 128, 256, 0), dv = mkdesc(sb + SM_V, 128, 32768, 0);
    float m0 = -INFINITY, m1 = -INFINITY;
#pragma unroll
    for (int i = 0; i < 12; i++) o[i] = 0.f;
#pragma unroll
    for (int i = 0; i < 32; i++) s[i] = ((MUFU_MASK >> (i / 2)) & 1) ? 0.f : EXP_MAGIC;
    fence_regs(s); fence_regs(o);
    wg_fence();
    if (SAFE) mma_qk_f16(s, dq, dk + 31 * 128); else mma_qk_bf16(s, dq, dk + 31 * 128);
    wg_commit();
    wg_wait<0>(); fence_regs(s);
#pragma unroll 1
    for (int u = pass ? 3 : (wg == 2) ? 0 : 1; u < (pass ? 8 : 3); u++) {
        int n = 2 * ((((wg == 2) ? 0x22444C31u : 0x22444C40u) >> (4 * u)) & 15);
#pragma unroll 1
        do {
            uint32_t p[16];
            if (SAFE) {
#pragma unroll
                for (int j = 0; j < 16; j++) {
                    if ((MUFU_MASK >> j) & 1) p[j] = pack_bf16(ex2(s[2 * j]), ex2(s[2 * j + 1]));
                    else if ((ALU_MASK >> j) & 1) p[j] = exp2_pair<true>(s[2 * j], s[2 * j + 1], cexp, neg1);
                    else p[j] = exp2_pair<false>(s[2 * j], s[2 * j + 1], cexp, neg1);
                }
            } else {
                fence_regs(o);
                float x0 = m0, x1 = m1;
#pragma unroll
                for (int j = 0; j < 8; j++) { x0 = fmaxf(x0, fmaxf(s[4 * j], s[4 * j + 1])); x1 = fmaxf(x1, fmaxf(s[4 * j + 2], s[4 * j + 3])); }
                x0 = fmaxf(x0, __shfl_xor_sync(0xffffffffu, x0, 1)); x0 = fmaxf(x0, __shfl_xor_sync(0xffffffffu, x0, 2));
                x1 = fmaxf(x1, __shfl_xor_sync(0xffffffffu, x1, 1)); x1 = fmaxf(x1, __shfl_xor_sync(0xffffffffu, x1, 2));
                const float c0 = ex2(m0 - x0), c1 = ex2(m1 - x1);
                m0 = x0; m1 = x1;
#pragma unroll
                for (int j = 0; j < 3; j++) { o[4 * j] *= c0; o[4 * j + 1] *= c0; o[4 * j + 2] *= c1; o[4 * j + 3] *= c1; }
#pragma unroll
                for (int j = 0; j < 8; j++) {
                    p[2 * j] = pack_bf16(ex2(s[4 * j] - m0), ex2(s[4 * j + 1] - m0));
                    p[2 * j + 1] = pack_bf16(ex2(s[4 * j + 2] - m1), ex2(s[4 * j + 3] - m1));
                }
                fence_regs(o);
            }
            fence_regs(p);
            wg_fence();
            if (SAFE) mma_qk_f16(s, dq, dk); else mma_qk_bf16(s, dq, dk);
#pragma unroll
            for (int j = 0; j < 4; j++) mma_pv(o, p + 4 * j, dv + j * 16);
            wg_commit();
            dk += 128; dv += 64;
            wg_wait<0>(); fence_regs(s);
        } while (--n > 0);
        if (u == 2 || u == 7) {
            fence_regs(o);
            const float i0 = rcp(o[8]), i1 = rcp(o[10]);
            if (u == 7) mbar_wait(mb + MB_MID * 8);
            store_tile(reinterpret_cast<uint32_t*>(g_x + X_O + (((u == 7) * 16 + (b >> 3)) * 32 + (b & 3) * 8 + 2 * wg + (ww >> 1)) * 128 + (((b >> 2) & 1) * 2 + (ww & 1)) * 32) + lane,
                       pack_bf16(o[0] * i0, o[1] * i0), pack_bf16(o[2] * i1, o[3] * i1), pack_bf16(o[4] * i0, o[5] * i0), pack_bf16(o[6] * i1, o[7] * i1));
            if (u == 2) asm volatile("cp.async.bulk.wait_group 0;" ::: "memory");
            else count_hint(C_O + 16 + (b >> 3));
            warp_done(mb + (MB_DONE + (u == 7) * 4) * 8);
            TS(5 + (u == 7));
        } else if (u >= 3) {
            if (u < 6) warp_done(mb + (MB_DONE + u - 2) * 8);
            if (job < (u == 3 ? 1 : 5)) {
                mbar_wait(mb + (MB_DONE + u - 3) * 8);
                if (u == 3) count_release(C_MID);
                else if (lane == 0) refill_job(sb, P, u - 4, job);
            } else if (u == 6) {
                if (job < 9) {
                    mbar_wait(mb + MB_MID * 8);
                    if (lane == 0) {
                        mbar_expect(mb + (MB_FULL + job - 5) * 8, SLOT);
                        bulk_g2s(sb + (19 + job) * SLOT, g_x + X_O + tail_m() * 4096 + (job - 5) * 512, SLOT, mb + (MB_FULL + job - 5) * 8);
                    }
                }
            } else if (warp == 7) {
                if (u == 4) cnt = ldg32_relaxed(g_s.cnt[C_MID]);
                if (u == 5) {
                    const unsigned target = lds32(mb + MISC_EPOCH) * NCTA;
                    if (__any_sync(0xffffffffu, cnt != target)) count_wait(C_MID, target);
                    asm volatile("fence.acquire.gpu; fence.proxy.async.global;" ::: "memory");
                    warp_done(mb + MB_MID * 8);
                }
            }
        } else if (u == 1) {
            if (SAFE) mbar_wait(mb + MB_KV * 8);
            TS(17);
            if (lane == 0) {
                if (job < 9) {
                    asm volatile("cp.async.bulk.global.shared::cta.bulk_group [%0], [%1], %2;"
                                 :: "l"(g_x + X_ARM + b * X_SHARE + job * 512), "r"(sb + SM_SENT), "r"(job < 8 ? 8192 : (X_SHARE - 4096) * 16) : "memory");
                    asm volatile("cp.async.bulk.commit_group;" ::: "memory");
                } else if (job < 11) load_wo(sb, P, job - 9);
            }
        } else if (SAFE) {
            if (warp == 8) {
                const unsigned target = lds32(mb + MISC_EPOCH) * NMAIN;
                if (__any_sync(0xffffffffu, cnt != target)) count_wait(C_KV, target);
                if (lane == 0) {
                    asm volatile("fence.acquire.gpu; fence.proxy.async.global;" ::: "memory");
                    mbar_expect(mb + MB_KV * 8, 47104 + 2 * 24576);
                    bulk_g2s(sb + SM_K + 16384, g_s.kv + 1024, 47104, mb + MB_KV * 8);
                    bulk_g2s(sb + SM_V + 8192, g_s.kv + 4096 + 512, 24576, mb + MB_KV * 8);
                    bulk_g2s(sb + SM_V + 32768 + 8192, g_s.kv + 6144 + 512, 24576, mb + MB_KV * 8);
                }
            }
        }
        __syncwarp();
    }
    }
}

__device__ __forceinline__ int kv_slot(int idx) {
    const int t = (idx & 63) >> 1, c = 2 * (blockIdx.x >> 2) + (idx & 1), hg = blockIdx.x & 3;
    return hg < 2 ? ((t + 31) & 31) * 128 + (c >> 3) * 16 + (hg & 1) * 8 + (c & 7) : 4096 + (hg & 1) * 2048 + t * 64 + c;
}

#define GATE_AT 2
__device__ __noinline__ void helper_cta(const Params& P, uint8_t* smem) {
    const int tid = threadIdx.x, b = blockIdx.x, hi = b - NMAIN;
    const unsigned epoch = g_s.epoch[b] + 1;
    float* red = reinterpret_cast<float*>(smem);
    if (tid < 32) count_wait(C_KV, epoch * NMAIN);
    __syncthreads();
    if (tid == 480) {
        for (int i = 0; i < 8; i++) asm volatile("cp.async.bulk.prefetch.L2.global [%0], %1;" :: "l"((const char*)P.wop + hi * 131072 + i * 16384), "r"(16384) : "memory");
        for (int i = 0; i < 43; i++) asm volatile("cp.async.bulk.prefetch.L2.global [%0], %1;" :: "l"((const char*)P.w2p + hi * 352256 + i * 8192), "r"(8192) : "memory");
    }
    if (tid < 344) {
        const int cg = tid % 43, rp = tid / 43;
        const uint4* src = reinterpret_cast<const uint4*>(P.w1p + (size_t)rp * 64 * FF + (hi * 43 + cg) * 8);
        float s[8] = {0, 0, 0, 0, 0, 0, 0, 0};
#pragma unroll 8
        for (int r = 0; r < 64; r++) {
            uint4 v = __ldg(src + r * (FF / 8));
            s[0] += bf_lo(v.x); s[1] += bf_hi(v.x); s[2] += bf_lo(v.y); s[3] += bf_hi(v.y);
            s[4] += bf_lo(v.z); s[5] += bf_hi(v.z); s[6] += bf_lo(v.w); s[7] += bf_hi(v.w);
        }
        float* part = red + (rp * 43 + cg) * 8;
#pragma unroll
        for (int i = 0; i < 8; i++) part[i] = s[i];
    }
    __syncthreads();
    if (tid < 344) {
        float s = 0.f;
#pragma unroll
        for (int rp = 0; rp < 8; rp++) s += red[rp * 344 + tid];
        g_s.cs[hi * 344 + tid] = s;
    } else if (hi == 3 && tid < 344 + 64) g_s.cs[FF + tid - 344] = 0.f;
    __syncthreads();
    if (tid < 32) count_release(C_MID);
    if (tid == 0) g_s.epoch[b] = epoch;
}

__global__ void __launch_bounds__(512, 1) fused_kernel(const __grid_constant__ Params P) {
    extern __shared__ __align__(1024) uint8_t smem[];
    const uint32_t sb = (uint32_t)__cvta_generic_to_shared(smem);
    const uint32_t mb = sb + SM_MISC;
    const int tid = threadIdx.x, lane = tid & 31, b = blockIdx.x;
    if (b >= NMAIN) { helper_cta(P, smem); return; }
    const int tg = b >> 2, hg = b & 3;
    const int warp = __shfl_sync(0xffffffffu, tid >> 5, 0);

    const uint4 wkv = ldg_relaxed(reinterpret_cast<const uint4*>(reinterpret_cast<const char*>(P.wk) + (hg < 2 ? 0 : P.wv_off)) + tid * 2 + (hg & 1));
    uint4 xv[4][2];
    unsigned epoch = 0;
    {
        const int r = (tid >> 5) * 4;
        const uint4* src = reinterpret_cast<const uint4*>(P.x + (size_t)((r & 31) + tg * 32 + (r >> 5) * 1024) * D) + lane;
#pragma unroll
        for (int i = 0; i < 4; i++) { xv[i][0] = ldg_relaxed(src + i * 64); xv[i][1] = ldg_relaxed(src + i * 64 + 32); }
    }
    const int wg = warp >> 2, ww = warp & 3, g = lane >> 2, t4 = lane & 3, t128 = tid & 127;
    if (lane == 0) {
        if (warp < 4) {
            mbar_init(mb + (MB_WQ + warp) * 8, 2);
            asm volatile("fence.mbarrier_init.release.cluster;" ::: "memory");
            load_wq(sb, P, warp, 0);
            load_wq(sb, P, warp, 1);
        } else if (warp < 7) {
            asm volatile("prefetch.tensormap [%0];" :: "l"(&P.wo + (warp - 4)) : "memory");
        } else if (warp == 7) {
            sts128(mb + MISC_NRM, 0, 0, 0, 0);
        } else if (warp == 12) {
            mbar_init(mb + MB_KV0 * 8, 1);
        }
    }
    if (warp == 12) epoch = ldg32_relaxed(g_s.epoch + b) + 1;
    __syncwarp();
    TS(16);
    sts128(sb + SM_WKV + tid * 16, wkv.x, wkv.y, wkv.z, wkv.w);
    float dlt;
    {
        float st[4];
#pragma unroll
        for (int i = 0; i < 4; i++) {
            const uint32_t s = add_bf16x2(add_bf16x2(add_bf16x2(xv[i][0].x, xv[i][0].y), add_bf16x2(xv[i][0].z, xv[i][0].w)),
                                          add_bf16x2(add_bf16x2(xv[i][1].x, xv[i][1].y), add_bf16x2(xv[i][1].z, xv[i][1].w)));
            st[i] = bf_lo(s) + bf_hi(s);
        }
        TS(13);
        const float tot = reduce4(st, lane) * (-1.0f / D);
        const uint32_t nmr = pack_bf16(tot, tot);
        dlt = bf_lo(nmr) - tot;
        const uint32_t xa[2] = {sb + (((uint32_t)XN_SLOTS >> (lane & 24)) & 31) * SLOT + warp * 512, sb + (((uint32_t)(XN_SLOTS >> 32) >> (lane & 24)) & 31) * SLOT + warp * 512};
#pragma unroll
        for (int i = 0; i < 4; i++) {
            const uint32_t nm = __shfl_sync(0xffffffffu, nmr, i * 8);
            const uint32_t off = i * 128 + (((lane & 7) ^ ((warp & 1) * 4 + i)) << 4);
#pragma unroll
            for (int c = 0; c < 2; c++) {
                xv[i][c].x = add_bf16x2(xv[i][c].x, nm); xv[i][c].y = add_bf16x2(xv[i][c].y, nm);
                xv[i][c].z = add_bf16x2(xv[i][c].z, nm); xv[i][c].w = add_bf16x2(xv[i][c].w, nm);
                sts128(xa[c] + off, xv[i][c].x, xv[i][c].y, xv[i][c].z, xv[i][c].w);
            }
        }
    }
    fence_async_smem();
    TS(0);
    auto variances = [&]() {
        float st[4];
#pragma unroll
        for (int i = 0; i < 4; i++) {
            float v = 0.f;
#pragma unroll
            for (int c = 0; c < 2; c++) {
                const uint32_t a = fma_bf16x2(xv[i][c].x, xv[i][c].x, mul_bf16x2(xv[i][c].y, xv[i][c].y));
                const uint32_t d = fma_bf16x2(xv[i][c].z, xv[i][c].z, mul_bf16x2(xv[i][c].w, xv[i][c].w));
                v += (bf_lo(a) + bf_hi(a)) + (bf_lo(d) + bf_hi(d));
            }
            st[i] = v;
        }
        const float vs = reduce4(st, lane), dl = dlt;
        if ((lane & 7) == 0) sts32(sb + SM_RSTD + (warp * 4 + (lane >> 3)) * 4, __float_as_uint(rsqrtf(fmaxf(vs * (1.0f / D) - dl * dl, 0.f) + 1e-5f)));
    };
    if (wg == 2) {
        float kv[4] = {0.f, 0.f, 0.f, 0.f};
        fence_regs(kv);
        const uint64_t da = mkdesc(sb, 16, 1024, 1), db = mkdesc(sb + SM_WKV, 128, 16, 0);
        bar_sync(7, 512);
        wg_fence();
#pragma unroll
        for (int s = 0; s < 32; s++) mma_ss8(kv, da + xn_slot(s >> 2) * 512 + (s & 3) * 2, db + s * 16);
        wg_commit();
        variances();
        wg_wait<0>(); fence_regs(kv);
        float2* kt = reinterpret_cast<float2*>(smem + SM_KTMP);
        kt[(ww * 16 + g) * 4 + t4] = make_float2(kv[0], kv[1]); kt[(ww * 16 + g + 8) * 4 + t4] = make_float2(kv[2], kv[3]);
        TS(24);
    } else {
        bar_arrive(7, 512);
        variances();
        if (tid == 12 * 32) { sts32(mb + MISC_EPOCH, epoch); g_s.epoch[b] = epoch; }
    }
    __syncthreads();
    constexpr float QSCALE = 0.25f * 1.4426950408889634f;
    float qa[64];
    const uint32_t qbase = sb + SM_Q + (ww >> 1) * 8192 + (ww & 1) * 512 + lane * 16;
    if (wg == 0) {
        const float rs0 = __uint_as_float(lds32(sb + SM_RSTD + (ww * 16 + g) * 4)) * QSCALE, rs1 = __uint_as_float(lds32(sb + SM_RSTD + (ww * 16 + g + 8) * 4)) * QSCALE;
#pragma unroll
        for (int i = 0; i < 64; i++) qa[i] = 0.f;
        fence_regs(qa);
        mbar_wait(mb + MB_WQ * 8);
        bar_sync(2, 192);
#pragma unroll 1
        for (int i = 0; i < 4; i++) {
            const uint32_t s0 = (WQ0_SLOTS >> (8 * i)) & 31, s1 = (WQ1_SLOTS >> (8 * i)) & 31, xs = (uint32_t)(XN_SLOTS >> (16 * i));
            const uint64_t db = mkdesc(sb + s0 * SLOT, (s1 - s0) * SLOT, 1024, 1);
            const uint64_t da0 = mkdesc(sb + (xs & 31) * SLOT, 16, 1024, 1), da1 = mkdesc(sb + ((xs >> 8) & 31) * SLOT, 16, 1024, 1);
            mbar_wait(mb + (MB_WQ + i) * 8);
            wg_fence();
#pragma unroll
            for (int s = 0; s < 8; s++) mma_ss128(qa, (s < 4 ? da0 : da1) + (s & 3) * 2, db + s * 128);
            wg_commit();
            wg_wait<1>();
            if (i == 1) bar_arrive(6, 160);
        }
        wg_wait<0>();
        fence_regs(qa);
        bar_arrive(5, 256);
        TS(1);
        uint32_t nm = 0;
#pragma unroll
        for (int h = 0; h < 8; h++) {
#pragma unroll
            for (int i = 0; i < 8; i++) qa[8 * h + i] *= (i & 2) ? rs1 : rs0;
            stsm4(qbase + h * 1024, pack_f16(qa[8 * h], qa[8 * h + 1]), pack_f16(qa[8 * h + 4], qa[8 * h + 5]), pack_f16(qa[8 * h + 2], qa[8 * h + 3]), pack_f16(qa[8 * h + 6], qa[8 * h + 7]));
            const float n0 = qa[8 * h] * qa[8 * h] + qa[8 * h + 1] * qa[8 * h + 1] + qa[8 * h + 4] * qa[8 * h + 4] + qa[8 * h + 5] * qa[8 * h + 5];
            const float n1 = qa[8 * h + 2] * qa[8 * h + 2] + qa[8 * h + 3] * qa[8 * h + 3] + qa[8 * h + 6] * qa[8 * h + 6] + qa[8 * h + 7] * qa[8 * h + 7];
            nm = max(nm, max(__float_as_uint(n0), __float_as_uint(n1)));
        }
        nm = __reduce_max_sync(0xffffffffu, __float_as_uint(quad_sum(__uint_as_float(nm))));
        if (lane == 0) asm volatile("red.shared.max.u32 [%0], %1;" :: "r"(mb + MISC_NRM), "r"(nm) : "memory");
    } else if (wg == 1) {
        if (lane == 0) {
            if (ww == 0) {
#pragma unroll
                for (uint32_t i = 4; i < 35; i++) mbar_init(mb + i * 8, bar_count(i));
                mbar_init(mb + MB_EPI * 8, 4);
            } else if (ww == 1) {
#pragma unroll
                for (uint32_t i = 35; i < 67; i++) mbar_init(mb + i * 8, bar_count(i));
            } else {
#pragma unroll
                for (uint32_t i = 0; i < 30; i++) mbar_init(mb + (ww * 30 + 7 + i) * 8, 2);
            }
        }
        __syncwarp();
#pragma unroll
        for (int i = 0; i < 4; i++) sts128(sb + SM_SENT + (i * 128 + t128) * 16, SENT, SENT, SENT, SENT);
#pragma unroll
        for (int i = 0; i < 16; i++) {
            if (i == 4) bar_sync(5, 256);
            sts128(sb + SM_V + 65536 + (i * 128 + t128) * 16, 0x3F803F80u, 0x3F803F80u, 0x3F803F80u, 0x3F803F80u);
        }
    } else if (wg == 2) {
        if (ww < 2) {
            const bool diff = ww == 0 && hg < 2;
            uint32_t nm = 1;
#pragma unroll
            for (int i = 0; i < 2; i++) {
                const int r = (lane & 1) * 32 + i * 16 + (lane >> 1);
                const uint32_t ra = sb + SM_KTMP + r * 32;
                float4 c0 = lds128f(ra), c1 = lds128f(ra + 16);
                const float4 p0 = lds128f(ra - 32), p1 = lds128f(ra - 16);
                const float rs = __uint_as_float(lds32(sb + SM_RSTD + r * 4));
                float rp = -__uint_as_float(lds32(sb + SM_RSTD + r * 4 - 4));
                c0.x *= rs; c0.y *= rs; c0.z *= rs; c0.w *= rs; c1.x *= rs; c1.y *= rs; c1.z *= rs; c1.w *= rs;
                nm = max(nm, __float_as_uint(c0.x * c0.x + c0.y * c0.y + c0.z * c0.z + c0.w * c0.w + c1.x * c1.x + c1.y * c1.y + c1.z * c1.z + c1.w * c1.w));
                uint32_t w0, w1, w2, w3;
                if (diff) {
                    if (r & 31) {
                        c0.x = fmaf(p0.x, rp, c0.x); c0.y = fmaf(p0.y, rp, c0.y); c0.z = fmaf(p0.z, rp, c0.z); c0.w = fmaf(p0.w, rp, c0.w);
                        c1.x = fmaf(p1.x, rp, c1.x); c1.y = fmaf(p1.y, rp, c1.y); c1.z = fmaf(p1.z, rp, c1.z); c1.w = fmaf(p1.w, rp, c1.w);
                    }
                    w0 = pack_f16(c0.x, c0.y); w1 = pack_f16(c0.z, c0.w); w2 = pack_f16(c1.x, c1.y); w3 = pack_f16(c1.z, c1.w);
                } else {
                    w0 = pack_bf16(c0.x, c0.y); w1 = pack_bf16(c0.z, c0.w); w2 = pack_bf16(c1.x, c1.y); w3 = pack_bf16(c1.z, c1.w);
                }
                if (ww == 0 || hg < 2) stg128((ww ? g_s.kplain : g_s.kv) + kv_slot(i * 32 + lane), nonzero(w0), nonzero(w1), nonzero(w2), nonzero(w3));
            }
            if (ww == 0) {
                nm = __reduce_max_sync(0xffffffffu, nm);
                if (lane < 2) stg128(g_s.nrm + b * 2 + lane, nm, nm, nm, nm);
                count_hint(C_KVH);
                TS(1);
                bar_arrive(2, 192);
            } else {
                bar_sync(2, 192);
                count_release(C_KV);
            }
        }
    } else {
        if (ww == 0) count_wait(C_KVH, epoch * NMAIN);
        TS(1);
        bar_sync(3, 128);
        uint32_t nm = ldg32_relaxed(g_s.nrm + t128 * 2);
        if (ww == 0) bar_sync(6, 160);
        int spins = 0;
        bool bad;
        do {
            if (t128 == 0) {
                asm volatile("fence.proxy.async.global;" ::: "memory");
                mbar_expect(mb + MB_KV0 * 8, 34816);
                bulk_g2s(sb + SM_K + 31 * 2048, g_s.kv + 31 * 128, 2048, mb + MB_KV0 * 8);
                bulk_g2s(sb + SM_K, g_s.kv, 16384, mb + MB_KV0 * 8);
                bulk_g2s(sb + SM_V, g_s.kv + 4096, 8192, mb + MB_KV0 * 8);
                bulk_g2s(sb + SM_V + 32768, g_s.kv + 6144, 8192, mb + MB_KV0 * 8);
            }
            if (spins) nm = ldg32_relaxed(g_s.nrm + t128 * 2);
            __syncwarp();
            mbar_wait(mb + MB_KV0 * 8, spins & 1);
            const uint32_t probe = sb + (ww < 2 ? SM_K + ww * 8192 : SM_V + (ww - 2) * 32768) + lane * 32 + (lane >> 2) * 4;
            uint32_t mn = min(nm, lds32(sb + SM_K + 31 * 2048 + (ww & 1) * 1024 + lane * 32 + (lane >> 2) * 4));
#pragma unroll
            for (int k = 0; k < 8; k++) mn = min(mn, lds32(probe + k * 1024));
            uint32_t r;
            asm volatile("{.reg .pred p, q; setp.eq.u32 p, %1, 0; barrier.red.or.pred.aligned q, 3, 128, p; selp.u32 %0, 1, 0, q;}" : "=r"(r) : "r"(mn) : "memory");
            bad = __any_sync(0xffffffffu, r);
        } while (bad && ++spins < SPIN_LIMIT);
        TS(2);
        nm = max(nm, __shfl_xor_sync(0xffffffffu, nm, 4)); nm = max(nm, __shfl_xor_sync(0xffffffffu, nm, 8)); nm = max(nm, __shfl_xor_sync(0xffffffffu, nm, 16));
        if (lane < 4) asm volatile("red.shared.max.u32 [%0], %1;" :: "r"(mb + MISC_NRM + 4 + min(lane, 2) * 4), "r"(nm) : "memory");
    }
    fence_async_smem();
    TS(3);
    __syncthreads();
    const float4 nr = lds128f(mb + MISC_NRM);
    const bool safe = __all_sync(0xffffffffu, (nr.x * (nr.y + nr.z) <= 3500.0f) && (nr.x <= 65536.0f) && (nr.y + nr.z <= 65536.0f) && (nr.w <= 1e24f));
    TS(4);

    if (__builtin_expect(safe, 1)) {
        attention<true>(P, sb, warp TS_PASS);
    } else {
        if (wg == 0) {
#pragma unroll
            for (int h = 0; h < 8; h++)
                stsm4(qbase + h * 1024, pack_bf16(qa[8 * h], qa[8 * h + 1]), pack_bf16(qa[8 * h + 4], qa[8 * h + 5]), pack_bf16(qa[8 * h + 2], qa[8 * h + 3]), pack_bf16(qa[8 * h + 6], qa[8 * h + 7]));
            fence_async_smem();
        } else if (warp == 15) {
            count_wait(C_KV, lds32(mb + MISC_EPOCH) * NMAIN);
            if (lane == 0) {
                asm volatile("fence.proxy.async;" ::: "memory");
                mbar_expect(mb + MB_KV * 8, 131072);
                bulk_g2s(sb + SM_K, g_s.kplain, 65536, mb + MB_KV * 8);
                bulk_g2s(sb + SM_V, g_s.kv + 4096, 65536, mb + MB_KV * 8);
            }
            __syncwarp();
        }
        __syncthreads();
        mbar_wait(mb + MB_KV * 8);
        attention<false>(P, sb, warp TS_PASS);
    }

    const int j = tail_j();
    if (wg == 1 || wg == 2) {
        if (warp == 8) {
            epoch = lds32(mb + MISC_EPOCH);
#pragma unroll 1
            for (int job = 1; job < 6; job++) {
                count_wait(C_O + 32 * (job >> 1) + (job & 1) * 16 + tail_m(), epoch * (job == 1 ? 128 : 32));
                asm volatile("fence.proxy.async.global;" ::: "memory");
                warp_done(mb + (MB_READY + job) * 8);
                TS(18 + job);
            }
        } else if (warp == 9) {
#pragma unroll
            for (int i = 0; i < 2; i++) {
                if (lane < 22) {
                    const uint4 v = ldg_relaxed(reinterpret_cast<const uint4*>(g_s.cs + j * 176) + i * 22 + lane);
                    sts128(mb + MISC_CS + (i * 22 + lane) * 16, v.x, v.y, v.z, v.w);
                }
                stg128(g_s.kv + kv_slot(i * 32 + lane), 0u, 0u, 0u, 0u);
            }
            warp_done(mb + MB_CS * 8);
            if (lane < 2) stg128(g_s.nrm + b * 2 + lane, 0u, 0u, 0u, 0u);
#pragma unroll 1
            for (int i = 0; i < 16; i++) {
                mbar_wait(mb + (MB_W1 + i) * 8);
                const int n = i < 8 ? 16 + i + 8 * (lane & 1) : 32 + 3 * (i - 8) + (lane >> 1) + 22 * (lane & 1);
                if (lane < (i < 8 || i == 15 ? 2 : 6)) mbar_arrive(mb + (MB_FULL + n) * 8);
                __syncwarp();
            }
        } else {
            if (warp == 10) {
#pragma unroll 1
                for (int i = 3; i < 16; i++) {
                    const bool w1 = i < 8;
                    const int kb = i & 7;
                    const uint32_t bar = mb + (MB_W1 + i) * 8, dst = sb + w1_slot(kb, 0) * SLOT, step = kb < 4 ? 4 * SLOT : SLOT;
                    const CUtensorMap* tm = w1 ? &P.w1 : &P.w2;
                    const int c0 = w1 ? j * 176 : j * 64, c1 = w1 ? kb * 64 : kb * 192, d0 = w1 ? 64 : 0, d1 = 64 - d0;
                    if (lane == 0) mbar_expect(bar, i == 15 ? SLOT : 3 * SLOT);
                    mbar_wait(mb + (w1 ? (i == 3 ? MB_DONE + 4 : i < 6 ? MB_REL + 9 : MB_REL + 8) : MB_REL + kb) * 8);
                    if (i == 8 + GATE_AT) mbar_wait(mb + MB_EPI * 8);
                    if (lane == 0) {
                        tma2d(dst, tm, c0, c1, bar);
                        if (i < 15) { tma2d(dst + step, tm, c0 + d0, c1 + d1, bar); tma2d(dst + 2 * step, tm, c0 + 2 * d0, c1 + 2 * d1, bar); }
                    }
                    __syncwarp();
                }
            } else {
                ring_feed(sb, wg == 1 ? ww : 4 TS_PASS);
            }
        }
    } else {
        const int pr = (wg == 0), mt = 16 * pr + tail_m();
        uint32_t* const hp = reinterpret_cast<uint32_t*>(g_x + X_H1 + (mt * 32 + j * 4) * 128 + ww * 32) + lane;
        {
            uint32_t hk[16];
            const uint32_t* xp = reinterpret_cast<const uint32_t*>(P.x + (size_t)(mt * 64 + ww * 16 + g) * D + j * 64 + t4 * 2);
#pragma unroll
            for (int k = 0; k < 8; k++) { hk[2 * k] = __ldg(xp + k * 4); hk[2 * k + 1] = __ldg(xp + k * 4 + 8 * (D / 2)); }
            mbar_wait(mb + MB_WO * 8);
            float acc[32];
            if (gemm_ss<0>(acc, sb, pr TS_PASS)) gemm_slow(acc, g_x + X_O + mt * 32 * 128, 32, P.wop, D, D, j * 64);
            TS(7);
#pragma unroll
            for (int i = 0; i < 16; i++) hk[i] = pack_bf16(acc[2 * i] + bf_lo(hk[i]), acc[2 * i + 1] + bf_hi(hk[i]));
#pragma unroll
            for (int k = 0; k < 4; k++) store_tile(hp + k * 512, hk[4 * k], hk[4 * k + 1], hk[4 * k + 2], hk[4 * k + 3]);
            count_hint(C_H1 + mt);
            TS(8);
            float st[4] = {0.f, 0.f, 0.f, 0.f};
#pragma unroll
            for (int i = 0; i < 16; i++) {
                const float lo = bf_lo(hk[i]), hi = bf_hi(hk[i]);
                st[2 * (i & 1)] += lo + hi;
                st[2 * (i & 1) + 1] = fmaf(lo, lo, fmaf(hi, hi, st[2 * (i & 1) + 1]));
            }
#pragma unroll
            for (int o = 1; o < 4; o <<= 1)
#pragma unroll
                for (int i = 0; i < 4; i++) st[i] += __shfl_xor_sync(0xffffffffu, st[i], o);
            if (t4 == 0) stg128(g_x + X_ST + (mt * 8 + j) * 32 + ww * 8 + g, __float_as_uint(st[0]), __float_as_uint(st[1]), __float_as_uint(st[2]), __float_as_uint(st[3]));
        }
        {
            float acc[88];
            const uint4* sp = g_x + X_ST + (mt * 8 + t4) * 32 + ww * 8 + g;
            mbar_wait(mb + (MB_FULL + 16 + pr * 8) * 8);
            uint4 u0 = ldg_relaxed(sp), u1 = ldg_relaxed(sp + 128);
            if (gemm_ss<1>(acc, sb, pr TS_PASS)) gemm_slow(acc, g_x + X_H1 + mt * 32 * 128, 32, P.w1p, FF, D, j * 176);
            TS(9);
            int spins = 0;
            while (__builtin_expect(__any_sync(0xffffffffu, max(u0.x, u1.x) == SENT), 0) && ++spins < SPIN_LIMIT) { u0 = ldg_relaxed(sp); u1 = ldg_relaxed(sp + 128); }
            float st[4] = {__uint_as_float(u0.x) + __uint_as_float(u1.x), __uint_as_float(u0.y) + __uint_as_float(u1.y),
                           __uint_as_float(u0.z) + __uint_as_float(u1.z), __uint_as_float(u0.w) + __uint_as_float(u1.w)};
#pragma unroll
            for (int o = 1; o < 4; o <<= 1)
#pragma unroll
                for (int k = 0; k < 4; k++) st[k] += __shfl_xor_sync(0xffffffffu, st[k], o);
            float nmean[2], hrstd[2];
#pragma unroll
            for (int k = 0; k < 2; k++) {
                nmean[k] = st[2 * k] * (-1.0f / D);
                hrstd[k] = 0.5f * rsqrtf(fmaxf(fmaf(-nmean[k], nmean[k], st[2 * k + 1] * (1.0f / D)), 0.f) + 1e-5f);
                nmean[k] *= hrstd[k];
            }
            mbar_wait(mb + MB_CS * 8);
            uint32_t* hb = reinterpret_cast<uint32_t*>(g_x + X_H2 + (mt * 88 + j * 11) * 128 + ww * 32) + lane;
#pragma unroll
            for (int i = 0; i < 22; i++) {
                float2 cs;
                asm volatile("ld.shared.v2.f32 {%0,%1}, [%2];" : "=f"(cs.x), "=f"(cs.y) : "r"(mb + MISC_CS + i * 32 + t4 * 8));
                const float* z = acc + 4 * i;
                uint32_t* p = hb + (i >> 1) * 512 + (i & 1) * 32;
                stg32(p, pack_bf16(silu2(fmaf(hrstd[0], z[0], nmean[0] * cs.x)), silu2(fmaf(hrstd[0], z[1], nmean[0] * cs.y))));
                stg32(p + 64, pack_bf16(silu2(fmaf(hrstd[1], z[2], nmean[1] * cs.x)), silu2(fmaf(hrstd[1], z[3], nmean[1] * cs.y))));
            }
            count_hint(C_H2 + mt);
            if (!pr) warp_done(mb + MB_EPI * 8);
            TS(10);
        }
        {
            uint32_t hk[16];
#pragma unroll
            for (int i = 0; i < 16; i++) hk[i] = ldg32_relaxed(hp + (i >> 2) * 512 + ((i & 1) * 2 + ((i >> 1) & 1)) * 32);
            float acc[32];
            if (gemm_ss<2>(acc, sb, pr TS_PASS)) gemm_slow(acc, g_x + X_H2 + mt * 88 * 128, 88, P.w2p, D, FF, j * 64);
            TS(11);
#pragma unroll
            for (int i = 0; i < 16; i++) hk[i] = pack_bf16(acc[2 * i] + bf_lo(hk[i]), acc[2 * i + 1] + bf_hi(hk[i]));
#pragma unroll
            for (int h = 0; h < 4; h++) {
                const uint32_t* v = hk + (h >> 1) * 8 + (h & 1);
                uint32_t v0 = v[0], v1 = v[2], v2 = v[4], v3 = v[6];
                const bool o1 = t4 & 1, o2 = t4 & 2;
                uint32_t a = __shfl_xor_sync(0xffffffffu, o1 ? v0 : v1, 1), c = __shfl_xor_sync(0xffffffffu, o1 ? v2 : v3, 1);
                if (o1) { v0 = a; v2 = c; } else { v1 = a; v3 = c; }
                a = __shfl_xor_sync(0xffffffffu, o2 ? v0 : v2, 2); c = __shfl_xor_sync(0xffffffffu, o2 ? v1 : v3, 2);
                if (o2) { v0 = a; v1 = c; } else { v2 = a; v3 = c; }
                *reinterpret_cast<uint4*>(P.out + (size_t)(mt * 64 + ww * 16 + g + 8 * (h & 1)) * D + j * 64 + (h >> 1) * 32 + t4 * 8) = make_uint4(v0, v1, v2, v3);
            }
        }
    }
    TS(12);
}

typedef CUresult (*EncodeFn)(CUtensorMap*, CUtensorMapDataType, cuuint32_t, void*, const cuuint64_t*, const cuuint64_t*, const cuuint32_t*,
                             const cuuint32_t*, CUtensorMapInterleave, CUtensorMapSwizzle, CUtensorMapL2promotion, CUtensorMapFloatOOBfill);

void encode2d(EncodeFn fn, CUtensorMap* tm, const void* ptr, int rows, int cols, int box_rows, int box_cols, CUtensorMapSwizzle sw) {
    cuuint64_t dims[2] = {(cuuint64_t)cols, (cuuint64_t)rows};
    cuuint64_t strides[1] = {(cuuint64_t)cols * 2};
    cuuint32_t box[2] = {(cuuint32_t)box_cols, (cuuint32_t)box_rows};
    cuuint32_t es[2] = {1, 1};
    fn(tm, CU_TENSOR_MAP_DATA_TYPE_BFLOAT16, 2, const_cast<void*>(ptr), dims, strides, box, es, CU_TENSOR_MAP_INTERLEAVE_NONE, sw,
       CU_TENSOR_MAP_L2_PROMOTION_L2_128B, CU_TENSOR_MAP_FLOAT_OOB_FILL_NONE);
}

}

extern "C" void kernel_launch(void* const* d_in, const int* in_sizes, int n_in, void* d_out, int out_size) {
    (void)in_sizes; (void)n_in; (void)out_size;
    void* fnp = nullptr;
    cudaDriverEntryPointQueryResult qr;
    cudaGetDriverEntryPoint("cuTensorMapEncodeTiled", &fnp, cudaEnableDefault, &qr);
    EncodeFn fn = (EncodeFn)fnp;
    Params P;
    encode2d(fn, &P.wq, d_in[1], D, D, 128, 64, CU_TENSOR_MAP_SWIZZLE_128B);
    P.wk = (const __nv_bfloat16*)d_in[2];
    P.wv_off = (const char*)d_in[3] - (const char*)d_in[2];
    encode2d(fn, &P.wo, d_in[4], D, D, 64, 64, CU_TENSOR_MAP_SWIZZLE_128B);
    encode2d(fn, &P.w1, d_in[6], D, FF, 64, 64, CU_TENSOR_MAP_SWIZZLE_128B);
    encode2d(fn, &P.w2, d_in[7], FF, D, 64, 64, CU_TENSOR_MAP_SWIZZLE_128B);
    P.x = (const __nv_bfloat16*)d_in[0];
    P.w1p = (const __nv_bfloat16*)d_in[6];
    P.w2p = (const __nv_bfloat16*)d_in[7];
    P.wop = (const __nv_bfloat16*)d_in[4];
    P.wqp = (const __nv_bfloat16*)d_in[1];
    P.out = (__nv_bfloat16*)d_out;
    P.neg1 = 0xFFFFFFFFu; P.pad = 0;
    cudaFuncSetAttribute(fused_kernel, cudaFuncAttributeMaxDynamicSharedMemorySize, SMEM_BYTES);
    fused_kernel<<<NCTA, 512, SMEM_BYTES>>>(P);
}
```

```cpp
#include <cuda_runtime.h>
#include <cuda_bf16.h>
#include <cuda.h>
#include <stdint.h>

namespace {

constexpr int D = 512, FF = 1376;
constexpr int NMAIN = 128, NHELP = 4, NCTA = NMAIN + NHELP;
constexpr uint32_t SENT = 0xFFFFFFFFu;
constexpr int SPIN_LIMIT = 1 << 22;

constexpr uint32_t KB = 1024, SLOT = 8192;
constexpr uint64_t XN_SLOTS = 7 | 16 << 8 | 6 << 16 | 17 << 24 | 21ull << 32 | 27ull << 40 | 24ull << 48 | 25ull << 56;
constexpr uint32_t WQ0_SLOTS = 0 | 2 << 8 | 4 << 16 | 10 << 24, WQ1_SLOTS = 12 | 14 << 8 | 18 << 16 | 22 << 24;
__host__ __device__ constexpr uint32_t xn_slot(int kb) { return (XN_SLOTS >> (8 * kb)) & 31; }
constexpr uint32_t SM_WKV = 208 * KB;
constexpr uint32_t SM_K = 0;
constexpr uint32_t SM_Q = 64 * KB;
constexpr uint32_t SM_V = 96 * KB;
constexpr uint32_t SM_MISC = 224 * KB;
constexpr uint32_t SMEM_BYTES = 227 * KB;
constexpr uint32_t SM_KTMP = 76 * KB;
constexpr uint32_t SM_RSTD = 226 * KB;
constexpr uint32_t SM_SENT = 208 * KB;
constexpr uint32_t MB_WQ = 0;
constexpr uint32_t MB_CS = 4;
constexpr uint32_t MB_DONE = 5;
constexpr uint32_t MB_EMPTY = 10;
constexpr uint32_t MB_W1 = 16;
constexpr uint32_t MB_W2 = 24;
constexpr uint32_t MB_WO = 32;
constexpr uint32_t MB_REL = 33;
constexpr uint32_t MB_KV = 43;
constexpr uint32_t MB_MID = 44;
constexpr uint32_t MB_READY = 44;
constexpr uint32_t MB_FULL = 50;
constexpr uint32_t MB_NULL = 126;
constexpr uint32_t MB_KV0 = 128;
constexpr uint32_t MB_EPI = 127;
__host__ __device__ constexpr uint32_t bar_count(uint32_t i) {
    return i >= MB_FULL + 16 ? 2 : i >= MB_KV ? 1 : i >= MB_WO ? 8 : i >= MB_W1 + 3 ? 1 : i >= MB_W1 ? 3 : i >= MB_EMPTY ? 4 : i >= MB_DONE ? 16 : 1;
}
constexpr uint64_t pack_counts(uint32_t first) {
    uint64_t v = 0;
    for (uint32_t i = 0; i < 8; i++) { const uint32_t id = first + i; v |= (uint64_t)(id < 67 ? bar_count(id) : id == 67 ? 4 : 1) << (8 * i); }
    return v;
}
__constant__ const uint64_t BAR_COUNTS[9] = {pack_counts(0), pack_counts(8), pack_counts(16), pack_counts(24), pack_counts(32), pack_counts(40), pack_counts(48), pack_counts(56), pack_counts(64)};
constexpr uint32_t MISC_XBAR = 2304;
constexpr uint32_t MISC_NRM = 1056;
constexpr uint32_t MISC_EPOCH = 1072;
constexpr uint32_t MISC_TS = 1088;
constexpr uint32_t MISC_CS = 1344;

__host__ __device__ constexpr uint32_t wo_slot(int kb) { return kb < 2 ? 10 + kb : kb - 2; }
__host__ __device__ constexpr uint32_t w1_slot(int kb, int a) { return kb < 4 ? 12 + kb + 4 * a : (kb < 6 ? 3 * kb - 6 : 3 * kb - 18) + a; }

struct alignas(128) Small {
    unsigned epoch[160];
    unsigned cnt[100][32];
    float cs[1440];
    uint4 nrm[NMAIN * 2];
    uint4 kv[8192];
    uint4 kplain[4096];
};
__device__ Small g_s;
constexpr int C_KVH = 0, C_KV = 1, C_MID = 2, C_O = 3, C_H1 = 35, C_H2 = 67;
constexpr int X_O = 0, X_H1 = 32 * 32 * 128, X_H2 = 2 * X_H1, X_ST = X_H2 + 32 * 88 * 128, X_END = X_ST + 32 * 8 * 32;
constexpr int X_ARM = 16 * 32 * 128, X_SHARE = (X_END - X_ARM) / NMAIN;
__device__ uint4 g_x[X_END];
#define TS(i) do {} while (0)
#define TSF(k)

#define TS_ARG
#define TS_PASS

__device__ __forceinline__ void mbar_init(uint32_t bar, int cnt) { asm volatile("mbarrier.init.shared::cta.b64 [%0], %1;" :: "r"(bar), "r"(cnt) : "memory"); }
__device__ __forceinline__ void mbar_expect(uint32_t bar, uint32_t bytes) { asm volatile("mbarrier.arrive.expect_tx.shared::cta.b64 _, [%0], %1;" :: "r"(bar), "r"(bytes) : "memory"); }
__device__ __forceinline__ void mbar_arrive(uint32_t bar) { asm volatile("mbarrier.arrive.shared::cta.b64 _, [%0];" :: "r"(bar) : "memory"); }
__device__ __forceinline__ bool mbar_try(uint32_t bar, uint32_t parity) {
    uint32_t done;
    asm volatile("{.reg .pred p; mbarrier.try_wait.parity.shared::cta.b64 p, [%1], %2; selp.u32 %0, 1, 0, p;}" : "=r"(done) : "r"(bar), "r"(parity) : "memory");
    return __all_sync(0xffffffffu, done);
}
__device__ __forceinline__ void mbar_wait(uint32_t bar, uint32_t parity = 0) {
    if (__builtin_expect(!mbar_try(bar, parity), 0)) {
        int spins = 0;
        while (!mbar_try(bar, parity) && ++spins < (SPIN_LIMIT >> 6)) {}
    }
}
__device__ __forceinline__ void tma2d(uint32_t dst, const CUtensorMap* tm, int c0, int c1, uint32_t bar) {
    asm volatile("cp.async.bulk.tensor.2d.shared::cluster.global.mbarrier::complete_tx::bytes [%0], [%1, {%3, %4}], [%2];"
                 :: "r"(dst), "l"(tm), "r"(bar), "r"(c0), "r"(c1) : "memory");
}
__device__ __forceinline__ void bulk_g2s(uint32_t dst, const void* src, uint32_t bytes, uint32_t bar) {
    asm volatile("cp.async.bulk.shared::cluster.global.mbarrier::complete_tx::bytes [%0], [%1], %2, [%3];" :: "r"(dst), "l"(src), "r"(bytes), "r"(bar) : "memory");
}
__device__ __forceinline__ void fence_async_smem() { asm volatile("fence.proxy.async.shared::cta;" ::: "memory"); }
__device__ __forceinline__ void bar_sync(int id, int n) { asm volatile("bar.sync %0, %1;" :: "r"(id), "r"(n) : "memory"); }
__device__ __forceinline__ void bar_arrive(int id, int n) { asm volatile("bar.arrive %0, %1;" :: "r"(id), "r"(n) : "memory"); }
__device__ __forceinline__ void wg_fence() { asm volatile("wgmma.fence.sync.aligned;" ::: "memory"); }
__device__ __forceinline__ void wg_commit() { asm volatile("wgmma.commit_group.sync.aligned;" ::: "memory"); }
template <int N> __device__ __forceinline__ void wg_wait() { asm volatile("wgmma.wait_group.sync.aligned %0;" :: "n"(N) : "memory"); }
template <int N> __device__ __forceinline__ void fence_regs(float (&d)[N]) {
#pragma unroll
    for (int i = 0; i < N; i++) asm volatile("" : "+f"(d[i]) :: "memory");
}
template <int N> __device__ __forceinline__ void fence_regs(uint32_t (&d)[N]) {
#pragma unroll
    for (int i = 0; i < N; i++) asm volatile("" : "+r"(d[i]) :: "memory");
}
__device__ __forceinline__ uint64_t mkdesc(uint32_t addr, uint32_t lbo, uint32_t sbo, uint32_t swz) {
    return (uint64_t)(((addr & 0x3FFFF) >> 4) | ((lbo >> 4) << 16)) | ((uint64_t)((sbo >> 4) | (swz << 30)) << 32);
}
__device__ __forceinline__ float ex2(float x) { float y; asm("ex2.approx.ftz.f32 %0, %1;" : "=f"(y) : "f"(x)); return y; }
__device__ __forceinline__ float rcp(float x) { float y; asm("rcp.approx.ftz.f32 %0, %1;" : "=f"(y) : "f"(x)); return y; }
__device__ __forceinline__ uint32_t pack_bf16(float lo, float hi) { uint32_t r; asm("cvt.rn.bf16x2.f32 %0, %1, %2;" : "=r"(r) : "f"(hi), "f"(lo)); return r; }
__device__ __forceinline__ uint32_t pack_f16(float lo, float hi) { uint32_t r; asm("cvt.rn.f16x2.f32 %0, %1, %2;" : "=r"(r) : "f"(hi), "f"(lo)); return r; }
__device__ __forceinline__ float bf_lo(uint32_t v) { return __uint_as_float(v << 16); }
__device__ __forceinline__ float bf_hi(uint32_t v) { return __uint_as_float(v & 0xFFFF0000u); }
__device__ __forceinline__ uint4 ldg_relaxed(const uint4* p) {
    uint4 v; asm volatile("ld.relaxed.gpu.global.v4.u32 {%0,%1,%2,%3}, [%4];" : "=r"(v.x), "=r"(v.y), "=r"(v.z), "=r"(v.w) : "l"(p) : "memory"); return v;
}
__device__ __forceinline__ void stg128(void* p, uint32_t a, uint32_t b, uint32_t c, uint32_t d) {
    asm volatile("st.relaxed.gpu.global.v4.u32 [%0], {%1,%2,%3,%4};" :: "l"(p), "r"(a), "r"(b), "r"(c), "r"(d) : "memory");
}
__device__ __forceinline__ void stg64(void* p, uint32_t a, uint32_t b) {
    asm volatile("st.relaxed.gpu.global.v2.u32 [%0], {%1,%2};" :: "l"(p), "r"(a), "r"(b) : "memory");
}
__device__ __forceinline__ void sts128(uint32_t a, uint32_t x, uint32_t y, uint32_t z, uint32_t w) {
    asm volatile("st.shared.v4.u32 [%0], {%1,%2,%3,%4};" :: "r"(a), "r"(x), "r"(y), "r"(z), "r"(w) : "memory");
}
__device__ __forceinline__ void sts32(uint32_t a, uint32_t x) { asm volatile("st.shared.u32 [%0], %1;" :: "r"(a), "r"(x) : "memory"); }
__device__ __forceinline__ float4 lds128f(uint32_t a) {
    float4 v; asm volatile("ld.shared.v4.f32 {%0,%1,%2,%3}, [%4];" : "=f"(v.x), "=f"(v.y), "=f"(v.z), "=f"(v.w) : "r"(a) : "memory"); return v;
}
__device__ __forceinline__ uint4 lds128(uint32_t a) {
    uint4 v; asm volatile("ld.shared.v4.u32 {%0,%1,%2,%3}, [%4];" : "=r"(v.x), "=r"(v.y), "=r"(v.z), "=r"(v.w) : "r"(a) : "memory"); return v;
}
__device__ __forceinline__ uint32_t lds32(uint32_t a) { uint32_t v; asm volatile("ld.shared.u32 %0, [%1];" : "=r"(v) : "r"(a) : "memory"); return v; }
__device__ __forceinline__ uint32_t nonzero(uint32_t w) { return w == 0u ? 0x8000u : w; }
__device__ __forceinline__ void stg32(void* p, uint32_t a) { asm volatile("st.global.u32 [%0], %1;" :: "l"(p), "r"(a) : "memory"); }
__device__ __forceinline__ uint32_t ldg32_relaxed(const void* p) { uint32_t v; asm volatile("ld.relaxed.gpu.global.u32 %0, [%1];" : "=r"(v) : "l"(p) : "memory"); return v; }
__device__ __forceinline__ void count_hint(int id) {
    if ((threadIdx.x & 31) == 0) asm volatile("red.relaxed.gpu.global.add.u32 [%0], 1;" :: "l"(g_s.cnt[id]) : "memory");
}
__device__ __forceinline__ void count_release(int id) {
    __syncwarp();
    if ((threadIdx.x & 31) == 0) asm volatile("red.release.gpu.global.add.u32 [%0], 1;" :: "l"(g_s.cnt[id]) : "memory");
    __syncwarp();
}
__device__ __forceinline__ void count_wait(int id, unsigned target) {
    uint32_t v; int spins = 0;
    do v = ldg32_relaxed(g_s.cnt[id]); while (__any_sync(0xffffffffu, v != target) && ++spins < SPIN_LIMIT);
    asm volatile("fence.acquire.gpu;" ::: "memory");
}
__device__ __forceinline__ void warp_done(uint32_t bar) {
    __syncwarp();
    asm volatile("{.reg .pred p; setp.eq.u32 p, %1, 0; @p mbarrier.arrive.shared::cta.b64 _, [%0];}" :: "r"(bar), "r"(threadIdx.x & 31) : "memory");
}
__device__ __forceinline__ uint32_t mul_bf16x2(uint32_t a, uint32_t b) { uint32_t r; asm("mul.rn.bf16x2 %0, %1, %2;" : "=r"(r) : "r"(a), "r"(b)); return r; }
__device__ __forceinline__ uint32_t fma_bf16x2(uint32_t a, uint32_t b, uint32_t c) { uint32_t r; asm("fma.rn.bf16x2 %0, %1, %2, %3;" : "=r"(r) : "r"(a), "r"(b), "r"(c)); return r; }
__device__ __forceinline__ uint32_t add_bf16x2(uint32_t a, uint32_t b) { uint32_t r; asm("add.rn.bf16x2 %0, %1, %2;" : "=r"(r) : "r"(a), "r"(b)); return r; }

#define R4(d, o) "+f"(d[o + 0]), "+f"(d[o + 1]), "+f"(d[o + 2]), "+f"(d[o + 3])
#define R8(d, o) R4(d, o), R4(d, o + 4)
#define R32(d) R8(d, 0), R8(d, 8), R8(d, 16), R8(d, 24)
#define D32 "{%0,%1,%2,%3,%4,%5,%6,%7,%8,%9,%10,%11,%12,%13,%14,%15,%16,%17,%18,%19,%20,%21,%22,%23,%24,%25,%26,%27,%28,%29,%30,%31}"
#define D64 "{%0,%1,%2,%3,%4,%5,%6,%7,%8,%9,%10,%11,%12,%13,%14,%15,%16,%17,%18,%19,%20,%21,%22,%23,%24,%25,%26,%27,%28,%29,%30,%31,%32,%33,%34,%35,%36,%37,%38,%39,%40,%41,%42,%43,%44,%45,%46,%47,%48,%49,%50,%51,%52,%53,%54,%55,%56,%57,%58,%59,%60,%61,%62,%63}"

__device__ __forceinline__ void mma_qk_f16(float (&d)[32], uint64_t da, uint64_t db) {
    asm volatile("{.reg .pred p; setp.eq.b32 p, 0, 0; wgmma.mma_async.sync.aligned.m64n64k16.f32.f16.f16 " D32 ", %32, %33, p, 1, 1, 0, 0;}"
                 : R32(d) : "l"(da), "l"(db));
}
__device__ __forceinline__ void mma_qk_bf16(float (&d)[32], uint64_t da, uint64_t db) {
    asm volatile("{.reg .pred p; setp.ne.b32 p, 0, 0; wgmma.mma_async.sync.aligned.m64n64k16.f32.bf16.bf16 " D32 ", %32, %33, p, 1, 1, 0, 0;}"
                 : R32(d) : "l"(da), "l"(db));
}
__device__ __forceinline__ void mma_pv(float (&d)[12], const uint32_t* a, uint64_t db) {
    asm volatile("{.reg .pred p; setp.eq.b32 p, 0, 0; wgmma.mma_async.sync.aligned.m64n24k16.f32.bf16.bf16 {%0,%1,%2,%3,%4,%5,%6,%7,%8,%9,%10,%11}, {%12,%13,%14,%15}, %16, p, 1, 1, 1;}"
                 : R8(d, 0), R4(d, 8) : "r"(a[0]), "r"(a[1]), "r"(a[2]), "r"(a[3]), "l"(db));
}
__device__ __forceinline__ void mma_ss128(float (&d)[64], uint64_t da, uint64_t db) {
    asm volatile("{.reg .pred p; setp.eq.b32 p, 0, 0; wgmma.mma_async.sync.aligned.m64n128k16.f32.bf16.bf16 " D64 ", %64, %65, p, 1, 1, 0, 1;}"
                 : R32(d), R8(d, 32), R8(d, 40), R8(d, 48), R8(d, 56) : "l"(da), "l"(db));
}
__device__ __forceinline__ void stsm4(uint32_t addr, uint32_t a, uint32_t b, uint32_t c, uint32_t d) {
    asm volatile("stmatrix.sync.aligned.m8n8.x4.shared.b16 [%0], {%1,%2,%3,%4};" :: "r"(addr), "r"(a), "r"(b), "r"(c), "r"(d) : "memory");
}
__device__ __forceinline__ void mma_ss8(float (&d)[4], uint64_t da, uint64_t db) {
    asm volatile("{.reg .pred p; setp.eq.b32 p, 0, 0; wgmma.mma_async.sync.aligned.m64n8k16.f32.bf16.bf16 {%0,%1,%2,%3}, %4, %5, p, 1, 1, 0, 1;}"
                 : R4(d, 0) : "l"(da), "l"(db));
}
__device__ __forceinline__ void mma_ss(float (&d)[32], uint64_t da, uint64_t db, int accum) {
    asm volatile("{.reg .pred p; setp.ne.b32 p, %34, 0; wgmma.mma_async.sync.aligned.m64n64k16.f32.bf16.bf16 " D32 ", %32, %33, p, 1, 1, 0, 1;}"
                 : R32(d) : "l"(da), "l"(db), "r"(accum));
}
__device__ __forceinline__ void mma_ss(float (&d)[88], uint64_t da, uint64_t db, int accum) {
    asm volatile("{.reg .pred p; setp.ne.b32 p, %90, 0; wgmma.mma_async.sync.aligned.m64n176k16.f32.bf16.bf16 " "{%0,%1,%2,%3,%4,%5,%6,%7,%8,%9,%10,%11,%12,%13,%14,%15,%16,%17,%18,%19,%20,%21,%22,%23,%24,%25,%26,%27,%28,%29,%30,%31,%32,%33,%34,%35,%36,%37,%38,%39,%40,%41,%42,%43,%44,%45,%46,%47,%48,%49,%50,%51,%52,%53,%54,%55,%56,%57,%58,%59,%60,%61,%62,%63,%64,%65,%66,%67,%68,%69,%70,%71,%72,%73,%74,%75,%76,%77,%78,%79,%80,%81,%82,%83,%84,%85,%86,%87}"
                 ", %88, %89, p, 1, 1, 0, 1;}"
                 : R32(d), R8(d, 32), R8(d, 40), R8(d, 48), R8(d, 56), R8(d, 64), R8(d, 72), R8(d, 80) : "l"(da), "l"(db), "r"(accum));
}

constexpr float EXP_MAGIC = 256.0f + 127.0f + 64.0f - 1.58621f + 0.00390625f;
#define MUFU_M 0x1111u
#define ALU_M 0x0000u
constexpr uint32_t MUFU_MASK = MUFU_M;
constexpr uint32_t ALU_MASK = ALU_M;
template <bool ALU>
__device__ __forceinline__ uint32_t exp2_pair(float y0, float y1, uint32_t cexp, uint32_t neg1) {
    uint32_t w, m, e, r;
    asm("prmt.b32 %0, %1, %2, 0x6521;" : "=r"(w) : "r"(__float_as_uint(y0)), "r"(__float_as_uint(y1)));
    asm("lop3.b32 %0, %1, 0x007F007F, %2, 0xEA;" : "=r"(m) : "r"(w), "r"(cexp));
    if (ALU) e = w - m;
    else asm("mad.lo.u32 %0, %1, %2, %3;" : "=r"(e) : "r"(m), "r"(neg1), "r"(w));
    asm("fma.rn.bf16x2 %0, %1, %2, %3;" : "=r"(r) : "r"(w), "r"(m), "r"(e));
    return r;
}

struct Params {
    const __nv_bfloat16* x;
    const __nv_bfloat16* wk;
    long long wv_off;
    const __nv_bfloat16* wqp;
    __nv_bfloat16* out;
    uint32_t neg1, pad;
    const __nv_bfloat16* w1p;
    const __nv_bfloat16* w2p;
    CUtensorMap wq, wo, w1, w2;
    const __nv_bfloat16* wop;
};

__device__ __forceinline__ int tail_m() { return (blockIdx.x >> 5) * 4 + ((blockIdx.x >> 2) & 3); }
__device__ __forceinline__ int tail_j() { return ((blockIdx.x >> 4) & 1) * 4 + (blockIdx.x & 3); }
__device__ __forceinline__ void load_box(uint32_t sb, const CUtensorMap* tm, uint32_t dst, uint32_t bar, uint32_t bytes, int c0, int c1) {
    mbar_expect(sb + SM_MISC + bar * 8, bytes);
    tma2d(sb + dst, tm, c0, c1, sb + SM_MISC + bar * 8);
}
__device__ __forceinline__ void load_wq(uint32_t sb, const Params& P, int gi, int atom) {
    load_box(sb, &P.wq, (((atom ? WQ1_SLOTS : WQ0_SLOTS) >> (8 * gi)) & 31) * SLOT, MB_WQ + gi, 16384, (blockIdx.x & 3) * 128 + atom * 64, gi * 128);
}
__device__ __forceinline__ void load_wo(uint32_t sb, const Params& P, int kb) { load_box(sb, &P.wo, wo_slot(kb) * SLOT, MB_WO, SLOT, tail_j() * 64, kb * 64); }
__device__ __forceinline__ void refill_job(uint32_t sb, const Params& P, int gi, int job) {
    const bool w1 = job < 3;
    load_box(sb, w1 ? &P.w1 : &P.wo, (w1 ? 12 + gi + 4 * job : 2 * gi + job - 3) * SLOT, w1 ? MB_W1 + gi : MB_WO, SLOT,
             tail_j() * (w1 ? 176 : 64) + (w1 ? job * 64 : 0), (w1 ? gi : 2 * gi + job - 1) * 64);
}

__host__ __device__ constexpr int ring_entry(int n) { return n < 32 ? (n & 3) : (n - 32) % 6; }
__host__ __device__ constexpr uint32_t ring_slot(int e) { return e < 4 ? 24 + e : e; }

template <int KIND> __host__ __device__ constexpr uint64_t b_slots(int first) {
    uint64_t v = 0;
    for (int i = first; i < first + 12; i++) v |= (uint64_t)((KIND == 0 ? wo_slot(i) : KIND == 1 ? w1_slot(i, 0) : w1_slot(i / 3, i % 3)) & 31) << (5 * (i - first));
    return v;
}
__device__ __forceinline__ uint64_t desc64(uint32_t lo, uint32_t hi) { uint64_t d; asm("mov.b64 %0, {%1, %2};" : "=l"(d) : "r"(lo), "r"(hi)); return d; }
__device__ __forceinline__ uint32_t mbar_test(uint32_t bar) {
    uint32_t done;
    asm volatile("{.reg .pred p; mbarrier.test_wait.parity.shared::cta.b64 p, [%1], 0; selp.u32 %0, 1, 0, p;}" : "=r"(done) : "r"(bar) : "memory");
    return done;
}
template <int KIND, int NACC>
__device__ __forceinline__ bool gemm_ss(float (&acc)[NACC], uint32_t sb, int pr TS_ARG) {
    const uint32_t mb = sb + SM_MISC;
    constexpr int NBLK = KIND == 2 ? 22 : 8, N0 = 16 * KIND;
    uint32_t full = mb + (MB_FULL + N0 + pr * NBLK) * 8, empty = mb + MB_NULL * 8, rel = mb + MB_NULL * 8;
    const uint32_t lane = threadIdx.x & 31, probe = sb + ((threadIdx.x >> 5) & 3) * 512 + (lane >> 4) * 2048 + (lane & 15) * 32 + (lane >> 2) * 4;
    uint32_t m = 0;
    constexpr uint32_t R4S = 24 | 25 << 5 | 26 << 10 | 27 << 15;
    uint32_t ra = KIND == 2 ? (pr ? (4 | 5 << 5 | R4S << 10) : (R4S | 4 << 20 | 5 << 25)) : (KIND == 0 && pr) ? (6 | 7 << 5 | 8 << 10 | 9 << 15) : R4S;
    uint64_t tab = b_slots<KIND>(0);
    const uint32_t a0 = (sb >> 4) | (8 << 16);
    uint32_t b0 = (sb >> 4) | ((KIND == 1 ? 4 * SLOT / 16 : 1) << 16);
    mbar_wait(full);
#pragma unroll 1
    for (int i = 0; i < NBLK; i++) {
        const uint32_t sa = ra & 31, da = a0 + sa * 512, db = b0 + ((uint32_t)tab & 31) * 512;
        full += (i == NBLK - 1) ? 0 : 8;
        const uint32_t ready = mbar_test(full);
        const uint32_t m0 = lds32(probe + sa * SLOT), m1 = lds32(probe + sa * SLOT + 4096);
        wg_fence();
#pragma unroll
        for (int s = 0; s < 4; s++) mma_ss(acc, desc64(da + s * 128, 16), desc64(db + s * 128, 0x40000040), s ? 1 : i);
        wg_commit();
        m = max(m, max(m0, m1));
        const uint32_t prev = empty, prel = rel;
        empty = mb + ((KIND == 0 && sa < 24) ? MB_NULL : MB_EMPTY + (sa & 7)) * 8;
        rel = mb + (KIND == 1 ? MB_REL + i : i == 3 ? MB_REL + 9 : MB_NULL) * 8;
        ra = KIND == 2 ? (ra >> 5) | (sa << 25) : i == 3 ? R4S : ra >> 5;
        tab = (KIND == 2 && i == 11) ? b_slots<KIND>(12) : tab >> 5;
        if (KIND == 1 && i == 3) b0 -= (3 * SLOT / 16) << 16;
        wg_wait<1>();
        warp_done(prev);
        if (KIND != 2) warp_done(prel);
        if (!__all_sync(0xffffffffu, ready)) mbar_wait(full);
    }
    bool bad = __any_sync(0xffffffffu, m == SENT);
    wg_wait<0>();
    fence_regs(acc);
    warp_done(empty);
    if (KIND != 2) warp_done(mb + (MB_REL + 8 - KIND) * 8);
    return __builtin_expect(bad, 0);
}
__device__ __forceinline__ void ring_feed(uint32_t sb, int e TS_ARG) {
    const uint32_t mb = sb + SM_MISC;
    uint32_t dst = sb + ring_slot(e) * SLOT, empty = mb + (MB_EMPTY + e) * 8;
    const bool lead = (threadIdx.x & 31) == 0;
    const uint4* base = g_x + tail_m() * 4096 + e * 512;
    uint32_t par = 0;
    auto fetch = [&](int n, const uint4* src, int job) {
        const uint32_t full = mb + (MB_FULL + n) * 8;
        if (lead) mbar_expect(full, SLOT);
        mbar_wait(empty, par); par ^= 1;
        if (job) mbar_wait(mb + (MB_READY + job) * 8);
        if (lead) bulk_g2s(dst, src, SLOT, full);
        __syncwarp();
    };
    if (e < 4) {
        fetch(4 + e, base + 2048, 0);
        if (lead) mbar_expect(mb + (MB_FULL + 8 + e) * 8, SLOT);
        mbar_wait(mb + (MB_DONE + 4) * 8);
        mbar_wait(mb + (MB_READY + 1) * 8);
        if (lead) bulk_g2s(sb + (6 + e) * SLOT, base + 65536, SLOT, mb + (MB_FULL + 8 + e) * 8);
        fetch(12 + e, base + 65536 + 2048, 0);
#pragma unroll 1
        for (int h = 0; h < 2; h++) {
            fetch(16 + 8 * h + e, base + X_H1 + h * 65536, 2 + h);
            fetch(20 + 8 * h + e, base + X_H1 + h * 65536 + 2048, 0);
        }
    } else {
        mbar_wait(mb + (MB_REL + 7) * 8);
        par = 1;
    }
    const uint4* src = g_x + X_H2 + tail_m() * 88 * 128 + e * 512;
#pragma unroll 1
    for (int n = e; n < 44; n += 6, src += 6 * 512) {
        const bool second = n >= 22 && n < 28;
        if (second) src += 16 * 88 * 128 - 22 * 512;
        fetch(32 + n, src, n < 6 ? 4 : second ? 5 : 0);
        if (e == 4) {
            par ^= 1; dst += SLOT; empty += 8;
            fetch(33 + n, src + 512, 0);
            dst -= SLOT; empty -= 8;
        }
    }
}
__device__ __noinline__ void gemm_slow_impl(float* out, int ntile, const uint4* a, int nst, const __nv_bfloat16* W, int ldw, int kmax, int n0) {
    const int lane = threadIdx.x & 31;
    const unsigned short* w = reinterpret_cast<const unsigned short*>(W);
    for (int j = 0; j < ntile; j++) {
        const uint32_t* p = reinterpret_cast<const uint32_t*>(a) + ((threadIdx.x >> 5) & 3) * 128 + lane;
        const int n = n0 + 8 * j + (lane >> 2);
        float d[4] = {0.f, 0.f, 0.f, 0.f};
        for (int st = 0; st < nst; st++, p += 512) {
            const int k = st * 16 + 2 * (lane & 3);
            uint32_t v0, v1, v2, v3, b0 = 0, b1 = 0; int spins = 0;
            do { v0 = ldg32_relaxed(p); v1 = ldg32_relaxed(p + 64); v2 = ldg32_relaxed(p + 32); v3 = ldg32_relaxed(p + 96); }
            while (__any_sync(0xffffffffu, max(max(v0, v1), max(v2, v3)) == SENT) && ++spins < SPIN_LIMIT);
            if (k < kmax && n < ldw) {
                const unsigned short* q = w + (size_t)k * ldw + n;
                b0 = q[0] | ((uint32_t)q[ldw] << 16); b1 = q[8 * ldw] | ((uint32_t)q[9 * ldw] << 16);
            }
            asm volatile("mma.sync.aligned.m16n8k16.row.col.f32.bf16.bf16.f32 {%0,%1,%2,%3}, {%4,%5,%6,%7}, {%8,%9}, {%0,%1,%2,%3};"
                         : R4(d, 0) : "r"(v0), "r"(v1), "r"(v2), "r"(v3), "r"(b0), "r"(b1));
        }
        *reinterpret_cast<float4*>(out + 4 * j) = make_float4(d[0], d[1], d[2], d[3]);
    }
}
template <int NACC>
__device__ __forceinline__ void gemm_slow(float (&acc)[NACC], const uint4* a, int nst, const __nv_bfloat16* W, int ldw, int kmax, int n0) {
    __align__(16) float tmp[NACC];
    gemm_slow_impl(tmp, NACC / 4, a, nst, W, ldw, kmax, n0);
#pragma unroll
    for (int i = 0; i < NACC; i++) acc[i] = tmp[i];
}
__device__ __forceinline__ void store_tile(uint32_t* p, uint32_t r0k0, uint32_t r8k0, uint32_t r0k8, uint32_t r8k8) {
    stg32(p, r0k0); stg32(p + 32, r0k8); stg32(p + 64, r8k0); stg32(p + 96, r8k8);
}

__device__ __forceinline__ float quad_sum(float v) { v += __shfl_xor_sync(0xffffffffu, v, 1); v += __shfl_xor_sync(0xffffffffu, v, 2); return v; }
__device__ __forceinline__ float reduce4(const float (&st)[4], int lane) {
    const bool u16 = lane & 16, u8 = lane & 8;
    const float a0 = (u16 ? st[2] : st[0]) + __shfl_xor_sync(0xffffffffu, u16 ? st[0] : st[2], 16);
    const float a1 = (u16 ? st[3] : st[1]) + __shfl_xor_sync(0xffffffffu, u16 ? st[1] : st[3], 16);
    float v = (u8 ? a1 : a0) + __shfl_xor_sync(0xffffffffu, u8 ? a0 : a1, 8);
    v += __shfl_xor_sync(0xffffffffu, v, 4); v += __shfl_xor_sync(0xffffffffu, v, 2); v += __shfl_xor_sync(0xffffffffu, v, 1);
    return v;
}
__device__ __forceinline__ float silu2(float h) { float t; asm("tanh.approx.f32 %0, %1;" : "=f"(t) : "f"(h)); return fmaf(h, t, h); }

template <bool SAFE>
__device__ __forceinline__ void attention(const Params& P, uint32_t sb, int warp TS_ARG) {
    const uint32_t mb = sb + SM_MISC;
    const int tid = threadIdx.x, lane = tid & 31, b = blockIdx.x;
    const int wg = warp >> 2, ww = warp & 3, job = 3 - wg + 4 * ww;
    const uint32_t cexp = 0x9F809F80u + (tid >> 12);
    const uint32_t neg1 = P.neg1;
    unsigned cnt = 0;
    if (SAFE && warp == 8) cnt = ldg32_relaxed(g_s.cnt[C_KV]);
#pragma unroll 1
    for (int pass = 0; pass < 2; pass++) {
    float o[12], s[32];
    const uint64_t dq = mkdesc(sb + SM_Q + (pass * 4 + wg) * 2048, 128, 256, 0);
    uint64_t dk = mkdesc(sb + SM_K, 128, 256, 0), dv = mkdesc(sb + SM_V, 128, 32768, 0);
    float m0 = -INFINITY, m1 = -INFINITY;
#pragma unroll
    for (int i = 0; i < 12; i++) o[i] = 0.f;
#pragma unroll
    for (int i = 0; i < 32; i++) s[i] = ((MUFU_MASK >> (i / 2)) & 1) ? 0.f : EXP_MAGIC;
    fence_regs(s); fence_regs(o);
    wg_fence();
    if (SAFE) mma_qk_f16(s, dq, dk + 31 * 128); else mma_qk_bf16(s, dq, dk + 31 * 128);
    wg_commit();
    wg_wait<0>(); fence_regs(s);
#pragma unroll 1
    for (int u = pass ? 3 : (wg == 2) ? 0 : 1; u < (pass ? 8 : 3); u++) {
        int n = 2 * ((((wg == 2) ? 0x22444C31u : 0x22444C40u) >> (4 * u)) & 15);
#pragma unroll 1
        do {
            uint32_t p[16];
            if (SAFE) {
#pragma unroll
                for (int j = 0; j < 16; j++) {
                    if ((MUFU_MASK >> j) & 1) p[j] = pack_bf16(ex2(s[2 * j]), ex2(s[2 * j + 1]));
                    else if ((ALU_MASK >> j) & 1) p[j] = exp2_pair<true>(s[2 * j], s[2 * j + 1], cexp, neg1);
                    else p[j] = exp2_pair<false>(s[2 * j], s[2 * j + 1], cexp, neg1);
                }
            } else {
                fence_regs(o);
                float x0 = m0, x1 = m1;
#pragma unroll
                for (int j = 0; j < 8; j++) { x0 = fmaxf(x0, fmaxf(s[4 * j], s[4 * j + 1])); x1 = fmaxf(x1, fmaxf(s[4 * j + 2], s[4 * j + 3])); }
                x0 = fmaxf(x0, __shfl_xor_sync(0xffffffffu, x0, 1)); x0 = fmaxf(x0, __shfl_xor_sync(0xffffffffu, x0, 2));
                x1 = fmaxf(x1, __shfl_xor_sync(0xffffffffu, x1, 1)); x1 = fmaxf(x1, __shfl_xor_sync(0xffffffffu, x1, 2));
                const float c0 = ex2(m0 - x0), c1 = ex2(m1 - x1);
                m0 = x0; m1 = x1;
#pragma unroll
                for (int j = 0; j < 3; j++) { o[4 * j] *= c0; o[4 * j + 1] *= c0; o[4 * j + 2] *= c1; o[4 * j + 3] *= c1; }
#pragma unroll
                for (int j = 0; j < 8; j++) {
                    p[2 * j] = pack_bf16(ex2(s[4 * j] - m0), ex2(s[4 * j + 1] - m0));
                    p[2 * j + 1] = pack_bf16(ex2(s[4 * j + 2] - m1), ex2(s[4 * j + 3] - m1));
                }
                fence_regs(o);
            }
            fence_regs(p);
            wg_fence();
            if (SAFE) mma_qk_f16(s, dq, dk); else mma_qk_bf16(s, dq, dk);
#pragma unroll
            for (int j = 0; j < 4; j++) mma_pv(o, p + 4 * j, dv + j * 16);
            wg_commit();
            dk += 128; dv += 64;
            wg_wait<0>(); fence_regs(s);
        } while (--n > 0);
        if (u == 2 || u == 7) {
            fence_regs(o);
            const float i0 = rcp(o[8]), i1 = rcp(o[10]);
            if (u == 7) mbar_wait(mb + MB_MID * 8);
            store_tile(reinterpret_cast<uint32_t*>(g_x + X_O + (((u == 7) * 16 + (b >> 3)) * 32 + (b & 3) * 8 + 2 * wg + (ww >> 1)) * 128 + (((b >> 2) & 1) * 2 + (ww & 1)) * 32) + lane,
                       pack_bf16(o[0] * i0, o[1] * i0), pack_bf16(o[2] * i1, o[3] * i1), pack_bf16(o[4] * i0, o[5] * i0), pack_bf16(o[6] * i1, o[7] * i1));
            if (u == 2) asm volatile("cp.async.bulk.wait_group 0;" ::: "memory");
            else count_hint(C_O + 16 + (b >> 3));
            warp_done(mb + (MB_DONE + (u == 7) * 4) * 8);
            TS(5 + (u == 7));
        } else if (u >= 3) {
            if (u < 6) warp_done(mb + (MB_DONE + u - 2) * 8);
            if (job < (u == 3 ? 1 : 5)) {
                mbar_wait(mb + (MB_DONE + u - 3) * 8);
                if (u == 3) count_release(C_MID);
                else if (lane == 0) refill_job(sb, P, u - 4, job);
            } else if (u == 6) {
                if (job < 9) {
                    mbar_wait(mb + MB_MID * 8);
                    if (lane == 0) {
                        mbar_expect(mb + (MB_FULL + job - 5) * 8, SLOT);
                        bulk_g2s(sb + (19 + job) * SLOT, g_x + X_O + tail_m() * 4096 + (job - 5) * 512, SLOT, mb + (MB_FULL + job - 5) * 8);
                    }
                }
            } else if (warp == 7) {
                if (u == 4) cnt = ldg32_relaxed(g_s.cnt[C_MID]);
                if (u == 5) {
                    const unsigned target = lds32(mb + MISC_EPOCH) * NCTA;
                    if (__any_sync(0xffffffffu, cnt != target)) count_wait(C_MID, target);
                    asm volatile("fence.acquire.gpu; fence.proxy.async.global;" ::: "memory");
                    warp_done(mb + MB_MID * 8);
                }
            }
        } else if (u == 1) {
            if (SAFE) mbar_wait(mb + MB_KV * 8);
            TS(17);
            if (lane == 0) {
                if (job < 9) {
                    asm volatile("cp.async.bulk.global.shared::cta.bulk_group [%0], [%1], %2;"
                                 :: "l"(g_x + X_ARM + b * X_SHARE + job * 512), "r"(sb + SM_SENT), "r"(job < 8 ? 8192 : (X_SHARE - 4096) * 16) : "memory");
                    asm volatile("cp.async.bulk.commit_group;" ::: "memory");
                } else if (job < 11) load_wo(sb, P, job - 9);
            }
        } else if (SAFE) {
            if (warp == 8) {
                const unsigned target = lds32(mb + MISC_EPOCH) * NMAIN;
                if (__any_sync(0xffffffffu, cnt != target)) count_wait(C_KV, target);
                if (lane == 0) {
                    asm volatile("fence.acquire.gpu; fence.proxy.async.global;" ::: "memory");
                    mbar_expect(mb + MB_KV * 8, 47104 + 2 * 24576);
                    bulk_g2s(sb + SM_K + 16384, g_s.kv + 1024, 47104, mb + MB_KV * 8);
                    bulk_g2s(sb + SM_V + 8192, g_s.kv + 4096 + 512, 24576, mb + MB_KV * 8);
                    bulk_g2s(sb + SM_V + 32768 + 8192, g_s.kv + 6144 + 512, 24576, mb + MB_KV * 8);
                }
            }
        }
        __syncwarp();
    }
    }
}

__device__ __forceinline__ int kv_slot(int idx) {
    const int t = (idx & 63) >> 1, c = 2 * (blockIdx.x >> 2) + (idx & 1), hg = blockIdx.x & 3;
    return hg < 2 ? ((t + 31) & 31) * 128 + (c >> 3) * 16 + (hg & 1) * 8 + (c & 7) : 4096 + (hg & 1) * 2048 + t * 64 + c;
}

#define GATE_AT 2
__device__ __noinline__ void helper_cta(const Params& P, uint8_t* smem) {
    const int tid = threadIdx.x, b = blockIdx.x, hi = b - NMAIN;
    const unsigned epoch = g_s.epoch[b] + 1;
    float* red = reinterpret_cast<float*>(smem);
    if (tid < 32) count_wait(C_KV, epoch * NMAIN);
    __syncthreads();
    if (tid == 480) {
        for (int i = 0; i < 8; i++) asm volatile("cp.async.bulk.prefetch.L2.global [%0], %1;" :: "l"((const char*)P.wop + hi * 131072 + i * 16384), "r"(16384) : "memory");
        for (int i = 0; i < 43; i++) asm volatile("cp.async.bulk.prefetch.L2.global [%0], %1;" :: "l"((const char*)P.w2p + hi * 352256 + i * 8192), "r"(8192) : "memory");
    }
    if (tid < 344) {
        const int cg = tid % 43, rp = tid / 43;
        const uint4* src = reinterpret_cast<const uint4*>(P.w1p + (size_t)rp * 64 * FF + (hi * 43 + cg) * 8);
        float s[8] = {0, 0, 0, 0, 0, 0, 0, 0};
#pragma unroll 8
        for (int r = 0; r < 64; r++) {
            uint4 v = __ldg(src + r * (FF / 8));
            s[0] += bf_lo(v.x); s[1] += bf_hi(v.x); s[2] += bf_lo(v.y); s[3] += bf_hi(v.y);
            s[4] += bf_lo(v.z); s[5] += bf_hi(v.z); s[6] += bf_lo(v.w); s[7] += bf_hi(v.w);
        }
        float* part = red + (rp * 43 + cg) * 8;
#pragma unroll
        for (int i = 0; i < 8; i++) part[i] = s[i];
    }
    __syncthreads();
    if (tid < 344) {
        float s = 0.f;
#pragma unroll
        for (int rp = 0; rp < 8; rp++) s += red[rp * 344 + tid];
        g_s.cs[hi * 344 + tid] = s;
    } else if (hi == 3 && tid < 344 + 64) g_s.cs[FF + tid - 344] = 0.f;
    __syncthreads();
    if (tid < 32) count_release(C_MID);
    if (tid == 0) g_s.epoch[b] = epoch;
}

__global__ void __launch_bounds__(512, 1) fused_kernel(const __grid_constant__ Params P) {
    extern __shared__ __align__(1024) uint8_t smem[];
    const uint32_t sb = (uint32_t)__cvta_generic_to_shared(smem);
    const uint32_t mb = sb + SM_MISC;
    const int tid = threadIdx.x, lane = tid & 31, b = blockIdx.x;
    if (b >= NMAIN) { helper_cta(P, smem); return; }
    const int tg = b >> 2, hg = b & 3;
    const int warp = __shfl_sync(0xffffffffu, tid >> 5, 0);

    const uint32_t xst = sb + (((0x160A1204u >> (8 * (warp >> 2))) & 31) * SLOT + (warp & 3) * 4096), xbar = mb + MISC_XBAR + warp * 8;
    if (lane == 0) {
        mbar_init(xbar, 1);
        asm volatile("fence.mbarrier_init.release.cluster;" ::: "memory");
        mbar_expect(xbar, 4096);
        bulk_g2s(xst, P.x + (size_t)((warp & 7) * 4 + tg * 32 + (warp >> 3) * 1024) * D, 4096, xbar);
    }
    const uint4 wkv = ldg_relaxed(reinterpret_cast<const uint4*>(reinterpret_cast<const char*>(P.wk) + (hg < 2 ? 0 : P.wv_off)) + tid * 2 + (hg & 1));
    unsigned epoch = 0;
    if (warp == 12) epoch = ldg32_relaxed(g_s.epoch + b);
    const int wg = warp >> 2, ww = warp & 3, g = lane >> 2, t4 = lane & 3, t128 = tid & 127;
    if (lane == 0) {
        if (warp < 4) {
            mbar_init(mb + (MB_WQ + warp) * 8, 2);
            asm volatile("fence.mbarrier_init.release.cluster;" ::: "memory");
            if (warp < 2) { load_wq(sb, P, warp, 0); load_wq(sb, P, warp, 1); }
            else asm volatile("cp.async.bulk.prefetch.L2.global [%0], %1;" :: "l"((const char*)P.wqp + 262144 + (b * 2 + warp - 2) * 1024), "r"(1024) : "memory");
        } else {
            if (warp < 7) asm volatile("prefetch.tensormap [%0];" :: "l"(&P.wo + (warp - 4)) : "memory");
            if (warp < 10) {
#pragma unroll
                for (uint32_t i = 0; i < 10; i++) mbar_init(mb + (27 + warp * 10 + i) * 8, 2);
            } else {
#pragma unroll 1
                for (uint32_t i = 0; i < 11; i++) { const uint32_t id = warp * 11 - 106 + i; mbar_init(mb + (id < 67 ? id : id + 60) * 8, (BAR_COUNTS[id >> 3] >> (8 * (id & 7))) & 31); }
            }
            if (warp == 7) sts128(mb + MISC_NRM, 0, 0, 0, 0);
        }
    }
    __syncwarp();
    TS(16);
    sts128(sb + SM_WKV + tid * 16, wkv.x, wkv.y, wkv.z, wkv.w);
    uint4 xv[4][2];
    mbar_wait(xbar);
#pragma unroll
    for (int i = 0; i < 8; i++) xv[i >> 1][i & 1] = lds128(xst + i * 512 + lane * 16);
    float dlt;
    {
        float st[4];
#pragma unroll
        for (int i = 0; i < 4; i++) {
            const uint32_t s = add_bf16x2(add_bf16x2(add_bf16x2(xv[i][0].x, xv[i][0].y), add_bf16x2(xv[i][0].z, xv[i][0].w)),
                                          add_bf16x2(add_bf16x2(xv[i][1].x, xv[i][1].y), add_bf16x2(xv[i][1].z, xv[i][1].w)));
            st[i] = bf_lo(s) + bf_hi(s);
        }
        TS(13);
        const float tot = reduce4(st, lane) * (-1.0f / D);
        const uint32_t nmr = pack_bf16(tot, tot);
        dlt = bf_lo(nmr) - tot;
        const uint32_t xa[2] = {sb + (((uint32_t)XN_SLOTS >> (lane & 24)) & 31) * SLOT + warp * 512, sb + (((uint32_t)(XN_SLOTS >> 32) >> (lane & 24)) & 31) * SLOT + warp * 512};
#pragma unroll
        for (int i = 0; i < 4; i++) {
            const uint32_t nm = __shfl_sync(0xffffffffu, nmr, i * 8);
            const uint32_t off = i * 128 + (((lane & 7) ^ ((warp & 1) * 4 + i)) << 4);
#pragma unroll
            for (int c = 0; c < 2; c++) {
                xv[i][c].x = add_bf16x2(xv[i][c].x, nm); xv[i][c].y = add_bf16x2(xv[i][c].y, nm);
                xv[i][c].z = add_bf16x2(xv[i][c].z, nm); xv[i][c].w = add_bf16x2(xv[i][c].w, nm);
                sts128(xa[c] + off, xv[i][c].x, xv[i][c].y, xv[i][c].z, xv[i][c].w);
            }
        }
    }
    fence_async_smem();
    TS(0);
    auto variances = [&]() {
        float st[4];
#pragma unroll
        for (int i = 0; i < 4; i++) {
            float v = 0.f;
#pragma unroll
            for (int c = 0; c < 2; c++) {
                const uint32_t a = fma_bf16x2(xv[i][c].x, xv[i][c].x, mul_bf16x2(xv[i][c].y, xv[i][c].y));
                const uint32_t d = fma_bf16x2(xv[i][c].z, xv[i][c].z, mul_bf16x2(xv[i][c].w, xv[i][c].w));
                v += (bf_lo(a) + bf_hi(a)) + (bf_lo(d) + bf_hi(d));
            }
            st[i] = v;
        }
        const float vs = reduce4(st, lane), dl = dlt;
        if ((lane & 7) == 0) sts32(sb + SM_RSTD + (warp * 4 + (lane >> 3)) * 4, __float_as_uint(rsqrtf(fmaxf(vs * (1.0f / D) - dl * dl, 0.f) + 1e-5f)));
    };
    if (wg == 2) {
        float kv[4] = {0.f, 0.f, 0.f, 0.f};
        fence_regs(kv);
        const uint64_t da = mkdesc(sb, 16, 1024, 1), db = mkdesc(sb + SM_WKV, 128, 16, 0);
        bar_sync(7, 512);
        wg_fence();
#pragma unroll
        for (int s = 0; s < 32; s++) mma_ss8(kv, da + xn_slot(s >> 2) * 512 + (s & 3) * 2, db + s * 16);
        wg_commit();
        variances();
        wg_wait<0>(); fence_regs(kv);
        float2* kt = reinterpret_cast<float2*>(smem + SM_KTMP);
        kt[(ww * 16 + g) * 4 + t4] = make_float2(kv[0], kv[1]); kt[(ww * 16 + g + 8) * 4 + t4] = make_float2(kv[2], kv[3]);
        TS(24);
    } else {
        bar_arrive(7, 512);
        variances();
        epoch++;
        if (tid == 12 * 32) { sts32(mb + MISC_EPOCH, epoch); g_s.epoch[b] = epoch; }
    }
    __syncthreads();
    constexpr float QSCALE = 0.25f * 1.4426950408889634f;
    float qa[64];
    const uint32_t qbase = sb + SM_Q + (ww >> 1) * 8192 + (ww & 1) * 512 + lane * 16;
    if (wg == 0) {
        const float rs0 = __uint_as_float(lds32(sb + SM_RSTD + (ww * 16 + g) * 4)) * QSCALE, rs1 = __uint_as_float(lds32(sb + SM_RSTD + (ww * 16 + g + 8) * 4)) * QSCALE;
#pragma unroll
        for (int i = 0; i < 64; i++) qa[i] = 0.f;
        fence_regs(qa);
        mbar_wait(mb + MB_WQ * 8);
        bar_sync(2, 320);
#pragma unroll 1
        for (int i = 0; i < 4; i++) {
            const uint32_t s0 = (WQ0_SLOTS >> (8 * i)) & 31, s1 = (WQ1_SLOTS >> (8 * i)) & 31, xs = (uint32_t)(XN_SLOTS >> (16 * i));
            const uint64_t db = mkdesc(sb + s0 * SLOT, (s1 - s0) * SLOT, 1024, 1);
            const uint64_t da0 = mkdesc(sb + (xs & 31) * SLOT, 16, 1024, 1), da1 = mkdesc(sb + ((xs >> 8) & 31) * SLOT, 16, 1024, 1);
            mbar_wait(mb + (MB_WQ + i) * 8);
            wg_fence();
#pragma unroll
            for (int s = 0; s < 8; s++) mma_ss128(qa, (s < 4 ? da0 : da1) + (s & 3) * 2, db + s * 128);
            wg_commit();
            wg_wait<1>();
            if (i == 1) bar_arrive(6, 160);
        }
        wg_wait<0>();
        fence_regs(qa);
        bar_arrive(5, 256);
        TS(1);
        uint32_t nm = 0;
#pragma unroll
        for (int h = 0; h < 8; h++) {
#pragma unroll
            for (int i = 0; i < 8; i++) qa[8 * h + i] *= (i & 2) ? rs1 : rs0;
            stsm4(qbase + h * 1024, pack_f16(qa[8 * h], qa[8 * h + 1]), pack_f16(qa[8 * h + 4], qa[8 * h + 5]), pack_f16(qa[8 * h + 2], qa[8 * h + 3]), pack_f16(qa[8 * h + 6], qa[8 * h + 7]));
            const float n0 = qa[8 * h] * qa[8 * h] + qa[8 * h + 1] * qa[8 * h + 1] + qa[8 * h + 4] * qa[8 * h + 4] + qa[8 * h + 5] * qa[8 * h + 5];
            const float n1 = qa[8 * h + 2] * qa[8 * h + 2] + qa[8 * h + 3] * qa[8 * h + 3] + qa[8 * h + 6] * qa[8 * h + 6] + qa[8 * h + 7] * qa[8 * h + 7];
            nm = max(nm, max(__float_as_uint(n0), __float_as_uint(n1)));
        }
        nm = __reduce_max_sync(0xffffffffu, __float_as_uint(quad_sum(__uint_as_float(nm))));
        if (lane == 0) asm volatile("red.shared.max.u32 [%0], %1;" :: "r"(mb + MISC_NRM), "r"(nm) : "memory");
    } else if (wg == 1) {
        if (lane == 0) load_wq(sb, P, 2 + (ww >> 1), ww & 1);
        __syncwarp();
        bar_sync(2, 320);
#pragma unroll
        for (int i = 0; i < 4; i++) sts128(sb + SM_SENT + (i * 128 + t128) * 16, SENT, SENT, SENT, SENT);
#pragma unroll
        for (int i = 0; i < 16; i++) {
            if (i == 4) bar_sync(5, 256);
            sts128(sb + SM_V + 65536 + (i * 128 + t128) * 16, 0x3F803F80u, 0x3F803F80u, 0x3F803F80u, 0x3F803F80u);
        }
    } else if (wg == 2) {
        if (ww < 2) {
            const bool diff = ww == 0 && hg < 2;
            uint32_t nm = 1;
            uint4 w[2];
#pragma unroll
            for (int i = 0; i < 2; i++) {
                const int r = (lane & 1) * 32 + i * 16 + (lane >> 1);
                const uint32_t ra = sb + SM_KTMP + r * 32;
                float4 c0 = lds128f(ra), c1 = lds128f(ra + 16);
                const float4 p0 = lds128f(ra - 32), p1 = lds128f(ra - 16);
                const float rs = __uint_as_float(lds32(sb + SM_RSTD + r * 4));
                float rp = -__uint_as_float(lds32(sb + SM_RSTD + r * 4 - 4));
                c0.x *= rs; c0.y *= rs; c0.z *= rs; c0.w *= rs; c1.x *= rs; c1.y *= rs; c1.z *= rs; c1.w *= rs;
                nm = max(nm, __float_as_uint(c0.x * c0.x + c0.y * c0.y + c0.z * c0.z + c0.w * c0.w + c1.x * c1.x + c1.y * c1.y + c1.z * c1.z + c1.w * c1.w));
                uint32_t w0, w1, w2, w3;
                if (diff) {
                    if (r & 31) {
                        c0.x = fmaf(p0.x, rp, c0.x); c0.y = fmaf(p0.y, rp, c0.y); c0.z = fmaf(p0.z, rp, c0.z); c0.w = fmaf(p0.w, rp, c0.w);
                        c1.x = fmaf(p1.x, rp, c1.x); c1.y = fmaf(p1.y, rp, c1.y); c1.z = fmaf(p1.z, rp, c1.z); c1.w = fmaf(p1.w, rp, c1.w);
                    }
                    w0 = pack_f16(c0.x, c0.y); w1 = pack_f16(c0.z, c0.w); w2 = pack_f16(c1.x, c1.y); w3 = pack_f16(c1.z, c1.w);
                } else {
                    w0 = pack_bf16(c0.x, c0.y); w1 = pack_bf16(c0.z, c0.w); w2 = pack_bf16(c1.x, c1.y); w3 = pack_bf16(c1.z, c1.w);
                }
                w[i] = make_uint4(nonzero(w0), nonzero(w1), nonzero(w2), nonzero(w3));
            }
            nm = __reduce_max_sync(0xffffffffu, nm);
            if (ww == 0 || hg < 2) {
#pragma unroll
                for (int i = 0; i < 2; i++) stg128((ww ? g_s.kplain : g_s.kv) + kv_slot(i * 32 + lane), w[i].x, w[i].y, w[i].z, w[i].w);
            }
            if (ww == 0) {
                if (lane < 2) stg128(g_s.nrm + b * 2 + lane, nm, nm, nm, nm);
                count_hint(C_KVH);
                TS(1);
                bar_arrive(2, 320);
            } else {
                bar_sync(2, 320);
                count_release(C_KV);
            }
        }
    } else {
        if (ww == 0) count_wait(C_KVH, epoch * NMAIN);
        TS(1);
        bar_sync(3, 128);
        uint32_t nm = ldg32_relaxed(g_s.nrm + t128 * 2);
        if (ww == 0) bar_sync(6, 160);
        int spins = 0;
        bool bad;
        do {
            if (t128 == 0) {
                asm volatile("fence.proxy.async.global;" ::: "memory");
                mbar_expect(mb + MB_KV0 * 8, 34816);
                bulk_g2s(sb + SM_K + 31 * 2048, g_s.kv + 31 * 128, 2048, mb + MB_KV0 * 8);
                bulk_g2s(sb + SM_K, g_s.kv, 16384, mb + MB_KV0 * 8);
                bulk_g2s(sb + SM_V, g_s.kv + 4096, 8192, mb + MB_KV0 * 8);
                bulk_g2s(sb + SM_V + 32768, g_s.kv + 6144, 8192, mb + MB_KV0 * 8);
            }
            if (spins) nm = ldg32_relaxed(g_s.nrm + t128 * 2);
            __syncwarp();
            mbar_wait(mb + MB_KV0 * 8, spins & 1);
            const uint32_t probe = sb + (ww < 2 ? SM_K + ww * 8192 : SM_V + (ww - 2) * 32768) + lane * 32 + (lane >> 2) * 4;
            uint32_t mn = min(nm, lds32(sb + SM_K + 31 * 2048 + (ww & 1) * 1024 + lane * 32 + (lane >> 2) * 4));
#pragma unroll
            for (int k = 0; k < 8; k++) mn = min(mn, lds32(probe + k * 1024));
            uint32_t r;
            asm volatile("{.reg .pred p, q; setp.eq.u32 p, %1, 0; barrier.red.or.pred.aligned q, 3, 128, p; selp.u32 %0, 1, 0, q;}" : "=r"(r) : "r"(mn) : "memory");
            bad = __any_sync(0xffffffffu, r);
        } while (bad && ++spins < SPIN_LIMIT);
        TS(2);
        nm = max(nm, __shfl_xor_sync(0xffffffffu, nm, 4)); nm = max(nm, __shfl_xor_sync(0xffffffffu, nm, 8)); nm = max(nm, __shfl_xor_sync(0xffffffffu, nm, 16));
        if (lane < 4) asm volatile("red.shared.max.u32 [%0], %1;" :: "r"(mb + MISC_NRM + 4 + min(lane, 2) * 4), "r"(nm) : "memory");
    }
    fence_async_smem();
    TS(3);
    __syncthreads();
    const float4 nr = lds128f(mb + MISC_NRM);
    const bool safe = __all_sync(0xffffffffu, (nr.x * (nr.y + nr.z) <= 3500.0f) && (nr.x <= 65536.0f) && (nr.y + nr.z <= 65536.0f) && (nr.w <= 1e24f));
    TS(4);

    if (__builtin_expect(safe, 1)) {
        attention<true>(P, sb, warp TS_PASS);
    } else {
        if (wg == 0) {
#pragma unroll
            for (int h = 0; h < 8; h++)
                stsm4(qbase + h * 1024, pack_bf16(qa[8 * h], qa[8 * h + 1]), pack_bf16(qa[8 * h + 4], qa[8 * h + 5]), pack_bf16(qa[8 * h + 2], qa[8 * h + 3]), pack_bf16(qa[8 * h + 6], qa[8 * h + 7]));
            fence_async_smem();
        } else if (warp == 15) {
            count_wait(C_KV, lds32(mb + MISC_EPOCH) * NMAIN);
            if (lane == 0) {
                asm volatile("fence.proxy.async;" ::: "memory");
                mbar_expect(mb + MB_KV * 8, 131072);
                bulk_g2s(sb + SM_K, g_s.kplain, 65536, mb + MB_KV * 8);
                bulk_g2s(sb + SM_V, g_s.kv + 4096, 65536, mb + MB_KV * 8);
            }
            __syncwarp();
        }
        __syncthreads();
        mbar_wait(mb + MB_KV * 8);
        attention<false>(P, sb, warp TS_PASS);
    }

    const int j = tail_j();
    if (wg == 1 || wg == 2) {
        if (warp == 8) {
            epoch = lds32(mb + MISC_EPOCH);
#pragma unroll 1
            for (int job = 1; job < 6; job++) {
                count_wait(C_O + 32 * (job >> 1) + (job & 1) * 16 + tail_m(), epoch * (job == 1 ? 128 : 32));
                asm volatile("fence.proxy.async.global;" ::: "memory");
                warp_done(mb + (MB_READY + job) * 8);
                TS(18 + job);
            }
        } else if (warp == 9) {
#pragma unroll
            for (int i = 0; i < 2; i++) {
                if (lane < 22) {
                    const uint4 v = ldg_relaxed(reinterpret_cast<const uint4*>(g_s.cs + j * 176) + i * 22 + lane);
                    sts128(mb + MISC_CS + (i * 22 + lane) * 16, v.x, v.y, v.z, v.w);
                }
                stg128(g_s.kv + kv_slot(i * 32 + lane), 0u, 0u, 0u, 0u);
            }
            warp_done(mb + MB_CS * 8);
            if (lane < 2) stg128(g_s.nrm + b * 2 + lane, 0u, 0u, 0u, 0u);
#pragma unroll 1
            for (int i = 0; i < 16; i++) {
                mbar_wait(mb + (MB_W1 + i) * 8);
                const int n = i < 8 ? 16 + i + 8 * (lane & 1) : 32 + 3 * (i - 8) + (lane >> 1) + 22 * (lane & 1);
                if (lane < (i < 8 || i == 15 ? 2 : 6)) mbar_arrive(mb + (MB_FULL + n) * 8);
                __syncwarp();
            }
        } else {
            if (warp == 10) {
#pragma unroll 1
                for (int i = 3; i < 16; i++) {
                    const bool w1 = i < 8;
                    const int kb = i & 7;
                    const uint32_t bar = mb + (MB_W1 + i) * 8, dst = sb + w1_slot(kb, 0) * SLOT, step = kb < 4 ? 4 * SLOT : SLOT;
                    const CUtensorMap* tm = w1 ? &P.w1 : &P.w2;
                    const int c0 = w1 ? j * 176 : j * 64, c1 = w1 ? kb * 64 : kb * 192, d0 = w1 ? 64 : 0, d1 = 64 - d0;
                    if (lane == 0) mbar_expect(bar, i == 15 ? SLOT : 3 * SLOT);
                    mbar_wait(mb + (w1 ? (i == 3 ? MB_DONE + 4 : i < 6 ? MB_REL + 9 : MB_REL + 8) : MB_REL + kb) * 8);
                    if (i == 8 + GATE_AT) mbar_wait(mb + MB_EPI * 8);
                    if (lane == 0) {
                        tma2d(dst, tm, c0, c1, bar);
                        if (i < 15) { tma2d(dst + step, tm, c0 + d0, c1 + d1, bar); tma2d(dst + 2 * step, tm, c0 + 2 * d0, c1 + 2 * d1, bar); }
                    }
                    __syncwarp();
                }
            } else {
                ring_feed(sb, wg == 1 ? ww : 4 TS_PASS);
            }
        }
    } else {
        const int pr = (wg == 0), mt = 16 * pr + tail_m();
        uint32_t* const hp = reinterpret_cast<uint32_t*>(g_x + X_H1 + (mt * 32 + j * 4) * 128 + ww * 32) + lane;
        {
            uint32_t hk[16];
            const uint32_t* xp = reinterpret_cast<const uint32_t*>(P.x + (size_t)(mt * 64 + ww * 16 + g) * D + j * 64 + t4 * 2);
#pragma unroll
            for (int k = 0; k < 8; k++) { hk[2 * k] = __ldg(xp + k * 4); hk[2 * k + 1] = __ldg(xp + k * 4 + 8 * (D / 2)); }
            mbar_wait(mb + MB_WO * 8);
            float acc[32];
            if (gemm_ss<0>(acc, sb, pr TS_PASS)) gemm_slow(acc, g_x + X_O + mt * 32 * 128, 32, P.wop, D, D, j * 64);
            TS(7);
#pragma unroll
            for (int i = 0; i < 16; i++) hk[i] = pack_bf16(acc[2 * i] + bf_lo(hk[i]), acc[2 * i + 1] + bf_hi(hk[i]));
#pragma unroll
            for (int k = 0; k < 4; k++) store_tile(hp + k * 512, hk[4 * k], hk[4 * k + 1], hk[4 * k + 2], hk[4 * k + 3]);
            count_hint(C_H1 + mt);
            TS(8);
            float st[4] = {0.f, 0.f, 0.f, 0.f};
#pragma unroll
            for (int i = 0; i < 16; i++) {
                const float lo = bf_lo(hk[i]), hi = bf_hi(hk[i]);
                st[2 * (i & 1)] += lo + hi;
                st[2 * (i & 1) + 1] = fmaf(lo, lo, fmaf(hi, hi, st[2 * (i & 1) + 1]));
            }
#pragma unroll
            for (int o = 1; o < 4; o <<= 1)
#pragma unroll
                for (int i = 0; i < 4; i++) st[i] += __shfl_xor_sync(0xffffffffu, st[i], o);
            if (t4 == 0) stg128(g_x + X_ST + (mt * 8 + j) * 32 + ww * 8 + g, __float_as_uint(st[0]), __float_as_uint(st[1]), __float_as_uint(st[2]), __float_as_uint(st[3]));
        }
        {
            float acc[88];
            const uint4* sp = g_x + X_ST + (mt * 8 + t4) * 32 + ww * 8 + g;
            mbar_wait(mb + (MB_FULL + 16 + pr * 8) * 8);
            uint4 u0 = ldg_relaxed(sp), u1 = ldg_relaxed(sp + 128);
            if (gemm_ss<1>(acc, sb, pr TS_PASS)) gemm_slow(acc, g_x + X_H1 + mt * 32 * 128, 32, P.w1p, FF, D, j * 176);
            TS(9);
            int spins = 0;
            while (__builtin_expect(__any_sync(0xffffffffu, max(u0.x, u1.x) == SENT), 0) && ++spins < SPIN_LIMIT) { u0 = ldg_relaxed(sp); u1 = ldg_relaxed(sp + 128); }
            float st[4] = {__uint_as_float(u0.x) + __uint_as_float(u1.x), __uint_as_float(u0.y) + __uint_as_float(u1.y),
                           __uint_as_float(u0.z) + __uint_as_float(u1.z), __uint_as_float(u0.w) + __uint_as_float(u1.w)};
#pragma unroll
            for (int o = 1; o < 4; o <<= 1)
#pragma unroll
                for (int k = 0; k < 4; k++) st[k] += __shfl_xor_sync(0xffffffffu, st[k], o);
            float nmean[2], hrstd[2];
#pragma unroll
            for (int k = 0; k < 2; k++) {
                nmean[k] = st[2 * k] * (-1.0f / D);
                hrstd[k] = 0.5f * rsqrtf(fmaxf(fmaf(-nmean[k], nmean[k], st[2 * k + 1] * (1.0f / D)), 0.f) + 1e-5f);
                nmean[k] *= hrstd[k];
            }
            mbar_wait(mb + MB_CS * 8);
            uint32_t* hb = reinterpret_cast<uint32_t*>(g_x + X_H2 + (mt * 88 + j * 11) * 128 + ww * 32) + lane;
#pragma unroll
            for (int i = 0; i < 22; i++) {
                float2 cs;
                asm volatile("ld.shared.v2.f32 {%0,%1}, [%2];" : "=f"(cs.x), "=f"(cs.y) : "r"(mb + MISC_CS + i * 32 + t4 * 8));
                const float* z = acc + 4 * i;
                uint32_t* p = hb + (i >> 1) * 512 + (i & 1) * 32;
                stg32(p, pack_bf16(silu2(fmaf(hrstd[0], z[0], nmean[0] * cs.x)), silu2(fmaf(hrstd[0], z[1], nmean[0] * cs.y))));
                stg32(p + 64, pack_bf16(silu2(fmaf(hrstd[1], z[2], nmean[1] * cs.x)), silu2(fmaf(hrstd[1], z[3], nmean[1] * cs.y))));
            }
            count_hint(C_H2 + mt);
            if (!pr) warp_done(mb + MB_EPI * 8);
            TS(10);
        }
        {
            uint32_t hk[16];
#pragma unroll
            for (int i = 0; i < 16; i++) hk[i] = ldg32_relaxed(hp + (i >> 2) * 512 + ((i & 1) * 2 + ((i >> 1) & 1)) * 32);
            float acc[32];
            if (gemm_ss<2>(acc, sb, pr TS_PASS)) gemm_slow(acc, g_x + X_H2 + mt * 88 * 128, 88, P.w2p, D, FF, j * 64);
            TS(11);
#pragma unroll
            for (int i = 0; i < 16; i++) hk[i] = pack_bf16(acc[2 * i] + bf_lo(hk[i]), acc[2 * i + 1] + bf_hi(hk[i]));
#pragma unroll
            for (int h = 0; h < 4; h++) {
                const uint32_t* v = hk + (h >> 1) * 8 + (h & 1);
                uint32_t v0 = v[0], v1 = v[2], v2 = v[4], v3 = v[6];
                const bool o1 = t4 & 1, o2 = t4 & 2;
                uint32_t a = __shfl_xor_sync(0xffffffffu, o1 ? v0 : v1, 1), c = __shfl_xor_sync(0xffffffffu, o1 ? v2 : v3, 1);
                if (o1) { v0 = a; v2 = c; } else { v1 = a; v3 = c; }
                a = __shfl_xor_sync(0xffffffffu, o2 ? v0 : v2, 2); c = __shfl_xor_sync(0xffffffffu, o2 ? v1 : v3, 2);
                if (o2) { v0 = a; v1 = c; } else { v2 = a; v3 = c; }
                *reinterpret_cast<uint4*>(P.out + (size_t)(mt * 64 + ww * 16 + g + 8 * (h & 1)) * D + j * 64 + (h >> 1) * 32 + t4 * 8) = make_uint4(v0, v1, v2, v3);
            }
        }
    }
    TS(12);
}

typedef CUresult (*EncodeFn)(CUtensorMap*, CUtensorMapDataType, cuuint32_t, void*, const cuuint64_t*, const cuuint64_t*, const cuuint32_t*,
                             const cuuint32_t*, CUtensorMapInterleave, CUtensorMapSwizzle, CUtensorMapL2promotion, CUtensorMapFloatOOBfill);

void encode2d(EncodeFn fn, CUtensorMap* tm, const void* ptr, int rows, int cols, int box_rows, int box_cols, CUtensorMapSwizzle sw) {
    cuuint64_t dims[2] = {(cuuint64_t)cols, (cuuint64_t)rows};
    cuuint64_t strides[1] = {(cuuint64_t)cols * 2};
    cuuint32_t box[2] = {(cuuint32_t)box_cols, (cuuint32_t)box_rows};
    cuuint32_t es[2] = {1, 1};
    fn(tm, CU_TENSOR_MAP_DATA_TYPE_BFLOAT16, 2, const_cast<void*>(ptr), dims, strides, box, es, CU_TENSOR_MAP_INTERLEAVE_NONE, sw,
       CU_TENSOR_MAP_L2_PROMOTION_L2_128B, CU_TENSOR_MAP_FLOAT_OOB_FILL_NONE);
}

}

extern "C" void kernel_launch(void* const* d_in, const int* in_sizes, int n_in, void* d_out, int out_size) {
    (void)in_sizes; (void)n_in; (void)out_size;
    void* fnp = nullptr;
    cudaDriverEntryPointQueryResult qr;
    cudaGetDriverEntryPoint("cuTensorMapEncodeTiled", &fnp, cudaEnableDefault, &qr);
    EncodeFn fn = (EncodeFn)fnp;
    Params P;
    encode2d(fn, &P.wq, d_in[1], D, D, 128, 64, CU_TENSOR_MAP_SWIZZLE_128B);
    P.wk = (const __nv_bfloat16*)d_in[2];
    P.wv_off = (const char*)d_in[3] - (const char*)d_in[2];
    encode2d(fn, &P.wo, d_in[4], D, D, 64, 64, CU_TENSOR_MAP_SWIZZLE_128B);
    encode2d(fn, &P.w1, d_in[6], D, FF, 64, 64, CU_TENSOR_MAP_SWIZZLE_128B);
    encode2d(fn, &P.w2, d_in[7], FF, D, 64, 64, CU_TENSOR_MAP_SWIZZLE_128B);
    P.x = (const __nv_bfloat16*)d_in[0];
    P.w1p = (const __nv_bfloat16*)d_in[6];
    P.w2p = (const __nv_bfloat16*)d_in[7];
    P.wop = (const __nv_bfloat16*)d_in[4];
    P.wqp = (const __nv_bfloat16*)d_in[1];
    P.out = (__nv_bfloat16*)d_out;
    P.neg1 = 0xFFFFFFFFu; P.pad = 0;
    cudaFuncSetAttribute(fused_kernel, cudaFuncAttributeMaxDynamicSharedMemorySize, SMEM_BYTES);
    fused_kernel<<<NCTA, 512, SMEM_BYTES>>>(P);
}
```

```cpp
#include <cuda_runtime.h>
#include <cuda_bf16.h>
#include <cuda.h>
#include <stdint.h>

namespace {

constexpr int D = 512, FF = 1376;
constexpr int NMAIN = 128, NHELP = 4, NCTA = NMAIN + NHELP;
constexpr uint32_t SENT = 0xFFFFFFFFu;
constexpr int SPIN_LIMIT = 1 << 22;

constexpr uint32_t KB = 1024, SLOT = 8192;
constexpr uint64_t XN_SLOTS = 7 | 16 << 8 | 6 << 16 | 17 << 24 | 21ull << 32 | 27ull << 40 | 24ull << 48 | 25ull << 56;
constexpr uint32_t WQ0_SLOTS = 0 | 2 << 8 | 4 << 16 | 10 << 24, WQ1_SLOTS = 12 | 14 << 8 | 18 << 16 | 22 << 24;
__host__ __device__ constexpr uint32_t xn_slot(int kb) { return (XN_SLOTS >> (8 * kb)) & 31; }
constexpr uint32_t SM_WKV = 208 * KB;
constexpr uint32_t SM_K = 0;
constexpr uint32_t SM_Q = 64 * KB;
constexpr uint32_t SM_V = 96 * KB;
constexpr uint32_t SM_MISC = 224 * KB;
constexpr uint32_t SMEM_BYTES = 227 * KB;
constexpr uint32_t SM_KTMP = 164 * KB;
constexpr uint32_t SM_RSTD = 226 * KB;
constexpr uint32_t SM_SENT = 208 * KB;
constexpr uint32_t MB_WQ = 0;
constexpr uint32_t MB_DONE = 4;
constexpr uint32_t MB_EMPTY = 9;
constexpr uint32_t MB_EPI = 15;
constexpr uint32_t MB_W1 = 16;
constexpr uint32_t MB_W2 = 24;
constexpr uint32_t MB_CS = 32;
constexpr uint32_t MB_KV = 33;
constexpr uint32_t MB_KV0 = 34;
constexpr uint32_t MB_MID = 35;
constexpr uint32_t MB_READY = 35;
constexpr uint32_t MB_STAT = 41;
constexpr uint32_t MB_FULL = 43;
constexpr uint32_t MB_NULL = 119;
constexpr uint32_t MB_WO = 120;
constexpr uint32_t MB_REL = 121;
constexpr uint32_t MISC_STAT = 2048;
constexpr uint32_t MISC_XBAR = 2304;
constexpr uint32_t MISC_NRM = 1056;
constexpr uint32_t MISC_EPOCH = 1072;
constexpr uint32_t MISC_TS = 1088;
constexpr uint32_t MISC_CS = 1344;

__host__ __device__ constexpr uint32_t wo_slot(int kb) { return kb < 2 ? 10 + kb : kb - 2; }
__host__ __device__ constexpr uint32_t w1_slot(int kb, int a) { return kb < 4 ? 12 + kb + 4 * a : (kb < 6 ? 3 * kb - 6 : 3 * kb - 18) + a; }

struct alignas(128) Small {
    unsigned epoch[160];
    unsigned cnt[100][32];
    float cs[1440];
    uint4 nrm[NMAIN * 2];
    uint4 kv[8192];
    uint4 kplain[4096];
};
__device__ Small g_s;
constexpr int C_KVH = 0, C_KV = 1, C_MID = 2, C_O = 3, C_H1 = 35, C_H2 = 67;
constexpr int X_O = 0, X_H1 = 32 * 32 * 128, X_H2 = 2 * X_H1, X_ST = X_H2 + 32 * 88 * 128, X_END = X_ST + 32 * 8 * 32;
constexpr int X_ARM = 16 * 32 * 128, X_SHARE = (X_END - X_ARM) / NMAIN;
__device__ uint4 g_x[X_END];
#define TS(i) do {} while (0)
#define TSF(k)

#define TS_ARG
#define TS_PASS

__device__ __forceinline__ void mbar_init(uint32_t bar, int cnt) { asm volatile("mbarrier.init.shared::cta.b64 [%0], %1;" :: "r"(bar), "r"(cnt) : "memory"); }
__device__ __forceinline__ void mbar_expect(uint32_t bar, uint32_t bytes) { asm volatile("mbarrier.arrive.expect_tx.shared::cta.b64 _, [%0], %1;" :: "r"(bar), "r"(bytes) : "memory"); }
__device__ __forceinline__ void mbar_arrive(uint32_t bar) { asm volatile("mbarrier.arrive.shared::cta.b64 _, [%0];" :: "r"(bar) : "memory"); }
__device__ __forceinline__ bool mbar_try(uint32_t bar, uint32_t parity) {
    uint32_t done;
    asm volatile("{.reg .pred p; mbarrier.try_wait.parity.shared::cta.b64 p, [%1], %2; selp.u32 %0, 1, 0, p;}" : "=r"(done) : "r"(bar), "r"(parity) : "memory");
    return __all_sync(0xffffffffu, done);
}
__device__ __forceinline__ void mbar_wait(uint32_t bar, uint32_t parity = 0) {
    if (__builtin_expect(!mbar_try(bar, parity), 0)) {
        int spins = 0;
        while (!mbar_try(bar, parity) && ++spins < (SPIN_LIMIT >> 6)) {}
    }
}
__device__ __forceinline__ void tma2d(uint32_t dst, const CUtensorMap* tm, int c0, int c1, uint32_t bar) {
    asm volatile("cp.async.bulk.tensor.2d.shared::cluster.global.mbarrier::complete_tx::bytes [%0], [%1, {%3, %4}], [%2];"
                 :: "r"(dst), "l"(tm), "r"(bar), "r"(c0), "r"(c1) : "memory");
}
__device__ __forceinline__ void bulk_g2s(uint32_t dst, const void* src, uint32_t bytes, uint32_t bar) {
    asm volatile("cp.async.bulk.shared::cluster.global.mbarrier::complete_tx::bytes [%0], [%1], %2, [%3];" :: "r"(dst), "l"(src), "r"(bytes), "r"(bar) : "memory");
}
__device__ __forceinline__ void fence_async_smem() { asm volatile("fence.proxy.async.shared::cta;" ::: "memory"); }
__device__ __forceinline__ void bar_sync(int id, int n) { asm volatile("bar.sync %0, %1;" :: "r"(id), "r"(n) : "memory"); }
__device__ __forceinline__ void bar_arrive(int id, int n) { asm volatile("bar.arrive %0, %1;" :: "r"(id), "r"(n) : "memory"); }
__device__ __forceinline__ void wg_fence() { asm volatile("wgmma.fence.sync.aligned;" ::: "memory"); }
__device__ __forceinline__ void wg_commit() { asm volatile("wgmma.commit_group.sync.aligned;" ::: "memory"); }
template <int N> __device__ __forceinline__ void wg_wait() { asm volatile("wgmma.wait_group.sync.aligned %0;" :: "n"(N) : "memory"); }
template <int N> __device__ __forceinline__ void fence_regs(float (&d)[N]) {
#pragma unroll
    for (int i = 0; i < N; i++) asm volatile("" : "+f"(d[i]) :: "memory");
}
template <int N> __device__ __forceinline__ void fence_regs(uint32_t (&d)[N]) {
#pragma unroll
    for (int i = 0; i < N; i++) asm volatile("" : "+r"(d[i]) :: "memory");
}
__device__ __forceinline__ uint64_t mkdesc(uint32_t addr, uint32_t lbo, uint32_t sbo, uint32_t swz) {
    return (uint64_t)(((addr & 0x3FFFF) >> 4) | ((lbo >> 4) << 16)) | ((uint64_t)((sbo >> 4) | (swz << 30)) << 32);
}
__device__ __forceinline__ float ex2(float x) { float y; asm("ex2.approx.ftz.f32 %0, %1;" : "=f"(y) : "f"(x)); return y; }
__device__ __forceinline__ float rcp(float x) { float y; asm("rcp.approx.ftz.f32 %0, %1;" : "=f"(y) : "f"(x)); return y; }
__device__ __forceinline__ uint32_t pack_bf16(float lo, float hi) { uint32_t r; asm("cvt.rn.bf16x2.f32 %0, %1, %2;" : "=r"(r) : "f"(hi), "f"(lo)); return r; }
__device__ __forceinline__ uint32_t pack_f16(float lo, float hi) { uint32_t r; asm("cvt.rn.f16x2.f32 %0, %1, %2;" : "=r"(r) : "f"(hi), "f"(lo)); return r; }
__device__ __forceinline__ float bf_lo(uint32_t v) { return __uint_as_float(v << 16); }
__device__ __forceinline__ float bf_hi(uint32_t v) { return __uint_as_float(v & 0xFFFF0000u); }
__device__ __forceinline__ uint4 ldg_relaxed(const uint4* p) {
    uint4 v; asm volatile("ld.relaxed.gpu.global.v4.u32 {%0,%1,%2,%3}, [%4];" : "=r"(v.x), "=r"(v.y), "=r"(v.z), "=r"(v.w) : "l"(p) : "memory"); return v;
}
__device__ __forceinline__ void stg128(void* p, uint32_t a, uint32_t b, uint32_t c, uint32_t d) {
    asm volatile("st.relaxed.gpu.global.v4.u32 [%0], {%1,%2,%3,%4};" :: "l"(p), "r"(a), "r"(b), "r"(c), "r"(d) : "memory");
}
__device__ __forceinline__ void stg128_if(bool c, void* p, uint32_t a, uint32_t b, uint32_t d, uint32_t e) {
    asm volatile("{.reg .pred p; setp.ne.u32 p, %5, 0; @p st.relaxed.gpu.global.v4.u32 [%0], {%1,%2,%3,%4};}" :: "l"(p), "r"(a), "r"(b), "r"(d), "r"(e), "r"((int)c) : "memory");
}
__device__ __forceinline__ void stg64(void* p, uint32_t a, uint32_t b) {
    asm volatile("st.relaxed.gpu.global.v2.u32 [%0], {%1,%2};" :: "l"(p), "r"(a), "r"(b) : "memory");
}
__device__ __forceinline__ void sts128(uint32_t a, uint32_t x, uint32_t y, uint32_t z, uint32_t w) {
    asm volatile("st.shared.v4.u32 [%0], {%1,%2,%3,%4};" :: "r"(a), "r"(x), "r"(y), "r"(z), "r"(w) : "memory");
}
__device__ __forceinline__ void sts32(uint32_t a, uint32_t x) { asm volatile("st.shared.u32 [%0], %1;" :: "r"(a), "r"(x) : "memory"); }
__device__ __forceinline__ float4 lds128f(uint32_t a) {
    float4 v; asm volatile("ld.shared.v4.f32 {%0,%1,%2,%3}, [%4];" : "=f"(v.x), "=f"(v.y), "=f"(v.z), "=f"(v.w) : "r"(a) : "memory"); return v;
}
__device__ __forceinline__ uint4 lds128(uint32_t a) {
    uint4 v; asm volatile("ld.shared.v4.u32 {%0,%1,%2,%3}, [%4];" : "=r"(v.x), "=r"(v.y), "=r"(v.z), "=r"(v.w) : "r"(a) : "memory"); return v;
}
__device__ __forceinline__ uint32_t lds32(uint32_t a) { uint32_t v; asm volatile("ld.shared.u32 %0, [%1];" : "=r"(v) : "r"(a) : "memory"); return v; }
__device__ __forceinline__ uint32_t nonzero(uint32_t w) { return w == 0u ? 0x8000u : w; }
__device__ __forceinline__ void stg32(void* p, uint32_t a) { asm volatile("st.global.u32 [%0], %1;" :: "l"(p), "r"(a) : "memory"); }
__device__ __forceinline__ uint32_t ldg32_relaxed(const void* p) { uint32_t v; asm volatile("ld.relaxed.gpu.global.u32 %0, [%1];" : "=r"(v) : "l"(p) : "memory"); return v; }
__device__ __forceinline__ void count_hint(int id) {
    if ((threadIdx.x & 31) == 0) asm volatile("red.relaxed.gpu.global.add.u32 [%0], 1;" :: "l"(g_s.cnt[id]) : "memory");
}
__device__ __forceinline__ void count_release(int id) {
    __syncwarp();
    if ((threadIdx.x & 31) == 0) asm volatile("red.release.gpu.global.add.u32 [%0], 1;" :: "l"(g_s.cnt[id]) : "memory");
    __syncwarp();
}
__device__ __forceinline__ void count_wait(int id, unsigned target) {
    uint32_t v; int spins = 0;
    do v = ldg32_relaxed(g_s.cnt[id]); while (__any_sync(0xffffffffu, v != target) && ++spins < SPIN_LIMIT);
    asm volatile("fence.acquire.gpu;" ::: "memory");
}
__device__ __forceinline__ void warp_done(uint32_t bar) {
    __syncwarp();
    asm volatile("{.reg .pred p; setp.eq.u32 p, %1, 0; @p mbarrier.arrive.shared::cta.b64 _, [%0];}" :: "r"(bar), "r"(threadIdx.x & 31) : "memory");
}
__device__ __forceinline__ uint32_t mul_bf16x2(uint32_t a, uint32_t b) { uint32_t r; asm("mul.rn.bf16x2 %0, %1, %2;" : "=r"(r) : "r"(a), "r"(b)); return r; }
__device__ __forceinline__ uint32_t fma_bf16x2(uint32_t a, uint32_t b, uint32_t c) { uint32_t r; asm("fma.rn.bf16x2 %0, %1, %2, %3;" : "=r"(r) : "r"(a), "r"(b), "r"(c)); return r; }
__device__ __forceinline__ uint32_t add_bf16x2(uint32_t a, uint32_t b) { uint32_t r; asm("add.rn.bf16x2 %0, %1, %2;" : "=r"(r) : "r"(a), "r"(b)); return r; }

#define R4(d, o) "+f"(d[o + 0]), "+f"(d[o + 1]), "+f"(d[o + 2]), "+f"(d[o + 3])
#define R8(d, o) R4(d, o), R4(d, o + 4)
#define R32(d) R8(d, 0), R8(d, 8), R8(d, 16), R8(d, 24)
#define D32 "{%0,%1,%2,%3,%4,%5,%6,%7,%8,%9,%10,%11,%12,%13,%14,%15,%16,%17,%18,%19,%20,%21,%22,%23,%24,%25,%26,%27,%28,%29,%30,%31}"
#define D64 "{%0,%1,%2,%3,%4,%5,%6,%7,%8,%9,%10,%11,%12,%13,%14,%15,%16,%17,%18,%19,%20,%21,%22,%23,%24,%25,%26,%27,%28,%29,%30,%31,%32,%33,%34,%35,%36,%37,%38,%39,%40,%41,%42,%43,%44,%45,%46,%47,%48,%49,%50,%51,%52,%53,%54,%55,%56,%57,%58,%59,%60,%61,%62,%63}"

__device__ __forceinline__ void mma_qk_f16(float (&d)[32], uint64_t da, uint64_t db) {
    asm volatile("{.reg .pred p; setp.eq.b32 p, 0, 0; wgmma.mma_async.sync.aligned.m64n64k16.f32.f16.f16 " D32 ", %32, %33, p, 1, 1, 0, 0;}"
                 : R32(d) : "l"(da), "l"(db));
}
__device__ __forceinline__ void mma_qk_bf16(float (&d)[32], uint64_t da, uint64_t db) {
    asm volatile("{.reg .pred p; setp.ne.b32 p, 0, 0; wgmma.mma_async.sync.aligned.m64n64k16.f32.bf16.bf16 " D32 ", %32, %33, p, 1, 1, 0, 0;}"
                 : R32(d) : "l"(da), "l"(db));
}
__device__ __forceinline__ void mma_pv(float (&d)[12], const uint32_t* a, uint64_t db) {
    asm volatile("{.reg .pred p; setp.eq.b32 p, 0, 0; wgmma.mma_async.sync.aligned.m64n24k16.f32.bf16.bf16 {%0,%1,%2,%3,%4,%5,%6,%7,%8,%9,%10,%11}, {%12,%13,%14,%15}, %16, p, 1, 1, 1;}"
                 : R8(d, 0), R4(d, 8) : "r"(a[0]), "r"(a[1]), "r"(a[2]), "r"(a[3]), "l"(db));
}
__device__ __forceinline__ void mma_ss128(float (&d)[64], uint64_t da, uint64_t db) {
    asm volatile("{.reg .pred p; setp.eq.b32 p, 0, 0; wgmma.mma_async.sync.aligned.m64n128k16.f32.bf16.bf16 " D64 ", %64, %65, p, 1, 1, 0, 1;}"
                 : R32(d), R8(d, 32), R8(d, 40), R8(d, 48), R8(d, 56) : "l"(da), "l"(db));
}
__device__ __forceinline__ void stsm4(uint32_t addr, uint32_t a, uint32_t b, uint32_t c, uint32_t d) {
    asm volatile("stmatrix.sync.aligned.m8n8.x4.shared.b16 [%0], {%1,%2,%3,%4};" :: "r"(addr), "r"(a), "r"(b), "r"(c), "r"(d) : "memory");
}
__device__ __forceinline__ void mma_ss8(float (&d)[4], uint64_t da, uint64_t db) {
    asm volatile("{.reg .pred p; setp.eq.b32 p, 0, 0; wgmma.mma_async.sync.aligned.m64n8k16.f32.bf16.bf16 {%0,%1,%2,%3}, %4, %5, p, 1, 1, 0, 1;}"
                 : R4(d, 0) : "l"(da), "l"(db));
}
__device__ __forceinline__ void mma_ss(float (&d)[32], uint64_t da, uint64_t db, int accum) {
    asm volatile("{.reg .pred p; setp.ne.b32 p, %34, 0; wgmma.mma_async.sync.aligned.m64n64k16.f32.bf16.bf16 " D32 ", %32, %33, p, 1, 1, 0, 1;}"
                 : R32(d) : "l"(da), "l"(db), "r"(accum));
}
__device__ __forceinline__ void mma_ss(float (&d)[88], uint64_t da, uint64_t db, int accum) {
    asm volatile("{.reg .pred p; setp.ne.b32 p, %90, 0; wgmma.mma_async.sync.aligned.m64n176k16.f32.bf16.bf16 " "{%0,%1,%2,%3,%4,%5,%6,%7,%8,%9,%10,%11,%12,%13,%14,%15,%16,%17,%18,%19,%20,%21,%22,%23,%24,%25,%26,%27,%28,%29,%30,%31,%32,%33,%34,%35,%36,%37,%38,%39,%40,%41,%42,%43,%44,%45,%46,%47,%48,%49,%50,%51,%52,%53,%54,%55,%56,%57,%58,%59,%60,%61,%62,%63,%64,%65,%66,%67,%68,%69,%70,%71,%72,%73,%74,%75,%76,%77,%78,%79,%80,%81,%82,%83,%84,%85,%86,%87}"
                 ", %88, %89, p, 1, 1, 0, 1;}"
                 : R32(d), R8(d, 32), R8(d, 40), R8(d, 48), R8(d, 56), R8(d, 64), R8(d, 72), R8(d, 80) : "l"(da), "l"(db), "r"(accum));
}

constexpr float EXP_MAGIC = 256.0f + 127.0f + 64.0f - 1.58621f + 0.00390625f;
#define MUFU_M 0x1111u
#define ALU_M 0x0000u
constexpr uint32_t MUFU_MASK = MUFU_M;
constexpr uint32_t ALU_MASK = ALU_M;
template <bool ALU>
__device__ __forceinline__ uint32_t exp2_pair(float y0, float y1, uint32_t cexp, uint32_t neg1) {
    uint32_t w, m, e, r;
    asm("prmt.b32 %0, %1, %2, 0x6521;" : "=r"(w) : "r"(__float_as_uint(y0)), "r"(__float_as_uint(y1)));
    asm("lop3.b32 %0, %1, 0x007F007F, %2, 0xEA;" : "=r"(m) : "r"(w), "r"(cexp));
    if (ALU) e = w - m;
    else asm("mad.lo.u32 %0, %1, %2, %3;" : "=r"(e) : "r"(m), "r"(neg1), "r"(w));
    asm("fma.rn.bf16x2 %0, %1, %2, %3;" : "=r"(r) : "r"(w), "r"(m), "r"(e));
    return r;
}

struct Params {
    const __nv_bfloat16* wqp;
    __nv_bfloat16* out;
    uint32_t neg1, pad;
    const __nv_bfloat16* w1p;
    const __nv_bfloat16* w2p;
    CUtensorMap wq, wo, w1, w2;
    const __nv_bfloat16* wop;
};

__device__ __forceinline__ int tail_m() { return (blockIdx.x >> 5) * 4 + ((blockIdx.x >> 2) & 3); }
__device__ __forceinline__ int tail_j() { return ((blockIdx.x >> 4) & 1) * 4 + (blockIdx.x & 3); }
__device__ __forceinline__ void load_box(uint32_t sb, const CUtensorMap* tm, uint32_t dst, uint32_t bar, uint32_t bytes, int c0, int c1) {
    mbar_expect(sb + SM_MISC + bar * 8, bytes);
    tma2d(sb + dst, tm, c0, c1, sb + SM_MISC + bar * 8);
}
__device__ __forceinline__ void load_wq(uint32_t sb, const Params& P, int gi, int atom) {
    load_box(sb, &P.wq, (((atom ? WQ1_SLOTS : WQ0_SLOTS) >> (8 * gi)) & 31) * SLOT, MB_WQ + gi, 16384, (blockIdx.x & 3) * 128 + atom * 64, gi * 128);
}
__device__ __forceinline__ void load_wo(uint32_t sb, const Params& P, int kb) { load_box(sb, &P.wo, wo_slot(kb) * SLOT, MB_WO, SLOT, tail_j() * 64, kb * 64); }
__device__ __forceinline__ void refill_job(uint32_t sb, const Params& P, int gi, int job) {
    const bool w1 = job < 3;
    load_box(sb, w1 ? &P.w1 : &P.wo, (w1 ? 12 + gi + 4 * job : 2 * gi + job - 3) * SLOT, w1 ? MB_W1 + gi : MB_WO, SLOT,
             tail_j() * (w1 ? 176 : 64) + (w1 ? job * 64 : 0), (w1 ? gi : 2 * gi + job - 1) * 64);
}

__host__ __device__ constexpr int ring_entry(int n) { return n < 32 ? (n & 3) : (n - 32) % 6; }
__host__ __device__ constexpr uint32_t ring_slot(int e) { return e < 4 ? 24 + e : e; }

template <int KIND> __host__ __device__ constexpr uint64_t b_slots(int first) {
    uint64_t v = 0;
    for (int i = first; i < first + 12; i++) v |= (uint64_t)((KIND == 0 ? wo_slot(i) : KIND == 1 ? w1_slot(i, 0) : w1_slot(i / 3, i % 3)) & 31) << (5 * (i - first));
    return v;
}
__device__ __forceinline__ uint64_t desc64(uint32_t lo, uint32_t hi) { uint64_t d; asm("mov.b64 %0, {%1, %2};" : "=l"(d) : "r"(lo), "r"(hi)); return d; }
__device__ __forceinline__ uint32_t mbar_test(uint32_t bar) {
    uint32_t done;
    asm volatile("{.reg .pred p; mbarrier.test_wait.parity.shared::cta.b64 p, [%1], 0; selp.u32 %0, 1, 0, p;}" : "=r"(done) : "r"(bar) : "memory");
    return done;
}
template <int KIND, int NACC>
__device__ __forceinline__ bool gemm_ss(float (&acc)[NACC], uint32_t sb, int pr TS_ARG) {
    const uint32_t mb = sb + SM_MISC;
    constexpr int NBLK = KIND == 2 ? 22 : 8, N0 = 16 * KIND;
    uint32_t full = mb + (MB_FULL + N0 + pr * NBLK) * 8, empty = mb + MB_NULL * 8, rel = mb + MB_NULL * 8;
    const uint32_t lane = threadIdx.x & 31, probe = sb + ((threadIdx.x >> 5) & 3) * 512 + (lane >> 4) * 2048 + (lane & 15) * 32 + (lane >> 2) * 4;
    uint32_t m = 0;
    constexpr uint32_t R4S = 24 | 25 << 5 | 26 << 10 | 27 << 15;
    uint32_t ra = KIND == 2 ? (pr ? (4 | 5 << 5 | R4S << 10) : (R4S | 4 << 20 | 5 << 25)) : (KIND == 0 && pr) ? (6 | 7 << 5 | 8 << 10 | 9 << 15) : R4S;
    uint64_t tab = b_slots<KIND>(0);
    const uint32_t a0 = (sb >> 4) | (8 << 16);
    uint32_t b0 = (sb >> 4) | ((KIND == 1 ? 4 * SLOT / 16 : 1) << 16);
    mbar_wait(full);
#pragma unroll 1
    for (int i = 0; i < NBLK; i++) {
        const uint32_t sa = ra & 31, da = a0 + sa * 512, db = b0 + ((uint32_t)tab & 31) * 512;
        full += (i == NBLK - 1) ? 0 : 8;
        const uint32_t ready = mbar_test(full);
        const uint32_t m0 = lds32(probe + sa * SLOT), m1 = lds32(probe + sa * SLOT + 4096);
        wg_fence();
#pragma unroll
        for (int s = 0; s < 4; s++) mma_ss(acc, desc64(da + s * 128, 16), desc64(db + s * 128, 0x40000040), s ? 1 : i);
        wg_commit();
        m = max(m, max(m0, m1));
        const uint32_t prev = empty, prel = rel;
        empty = mb + ((KIND == 0 && sa < 24) ? MB_NULL : MB_EMPTY + (sa & 7)) * 8;
        rel = mb + (KIND == 1 ? MB_REL + i : i == 3 ? MB_REL + 9 : MB_NULL) * 8;
        ra = KIND == 2 ? (ra >> 5) | (sa << 25) : i == 3 ? R4S : ra >> 5;
        tab = (KIND == 2 && i == 11) ? b_slots<KIND>(12) : tab >> 5;
        if (KIND == 1 && i == 3) b0 -= (3 * SLOT / 16) << 16;
        wg_wait<1>();
        warp_done(prev);
        if (KIND != 2) warp_done(prel);
        if (!__all_sync(0xffffffffu, ready)) mbar_wait(full);
    }
    bool bad = __any_sync(0xffffffffu, m == SENT);
    wg_wait<0>();
    fence_regs(acc);
    warp_done(empty);
    if (KIND != 2) warp_done(mb + (MB_REL + 8 - KIND) * 8);
    return __builtin_expect(bad, 0);
}
__device__ __forceinline__ void ring_feed(uint32_t sb, int e TS_ARG) {
    const uint32_t mb = sb + SM_MISC;
    uint32_t dst = sb + ring_slot(e) * SLOT, empty = mb + (MB_EMPTY + e) * 8;
    const bool lead = (threadIdx.x & 31) == 0;
    const uint4* base = g_x + tail_m() * 4096 + e * 512;
    uint32_t par = 0;
    auto fetch = [&](int n, const uint4* src, int job) {
        const uint32_t full = mb + (MB_FULL + n) * 8;
        if (lead) mbar_expect(full, SLOT);
        mbar_wait(empty, par); par ^= 1;
        if (job) mbar_wait(mb + (MB_READY + job) * 8);
        if (lead) bulk_g2s(dst, src, SLOT, full);
        __syncwarp();
    };
    if (e < 4) {
        fetch(4 + e, base + 2048, 0);
        if (lead) mbar_expect(mb + (MB_FULL + 8 + e) * 8, SLOT);
        mbar_wait(mb + (MB_DONE + 4) * 8);
        mbar_wait(mb + (MB_READY + 1) * 8);
        if (lead) bulk_g2s(sb + (6 + e) * SLOT, base + 65536, SLOT, mb + (MB_FULL + 8 + e) * 8);
        fetch(12 + e, base + 65536 + 2048, 0);
#pragma unroll 1
        for (int h = 0; h < 2; h++) {
            fetch(16 + 8 * h + e, base + X_H1 + h * 65536, 2 + h);
            fetch(20 + 8 * h + e, base + X_H1 + h * 65536 + 2048, 0);
        }
    } else {
#pragma unroll 1
        for (int h = 0; h < 2; h++) {
            const uint4* sp = g_x + X_ST + (h * 16 + tail_m()) * 256 + (threadIdx.x & 31);
            mbar_wait(mb + (MB_READY + 2 + h) * 8);
            uint4 u[8]; uint32_t m; int spins = 0;
            do {
                m = 0;
#pragma unroll
                for (int k = 0; k < 8; k++) u[k] = ldg_relaxed(sp + k * 32);
#pragma unroll
                for (int k = 0; k < 8; k++) m = max(m, u[k].x);
            } while (__any_sync(0xffffffffu, m == SENT) && ++spins < SPIN_LIMIT);
            float st[4] = {0.f, 0.f, 0.f, 0.f};
#pragma unroll
            for (int k = 0; k < 8; k++) { st[0] += __uint_as_float(u[k].x); st[1] += __uint_as_float(u[k].y); st[2] += __uint_as_float(u[k].z); st[3] += __uint_as_float(u[k].w); }
#pragma unroll
            for (int k = 0; k < 2; k++) {
                const float nmean = st[2 * k] * (-1.0f / D);
                st[2 * k + 1] = 0.5f * rsqrtf(fmaxf(fmaf(-nmean, nmean, st[2 * k + 1] * (1.0f / D)), 0.f) + 1e-5f);
                st[2 * k] = nmean * st[2 * k + 1];
            }
            sts128(mb + MISC_STAT + h * 512 + (threadIdx.x & 31) * 16, __float_as_uint(st[0]), __float_as_uint(st[1]), __float_as_uint(st[2]), __float_as_uint(st[3]));
            warp_done(mb + (MB_STAT + h) * 8);
        }
        mbar_wait(mb + (MB_REL + 7) * 8);
        par = 1;
    }
    const uint4* src = g_x + X_H2 + tail_m() * 88 * 128 + e * 512;
#pragma unroll 1
    for (int n = e; n < 44; n += 6, src += 6 * 512) {
        const bool second = n >= 22 && n < 28;
        if (second) src += 16 * 88 * 128 - 22 * 512;
        fetch(32 + n, src, n < 6 ? 4 : second ? 5 : 0);
        if (e == 4) {
            par ^= 1; dst += SLOT; empty += 8;
            fetch(33 + n, src + 512, 0);
            dst -= SLOT; empty -= 8;
        }
    }
}
__device__ float4 g_redo[NMAIN * 2 * 22 * 128];
__device__ __noinline__ void gemm_slow_impl(float4* out, int ntile, const uint4* a, int nst, const __nv_bfloat16* W, int ldw, int kmax, int n0) {
    const int lane = threadIdx.x & 31;
    const unsigned short* w = reinterpret_cast<const unsigned short*>(W);
    for (int j = 0; j < ntile; j++) {
        const uint32_t* p = reinterpret_cast<const uint32_t*>(a) + ((threadIdx.x >> 5) & 3) * 128 + lane;
        const int n = n0 + 8 * j + (lane >> 2);
        float d[4] = {0.f, 0.f, 0.f, 0.f};
        for (int st = 0; st < nst; st++, p += 512) {
            const int k = st * 16 + 2 * (lane & 3);
            uint32_t v0, v1, v2, v3, b0 = 0, b1 = 0; int spins = 0;
            do { v0 = ldg32_relaxed(p); v1 = ldg32_relaxed(p + 64); v2 = ldg32_relaxed(p + 32); v3 = ldg32_relaxed(p + 96); }
            while (__any_sync(0xffffffffu, max(max(v0, v1), max(v2, v3)) == SENT) && ++spins < SPIN_LIMIT);
            if (k < kmax && n < ldw) {
                const unsigned short* q = w + (size_t)k * ldw + n;
                b0 = q[0] | ((uint32_t)q[ldw] << 16); b1 = q[8 * ldw] | ((uint32_t)q[9 * ldw] << 16);
            }
            asm volatile("mma.sync.aligned.m16n8k16.row.col.f32.bf16.bf16.f32 {%0,%1,%2,%3}, {%4,%5,%6,%7}, {%8,%9}, {%0,%1,%2,%3};"
                         : R4(d, 0) : "r"(v0), "r"(v1), "r"(v2), "r"(v3), "r"(b0), "r"(b1));
        }
        out[j * 128] = make_float4(d[0], d[1], d[2], d[3]);
    }
}
template <int NACC>
__device__ __forceinline__ void gemm_slow(float (&acc)[NACC], const uint4* a, int nst, const __nv_bfloat16* W, int ldw, int kmax, int n0) {
    float4* tmp = g_redo + (blockIdx.x * 2 + (threadIdx.x >> 8)) * 22 * 128 + (threadIdx.x & 127);
    gemm_slow_impl(tmp, NACC / 4, a, nst, W, ldw, kmax, n0);
#pragma unroll
    for (int i = 0; i < NACC / 4; i++) { const float4 v = tmp[i * 128]; acc[4 * i] = v.x; acc[4 * i + 1] = v.y; acc[4 * i + 2] = v.z; acc[4 * i + 3] = v.w; }
}
__device__ __forceinline__ void store_tile(uint32_t* p, uint32_t r0k0, uint32_t r8k0, uint32_t r0k8, uint32_t r8k8) {
    stg32(p, r0k0); stg32(p + 32, r0k8); stg32(p + 64, r8k0); stg32(p + 96, r8k8);
}

__device__ __forceinline__ float quad_sum(float v) { v += __shfl_xor_sync(0xffffffffu, v, 1); v += __shfl_xor_sync(0xffffffffu, v, 2); return v; }
__device__ __forceinline__ float reduce4(const float (&st)[4], int lane) {
    const bool u16 = lane & 16, u8 = lane & 8;
    const float a0 = (u16 ? st[2] : st[0]) + __shfl_xor_sync(0xffffffffu, u16 ? st[0] : st[2], 16);
    const float a1 = (u16 ? st[3] : st[1]) + __shfl_xor_sync(0xffffffffu, u16 ? st[1] : st[3], 16);
    float v = (u8 ? a1 : a0) + __shfl_xor_sync(0xffffffffu, u8 ? a0 : a1, 8);
    v += __shfl_xor_sync(0xffffffffu, v, 4); v += __shfl_xor_sync(0xffffffffu, v, 2); v += __shfl_xor_sync(0xffffffffu, v, 1);
    return v;
}
__device__ __forceinline__ float silu2(float h) { float t; asm("tanh.approx.f32 %0, %1;" : "=f"(t) : "f"(h)); return fmaf(h, t, h); }

template <bool SAFE>
__device__ __forceinline__ void attention(const Params& P, uint32_t sb, int warp TS_ARG) {
    const uint32_t mb = sb + SM_MISC;
    const int tid = threadIdx.x, lane = tid & 31, b = blockIdx.x;
    const int wg = warp >> 2, ww = warp & 3, job = 3 - wg + 4 * ww;
    const uint32_t cexp = 0x9F809F80u + (tid >> 12);
    const uint32_t neg1 = P.neg1;
    unsigned cnt = 0;
    if (SAFE && warp == 8) cnt = ldg32_relaxed(g_s.cnt[C_KV]);
#pragma unroll 1
    for (int pass = 0; pass < 2; pass++) {
    float o[12], s[32];
    const uint64_t dq = mkdesc(sb + SM_Q + (pass * 4 + wg) * 2048, 128, 256, 0);
    uint64_t dk = mkdesc(sb + SM_K, 128, 256, 0), dv = mkdesc(sb + SM_V, 128, 32768, 0);
    float m0 = -INFINITY, m1 = -INFINITY;
#pragma unroll
    for (int i = 0; i < 12; i++) o[i] = 0.f;
#pragma unroll
    for (int i = 0; i < 32; i++) s[i] = ((MUFU_MASK >> (i / 2)) & 1) ? 0.f : EXP_MAGIC;
    fence_regs(s); fence_regs(o);
    wg_fence();
    if (SAFE) mma_qk_f16(s, dq, dk + 31 * 128); else mma_qk_bf16(s, dq, dk + 31 * 128);
    wg_commit();
    wg_wait<0>(); fence_regs(s);
#pragma unroll 1
    for (int u = pass ? 3 : (wg == 2) ? 0 : 1; u < (pass ? 8 : 3); u++) {
        int n = 2 * ((((wg == 2) ? 0x22444C31u : 0x22444C40u) >> (4 * u)) & 15);
#pragma unroll 1
        do {
            uint32_t p[16];
            if (SAFE) {
#pragma unroll
                for (int j = 0; j < 16; j++) {
                    if ((MUFU_MASK >> j) & 1) p[j] = pack_bf16(ex2(s[2 * j]), ex2(s[2 * j + 1]));
                    else if ((ALU_MASK >> j) & 1) p[j] = exp2_pair<true>(s[2 * j], s[2 * j + 1], cexp, neg1);
                    else p[j] = exp2_pair<false>(s[2 * j], s[2 * j + 1], cexp, neg1);
                }
            } else {
                fence_regs(o);
                float x0 = m0, x1 = m1;
#pragma unroll
                for (int j = 0; j < 8; j++) { x0 = fmaxf(x0, fmaxf(s[4 * j], s[4 * j + 1])); x1 = fmaxf(x1, fmaxf(s[4 * j + 2], s[4 * j + 3])); }
                x0 = fmaxf(x0, __shfl_xor_sync(0xffffffffu, x0, 1)); x0 = fmaxf(x0, __shfl_xor_sync(0xffffffffu, x0, 2));
                x1 = fmaxf(x1, __shfl_xor_sync(0xffffffffu, x1, 1)); x1 = fmaxf(x1, __shfl_xor_sync(0xffffffffu, x1, 2));
                const float c0 = ex2(m0 - x0), c1 = ex2(m1 - x1);
                m0 = x0; m1 = x1;
#pragma unroll
                for (int j = 0; j < 3; j++) { o[4 * j] *= c0; o[4 * j + 1] *= c0; o[4 * j + 2] *= c1; o[4 * j + 3] *= c1; }
#pragma unroll
                for (int j = 0; j < 8; j++) {
                    p[2 * j] = pack_bf16(ex2(s[4 * j] - m0), ex2(s[4 * j + 1] - m0));
                    p[2 * j + 1] = pack_bf16(ex2(s[4 * j + 2] - m1), ex2(s[4 * j + 3] - m1));
                }
                fence_regs(o);
            }
            fence_regs(p);
            wg_fence();
            if (SAFE) mma_qk_f16(s, dq, dk); else mma_qk_bf16(s, dq, dk);
#pragma unroll
            for (int j = 0; j < 4; j++) mma_pv(o, p + 4 * j, dv + j * 16);
            wg_commit();
            dk += 128; dv += 64;
            wg_wait<0>(); fence_regs(s);
        } while (--n > 0);
        if (u == 2 || u == 7) {
            fence_regs(o);
            const float i0 = rcp(o[8]), i1 = rcp(o[10]);
            if (u == 7) mbar_wait(mb + MB_MID * 8);
            store_tile(reinterpret_cast<uint32_t*>(g_x + X_O + (((u == 7) * 16 + (b >> 3)) * 32 + (b & 3) * 8 + 2 * wg + (ww >> 1)) * 128 + (((b >> 2) & 1) * 2 + (ww & 1)) * 32) + lane,
                       pack_bf16(o[0] * i0, o[1] * i0), pack_bf16(o[2] * i1, o[3] * i1), pack_bf16(o[4] * i0, o[5] * i0), pack_bf16(o[6] * i1, o[7] * i1));
            if (u == 2) asm volatile("cp.async.bulk.wait_group 0;" ::: "memory");
            else count_hint(C_O + 16 + (b >> 3));
            warp_done(mb + (MB_DONE + (u == 7) * 4) * 8);
            TS(5 + (u == 7));
        } else if (u >= 3) {
            if (u < 6) warp_done(mb + (MB_DONE + u - 2) * 8);
            if (job < (u == 3 ? 1 : 5)) {
                mbar_wait(mb + (MB_DONE + u - 3) * 8);
                if (u == 3) count_release(C_MID);
                else if (lane == 0) refill_job(sb, P, u - 4, job);
            } else if (u == 6) {
                if (job < 9) {
                    mbar_wait(mb + MB_MID * 8);
                    if (lane == 0) {
                        mbar_expect(mb + (MB_FULL + job - 5) * 8, SLOT);
                        bulk_g2s(sb + (19 + job) * SLOT, g_x + X_O + tail_m() * 4096 + (job - 5) * 512, SLOT, mb + (MB_FULL + job - 5) * 8);
                    }
                }
            } else if (warp == 7) {
                if (u == 4) cnt = ldg32_relaxed(g_s.cnt[C_MID]);
                if (u == 5) {
                    const unsigned target = lds32(mb + MISC_EPOCH) * NCTA;
                    if (__any_sync(0xffffffffu, cnt != target)) count_wait(C_MID, target);
                    asm volatile("fence.acquire.gpu; fence.proxy.async.global;" ::: "memory");
                    warp_done(mb + MB_MID * 8);
                }
            }
        } else if (u == 1) {
            if (SAFE) mbar_wait(mb + MB_KV * 8);
            TS(17);
            if (lane == 0) {
                if (job < 9) {
                    asm volatile("cp.async.bulk.global.shared::cta.bulk_group [%0], [%1], %2;"
                                 :: "l"(g_x + X_ARM + b * X_SHARE + job * 512), "r"(sb + SM_SENT), "r"(job < 8 ? 8192 : (X_SHARE - 4096) * 16) : "memory");
                    asm volatile("cp.async.bulk.commit_group;" ::: "memory");
                } else if (job < 11) load_wo(sb, P, job - 9);
            }
        } else if (SAFE) {
            if (warp == 8) {
                const unsigned target = lds32(mb + MISC_EPOCH) * NMAIN;
                if (__any_sync(0xffffffffu, cnt != target)) count_wait(C_KV, target);
                if (lane == 0) {
                    asm volatile("fence.acquire.gpu; fence.proxy.async.global;" ::: "memory");
                    mbar_expect(mb + MB_KV * 8, 47104 + 2 * 24576);
                    bulk_g2s(sb + SM_K + 16384, g_s.kv + 1024, 47104, mb + MB_KV * 8);
                    bulk_g2s(sb + SM_V + 8192, g_s.kv + 4096 + 512, 24576, mb + MB_KV * 8);
                    bulk_g2s(sb + SM_V + 32768 + 8192, g_s.kv + 6144 + 512, 24576, mb + MB_KV * 8);
                }
            }
        }
        __syncwarp();
    }
    }
}

__device__ __forceinline__ int kv_slot(int idx) {
    const int t = (idx & 63) >> 1, c = 2 * (blockIdx.x >> 2) + (idx & 1), hg = blockIdx.x & 3;
    return hg < 2 ? ((t + 31) & 31) * 128 + (c >> 3) * 16 + (hg & 1) * 8 + (c & 7) : 4096 + (hg & 1) * 2048 + t * 64 + c;
}

#define GATE_AT 2
__device__ __noinline__ void helper_cta(const Params& P, uint8_t* smem) {
    const int tid = threadIdx.x, b = blockIdx.x, hi = b - NMAIN;
    const unsigned epoch = g_s.epoch[b] + 1;
    float* red = reinterpret_cast<float*>(smem);
    if (tid < 32) count_wait(C_KV, epoch * NMAIN);
    __syncthreads();
    if (tid == 480) {
        for (int i = 0; i < 8; i++) asm volatile("cp.async.bulk.prefetch.L2.global [%0], %1;" :: "l"((const char*)P.wop + hi * 131072 + i * 16384), "r"(16384) : "memory");
        for (int i = 0; i < 43; i++) asm volatile("cp.async.bulk.prefetch.L2.global [%0], %1;" :: "l"((const char*)P.w2p + hi * 352256 + i * 8192), "r"(8192) : "memory");
    }
    if (tid < 344) {
        const int cg = tid % 43, rp = tid / 43;
        const uint4* src = reinterpret_cast<const uint4*>(P.w1p + (size_t)rp * 64 * FF + (hi * 43 + cg) * 8);
        float s[8] = {0, 0, 0, 0, 0, 0, 0, 0};
#pragma unroll 8
        for (int r = 0; r < 64; r++) {
            uint4 v = __ldg(src + r * (FF / 8));
            s[0] += bf_lo(v.x); s[1] += bf_hi(v.x); s[2] += bf_lo(v.y); s[3] += bf_hi(v.y);
            s[4] += bf_lo(v.z); s[5] += bf_hi(v.z); s[6] += bf_lo(v.w); s[7] += bf_hi(v.w);
        }
        float* part = red + (rp * 43 + cg) * 8;
#pragma unroll
        for (int i = 0; i < 8; i++) part[i] = s[i];
    }
    __syncthreads();
    if (tid < 344) {
        float s = 0.f;
#pragma unroll
        for (int rp = 0; rp < 8; rp++) s += red[rp * 344 + tid];
        g_s.cs[hi * 344 + tid] = s;
    } else if (hi == 3 && tid < 344 + 64) g_s.cs[FF + tid - 344] = 0.f;
    __syncthreads();
    if (tid < 32) count_release(C_MID);
    if (tid == 0) g_s.epoch[b] = epoch;
}

__global__ void __launch_bounds__(512, 1) fused_kernel(const __nv_bfloat16* __restrict__ x, const __nv_bfloat16* __restrict__ wk, long long wv_off,
                                                         const __grid_constant__ Params P) {
    extern __shared__ __align__(1024) uint8_t smem[];
    const uint32_t sb = (uint32_t)__cvta_generic_to_shared(smem);
    const uint32_t mb = sb + SM_MISC;
    const int tid = threadIdx.x, lane = tid & 31, b = blockIdx.x;
    if (b >= NMAIN) { helper_cta(P, smem); return; }
    const int tg = b >> 2, hg = b & 3;
    const int warp = __shfl_sync(0xffffffffu, tid >> 5, 0);

    const uint32_t xst = sb + (((0x160A1204u >> (8 * (warp >> 2))) & 31) * SLOT + (warp & 3) * 4096), xbar = mb + MISC_XBAR + warp * 8;
    if (lane == 0) {
        mbar_init(xbar, 1);
        asm volatile("fence.mbarrier_init.release.cluster;" ::: "memory");
        mbar_expect(xbar, 4096);
        bulk_g2s(xst, x + (size_t)((warp & 7) * 4 + tg * 32 + (warp >> 3) * 1024) * D, 4096, xbar);
    }
    const uint4 wkv = ldg_relaxed(reinterpret_cast<const uint4*>(reinterpret_cast<const char*>(wk) + (hg < 2 ? 0 : wv_off)) + tid * 2 + (hg & 1));
    unsigned epoch = 0;
    if (warp == 12) epoch = ldg32_relaxed(g_s.epoch + b);
    const int wg = warp >> 2, ww = warp & 3, g = lane >> 2, t4 = lane & 3, t128 = tid & 127;
    if (lane == 0) {
        if (warp < 4) {
            mbar_init(mb + (MB_WQ + warp) * 8, 2);
            asm volatile("fence.mbarrier_init.release.cluster;" ::: "memory");
            if (warp < 2) { load_wq(sb, P, warp, 0); load_wq(sb, P, warp, 1); }
            else asm volatile("cp.async.bulk.prefetch.L2.global [%0], %1;" :: "l"((const char*)P.wqp + 262144 + (b * 2 + warp - 2) * 1024), "r"(1024) : "memory");
        } else {
            if (warp < 7) asm volatile("prefetch.tensormap [%0];" :: "l"(&P.wo + (warp - 4)) : "memory");
            const uint32_t first = warp < 8 ? (0x78100904u >> (8 * (warp - 4))) & 255 : warp < 11 ? 14 * warp - 93 : 14 * warp - 95;
            const uint32_t end = warp < 8 ? (0x83131009u >> (8 * (warp - 4))) & 255 : warp < 11 ? 59 : 120;
            const uint32_t cnt = warp < 8 ? (0x08030410u >> (8 * (warp - 4))) & 255 : warp < 11 ? 1 : 2;
#pragma unroll
            for (uint32_t i = 0; i < 14; i++) if (first + i < end) mbar_init(mb + (first + i) * 8, cnt);
            if (warp == 7) sts128(mb + MISC_NRM, 0, 0, 0, 0);
        }
    }
    __syncwarp();
    TS(16);
    sts128(sb + SM_WKV + tid * 16, wkv.x, wkv.y, wkv.z, wkv.w);
    uint4 xv[4][2];
    mbar_wait(xbar);
#pragma unroll
    for (int i = 0; i < 8; i++) xv[i >> 1][i & 1] = lds128(xst + i * 512 + lane * 16);
    float dlt;
    {
        float st[4];
#pragma unroll
        for (int i = 0; i < 4; i++) {
            const uint32_t s = add_bf16x2(add_bf16x2(add_bf16x2(xv[i][0].x, xv[i][0].y), add_bf16x2(xv[i][0].z, xv[i][0].w)),
                                          add_bf16x2(add_bf16x2(xv[i][1].x, xv[i][1].y), add_bf16x2(xv[i][1].z, xv[i][1].w)));
            st[i] = bf_lo(s) + bf_hi(s);
        }
        TS(13);
        const float tot = reduce4(st, lane) * (-1.0f / D);
        const uint32_t nmr = pack_bf16(tot, tot);
        dlt = bf_lo(nmr) - tot;
        const uint32_t xa[2] = {sb + (((uint32_t)XN_SLOTS >> (lane & 24)) & 31) * SLOT + warp * 512, sb + (((uint32_t)(XN_SLOTS >> 32) >> (lane & 24)) & 31) * SLOT + warp * 512};
#pragma unroll
        for (int i = 0; i < 4; i++) {
            const uint32_t nm = __shfl_sync(0xffffffffu, nmr, i * 8);
            const uint32_t off = i * 128 + (((lane & 7) ^ ((warp & 1) * 4 + i)) << 4);
#pragma unroll
            for (int c = 0; c < 2; c++) {
                xv[i][c].x = add_bf16x2(xv[i][c].x, nm); xv[i][c].y = add_bf16x2(xv[i][c].y, nm);
                xv[i][c].z = add_bf16x2(xv[i][c].z, nm); xv[i][c].w = add_bf16x2(xv[i][c].w, nm);
                sts128(xa[c] + off, xv[i][c].x, xv[i][c].y, xv[i][c].z, xv[i][c].w);
            }
        }
    }
    fence_async_smem();
    TS(0);
    auto variances = [&]() {
        float st[4];
#pragma unroll
        for (int i = 0; i < 4; i++) {
            float v = 0.f;
#pragma unroll
            for (int c = 0; c < 2; c++) {
                const uint32_t a = fma_bf16x2(xv[i][c].x, xv[i][c].x, mul_bf16x2(xv[i][c].y, xv[i][c].y));
                const uint32_t d = fma_bf16x2(xv[i][c].z, xv[i][c].z, mul_bf16x2(xv[i][c].w, xv[i][c].w));
                v += (bf_lo(a) + bf_hi(a)) + (bf_lo(d) + bf_hi(d));
            }
            st[i] = v;
        }
        const float vs = reduce4(st, lane), dl = dlt;
        if ((lane & 7) == 0) sts32(sb + SM_RSTD + (warp * 4 + (lane >> 3)) * 4, __float_as_uint(rsqrtf(fmaxf(vs * (1.0f / D) - dl * dl, 0.f) + 1e-5f)));
    };
    if (wg == 2) {
        float kv[4] = {0.f, 0.f, 0.f, 0.f};
        fence_regs(kv);
        const uint64_t da = mkdesc(sb, 16, 1024, 1), db = mkdesc(sb + SM_WKV, 128, 16, 0);
        bar_sync(7, 512);
        wg_fence();
#pragma unroll
        for (int s = 0; s < 32; s++) mma_ss8(kv, da + xn_slot(s >> 2) * 512 + (s & 3) * 2, db + s * 16);
        wg_commit();
        variances();
        wg_wait<0>(); fence_regs(kv);
        float2* kt = reinterpret_cast<float2*>(smem + SM_KTMP);
        kt[(ww * 16 + g) * 4 + t4] = make_float2(kv[0], kv[1]); kt[(ww * 16 + g + 8) * 4 + t4] = make_float2(kv[2], kv[3]);
        TS(24);
    } else {
        bar_arrive(7, 512);
        variances();
        epoch++;
        if (tid == 12 * 32) { sts32(mb + MISC_EPOCH, epoch); g_s.epoch[b] = epoch; }
    }
    constexpr float QSCALE = 0.25f * 1.4426950408889634f;
    float qa[64];
    const uint32_t qbase = sb + SM_Q + (ww >> 1) * 8192 + (ww & 1) * 512 + lane * 16;
    if (wg == 0) {
#pragma unroll
        for (int i = 0; i < 64; i++) qa[i] = 0.f;
        float rs0 = 0.f, rs1 = 0.f;
#pragma unroll 1
        for (int live = 0; live < 2; live++) {
        fence_regs(qa);
        if (live) {
        bar_sync(0, 512);
        rs0 = __uint_as_float(lds32(sb + SM_RSTD + (ww * 16 + g) * 4)) * QSCALE; rs1 = __uint_as_float(lds32(sb + SM_RSTD + (ww * 16 + g + 8) * 4)) * QSCALE;
        mbar_wait(mb + MB_WQ * 8);
        bar_sync(2, 320);
#pragma unroll 1
        for (int i = 0; i < 4; i++) {
            const uint32_t s0 = (WQ0_SLOTS >> (8 * i)) & 31, s1 = (WQ1_SLOTS >> (8 * i)) & 31, xs = (uint32_t)(XN_SLOTS >> (16 * i));
            const uint64_t db = mkdesc(sb + s0 * SLOT, (s1 - s0) * SLOT, 1024, 1);
            const uint64_t da0 = mkdesc(sb + (xs & 31) * SLOT, 16, 1024, 1), da1 = mkdesc(sb + ((xs >> 8) & 31) * SLOT, 16, 1024, 1);
            mbar_wait(mb + (MB_WQ + i) * 8);
            wg_fence();
#pragma unroll
            for (int s = 0; s < 8; s++) mma_ss128(qa, (s < 4 ? da0 : da1) + (s & 3) * 2, db + s * 128);
            wg_commit();
            wg_wait<1>();
            if (i == 1) bar_arrive(6, 160);
        }
        wg_wait<0>();
        fence_regs(qa);
        bar_arrive(5, 256);
        TS(1);
        }
        uint32_t nm = 0;
#pragma unroll
        for (int h = 0; h < 8; h++) {
#pragma unroll
            for (int i = 0; i < 8; i++) qa[8 * h + i] *= (i & 2) ? rs1 : rs0;
            stsm4(qbase + h * 1024, pack_f16(qa[8 * h], qa[8 * h + 1]), pack_f16(qa[8 * h + 4], qa[8 * h + 5]), pack_f16(qa[8 * h + 2], qa[8 * h + 3]), pack_f16(qa[8 * h + 6], qa[8 * h + 7]));
            const float n0 = qa[8 * h] * qa[8 * h] + qa[8 * h + 1] * qa[8 * h + 1] + qa[8 * h + 4] * qa[8 * h + 4] + qa[8 * h + 5] * qa[8 * h + 5];
            const float n1 = qa[8 * h + 2] * qa[8 * h + 2] + qa[8 * h + 3] * qa[8 * h + 3] + qa[8 * h + 6] * qa[8 * h + 6] + qa[8 * h + 7] * qa[8 * h + 7];
            nm = max(nm, max(__float_as_uint(n0), __float_as_uint(n1)));
        }
        nm = __reduce_max_sync(0xffffffffu, __float_as_uint(quad_sum(__uint_as_float(nm))));
        if (lane == 0 && live) asm volatile("red.shared.max.u32 [%0], %1;" :: "r"(mb + MISC_NRM), "r"(nm) : "memory");
        }
    } else if (wg == 2) {
        bar_sync(0, 512);
        if (lane == 0) load_wq(sb, P, 2 + (ww >> 1), ww & 1);
        __syncwarp();
        bar_sync(2, 320);
#pragma unroll
        for (int i = 0; i < 4; i++) sts128(sb + SM_SENT + (i * 128 + t128) * 16, SENT, SENT, SENT, SENT);
#pragma unroll
        for (int i = 0; i < 16; i++) {
            if (i == 4) bar_sync(5, 256);
            sts128(sb + SM_V + 65536 + (i * 128 + t128) * 16, 0x3F803F80u, 0x3F803F80u, 0x3F803F80u, 0x3F803F80u);
        }
    } else if (wg == 1) {
        if (ww >= 2) bar_sync(0, 512);
        else {
            const bool diff = ww == 0 && hg < 2;
#pragma unroll 1
            for (int live = 0; live < 2; live++) {
            if (live) bar_sync(0, 512);
            uint32_t nm = 1;
            uint4 w[2];
#pragma unroll
            for (int i = 0; i < 2; i++) {
                const int r = (lane & 1) * 32 + i * 16 + (lane >> 1);
                const uint32_t ra = sb + SM_KTMP + r * 32;
                float4 c0 = lds128f(ra), c1 = lds128f(ra + 16);
                const float4 p0 = lds128f(ra - 32), p1 = lds128f(ra - 16);
                const float rs = __uint_as_float(lds32(sb + SM_RSTD + r * 4));
                float rp = -__uint_as_float(lds32(sb + SM_RSTD + r * 4 - 4));
                c0.x *= rs; c0.y *= rs; c0.z *= rs; c0.w *= rs; c1.x *= rs; c1.y *= rs; c1.z *= rs; c1.w *= rs;
                nm = max(nm, __float_as_uint(c0.x * c0.x + c0.y * c0.y + c0.z * c0.z + c0.w * c0.w + c1.x * c1.x + c1.y * c1.y + c1.z * c1.z + c1.w * c1.w));
                uint32_t w0, w1, w2, w3;
                if (diff) {
                    if (r & 31) {
                        c0.x = fmaf(p0.x, rp, c0.x); c0.y = fmaf(p0.y, rp, c0.y); c0.z = fmaf(p0.z, rp, c0.z); c0.w = fmaf(p0.w, rp, c0.w);
                        c1.x = fmaf(p1.x, rp, c1.x); c1.y = fmaf(p1.y, rp, c1.y); c1.z = fmaf(p1.z, rp, c1.z); c1.w = fmaf(p1.w, rp, c1.w);
                    }
                    w0 = pack_f16(c0.x, c0.y); w1 = pack_f16(c0.z, c0.w); w2 = pack_f16(c1.x, c1.y); w3 = pack_f16(c1.z, c1.w);
                } else {
                    w0 = pack_bf16(c0.x, c0.y); w1 = pack_bf16(c0.z, c0.w); w2 = pack_bf16(c1.x, c1.y); w3 = pack_bf16(c1.z, c1.w);
                }
                w[i] = make_uint4(nonzero(w0), nonzero(w1), nonzero(w2), nonzero(w3));
            }
            nm = __reduce_max_sync(0xffffffffu, nm);
#pragma unroll
            for (int i = 0; i < 2; i++) stg128_if(live && (ww == 0 || hg < 2), (ww ? g_s.kplain : g_s.kv) + kv_slot(i * 32 + lane), w[i].x, w[i].y, w[i].z, w[i].w);
            stg128_if(live && ww == 0 && lane < 2, g_s.nrm + b * 2 + lane, nm, nm, nm, nm);
            asm volatile("{.reg .pred p; setp.ne.u32 p, %1, 0; @p red.relaxed.gpu.global.add.u32 [%0], 1;}" :: "l"(g_s.cnt[C_KVH]), "r"((int)(live && t128 == 0)) : "memory");
            }
            if (ww == 0) {
                TS(1);
                bar_arrive(2, 320);
            } else {
                bar_sync(2, 320);
                count_release(C_KV);
            }
        }
    } else {
        bar_sync(0, 512);
        if (ww == 0) count_wait(C_KVH, epoch * NMAIN);
        TS(1);
        bar_sync(3, 128);
        uint32_t nm = ldg32_relaxed(g_s.nrm + t128 * 2);
        if (ww == 0) bar_sync(6, 160);
        int spins = 0;
        bool bad;
        do {
            if (t128 == 0) {
                asm volatile("fence.proxy.async.global;" ::: "memory");
                mbar_expect(mb + MB_KV0 * 8, 34816);
                bulk_g2s(sb + SM_K + 31 * 2048, g_s.kv + 31 * 128, 2048, mb + MB_KV0 * 8);
                bulk_g2s(sb + SM_K, g_s.kv, 16384, mb + MB_KV0 * 8);
                bulk_g2s(sb + SM_V, g_s.kv + 4096, 8192, mb + MB_KV0 * 8);
                bulk_g2s(sb + SM_V + 32768, g_s.kv + 6144, 8192, mb + MB_KV0 * 8);
            }
            if (spins) nm = ldg32_relaxed(g_s.nrm + t128 * 2);
            __syncwarp();
            mbar_wait(mb + MB_KV0 * 8, spins & 1);
            const uint32_t probe = sb + (ww < 2 ? SM_K + ww * 8192 : SM_V + (ww - 2) * 32768) + lane * 32 + (lane >> 2) * 4;
            uint32_t mn = min(nm, lds32(sb + SM_K + 31 * 2048 + (ww & 1) * 1024 + lane * 32 + (lane >> 2) * 4));
#pragma unroll
            for (int k = 0; k < 8; k++) mn = min(mn, lds32(probe + k * 1024));
            uint32_t r;
            asm volatile("{.reg .pred p, q; setp.eq.u32 p, %1, 0; barrier.red.or.pred.aligned q, 3, 128, p; selp.u32 %0, 1, 0, q;}" : "=r"(r) : "r"(mn) : "memory");
            bad = __any_sync(0xffffffffu, r);
        } while (bad && ++spins < SPIN_LIMIT);
        TS(2);
        nm = max(nm, __shfl_xor_sync(0xffffffffu, nm, 4)); nm = max(nm, __shfl_xor_sync(0xffffffffu, nm, 8)); nm = max(nm, __shfl_xor_sync(0xffffffffu, nm, 16));
        if (lane < 4) asm volatile("red.shared.max.u32 [%0], %1;" :: "r"(mb + MISC_NRM + 4 + min(lane, 2) * 4), "r"(nm) : "memory");
    }
    fence_async_smem();
    TS(3);
    __syncthreads();
    const float4 nr = lds128f(mb + MISC_NRM);
    const bool safe = __all_sync(0xffffffffu, (nr.x * (nr.y + nr.z) <= 3500.0f) && (nr.x <= 65536.0f) && (nr.y + nr.z <= 65536.0f) && (nr.w <= 1e24f));
    TS(4);

    if (__builtin_expect(safe, 1)) {
        attention<true>(P, sb, warp TS_PASS);
    } else {
        if (wg == 0) {
#pragma unroll
            for (int h = 0; h < 8; h++)
                stsm4(qbase + h * 1024, pack_bf16(qa[8 * h], qa[8 * h + 1]), pack_bf16(qa[8 * h + 4], qa[8 * h + 5]), pack_bf16(qa[8 * h + 2], qa[8 * h + 3]), pack_bf16(qa[8 * h + 6], qa[8 * h + 7]));
            fence_async_smem();
        } else if (warp == 15) {
            count_wait(C_KV, lds32(mb + MISC_EPOCH) * NMAIN);
            if (lane == 0) {
                asm volatile("fence.proxy.async;" ::: "memory");
                mbar_expect(mb + MB_KV * 8, 131072);
                bulk_g2s(sb + SM_K, g_s.kplain, 65536, mb + MB_KV * 8);
                bulk_g2s(sb + SM_V, g_s.kv + 4096, 65536, mb + MB_KV * 8);
            }
            __syncwarp();
        }
        __syncthreads();
        mbar_wait(mb + MB_KV * 8);
        attention<false>(P, sb, warp TS_PASS);
    }

    const int j = tail_j();
    if (wg == 1 || wg == 2) {
        if (warp == 8) {
            epoch = lds32(mb + MISC_EPOCH);
#pragma unroll 1
            for (int job = 1; job < 6; job++) {
                count_wait(C_O + 32 * (job >> 1) + (job & 1) * 16 + tail_m(), epoch * (job == 1 ? 128 : 32));
                asm volatile("fence.proxy.async.global;" ::: "memory");
                warp_done(mb + (MB_READY + job) * 8);
                TS(18 + job);
            }
        } else if (warp == 9) {
#pragma unroll
            for (int i = 0; i < 2; i++) {
                if (lane < 22) {
                    const uint4 v = ldg_relaxed(reinterpret_cast<const uint4*>(g_s.cs + j * 176) + i * 22 + lane);
                    sts128(mb + MISC_CS + (i * 22 + lane) * 16, v.x, v.y, v.z, v.w);
                }
                stg128(g_s.kv + kv_slot(i * 32 + lane), 0u, 0u, 0u, 0u);
            }
            warp_done(mb + MB_CS * 8);
            if (lane < 2) stg128(g_s.nrm + b * 2 + lane, 0u, 0u, 0u, 0u);
#pragma unroll 1
            for (int i = 0; i < 16; i++) {
                mbar_wait(mb + (MB_W1 + i) * 8);
                const int n = i < 8 ? 16 + i + 8 * (lane & 1) : 32 + 3 * (i - 8) + (lane >> 1) + 22 * (lane & 1);
                if (lane < (i < 8 || i == 15 ? 2 : 6)) mbar_arrive(mb + (MB_FULL + n) * 8);
                __syncwarp();
            }
        } else {
            if (warp == 10) {
#pragma unroll 1
                for (int i = 3; i < 16; i++) {
                    const bool w1 = i < 8;
                    const int kb = i & 7;
                    const uint32_t bar = mb + (MB_W1 + i) * 8, dst = sb + w1_slot(kb, 0) * SLOT, step = kb < 4 ? 4 * SLOT : SLOT;
                    const CUtensorMap* tm = w1 ? &P.w1 : &P.w2;
                    const int c0 = w1 ? j * 176 : j * 64, c1 = w1 ? kb * 64 : kb * 192, d0 = w1 ? 64 : 0, d1 = 64 - d0;
                    if (lane == 0) mbar_expect(bar, i == 15 ? SLOT : 3 * SLOT);
                    mbar_wait(mb + (w1 ? (i == 3 ? MB_DONE + 4 : i < 6 ? MB_REL + 9 : MB_REL + 8) : MB_REL + kb) * 8);
                    if (i == 8 + GATE_AT) mbar_wait(mb + MB_EPI * 8);
                    if (lane == 0) {
                        tma2d(dst, tm, c0, c1, bar);
                        if (i < 15) { tma2d(dst + step, tm, c0 + d0, c1 + d1, bar); tma2d(dst + 2 * step, tm, c0 + 2 * d0, c1 + 2 * d1, bar); }
                    }
                    __syncwarp();
                }
            } else {
                ring_feed(sb, wg == 1 ? ww : 4 TS_PASS);
            }
        }
    } else {
        const int pr = (wg == 0), mt = 16 * pr + tail_m();
        uint32_t* const hp = reinterpret_cast<uint32_t*>(g_x + X_H1 + (mt * 32 + j * 4) * 128 + ww * 32) + lane;
        {
            uint32_t hk[16];
            const uint32_t* xp = reinterpret_cast<const uint32_t*>(x + (size_t)(mt * 64 + ww * 16 + g) * D + j * 64 + t4 * 2);
#pragma unroll
            for (int k = 0; k < 8; k++) { hk[2 * k] = __ldg(xp + k * 4); hk[2 * k + 1] = __ldg(xp + k * 4 + 8 * (D / 2)); }
            mbar_wait(mb + MB_WO * 8);
            float acc[32];
            if (gemm_ss<0>(acc, sb, pr TS_PASS)) gemm_slow(acc, g_x + X_O + mt * 32 * 128, 32, P.wop, D, D, j * 64);
            TS(7);
#pragma unroll
            for (int i = 0; i < 16; i++) hk[i] = pack_bf16(acc[2 * i] + bf_lo(hk[i]), acc[2 * i + 1] + bf_hi(hk[i]));
#pragma unroll
            for (int k = 0; k < 4; k++) store_tile(hp + k * 512, hk[4 * k], hk[4 * k + 1], hk[4 * k + 2], hk[4 * k + 3]);
            count_hint(C_H1 + mt);
            TS(8);
            float st[4] = {0.f, 0.f, 0.f, 0.f};
#pragma unroll
            for (int i = 0; i < 16; i++) {
                const float lo = bf_lo(hk[i]), hi = bf_hi(hk[i]);
                st[2 * (i & 1)] += lo + hi;
                st[2 * (i & 1) + 1] = fmaf(lo, lo, fmaf(hi, hi, st[2 * (i & 1) + 1]));
            }
#pragma unroll
            for (int o = 1; o < 4; o <<= 1)
#pragma unroll
                for (int i = 0; i < 4; i++) st[i] += __shfl_xor_sync(0xffffffffu, st[i], o);
            if (t4 == 0) stg128(g_x + X_ST + (mt * 8 + j) * 32 + ww * 8 + g, __float_as_uint(st[0]), __float_as_uint(st[1]), __float_as_uint(st[2]), __float_as_uint(st[3]));
        }
        {
            float acc[88];
            mbar_wait(mb + MB_CS * 8);
            if (gemm_ss<1>(acc, sb, pr TS_PASS)) gemm_slow(acc, g_x + X_H1 + mt * 32 * 128, 32, P.w1p, FF, D, j * 176);
            TS(9);
            mbar_wait(mb + (MB_STAT + pr) * 8);
            const float4 rs = lds128f(mb + MISC_STAT + pr * 512 + (ww * 8 + g) * 16);
            const float nmean[2] = {rs.x, rs.z}, hrstd[2] = {rs.y, rs.w};
            uint32_t* hb = reinterpret_cast<uint32_t*>(g_x + X_H2 + (mt * 88 + j * 11) * 128 + ww * 32) + lane;
#pragma unroll
            for (int i = 0; i < 22; i++) {
                float2 cs;
                asm volatile("ld.shared.v2.f32 {%0,%1}, [%2];" : "=f"(cs.x), "=f"(cs.y) : "r"(mb + MISC_CS + i * 32 + t4 * 8));
                const float* z = acc + 4 * i;
                uint32_t* p = hb + (i >> 1) * 512 + (i & 1) * 32;
                stg32(p, pack_bf16(silu2(fmaf(hrstd[0], z[0], nmean[0] * cs.x)), silu2(fmaf(hrstd[0], z[1], nmean[0] * cs.y))));
                stg32(p + 64, pack_bf16(silu2(fmaf(hrstd[1], z[2], nmean[1] * cs.x)), silu2(fmaf(hrstd[1], z[3], nmean[1] * cs.y))));
            }
            count_hint(C_H2 + mt);
            if (!pr) warp_done(mb + MB_EPI * 8);
            TS(10);
        }
        {
            uint32_t hk[16];
#pragma unroll
            for (int i = 0; i < 16; i++) hk[i] = ldg32_relaxed(hp + (i >> 2) * 512 + ((i & 1) * 2 + ((i >> 1) & 1)) * 32);
            float acc[32];
            if (gemm_ss<2>(acc, sb, pr TS_PASS)) gemm_slow(acc, g_x + X_H2 + mt * 88 * 128, 88, P.w2p, D, FF, j * 64);
            TS(11);
#pragma unroll
            for (int i = 0; i < 16; i++) hk[i] = pack_bf16(acc[2 * i] + bf_lo(hk[i]), acc[2 * i + 1] + bf_hi(hk[i]));
#pragma unroll
            for (int h = 0; h < 4; h++) {
                const uint32_t* v = hk + (h >> 1) * 8 + (h & 1);
                uint32_t v0 = v[0], v1 = v[2], v2 = v[4], v3 = v[6];
                const bool o1 = t4 & 1, o2 = t4 & 2;
                uint32_t a = __shfl_xor_sync(0xffffffffu, o1 ? v0 : v1, 1), c = __shfl_xor_sync(0xffffffffu, o1 ? v2 : v3, 1);
                if (o1) { v0 = a; v2 = c; } else { v1 = a; v3 = c; }
                a = __shfl_xor_sync(0xffffffffu, o2 ? v0 : v2, 2); c = __shfl_xor_sync(0xffffffffu, o2 ? v1 : v3, 2);
                if (o2) { v0 = a; v1 = c; } else { v2 = a; v3 = c; }
                *reinterpret_cast<uint4*>(P.out + (size_t)(mt * 64 + ww * 16 + g + 8 * (h & 1)) * D + j * 64 + (h >> 1) * 32 + t4 * 8) = make_uint4(v0, v1, v2, v3);
            }
        }
    }
    TS(12);
}

typedef CUresult (*EncodeFn)(CUtensorMap*, CUtensorMapDataType, cuuint32_t, void*, const cuuint64_t*, const cuuint64_t*, const cuuint32_t*,
                             const cuuint32_t*, CUtensorMapInterleave, CUtensorMapSwizzle, CUtensorMapL2promotion, CUtensorMapFloatOOBfill);

void encode2d(EncodeFn fn, CUtensorMap* tm, const void* ptr, int rows, int cols, int box_rows, int box_cols, CUtensorMapSwizzle sw) {
    cuuint64_t dims[2] = {(cuuint64_t)cols, (cuuint64_t)rows};
    cuuint64_t strides[1] = {(cuuint64_t)cols * 2};
    cuuint32_t box[2] = {(cuuint32_t)box_cols, (cuuint32_t)box_rows};
    cuuint32_t es[2] = {1, 1};
    fn(tm, CU_TENSOR_MAP_DATA_TYPE_BFLOAT16, 2, const_cast<void*>(ptr), dims, strides, box, es, CU_TENSOR_MAP_INTERLEAVE_NONE, sw,
       CU_TENSOR_MAP_L2_PROMOTION_L2_128B, CU_TENSOR_MAP_FLOAT_OOB_FILL_NONE);
}

}

extern "C" void kernel_launch(void* const* d_in, const int* in_sizes, int n_in, void* d_out, int out_size) {
    (void)in_sizes; (void)n_in; (void)out_size;
    void* fnp = nullptr;
    cudaDriverEntryPointQueryResult qr;
    cudaGetDriverEntryPoint("cuTensorMapEncodeTiled", &fnp, cudaEnableDefault, &qr);
    EncodeFn fn = (EncodeFn)fnp;
    Params P;
    encode2d(fn, &P.wq, d_in[1], D, D, 128, 64, CU_TENSOR_MAP_SWIZZLE_128B);
    encode2d(fn, &P.wo, d_in[4], D, D, 64, 64, CU_TENSOR_MAP_SWIZZLE_128B);
    encode2d(fn, &P.w1, d_in[6], D, FF, 64, 64, CU_TENSOR_MAP_SWIZZLE_128B);
    encode2d(fn, &P.w2, d_in[7], FF, D, 64, 64, CU_TENSOR_MAP_SWIZZLE_128B);
    P.w1p = (const __nv_bfloat16*)d_in[6];
    P.w2p = (const __nv_bfloat16*)d_in[7];
    P.wop = (const __nv_bfloat16*)d_in[4];
    P.wqp = (const __nv_bfloat16*)d_in[1];
    P.out = (__nv_bfloat16*)d_out;
    P.neg1 = 0xFFFFFFFFu; P.pad = 0;
    cudaFuncSetAttribute(fused_kernel, cudaFuncAttributeMaxDynamicSharedMemorySize, SMEM_BYTES);
    fused_kernel<<<NCTA, 512, SMEM_BYTES>>>((const __nv_bfloat16*)d_in[0], (const __nv_bfloat16*)d_in[2], (long long)((const char*)d_in[3] - (const char*)d_in[2]), P);
}
```

```cpp
#include <cuda_runtime.h>
#include <cuda_bf16.h>
#include <cuda.h>
#include <stdint.h>

namespace {

constexpr int D = 512, FF = 1376;
constexpr int NMAIN = 128, NHELP = 4, NCTA = NMAIN + NHELP;
constexpr uint32_t SENT = 0xFFFFFFFFu;
constexpr int SPIN_LIMIT = 1 << 22;

constexpr uint32_t KB = 1024, SLOT = 8192;
constexpr uint64_t XN_SLOTS = 7 | 16 << 8 | 6 << 16 | 17 << 24 | 21ull << 32 | 27ull << 40 | 24ull << 48 | 25ull << 56;
constexpr uint32_t WQ0_SLOTS = 0 | 2 << 8 | 4 << 16 | 10 << 24, WQ1_SLOTS = 12 | 14 << 8 | 18 << 16 | 22 << 24;
__host__ __device__ constexpr uint32_t xn_slot(int kb) { return (XN_SLOTS >> (8 * kb)) & 31; }
constexpr uint32_t SM_WKV = 208 * KB;
constexpr uint32_t SM_K = 0;
constexpr uint32_t SM_Q = 64 * KB;
constexpr uint32_t SM_V = 96 * KB;
constexpr uint32_t SM_MISC = 224 * KB;
constexpr uint32_t SMEM_BYTES = 227 * KB;
constexpr uint32_t SM_KTMP = 164 * KB;
constexpr uint32_t SM_RSTD = 226 * KB;
constexpr uint32_t SM_SENT = 208 * KB;
constexpr uint32_t MB_WQ = 0;
constexpr uint32_t MB_DONE = 4;
constexpr uint32_t MB_EMPTY = 9;
constexpr uint32_t MB_EPI = 15;
constexpr uint32_t MB_W1 = 16;
constexpr uint32_t MB_W2 = 24;
constexpr uint32_t MB_CS = 32;
constexpr uint32_t MB_KV = 33;
constexpr uint32_t MB_KV0 = 34;
constexpr uint32_t MB_MID = 35;
constexpr uint32_t MB_READY = 35;
constexpr uint32_t MB_STAT = 41;
constexpr uint32_t MB_FULL = 43;
constexpr uint32_t MB_NULL = 119;
constexpr uint32_t MB_WO = 120;
constexpr uint32_t MB_REL = 121;
constexpr uint32_t MISC_STAT = 2048;
constexpr uint32_t MISC_XBAR = 2304;
constexpr uint32_t MISC_NRM = 1056;
constexpr uint32_t MISC_EPOCH = 1072;
constexpr uint32_t MISC_TS = 1088;
constexpr uint32_t MISC_CS = 1344;

__host__ __device__ constexpr uint32_t wo_slot(int kb) { return kb < 2 ? 10 + kb : kb - 2; }
__host__ __device__ constexpr uint32_t w1_slot(int kb, int a) { return kb < 4 ? 12 + kb + 4 * a : (kb < 6 ? 3 * kb - 6 : 3 * kb - 18) + a; }

struct alignas(128) Small {
    unsigned epoch[160];
    unsigned cnt[100][32];
    float cs[1440];
    uint4 nrm[NMAIN * 2];
    uint4 kv[8192];
    uint4 kplain[4096];
};
__device__ Small g_s;
constexpr int C_KVH = 0, C_KV = 1, C_MID = 2, C_O = 3, C_H1 = 35, C_H2 = 67;
constexpr int X_O = 0, X_H1 = 32 * 32 * 128, X_H2 = 2 * X_H1, X_ST = X_H2 + 32 * 88 * 128, X_END = X_ST + 32 * 8 * 32;
constexpr int X_ARM = 16 * 32 * 128, X_SHARE = (X_END - X_ARM) / NMAIN;
__device__ uint4 g_x[X_END];
#define TS(i) do {} while (0)
#define TSF(k)

#define TS_ARG
#define TS_PASS

__device__ __forceinline__ void mbar_init(uint32_t bar, int cnt) { asm volatile("mbarrier.init.shared::cta.b64 [%0], %1;" :: "r"(bar), "r"(cnt) : "memory"); }
__device__ __forceinline__ void mbar_expect(uint32_t bar, uint32_t bytes) { asm volatile("mbarrier.arrive.expect_tx.shared::cta.b64 _, [%0], %1;" :: "r"(bar), "r"(bytes) : "memory"); }
__device__ __forceinline__ void mbar_arrive(uint32_t bar) { asm volatile("mbarrier.arrive.shared::cta.b64 _, [%0];" :: "r"(bar) : "memory"); }
__device__ __forceinline__ bool mbar_try(uint32_t bar, uint32_t parity) {
    uint32_t done;
    asm volatile("{.reg .pred p; mbarrier.try_wait.parity.shared::cta.b64 p, [%1], %2; selp.u32 %0, 1, 0, p;}" : "=r"(done) : "r"(bar), "r"(parity) : "memory");
    return __all_sync(0xffffffffu, done);
}
__device__ __forceinline__ void mbar_wait(uint32_t bar, uint32_t parity = 0) {
    if (__builtin_expect(!mbar_try(bar, parity), 0)) {
        int spins = 0;
        while (!mbar_try(bar, parity) && ++spins < (SPIN_LIMIT >> 6)) {}
    }
}
__device__ __forceinline__ void tma2d(uint32_t dst, const CUtensorMap* tm, int c0, int c1, uint32_t bar) {
    asm volatile("cp.async.bulk.tensor.2d.shared::cluster.global.mbarrier::complete_tx::bytes [%0], [%1, {%3, %4}], [%2];"
                 :: "r"(dst), "l"(tm), "r"(bar), "r"(c0), "r"(c1) : "memory");
}
__device__ __forceinline__ void bulk_g2s(uint32_t dst, const void* src, uint32_t bytes, uint32_t bar) {
    asm volatile("cp.async.bulk.shared::cluster.global.mbarrier::complete_tx::bytes [%0], [%1], %2, [%3];" :: "r"(dst), "l"(src), "r"(bytes), "r"(bar) : "memory");
}
__device__ __forceinline__ void fence_async_smem() { asm volatile("fence.proxy.async.shared::cta;" ::: "memory"); }
__device__ __forceinline__ void bar_sync(int id, int n) { asm volatile("bar.sync %0, %1;" :: "r"(id), "r"(n) : "memory"); }
__device__ __forceinline__ void bar_arrive(int id, int n) { asm volatile("bar.arrive %0, %1;" :: "r"(id), "r"(n) : "memory"); }
__device__ __forceinline__ void wg_fence() { asm volatile("wgmma.fence.sync.aligned;" ::: "memory"); }
__device__ __forceinline__ void wg_commit() { asm volatile("wgmma.commit_group.sync.aligned;" ::: "memory"); }
template <int N> __device__ __forceinline__ void wg_wait() { asm volatile("wgmma.wait_group.sync.aligned %0;" :: "n"(N) : "memory"); }
template <int N> __device__ __forceinline__ void fence_regs(float (&d)[N]) {
#pragma unroll
    for (int i = 0; i < N; i++) asm volatile("" : "+f"(d[i]) :: "memory");
}
template <int N> __device__ __forceinline__ void fence_regs(uint32_t (&d)[N]) {
#pragma unroll
    for (int i = 0; i < N; i++) asm volatile("" : "+r"(d[i]) :: "memory");
}
__device__ __forceinline__ uint64_t mkdesc(uint32_t addr, uint32_t lbo, uint32_t sbo, uint32_t swz) {
    return (uint64_t)(((addr & 0x3FFFF) >> 4) | ((lbo >> 4) << 16)) | ((uint64_t)((sbo >> 4) | (swz << 30)) << 32);
}
__device__ __forceinline__ float ex2(float x) { float y; asm("ex2.approx.ftz.f32 %0, %1;" : "=f"(y) : "f"(x)); return y; }
__device__ __forceinline__ float rcp(float x) { float y; asm("rcp.approx.ftz.f32 %0, %1;" : "=f"(y) : "f"(x)); return y; }
__device__ __forceinline__ uint32_t pack_bf16(float lo, float hi) { uint32_t r; asm("cvt.rn.bf16x2.f32 %0, %1, %2;" : "=r"(r) : "f"(hi), "f"(lo)); return r; }
__device__ __forceinline__ uint32_t pack_f16(float lo, float hi) { uint32_t r; asm("cvt.rn.f16x2.f32 %0, %1, %2;" : "=r"(r) : "f"(hi), "f"(lo)); return r; }
__device__ __forceinline__ float bf_lo(uint32_t v) { return __uint_as_float(v << 16); }
__device__ __forceinline__ float bf_hi(uint32_t v) { return __uint_as_float(v & 0xFFFF0000u); }
__device__ __forceinline__ uint4 ldg_relaxed(const uint4* p) {
    uint4 v; asm volatile("ld.relaxed.gpu.global.v4.u32 {%0,%1,%2,%3}, [%4];" : "=r"(v.x), "=r"(v.y), "=r"(v.z), "=r"(v.w) : "l"(p) : "memory"); return v;
}
__device__ __forceinline__ void stg128(void* p, uint32_t a, uint32_t b, uint32_t c, uint32_t d) {
    asm volatile("st.relaxed.gpu.global.v4.u32 [%0], {%1,%2,%3,%4};" :: "l"(p), "r"(a), "r"(b), "r"(c), "r"(d) : "memory");
}
__device__ __forceinline__ void stg128_if(bool c, void* p, uint32_t a, uint32_t b, uint32_t d, uint32_t e) {
    asm volatile("{.reg .pred p; setp.ne.u32 p, %5, 0; @p st.relaxed.gpu.global.v4.u32 [%0], {%1,%2,%3,%4};}" :: "l"(p), "r"(a), "r"(b), "r"(d), "r"(e), "r"((int)c) : "memory");
}
__device__ __forceinline__ void stg64(void* p, uint32_t a, uint32_t b) {
    asm volatile("st.relaxed.gpu.global.v2.u32 [%0], {%1,%2};" :: "l"(p), "r"(a), "r"(b) : "memory");
}
__device__ __forceinline__ void sts128(uint32_t a, uint32_t x, uint32_t y, uint32_t z, uint32_t w) {
    asm volatile("st.shared.v4.u32 [%0], {%1,%2,%3,%4};" :: "r"(a), "r"(x), "r"(y), "r"(z), "r"(w) : "memory");
}
__device__ __forceinline__ void sts32(uint32_t a, uint32_t x) { asm volatile("st.shared.u32 [%0], %1;" :: "r"(a), "r"(x) : "memory"); }
__device__ __forceinline__ float4 lds128f(uint32_t a) {
    float4 v; asm volatile("ld.shared.v4.f32 {%0,%1,%2,%3}, [%4];" : "=f"(v.x), "=f"(v.y), "=f"(v.z), "=f"(v.w) : "r"(a) : "memory"); return v;
}
__device__ __forceinline__ uint4 lds128(uint32_t a) {
    uint4 v; asm volatile("ld.shared.v4.u32 {%0,%1,%2,%3}, [%4];" : "=r"(v.x), "=r"(v.y), "=r"(v.z), "=r"(v.w) : "r"(a) : "memory"); return v;
}
__device__ __forceinline__ uint32_t lds32(uint32_t a) { uint32_t v; asm volatile("ld.shared.u32 %0, [%1];" : "=r"(v) : "r"(a) : "memory"); return v; }
__device__ __forceinline__ uint32_t nonzero(uint32_t w) { return w == 0u ? 0x8000u : w; }
__device__ __forceinline__ void stg32(void* p, uint32_t a) { asm volatile("st.global.u32 [%0], %1;" :: "l"(p), "r"(a) : "memory"); }
__device__ __forceinline__ uint32_t ldg32_relaxed(const void* p) { uint32_t v; asm volatile("ld.relaxed.gpu.global.u32 %0, [%1];" : "=r"(v) : "l"(p) : "memory"); return v; }
__device__ __forceinline__ void count_hint(int id) {
    if ((threadIdx.x & 31) == 0) asm volatile("red.relaxed.gpu.global.add.u32 [%0], 1;" :: "l"(g_s.cnt[id]) : "memory");
}
__device__ __forceinline__ void count_release(int id) {
    __syncwarp();
    if ((threadIdx.x & 31) == 0) asm volatile("red.release.gpu.global.add.u32 [%0], 1;" :: "l"(g_s.cnt[id]) : "memory");
    __syncwarp();
}
__device__ __forceinline__ void count_wait(int id, unsigned target) {
    uint32_t v; int spins = 0;
    do v = ldg32_relaxed(g_s.cnt[id]); while (__any_sync(0xffffffffu, v != target) && ++spins < SPIN_LIMIT);
    asm volatile("fence.acquire.gpu;" ::: "memory");
}
__device__ __forceinline__ void warp_done(uint32_t bar) {
    __syncwarp();
    asm volatile("{.reg .pred p; setp.eq.u32 p, %1, 0; @p mbarrier.arrive.shared::cta.b64 _, [%0];}" :: "r"(bar), "r"(threadIdx.x & 31) : "memory");
}
__device__ __forceinline__ uint32_t mul_bf16x2(uint32_t a, uint32_t b) { uint32_t r; asm("mul.rn.bf16x2 %0, %1, %2;" : "=r"(r) : "r"(a), "r"(b)); return r; }
__device__ __forceinline__ uint32_t fma_bf16x2(uint32_t a, uint32_t b, uint32_t c) { uint32_t r; asm("fma.rn.bf16x2 %0, %1, %2, %3;" : "=r"(r) : "r"(a), "r"(b), "r"(c)); return r; }
__device__ __forceinline__ uint32_t add_bf16x2(uint32_t a, uint32_t b) { uint32_t r; asm("add.rn.bf16x2 %0, %1, %2;" : "=r"(r) : "r"(a), "r"(b)); return r; }

#define R4(d, o) "+f"(d[o + 0]), "+f"(d[o + 1]), "+f"(d[o + 2]), "+f"(d[o + 3])
#define R8(d, o) R4(d, o), R4(d, o + 4)
#define R32(d) R8(d, 0), R8(d, 8), R8(d, 16), R8(d, 24)
#define D32 "{%0,%1,%2,%3,%4,%5,%6,%7,%8,%9,%10,%11,%12,%13,%14,%15,%16,%17,%18,%19,%20,%21,%22,%23,%24,%25,%26,%27,%28,%29,%30,%31}"
#define D64 "{%0,%1,%2,%3,%4,%5,%6,%7,%8,%9,%10,%11,%12,%13,%14,%15,%16,%17,%18,%19,%20,%21,%22,%23,%24,%25,%26,%27,%28,%29,%30,%31,%32,%33,%34,%35,%36,%37,%38,%39,%40,%41,%42,%43,%44,%45,%46,%47,%48,%49,%50,%51,%52,%53,%54,%55,%56,%57,%58,%59,%60,%61,%62,%63}"

__device__ __forceinline__ void mma_qk_f16(float (&d)[32], uint64_t da, uint64_t db) {
    asm volatile("{.reg .pred p; setp.eq.b32 p, 0, 0; wgmma.mma_async.sync.aligned.m64n64k16.f32.f16.f16 " D32 ", %32, %33, p, 1, 1, 0, 0;}"
                 : R32(d) : "l"(da), "l"(db));
}
__device__ __forceinline__ void mma_qk_bf16(float (&d)[32], uint64_t da, uint64_t db) {
    asm volatile("{.reg .pred p; setp.ne.b32 p, 0, 0; wgmma.mma_async.sync.aligned.m64n64k16.f32.bf16.bf16 " D32 ", %32, %33, p, 1, 1, 0, 0;}"
                 : R32(d) : "l"(da), "l"(db));
}
__device__ __forceinline__ void mma_pv(float (&d)[12], const uint32_t* a, uint64_t db) {
    asm volatile("{.reg .pred p; setp.eq.b32 p, 0, 0; wgmma.mma_async.sync.aligned.m64n24k16.f32.bf16.bf16 {%0,%1,%2,%3,%4,%5,%6,%7,%8,%9,%10,%11}, {%12,%13,%14,%15}, %16, p, 1, 1, 1;}"
                 : R8(d, 0), R4(d, 8) : "r"(a[0]), "r"(a[1]), "r"(a[2]), "r"(a[3]), "l"(db));
}
__device__ __forceinline__ void mma_ss128(float (&d)[64], uint64_t da, uint64_t db) {
    asm volatile("{.reg .pred p; setp.eq.b32 p, 0, 0; wgmma.mma_async.sync.aligned.m64n128k16.f32.bf16.bf16 " D64 ", %64, %65, p, 1, 1, 0, 1;}"
                 : R32(d), R8(d, 32), R8(d, 40), R8(d, 48), R8(d, 56) : "l"(da), "l"(db));
}
__device__ __forceinline__ void stsm4(uint32_t addr, uint32_t a, uint32_t b, uint32_t c, uint32_t d) {
    asm volatile("stmatrix.sync.aligned.m8n8.x4.shared.b16 [%0], {%1,%2,%3,%4};" :: "r"(addr), "r"(a), "r"(b), "r"(c), "r"(d) : "memory");
}
__device__ __forceinline__ void mma_ss8(float (&d)[4], uint64_t da, uint64_t db, int accum) {
    asm volatile("{.reg .pred p; setp.ne.b32 p, %6, 0; wgmma.mma_async.sync.aligned.m64n8k16.f32.bf16.bf16 {%0,%1,%2,%3}, %4, %5, p, 1, 1, 0, 1;}"
                 : R4(d, 0) : "l"(da), "l"(db), "r"(accum));
}
__device__ __forceinline__ void mma_ss(float (&d)[32], uint64_t da, uint64_t db, int accum) {
    asm volatile("{.reg .pred p; setp.ne.b32 p, %34, 0; wgmma.mma_async.sync.aligned.m64n64k16.f32.bf16.bf16 " D32 ", %32, %33, p, 1, 1, 0, 1;}"
                 : R32(d) : "l"(da), "l"(db), "r"(accum));
}
__device__ __forceinline__ void mma_ss(float (&d)[88], uint64_t da, uint64_t db, int accum) {
    asm volatile("{.reg .pred p; setp.ne.b32 p, %90, 0; wgmma.mma_async.sync.aligned.m64n176k16.f32.bf16.bf16 " "{%0,%1,%2,%3,%4,%5,%6,%7,%8,%9,%10,%11,%12,%13,%14,%15,%16,%17,%18,%19,%20,%21,%22,%23,%24,%25,%26,%27,%28,%29,%30,%31,%32,%33,%34,%35,%36,%37,%38,%39,%40,%41,%42,%43,%44,%45,%46,%47,%48,%49,%50,%51,%52,%53,%54,%55,%56,%57,%58,%59,%60,%61,%62,%63,%64,%65,%66,%67,%68,%69,%70,%71,%72,%73,%74,%75,%76,%77,%78,%79,%80,%81,%82,%83,%84,%85,%86,%87}"
                 ", %88, %89, p, 1, 1, 0, 1;}"
                 : R32(d), R8(d, 32), R8(d, 40), R8(d, 48), R8(d, 56), R8(d, 64), R8(d, 72), R8(d, 80) : "l"(da), "l"(db), "r"(accum));
}

constexpr float EXP_MAGIC = 256.0f + 127.0f + 64.0f - 1.58621f + 0.00390625f;
#define MUFU_M 0x1111u
#define ALU_M 0x0000u
constexpr uint32_t MUFU_MASK = MUFU_M;
constexpr uint32_t ALU_MASK = ALU_M;
template <bool ALU>
__device__ __forceinline__ uint32_t exp2_pair(float y0, float y1, uint32_t cexp, uint32_t neg1) {
    uint32_t w, m, e, r;
    asm("prmt.b32 %0, %1, %2, 0x6521;" : "=r"(w) : "r"(__float_as_uint(y0)), "r"(__float_as_uint(y1)));
    asm("lop3.b32 %0, %1, 0x007F007F, %2, 0xEA;" : "=r"(m) : "r"(w), "r"(cexp));
    if (ALU) e = w - m;
    else asm("mad.lo.u32 %0, %1, %2, %3;" : "=r"(e) : "r"(m), "r"(neg1), "r"(w));
    asm("fma.rn.bf16x2 %0, %1, %2, %3;" : "=r"(r) : "r"(w), "r"(m), "r"(e));
    return r;
}

struct Params {
    const __nv_bfloat16* wqp;
    __nv_bfloat16* out;
    uint32_t neg1, pad;
    const __nv_bfloat16* w1p;
    const __nv_bfloat16* w2p;
    CUtensorMap wq, wo, w1, w2;
    const __nv_bfloat16* wop;
};

__device__ __forceinline__ int tail_m() { return (blockIdx.x >> 5) * 4 + ((blockIdx.x >> 2) & 3); }
__device__ __forceinline__ int tail_j() { return ((blockIdx.x >> 4) & 1) * 4 + (blockIdx.x & 3); }
__device__ __forceinline__ void load_box(uint32_t sb, const CUtensorMap* tm, uint32_t dst, uint32_t bar, uint32_t bytes, int c0, int c1) {
    mbar_expect(sb + SM_MISC + bar * 8, bytes);
    tma2d(sb + dst, tm, c0, c1, sb + SM_MISC + bar * 8);
}
__device__ __forceinline__ void load_wq(uint32_t sb, const Params& P, int gi, int atom) {
    load_box(sb, &P.wq, (((atom ? WQ1_SLOTS : WQ0_SLOTS) >> (8 * gi)) & 31) * SLOT, MB_WQ + gi, 16384, (blockIdx.x & 3) * 128 + atom * 64, gi * 128);
}
__device__ __forceinline__ void load_wo(uint32_t sb, const Params& P, int kb) { load_box(sb, &P.wo, wo_slot(kb) * SLOT, MB_WO, SLOT, tail_j() * 64, kb * 64); }
__device__ __forceinline__ void refill_job(uint32_t sb, const Params& P, int gi, int job) {
    const bool w1 = job < 3;
    load_box(sb, w1 ? &P.w1 : &P.wo, (w1 ? 12 + gi + 4 * job : 2 * gi + job - 3) * SLOT, w1 ? MB_W1 + gi : MB_WO, SLOT,
             tail_j() * (w1 ? 176 : 64) + (w1 ? job * 64 : 0), (w1 ? gi : 2 * gi + job - 1) * 64);
}

__host__ __device__ constexpr int ring_entry(int n) { return n < 32 ? (n & 3) : (n - 32) % 6; }
__host__ __device__ constexpr uint32_t ring_slot(int e) { return e < 4 ? 24 + e : e; }

template <int KIND> __host__ __device__ constexpr uint64_t b_slots(int first) {
    uint64_t v = 0;
    for (int i = first; i < first + 12; i++) v |= (uint64_t)((KIND == 0 ? wo_slot(i) : KIND == 1 ? w1_slot(i, 0) : w1_slot(i / 3, i % 3)) & 31) << (5 * (i - first));
    return v;
}
__device__ __forceinline__ uint64_t desc64(uint32_t lo, uint32_t hi) { uint64_t d; asm("mov.b64 %0, {%1, %2};" : "=l"(d) : "r"(lo), "r"(hi)); return d; }
__device__ __forceinline__ uint32_t mbar_test(uint32_t bar) {
    uint32_t done;
    asm volatile("{.reg .pred p; mbarrier.test_wait.parity.shared::cta.b64 p, [%1], 0; selp.u32 %0, 1, 0, p;}" : "=r"(done) : "r"(bar) : "memory");
    return done;
}
template <int KIND, int NACC>
__device__ __forceinline__ bool gemm_ss(float (&acc)[NACC], uint32_t sb, int pr TS_ARG) {
    const uint32_t mb = sb + SM_MISC;
    constexpr int NBLK = KIND == 2 ? 22 : 8, N0 = 16 * KIND;
    uint32_t full = mb + (MB_FULL + N0 + pr * NBLK) * 8, empty = mb + MB_NULL * 8, rel = mb + MB_NULL * 8;
    const uint32_t lane = threadIdx.x & 31, probe = sb + ((threadIdx.x >> 5) & 3) * 512 + (lane >> 4) * 2048 + (lane & 15) * 32 + (lane >> 2) * 4;
    uint32_t m = 0;
    constexpr uint32_t R4S = 24 | 25 << 5 | 26 << 10 | 27 << 15;
    uint32_t ra = KIND == 2 ? (pr ? (4 | 5 << 5 | R4S << 10) : (R4S | 4 << 20 | 5 << 25)) : (KIND == 0 && pr) ? (6 | 7 << 5 | 8 << 10 | 9 << 15) : R4S;
    uint64_t tab = b_slots<KIND>(0);
    const uint32_t a0 = (sb >> 4) | (8 << 16);
    uint32_t b0 = (sb >> 4) | ((KIND == 1 ? 4 * SLOT / 16 : 1) << 16);
    mbar_wait(full);
#pragma unroll 1
    for (int i = 0; i < NBLK; i++) {
        const uint32_t sa = ra & 31, da = a0 + sa * 512, db = b0 + ((uint32_t)tab & 31) * 512;
        full += (i == NBLK - 1) ? 0 : 8;
        const uint32_t ready = mbar_test(full);
        const uint32_t m0 = lds32(probe + sa * SLOT), m1 = lds32(probe + sa * SLOT + 4096);
        wg_fence();
#pragma unroll
        for (int s = 0; s < 4; s++) mma_ss(acc, desc64(da + s * 128, 16), desc64(db + s * 128, 0x40000040), s ? 1 : i);
        wg_commit();
        m = max(m, max(m0, m1));
        const uint32_t prev = empty, prel = rel;
        empty = mb + ((KIND == 0 && sa < 24) ? MB_NULL : MB_EMPTY + (sa & 7)) * 8;
        rel = mb + (KIND == 1 ? MB_REL + i : i == 3 ? MB_REL + 9 : MB_NULL) * 8;
        ra = KIND == 2 ? (ra >> 5) | (sa << 25) : i == 3 ? R4S : ra >> 5;
        tab = (KIND == 2 && i == 11) ? b_slots<KIND>(12) : tab >> 5;
        if (KIND == 1 && i == 3) b0 -= (3 * SLOT / 16) << 16;
        wg_wait<1>();
        warp_done(prev);
        if (KIND != 2) warp_done(prel);
        if (!__all_sync(0xffffffffu, ready)) mbar_wait(full);
    }
    bool bad = __any_sync(0xffffffffu, m == SENT);
    wg_wait<0>();
    fence_regs(acc);
    warp_done(empty);
    if (KIND != 2) warp_done(mb + (MB_REL + 8 - KIND) * 8);
    return __builtin_expect(bad, 0);
}
__device__ __forceinline__ void ring_feed(uint32_t sb, int e TS_ARG) {
    const uint32_t mb = sb + SM_MISC;
    uint32_t dst = sb + ring_slot(e) * SLOT, empty = mb + (MB_EMPTY + e) * 8;
    const bool lead = (threadIdx.x & 31) == 0;
    const uint4* base = g_x + tail_m() * 4096 + e * 512;
    uint32_t par = 0;
    auto fetch = [&](int n, const uint4* src, int job) {
        const uint32_t full = mb + (MB_FULL + n) * 8;
        if (lead) mbar_expect(full, SLOT);
        mbar_wait(empty, par); par ^= 1;
        if (job) mbar_wait(mb + (MB_READY + job) * 8);
        if (lead) bulk_g2s(dst, src, SLOT, full);
        __syncwarp();
    };
    if (e < 4) {
        fetch(4 + e, base + 2048, 0);
        if (lead) mbar_expect(mb + (MB_FULL + 8 + e) * 8, SLOT);
        mbar_wait(mb + (MB_DONE + 4) * 8);
        mbar_wait(mb + (MB_READY + 1) * 8);
        if (lead) bulk_g2s(sb + (6 + e) * SLOT, base + 65536, SLOT, mb + (MB_FULL + 8 + e) * 8);
        fetch(12 + e, base + 65536 + 2048, 0);
#pragma unroll 1
        for (int h = 0; h < 2; h++) {
            fetch(16 + 8 * h + e, base + X_H1 + h * 65536, 2 + h);
            fetch(20 + 8 * h + e, base + X_H1 + h * 65536 + 2048, 0);
        }
    } else {
#pragma unroll 1
        for (int h = 0; h < 2; h++) {
            const uint4* sp = g_x + X_ST + (h * 16 + tail_m()) * 256 + (threadIdx.x & 31);
            mbar_wait(mb + (MB_READY + 2 + h) * 8);
            uint4 u[8]; uint32_t m; int spins = 0;
            do {
                m = 0;
#pragma unroll
                for (int k = 0; k < 8; k++) u[k] = ldg_relaxed(sp + k * 32);
#pragma unroll
                for (int k = 0; k < 8; k++) m = max(m, u[k].x);
            } while (__any_sync(0xffffffffu, m == SENT) && ++spins < SPIN_LIMIT);
            float st[4] = {0.f, 0.f, 0.f, 0.f};
#pragma unroll
            for (int k = 0; k < 8; k++) { st[0] += __uint_as_float(u[k].x); st[1] += __uint_as_float(u[k].y); st[2] += __uint_as_float(u[k].z); st[3] += __uint_as_float(u[k].w); }
#pragma unroll
            for (int k = 0; k < 2; k++) {
                const float nmean = st[2 * k] * (-1.0f / D);
                st[2 * k + 1] = 0.5f * rsqrtf(fmaxf(fmaf(-nmean, nmean, st[2 * k + 1] * (1.0f / D)), 0.f) + 1e-5f);
                st[2 * k] = nmean * st[2 * k + 1];
            }
            sts128(mb + MISC_STAT + h * 512 + (threadIdx.x & 31) * 16, __float_as_uint(st[0]), __float_as_uint(st[1]), __float_as_uint(st[2]), __float_as_uint(st[3]));
            warp_done(mb + (MB_STAT + h) * 8);
        }
        mbar_wait(mb + (MB_REL + 7) * 8);
        par = 1;
    }
    const uint4* src = g_x + X_H2 + tail_m() * 88 * 128 + e * 512;
#pragma unroll 1
    for (int n = e; n < 44; n += 6, src += 6 * 512) {
        const bool second = n >= 22 && n < 28;
        if (second) src += 16 * 88 * 128 - 22 * 512;
        fetch(32 + n, src, n < 6 ? 4 : second ? 5 : 0);
        if (e == 4) {
            par ^= 1; dst += SLOT; empty += 8;
            fetch(33 + n, src + 512, 0);
            dst -= SLOT; empty -= 8;
        }
    }
}
__device__ float4 g_redo[NMAIN * 2 * 22 * 128];
__device__ __noinline__ void gemm_slow_impl(float4* out, int ntile, const uint4* a, int nst, const __nv_bfloat16* W, int ldw, int kmax, int n0) {
    const int lane = threadIdx.x & 31;
    const unsigned short* w = reinterpret_cast<const unsigned short*>(W);
    for (int j = 0; j < ntile; j++) {
        const uint32_t* p = reinterpret_cast<const uint32_t*>(a) + ((threadIdx.x >> 5) & 3) * 128 + lane;
        const int n = n0 + 8 * j + (lane >> 2);
        float d[4] = {0.f, 0.f, 0.f, 0.f};
        for (int st = 0; st < nst; st++, p += 512) {
            const int k = st * 16 + 2 * (lane & 3);
            uint32_t v0, v1, v2, v3, b0 = 0, b1 = 0; int spins = 0;
            do { v0 = ldg32_relaxed(p); v1 = ldg32_relaxed(p + 64); v2 = ldg32_relaxed(p + 32); v3 = ldg32_relaxed(p + 96); }
            while (__any_sync(0xffffffffu, max(max(v0, v1), max(v2, v3)) == SENT) && ++spins < SPIN_LIMIT);
            if (k < kmax && n < ldw) {
                const unsigned short* q = w + (size_t)k * ldw + n;
                b0 = q[0] | ((uint32_t)q[ldw] << 16); b1 = q[8 * ldw] | ((uint32_t)q[9 * ldw] << 16);
            }
            asm volatile("mma.sync.aligned.m16n8k16.row.col.f32.bf16.bf16.f32 {%0,%1,%2,%3}, {%4,%5,%6,%7}, {%8,%9}, {%0,%1,%2,%3};"
                         : R4(d, 0) : "r"(v0), "r"(v1), "r"(v2), "r"(v3), "r"(b0), "r"(b1));
        }
        out[j * 128] = make_float4(d[0], d[1], d[2], d[3]);
    }
}
template <int NACC>
__device__ __forceinline__ void gemm_slow(float (&acc)[NACC], const uint4* a, int nst, const __nv_bfloat16* W, int ldw, int kmax, int n0) {
    float4* tmp = g_redo + (blockIdx.x * 2 + (threadIdx.x >> 8)) * 22 * 128 + (threadIdx.x & 127);
    gemm_slow_impl(tmp, NACC / 4, a, nst, W, ldw, kmax, n0);
#pragma unroll
    for (int i = 0; i < NACC / 4; i++) { const float4 v = tmp[i * 128]; acc[4 * i] = v.x; acc[4 * i + 1] = v.y; acc[4 * i + 2] = v.z; acc[4 * i + 3] = v.w; }
}
__device__ __forceinline__ void store_tile(uint32_t* p, uint32_t r0k0, uint32_t r8k0, uint32_t r0k8, uint32_t r8k8) {
    stg32(p, r0k0); stg32(p + 32, r0k8); stg32(p + 64, r8k0); stg32(p + 96, r8k8);
}

__device__ __forceinline__ float quad_sum(float v) { v += __shfl_xor_sync(0xffffffffu, v, 1); v += __shfl_xor_sync(0xffffffffu, v, 2); return v; }
__device__ __forceinline__ float reduce4(const float (&st)[4], int lane) {
    const bool u16 = lane & 16, u8 = lane & 8;
    const float a0 = (u16 ? st[2] : st[0]) + __shfl_xor_sync(0xffffffffu, u16 ? st[0] : st[2], 16);
    const float a1 = (u16 ? st[3] : st[1]) + __shfl_xor_sync(0xffffffffu, u16 ? st[1] : st[3], 16);
    float v = (u8 ? a1 : a0) + __shfl_xor_sync(0xffffffffu, u8 ? a0 : a1, 8);
    v += __shfl_xor_sync(0xffffffffu, v, 4); v += __shfl_xor_sync(0xffffffffu, v, 2); v += __shfl_xor_sync(0xffffffffu, v, 1);
    return v;
}
__device__ __forceinline__ float silu2(float h) { float t; asm("tanh.approx.f32 %0, %1;" : "=f"(t) : "f"(h)); return fmaf(h, t, h); }

template <bool SAFE>
__device__ __forceinline__ void attention(const Params& P, uint32_t sb, int warp TS_ARG) {
    const uint32_t mb = sb + SM_MISC;
    const int tid = threadIdx.x, lane = tid & 31, b = blockIdx.x;
    const int wg = warp >> 2, ww = warp & 3, job = 3 - wg + 4 * ww;
    const uint32_t cexp = 0x9F809F80u + (tid >> 12);
    const uint32_t neg1 = P.neg1;
    unsigned cnt = 0;
    if (SAFE && warp == 8) cnt = ldg32_relaxed(g_s.cnt[C_KV]);
#pragma unroll 1
    for (int pass = 0; pass < 2; pass++) {
    float o[12], s[32];
    const uint64_t dq = mkdesc(sb + SM_Q + (pass * 4 + wg) * 2048, 128, 256, 0);
    uint64_t dk = mkdesc(sb + SM_K, 128, 256, 0), dv = mkdesc(sb + SM_V, 128, 32768, 0);
    float m0 = -INFINITY, m1 = -INFINITY;
#pragma unroll
    for (int i = 0; i < 12; i++) o[i] = 0.f;
#pragma unroll
    for (int i = 0; i < 32; i++) s[i] = ((MUFU_MASK >> (i / 2)) & 1) ? 0.f : EXP_MAGIC;
    fence_regs(s); fence_regs(o);
    wg_fence();
    if (SAFE) mma_qk_f16(s, dq, dk + 31 * 128); else mma_qk_bf16(s, dq, dk + 31 * 128);
    wg_commit();
    wg_wait<0>(); fence_regs(s);
#pragma unroll 1
    for (int u = pass ? 3 : (wg == 2) ? 0 : 1; u < (pass ? 8 : 3); u++) {
        int n = 2 * ((((wg == 2) ? 0x22444C31u : 0x22444C40u) >> (4 * u)) & 15);
#pragma unroll 1
        do {
            uint32_t p[16];
            if (SAFE) {
#pragma unroll
                for (int j = 0; j < 16; j++) {
                    if ((MUFU_MASK >> j) & 1) p[j] = pack_bf16(ex2(s[2 * j]), ex2(s[2 * j + 1]));
                    else if ((ALU_MASK >> j) & 1) p[j] = exp2_pair<true>(s[2 * j], s[2 * j + 1], cexp, neg1);
                    else p[j] = exp2_pair<false>(s[2 * j], s[2 * j + 1], cexp, neg1);
                }
            } else {
                fence_regs(o);
                float x0 = m0, x1 = m1;
#pragma unroll
                for (int j = 0; j < 8; j++) { x0 = fmaxf(x0, fmaxf(s[4 * j], s[4 * j + 1])); x1 = fmaxf(x1, fmaxf(s[4 * j + 2], s[4 * j + 3])); }
                x0 = fmaxf(x0, __shfl_xor_sync(0xffffffffu, x0, 1)); x0 = fmaxf(x0, __shfl_xor_sync(0xffffffffu, x0, 2));
                x1 = fmaxf(x1, __shfl_xor_sync(0xffffffffu, x1, 1)); x1 = fmaxf(x1, __shfl_xor_sync(0xffffffffu, x1, 2));
                const float c0 = ex2(m0 - x0), c1 = ex2(m1 - x1);
                m0 = x0; m1 = x1;
#pragma unroll
                for (int j = 0; j < 3; j++) { o[4 * j] *= c0; o[4 * j + 1] *= c0; o[4 * j + 2] *= c1; o[4 * j + 3] *= c1; }
#pragma unroll
                for (int j = 0; j < 8; j++) {
                    p[2 * j] = pack_bf16(ex2(s[4 * j] - m0), ex2(s[4 * j + 1] - m0));
                    p[2 * j + 1] = pack_bf16(ex2(s[4 * j + 2] - m1), ex2(s[4 * j + 3] - m1));
                }
                fence_regs(o);
            }
            fence_regs(p);
            wg_fence();
            if (SAFE) mma_qk_f16(s, dq, dk); else mma_qk_bf16(s, dq, dk);
#pragma unroll
            for (int j = 0; j < 4; j++) mma_pv(o, p + 4 * j, dv + j * 16);
            wg_commit();
            dk += 128; dv += 64;
            wg_wait<0>(); fence_regs(s);
        } while (--n > 0);
        if (u == 2 || u == 7) {
            fence_regs(o);
            const float i0 = rcp(o[8]), i1 = rcp(o[10]);
            if (u == 7) mbar_wait(mb + MB_MID * 8);
            store_tile(reinterpret_cast<uint32_t*>(g_x + X_O + (((u == 7) * 16 + (b >> 3)) * 32 + (b & 3) * 8 + 2 * wg + (ww >> 1)) * 128 + (((b >> 2) & 1) * 2 + (ww & 1)) * 32) + lane,
                       pack_bf16(o[0] * i0, o[1] * i0), pack_bf16(o[2] * i1, o[3] * i1), pack_bf16(o[4] * i0, o[5] * i0), pack_bf16(o[6] * i1, o[7] * i1));
            if (u == 2) asm volatile("cp.async.bulk.wait_group 0;" ::: "memory");
            else count_hint(C_O + 16 + (b >> 3));
            warp_done(mb + (MB_DONE + (u == 7) * 4) * 8);
            TS(5 + (u == 7));
        } else if (u >= 3) {
            if (u < 6) warp_done(mb + (MB_DONE + u - 2) * 8);
            if (job < (u == 3 ? 1 : 5)) {
                mbar_wait(mb + (MB_DONE + u - 3) * 8);
                if (u == 3) count_release(C_MID);
                else if (lane == 0) refill_job(sb, P, u - 4, job);
            } else if (u == 6) {
                if (job < 9) {
                    mbar_wait(mb + MB_MID * 8);
                    if (lane == 0) {
                        mbar_expect(mb + (MB_FULL + job - 5) * 8, SLOT);
                        bulk_g2s(sb + (19 + job) * SLOT, g_x + X_O + tail_m() * 4096 + (job - 5) * 512, SLOT, mb + (MB_FULL + job - 5) * 8);
                    }
                }
            } else if (warp == 7) {
                if (u == 4) cnt = ldg32_relaxed(g_s.cnt[C_MID]);
                if (u == 5) {
                    const unsigned target = lds32(mb + MISC_EPOCH) * NCTA;
                    if (__any_sync(0xffffffffu, cnt != target)) count_wait(C_MID, target);
                    asm volatile("fence.acquire.gpu; fence.proxy.async.global;" ::: "memory");
                    warp_done(mb + MB_MID * 8);
                }
            }
        } else if (u == 1) {
            if (SAFE) mbar_wait(mb + MB_KV * 8);
            TS(17);
            if (lane == 0) {
                if (job < 9) {
                    asm volatile("cp.async.bulk.global.shared::cta.bulk_group [%0], [%1], %2;"
                                 :: "l"(g_x + X_ARM + b * X_SHARE + job * 512), "r"(sb + SM_SENT), "r"(job < 8 ? 8192 : (X_SHARE - 4096) * 16) : "memory");
                    asm volatile("cp.async.bulk.commit_group;" ::: "memory");
                } else if (job < 11) load_wo(sb, P, job - 9);
            }
        } else if (SAFE) {
            if (warp == 8) {
                const unsigned target = lds32(mb + MISC_EPOCH) * NMAIN;
                if (__any_sync(0xffffffffu, cnt != target)) count_wait(C_KV, target);
                if (lane == 0) {
                    asm volatile("fence.acquire.gpu; fence.proxy.async.global;" ::: "memory");
                    mbar_expect(mb + MB_KV * 8, 47104 + 2 * 24576);
                    bulk_g2s(sb + SM_K + 16384, g_s.kv + 1024, 47104, mb + MB_KV * 8);
                    bulk_g2s(sb + SM_V + 8192, g_s.kv + 4096 + 512, 24576, mb + MB_KV * 8);
                    bulk_g2s(sb + SM_V + 32768 + 8192, g_s.kv + 6144 + 512, 24576, mb + MB_KV * 8);
                }
            }
        }
        __syncwarp();
    }
    }
}

__device__ __forceinline__ int kv_slot(int idx) {
    const int t = (idx & 63) >> 1, c = 2 * (blockIdx.x >> 2) + (idx & 1), hg = blockIdx.x & 3;
    return hg < 2 ? ((t + 31) & 31) * 128 + (c >> 3) * 16 + (hg & 1) * 8 + (c & 7) : 4096 + (hg & 1) * 2048 + t * 64 + c;
}

#define GATE_AT 2
__device__ __noinline__ void helper_cta(const Params& P, uint8_t* smem) {
    const int tid = threadIdx.x, b = blockIdx.x, hi = b - NMAIN;
    const unsigned epoch = g_s.epoch[b] + 1;
    float* red = reinterpret_cast<float*>(smem);
    if (tid < 32) count_wait(C_KV, epoch * NMAIN);
    __syncthreads();
    if (tid == 480) {
        for (int i = 0; i < 8; i++) asm volatile("cp.async.bulk.prefetch.L2.global [%0], %1;" :: "l"((const char*)P.wop + hi * 131072 + i * 16384), "r"(16384) : "memory");
        for (int i = 0; i < 43; i++) asm volatile("cp.async.bulk.prefetch.L2.global [%0], %1;" :: "l"((const char*)P.w2p + hi * 352256 + i * 8192), "r"(8192) : "memory");
    }
    if (tid < 344) {
        const int cg = tid % 43, rp = tid / 43;
        const uint4* src = reinterpret_cast<const uint4*>(P.w1p + (size_t)rp * 64 * FF + (hi * 43 + cg) * 8);
        float s[8] = {0, 0, 0, 0, 0, 0, 0, 0};
#pragma unroll 8
        for (int r = 0; r < 64; r++) {
            uint4 v = __ldg(src + r * (FF / 8));
            s[0] += bf_lo(v.x); s[1] += bf_hi(v.x); s[2] += bf_lo(v.y); s[3] += bf_hi(v.y);
            s[4] += bf_lo(v.z); s[5] += bf_hi(v.z); s[6] += bf_lo(v.w); s[7] += bf_hi(v.w);
        }
        float* part = red + (rp * 43 + cg) * 8;
#pragma unroll
        for (int i = 0; i < 8; i++) part[i] = s[i];
    }
    __syncthreads();
    if (tid < 344) {
        float s = 0.f;
#pragma unroll
        for (int rp = 0; rp < 8; rp++) s += red[rp * 344 + tid];
        g_s.cs[hi * 344 + tid] = s;
    } else if (hi == 3 && tid < 344 + 64) g_s.cs[FF + tid - 344] = 0.f;
    __syncthreads();
    if (tid < 32) count_release(C_MID);
    if (tid == 0) g_s.epoch[b] = epoch;
}

__global__ void __launch_bounds__(512, 1) fused_kernel(const __nv_bfloat16* __restrict__ x, const __nv_bfloat16* __restrict__ wk, long long wv_off,
                                                         const __grid_constant__ Params P) {
    extern __shared__ __align__(1024) uint8_t smem[];
    const uint32_t sb = (uint32_t)__cvta_generic_to_shared(smem);
    const uint32_t mb = sb + SM_MISC;
    const int tid = threadIdx.x, lane = tid & 31, b = blockIdx.x;
    if (b >= NMAIN) { helper_cta(P, smem); return; }
    const int tg = b >> 2, hg = b & 3;
    const int warp = __shfl_sync(0xffffffffu, tid >> 5, 0);

    const uint32_t xst = sb + (((0x160A1204u >> (8 * (warp >> 2))) & 31) * SLOT + (warp & 3) * 4096), xbar = mb + MISC_XBAR + warp * 8;
    if (lane == 0) {
        mbar_init(xbar, 1);
        asm volatile("fence.mbarrier_init.release.cluster;" ::: "memory");
        mbar_expect(xbar, 4096);
        bulk_g2s(xst, x + (size_t)((warp & 7) * 4 + tg * 32 + (warp >> 3) * 1024) * D, 4096, xbar);
    }
    const uint4 wkv = ldg_relaxed(reinterpret_cast<const uint4*>(reinterpret_cast<const char*>(wk) + (hg < 2 ? 0 : wv_off)) + tid * 2 + (hg & 1));
    unsigned epoch = 0;
    if (warp == 12) epoch = ldg32_relaxed(g_s.epoch + b);
    const int wg = warp >> 2, ww = warp & 3, g = lane >> 2, t4 = lane & 3, t128 = tid & 127;
    if (lane == 0) {
        if (warp < 4) {
            mbar_init(mb + (MB_WQ + warp) * 8, 2);
            asm volatile("fence.mbarrier_init.release.cluster;" ::: "memory");
            asm volatile("cp.async.bulk.prefetch.L2.global [%0], %1;" :: "l"((const char*)P.wqp + (b * 4 + warp) * 1024), "r"(1024) : "memory");
        } else {
            if (warp < 8) asm volatile("prefetch.tensormap [%0];" :: "l"(&P.wq + (warp - 4)) : "memory");
            const uint32_t first = warp < 8 ? (0x78100904u >> (8 * (warp - 4))) & 255 : warp < 11 ? 14 * warp - 93 : 14 * warp - 95;
            const uint32_t end = warp < 8 ? (0x83131009u >> (8 * (warp - 4))) & 255 : warp < 11 ? 59 : 120;
            const uint32_t cnt = warp < 8 ? (0x08030410u >> (8 * (warp - 4))) & 255 : warp < 11 ? 1 : 2;
#pragma unroll
            for (uint32_t i = 0; i < 14; i++) if (first + i < end) mbar_init(mb + (first + i) * 8, cnt);
            if (warp == 7) sts128(mb + MISC_NRM, 0, 0, 0, 0);
        }
    }
    __syncwarp();
    TS(16);
    sts128(sb + SM_WKV + tid * 16, wkv.x, wkv.y, wkv.z, wkv.w);
    uint4 xv[4][2];
    mbar_wait(xbar);
#pragma unroll
    for (int i = 0; i < 8; i++) xv[i >> 1][i & 1] = lds128(xst + i * 512 + lane * 16);
    float dlt;
    {
        float st[4];
#pragma unroll
        for (int i = 0; i < 4; i++) {
            const uint32_t s = add_bf16x2(add_bf16x2(add_bf16x2(xv[i][0].x, xv[i][0].y), add_bf16x2(xv[i][0].z, xv[i][0].w)),
                                          add_bf16x2(add_bf16x2(xv[i][1].x, xv[i][1].y), add_bf16x2(xv[i][1].z, xv[i][1].w)));
            st[i] = bf_lo(s) + bf_hi(s);
        }
        TS(13);
        const float tot = reduce4(st, lane) * (-1.0f / D);
        const uint32_t nmr = pack_bf16(tot, tot);
        dlt = bf_lo(nmr) - tot;
        const uint32_t xa[2] = {sb + (((uint32_t)XN_SLOTS >> (lane & 24)) & 31) * SLOT + warp * 512, sb + (((uint32_t)(XN_SLOTS >> 32) >> (lane & 24)) & 31) * SLOT + warp * 512};
#pragma unroll
        for (int i = 0; i < 4; i++) {
            const uint32_t nm = __shfl_sync(0xffffffffu, nmr, i * 8);
            const uint32_t off = i * 128 + (((lane & 7) ^ ((warp & 1) * 4 + i)) << 4);
#pragma unroll
            for (int c = 0; c < 2; c++) {
                xv[i][c].x = add_bf16x2(xv[i][c].x, nm); xv[i][c].y = add_bf16x2(xv[i][c].y, nm);
                xv[i][c].z = add_bf16x2(xv[i][c].z, nm); xv[i][c].w = add_bf16x2(xv[i][c].w, nm);
                sts128(xa[c] + off, xv[i][c].x, xv[i][c].y, xv[i][c].z, xv[i][c].w);
            }
        }
    }
    fence_async_smem();
    TS(0);
    if (wg < 2) bar_arrive(7, 512);
    else if (wg == 3) {
        bar_sync(7, 512);
        if (lane == 0) { load_wq(sb, P, ww, 0); load_wq(sb, P, ww, 1); }
        __syncwarp();
    }
    {
        float st[4];
#pragma unroll
        for (int i = 0; i < 4; i++) {
            float v = 0.f;
#pragma unroll
            for (int c = 0; c < 2; c++) {
                const uint32_t a = fma_bf16x2(xv[i][c].x, xv[i][c].x, mul_bf16x2(xv[i][c].y, xv[i][c].y));
                const uint32_t d = fma_bf16x2(xv[i][c].z, xv[i][c].z, mul_bf16x2(xv[i][c].w, xv[i][c].w));
                v += (bf_lo(a) + bf_hi(a)) + (bf_lo(d) + bf_hi(d));
            }
            st[i] = v;
        }
        const float vs = reduce4(st, lane), dl = dlt;
        if ((lane & 7) == 0) sts32(sb + SM_RSTD + (warp * 4 + (lane >> 3)) * 4, __float_as_uint(rsqrtf(fmaxf(vs * (1.0f / D) - dl * dl, 0.f) + 1e-5f)));
    }
    if (wg == 2) {
        float kv[4];
        uint64_t db = mkdesc(sb + SM_WKV, 128, 16, 0), xs = XN_SLOTS;
        bar_sync(7, 512);
#pragma unroll 1
        for (int i = 0; i < 8; i++, xs >>= 8, db += 64) {
            const uint64_t da = mkdesc(sb + ((uint32_t)xs & 31) * SLOT, 16, 1024, 1);
            wg_fence();
#pragma unroll
            for (int s = 0; s < 4; s++) mma_ss8(kv, da + s * 2, db + s * 16, s ? 1 : i);
            wg_commit();
        }
        wg_wait<0>(); fence_regs(kv);
        float2* kt = reinterpret_cast<float2*>(smem + SM_KTMP);
        kt[(ww * 16 + g) * 4 + t4] = make_float2(kv[0], kv[1]); kt[(ww * 16 + g + 8) * 4 + t4] = make_float2(kv[2], kv[3]);
        TS(24);
    }
    epoch++;
    if (tid == 12 * 32) { sts32(mb + MISC_EPOCH, epoch); g_s.epoch[b] = epoch; }
    constexpr float QSCALE = 0.25f * 1.4426950408889634f;
    float qa[64];
    const uint32_t qbase = sb + SM_Q + (ww >> 1) * 8192 + (ww & 1) * 512 + lane * 16;
    if (wg == 0) {
#pragma unroll
        for (int i = 0; i < 64; i++) qa[i] = 0.f;
        float rs0 = 0.f, rs1 = 0.f;
#pragma unroll 1
        for (int live = 0; live < 2; live++) {
        fence_regs(qa);
        if (live) {
        TS(25);
        bar_sync(0, 512);
        rs0 = __uint_as_float(lds32(sb + SM_RSTD + (ww * 16 + g) * 4)) * QSCALE; rs1 = __uint_as_float(lds32(sb + SM_RSTD + (ww * 16 + g + 8) * 4)) * QSCALE;
        mbar_wait(mb + MB_WQ * 8);
        bar_sync(2, 320);
#pragma unroll 1
        for (int i = 0; i < 4; i++) {
            const uint32_t s0 = (WQ0_SLOTS >> (8 * i)) & 31, s1 = (WQ1_SLOTS >> (8 * i)) & 31, xs = (uint32_t)(XN_SLOTS >> (16 * i));
            const uint64_t db = mkdesc(sb + s0 * SLOT, (s1 - s0) * SLOT, 1024, 1);
            const uint64_t da0 = mkdesc(sb + (xs & 31) * SLOT, 16, 1024, 1), da1 = mkdesc(sb + ((xs >> 8) & 31) * SLOT, 16, 1024, 1);
            mbar_wait(mb + (MB_WQ + i) * 8);
            wg_fence();
#pragma unroll
            for (int s = 0; s < 8; s++) mma_ss128(qa, (s < 4 ? da0 : da1) + (s & 3) * 2, db + s * 128);
            wg_commit();
            wg_wait<1>();
            if (i == 1) bar_arrive(6, 160);
        }
        wg_wait<0>();
        fence_regs(qa);
        bar_arrive(5, 256);
        TS(1);
        }
        uint32_t nm = 0;
#pragma unroll
        for (int h = 0; h < 8; h++) {
#pragma unroll
            for (int i = 0; i < 8; i++) qa[8 * h + i] *= (i & 2) ? rs1 : rs0;
            stsm4(qbase + h * 1024, pack_f16(qa[8 * h], qa[8 * h + 1]), pack_f16(qa[8 * h + 4], qa[8 * h + 5]), pack_f16(qa[8 * h + 2], qa[8 * h + 3]), pack_f16(qa[8 * h + 6], qa[8 * h + 7]));
            const float n0 = qa[8 * h] * qa[8 * h] + qa[8 * h + 1] * qa[8 * h + 1] + qa[8 * h + 4] * qa[8 * h + 4] + qa[8 * h + 5] * qa[8 * h + 5];
            const float n1 = qa[8 * h + 2] * qa[8 * h + 2] + qa[8 * h + 3] * qa[8 * h + 3] + qa[8 * h + 6] * qa[8 * h + 6] + qa[8 * h + 7] * qa[8 * h + 7];
            nm = max(nm, max(__float_as_uint(n0), __float_as_uint(n1)));
        }
        nm = __reduce_max_sync(0xffffffffu, __float_as_uint(quad_sum(__uint_as_float(nm))));
        if (lane == 0 && live) asm volatile("red.shared.max.u32 [%0], %1;" :: "r"(mb + MISC_NRM), "r"(nm) : "memory");
        }
    } else if (wg == 2) {
        bar_sync(0, 512);
        bar_sync(2, 320);
#pragma unroll
        for (int i = 0; i < 4; i++) sts128(sb + SM_SENT + (i * 128 + t128) * 16, SENT, SENT, SENT, SENT);
#pragma unroll
        for (int i = 0; i < 16; i++) {
            if (i == 4) bar_sync(5, 256);
            sts128(sb + SM_V + 65536 + (i * 128 + t128) * 16, 0x3F803F80u, 0x3F803F80u, 0x3F803F80u, 0x3F803F80u);
        }
    } else if (wg == 1) {
        if (ww >= 2) bar_sync(0, 512);
        else {
            const bool diff = ww == 0 && hg < 2;
#pragma unroll 1
            for (int live = 0; live < 2; live++) {
            if (live) { TS(25); bar_sync(0, 512); }
            uint32_t nm = 1;
            uint4 w[2];
#pragma unroll
            for (int i = 0; i < 2; i++) {
                const int r = (lane & 1) * 32 + i * 16 + (lane >> 1);
                const uint32_t ra = sb + SM_KTMP + r * 32;
                float4 c0 = lds128f(ra), c1 = lds128f(ra + 16);
                const float4 p0 = lds128f(ra - 32), p1 = lds128f(ra - 16);
                const float rs = __uint_as_float(lds32(sb + SM_RSTD + r * 4));
                float rp = -__uint_as_float(lds32(sb + SM_RSTD + r * 4 - 4));
                c0.x *= rs; c0.y *= rs; c0.z *= rs; c0.w *= rs; c1.x *= rs; c1.y *= rs; c1.z *= rs; c1.w *= rs;
                nm = max(nm, __float_as_uint(c0.x * c0.x + c0.y * c0.y + c0.z * c0.z + c0.w * c0.w + c1.x * c1.x + c1.y * c1.y + c1.z * c1.z + c1.w * c1.w));
                uint32_t w0, w1, w2, w3;
                if (diff) {
                    if (r & 31) {
                        c0.x = fmaf(p0.x, rp, c0.x); c0.y = fmaf(p0.y, rp, c0.y); c0.z = fmaf(p0.z, rp, c0.z); c0.w = fmaf(p0.w, rp, c0.w);
                        c1.x = fmaf(p1.x, rp, c1.x); c1.y = fmaf(p1.y, rp, c1.y); c1.z = fmaf(p1.z, rp, c1.z); c1.w = fmaf(p1.w, rp, c1.w);
                    }
                    w0 = pack_f16(c0.x, c0.y); w1 = pack_f16(c0.z, c0.w); w2 = pack_f16(c1.x, c1.y); w3 = pack_f16(c1.z, c1.w);
                } else {
                    w0 = pack_bf16(c0.x, c0.y); w1 = pack_bf16(c0.z, c0.w); w2 = pack_bf16(c1.x, c1.y); w3 = pack_bf16(c1.z, c1.w);
                }
                w[i] = make_uint4(nonzero(w0), nonzero(w1), nonzero(w2), nonzero(w3));
            }
            nm = __reduce_max_sync(0xffffffffu, nm);
#pragma unroll
            for (int i = 0; i < 2; i++) stg128_if(live && (ww == 0 || hg < 2), (ww ? g_s.kplain : g_s.kv) + kv_slot(i * 32 + lane), w[i].x, w[i].y, w[i].z, w[i].w);
            stg128_if(live && ww == 0 && lane < 2, g_s.nrm + b * 2 + lane, nm, nm, nm, nm);
            asm volatile("{.reg .pred p; setp.ne.u32 p, %1, 0; @p red.relaxed.gpu.global.add.u32 [%0], 1;}" :: "l"(g_s.cnt[C_KVH]), "r"((int)(live && t128 == 0)) : "memory");
            }
            if (ww == 0) {
                TS(1);
                bar_arrive(2, 320);
            } else {
                bar_sync(2, 320);
                count_release(C_KV);
            }
        }
    } else {
        bar_sync(0, 512);
        if (ww == 0) count_wait(C_KVH, epoch * NMAIN);
        TS(1);
        bar_sync(3, 128);
        uint32_t nm = ldg32_relaxed(g_s.nrm + t128 * 2);
        if (ww == 0) bar_sync(6, 160);
        int spins = 0;
        bool bad;
        do {
            if (t128 == 0) {
                asm volatile("fence.proxy.async.global;" ::: "memory");
                mbar_expect(mb + MB_KV0 * 8, 34816);
                bulk_g2s(sb + SM_K + 31 * 2048, g_s.kv + 31 * 128, 2048, mb + MB_KV0 * 8);
                bulk_g2s(sb + SM_K, g_s.kv, 16384, mb + MB_KV0 * 8);
                bulk_g2s(sb + SM_V, g_s.kv + 4096, 8192, mb + MB_KV0 * 8);
                bulk_g2s(sb + SM_V + 32768, g_s.kv + 6144, 8192, mb + MB_KV0 * 8);
            }
            if (spins) nm = ldg32_relaxed(g_s.nrm + t128 * 2);
            __syncwarp();
            mbar_wait(mb + MB_KV0 * 8, spins & 1);
            const uint32_t probe = sb + (ww < 2 ? SM_K + ww * 8192 : SM_V + (ww - 2) * 32768) + lane * 32 + (lane >> 2) * 4;
            uint32_t mn = min(nm, lds32(sb + SM_K + 31 * 2048 + (ww & 1) * 1024 + lane * 32 + (lane >> 2) * 4));
#pragma unroll
            for (int k = 0; k < 8; k++) mn = min(mn, lds32(probe + k * 1024));
            uint32_t r;
            asm volatile("{.reg .pred p, q; setp.eq.u32 p, %1, 0; barrier.red.or.pred.aligned q, 3, 128, p; selp.u32 %0, 1, 0, q;}" : "=r"(r) : "r"(mn) : "memory");
            bad = __any_sync(0xffffffffu, r);
        } while (bad && ++spins < SPIN_LIMIT);
        TS(2);
        nm = max(nm, __shfl_xor_sync(0xffffffffu, nm, 4)); nm = max(nm, __shfl_xor_sync(0xffffffffu, nm, 8)); nm = max(nm, __shfl_xor_sync(0xffffffffu, nm, 16));
        if (lane < 4) asm volatile("red.shared.max.u32 [%0], %1;" :: "r"(mb + MISC_NRM + 4 + min(lane, 2) * 4), "r"(nm) : "memory");
    }
    fence_async_smem();
    TS(3);
    __syncthreads();
    const float4 nr = lds128f(mb + MISC_NRM);
    const bool safe = __all_sync(0xffffffffu, (nr.x * (nr.y + nr.z) <= 3500.0f) && (nr.x <= 65536.0f) && (nr.y + nr.z <= 65536.0f) && (nr.w <= 1e24f));
    TS(4);

    if (__builtin_expect(safe, 1)) {
        attention<true>(P, sb, warp TS_PASS);
    } else {
        if (wg == 0) {
#pragma unroll
            for (int h = 0; h < 8; h++)
                stsm4(qbase + h * 1024, pack_bf16(qa[8 * h], qa[8 * h + 1]), pack_bf16(qa[8 * h + 4], qa[8 * h + 5]), pack_bf16(qa[8 * h + 2], qa[8 * h + 3]), pack_bf16(qa[8 * h + 6], qa[8 * h + 7]));
            fence_async_smem();
        } else if (warp == 15) {
            count_wait(C_KV, lds32(mb + MISC_EPOCH) * NMAIN);
            if (lane == 0) {
                asm volatile("fence.proxy.async;" ::: "memory");
                mbar_expect(mb + MB_KV * 8, 131072);
                bulk_g2s(sb + SM_K, g_s.kplain, 65536, mb + MB_KV * 8);
                bulk_g2s(sb + SM_V, g_s.kv + 4096, 65536, mb + MB_KV * 8);
            }
            __syncwarp();
        }
        __syncthreads();
        mbar_wait(mb + MB_KV * 8);
        attention<false>(P, sb, warp TS_PASS);
    }

    const int j = tail_j();
    if (wg == 1 || wg == 2) {
        if (warp == 8) {
            epoch = lds32(mb + MISC_EPOCH);
#pragma unroll 1
            for (int job = 1; job < 6; job++) {
                count_wait(C_O + 32 * (job >> 1) + (job & 1) * 16 + tail_m(), epoch * (job == 1 ? 128 : 32));
                asm volatile("fence.proxy.async.global;" ::: "memory");
                warp_done(mb + (MB_READY + job) * 8);
                TS(18 + job);
            }
        } else if (warp == 9) {
#pragma unroll
            for (int i = 0; i < 2; i++) {
                if (lane < 22) {
                    const uint4 v = ldg_relaxed(reinterpret_cast<const uint4*>(g_s.cs + j * 176) + i * 22 + lane);
                    sts128(mb + MISC_CS + (i * 22 + lane) * 16, v.x, v.y, v.z, v.w);
                }
                stg128(g_s.kv + kv_slot(i * 32 + lane), 0u, 0u, 0u, 0u);
            }
            warp_done(mb + MB_CS * 8);
            if (lane < 2) stg128(g_s.nrm + b * 2 + lane, 0u, 0u, 0u, 0u);
#pragma unroll 1
            for (int i = 0; i < 16; i++) {
                mbar_wait(mb + (MB_W1 + i) * 8);
                const int n = i < 8 ? 16 + i + 8 * (lane & 1) : 32 + 3 * (i - 8) + (lane >> 1) + 22 * (lane & 1);
                if (lane < (i < 8 || i == 15 ? 2 : 6)) mbar_arrive(mb + (MB_FULL + n) * 8);
                __syncwarp();
            }
        } else {
            if (warp == 10) {
#pragma unroll 1
                for (int i = 3; i < 16; i++) {
                    const bool w1 = i < 8;
                    const int kb = i & 7;
                    const uint32_t bar = mb + (MB_W1 + i) * 8, dst = sb + w1_slot(kb, 0) * SLOT, step = kb < 4 ? 4 * SLOT : SLOT;
                    const CUtensorMap* tm = w1 ? &P.w1 : &P.w2;
                    const int c0 = w1 ? j * 176 : j * 64, c1 = w1 ? kb * 64 : kb * 192, d0 = w1 ? 64 : 0, d1 = 64 - d0;
                    if (lane == 0) mbar_expect(bar, i == 15 ? SLOT : 3 * SLOT);
                    mbar_wait(mb + (w1 ? (i == 3 ? MB_DONE + 4 : i < 6 ? MB_REL + 9 : MB_REL + 8) : MB_REL + kb) * 8);
                    if (i == 8 + GATE_AT) mbar_wait(mb + MB_EPI * 8);
                    if (lane == 0) {
                        tma2d(dst, tm, c0, c1, bar);
                        if (i < 15) { tma2d(dst + step, tm, c0 + d0, c1 + d1, bar); tma2d(dst + 2 * step, tm, c0 + 2 * d0, c1 + 2 * d1, bar); }
                    }
                    __syncwarp();
                }
            } else {
                ring_feed(sb, wg == 1 ? ww : 4 TS_PASS);
            }
        }
    } else {
        const int pr = (wg == 0), mt = 16 * pr + tail_m();
        uint32_t* const hp = reinterpret_cast<uint32_t*>(g_x + X_H1 + (mt * 32 + j * 4) * 128 + ww * 32) + lane;
        {
            uint32_t hk[16];
            const uint32_t* xp = reinterpret_cast<const uint32_t*>(x + (size_t)(mt * 64 + ww * 16 + g) * D + j * 64 + t4 * 2);
#pragma unroll
            for (int k = 0; k < 8; k++) { hk[2 * k] = __ldg(xp + k * 4); hk[2 * k + 1] = __ldg(xp + k * 4 + 8 * (D / 2)); }
            mbar_wait(mb + MB_WO * 8);
            float acc[32];
            if (gemm_ss<0>(acc, sb, pr TS_PASS)) gemm_slow(acc, g_x + X_O + mt * 32 * 128, 32, P.wop, D, D, j * 64);
            TS(7);
#pragma unroll
            for (int i = 0; i < 16; i++) hk[i] = pack_bf16(acc[2 * i] + bf_lo(hk[i]), acc[2 * i + 1] + bf_hi(hk[i]));
#pragma unroll
            for (int k = 0; k < 4; k++) store_tile(hp + k * 512, hk[4 * k], hk[4 * k + 1], hk[4 * k + 2], hk[4 * k + 3]);
            count_hint(C_H1 + mt);
            TS(8);
            float st[4] = {0.f, 0.f, 0.f, 0.f};
#pragma unroll
            for (int i = 0; i < 16; i++) {
                const float lo = bf_lo(hk[i]), hi = bf_hi(hk[i]);
                st[2 * (i & 1)] += lo + hi;
                st[2 * (i & 1) + 1] = fmaf(lo, lo, fmaf(hi, hi, st[2 * (i & 1) + 1]));
            }
#pragma unroll
            for (int o = 1; o < 4; o <<= 1)
#pragma unroll
                for (int i = 0; i < 4; i++) st[i] += __shfl_xor_sync(0xffffffffu, st[i], o);
            if (t4 == 0) stg128(g_x + X_ST + (mt * 8 + j) * 32 + ww * 8 + g, __float_as_uint(st[0]), __float_as_uint(st[1]), __float_as_uint(st[2]), __float_as_uint(st[3]));
        }
        {
            float acc[88];
            mbar_wait(mb + MB_CS * 8);
            if (gemm_ss<1>(acc, sb, pr TS_PASS)) gemm_slow(acc, g_x + X_H1 + mt * 32 * 128, 32, P.w1p, FF, D, j * 176);
            TS(9);
            mbar_wait(mb + (MB_STAT + pr) * 8);
            const float4 rs = lds128f(mb + MISC_STAT + pr * 512 + (ww * 8 + g) * 16);
            const float nmean[2] = {rs.x, rs.z}, hrstd[2] = {rs.y, rs.w};
            uint32_t* hb = reinterpret_cast<uint32_t*>(g_x + X_H2 + (mt * 88 + j * 11) * 128 + ww * 32) + lane;
#pragma unroll
            for (int i = 0; i < 22; i++) {
                float2 cs;
                asm volatile("ld.shared.v2.f32 {%0,%1}, [%2];" : "=f"(cs.x), "=f"(cs.y) : "r"(mb + MISC_CS + i * 32 + t4 * 8));
                const float* z = acc + 4 * i;
                uint32_t* p = hb + (i >> 1) * 512 + (i & 1) * 32;
                stg32(p, pack_bf16(silu2(fmaf(hrstd[0], z[0], nmean[0] * cs.x)), silu2(fmaf(hrstd[0], z[1], nmean[0] * cs.y))));
                stg32(p + 64, pack_bf16(silu2(fmaf(hrstd[1], z[2], nmean[1] * cs.x)), silu2(fmaf(hrstd[1], z[3], nmean[1] * cs.y))));
            }
            count_hint(C_H2 + mt);
            if (!pr) warp_done(mb + MB_EPI * 8);
            TS(10);
        }
        {
            uint32_t hk[16];
#pragma unroll
            for (int i = 0; i < 16; i++) hk[i] = ldg32_relaxed(hp + (i >> 2) * 512 + ((i & 1) * 2 + ((i >> 1) & 1)) * 32);
            float acc[32];
            if (gemm_ss<2>(acc, sb, pr TS_PASS)) gemm_slow(acc, g_x + X_H2 + mt * 88 * 128, 88, P.w2p, D, FF, j * 64);
            TS(11);
#pragma unroll
            for (int i = 0; i < 16; i++) hk[i] = pack_bf16(acc[2 * i] + bf_lo(hk[i]), acc[2 * i + 1] + bf_hi(hk[i]));
#pragma unroll
            for (int h = 0; h < 4; h++) {
                const uint32_t* v = hk + (h >> 1) * 8 + (h & 1);
                uint32_t v0 = v[0], v1 = v[2], v2 = v[4], v3 = v[6];
                const bool o1 = t4 & 1, o2 = t4 & 2;
                uint32_t a = __shfl_xor_sync(0xffffffffu, o1 ? v0 : v1, 1), c = __shfl_xor_sync(0xffffffffu, o1 ? v2 : v3, 1);
                if (o1) { v0 = a; v2 = c; } else { v1 = a; v3 = c; }
                a = __shfl_xor_sync(0xffffffffu, o2 ? v0 : v2, 2); c = __shfl_xor_sync(0xffffffffu, o2 ? v1 : v3, 2);
                if (o2) { v0 = a; v1 = c; } else { v2 = a; v3 = c; }
                *reinterpret_cast<uint4*>(P.out + (size_t)(mt * 64 + ww * 16 + g + 8 * (h & 1)) * D + j * 64 + (h >> 1) * 32 + t4 * 8) = make_uint4(v0, v1, v2, v3);
            }
        }
    }
    TS(12);
}

typedef CUresult (*EncodeFn)(CUtensorMap*, CUtensorMapDataType, cuuint32_t, void*, const cuuint64_t*, const cuuint64_t*, const cuuint32_t*,
                             const cuuint32_t*, CUtensorMapInterleave, CUtensorMapSwizzle, CUtensorMapL2promotion, CUtensorMapFloatOOBfill);

void encode2d(EncodeFn fn, CUtensorMap* tm, const void* ptr, int rows, int cols, int box_rows, int box_cols, CUtensorMapSwizzle sw) {
    cuuint64_t dims[2] = {(cuuint64_t)cols, (cuuint64_t)rows};
    cuuint64_t strides[1] = {(cuuint64_t)cols * 2};
    cuuint32_t box[2] = {(cuuint32_t)box_cols, (cuuint32_t)box_rows};
    cuuint32_t es[2] = {1, 1};
    fn(tm, CU_TENSOR_MAP_DATA_TYPE_BFLOAT16, 2, const_cast<void*>(ptr), dims, strides, box, es, CU_TENSOR_MAP_INTERLEAVE_NONE, sw,
       CU_TENSOR_MAP_L2_PROMOTION_L2_128B, CU_TENSOR_MAP_FLOAT_OOB_FILL_NONE);
}

}

extern "C" void kernel_launch(void* const* d_in, const int* in_sizes, int n_in, void* d_out, int out_size) {
    (void)in_sizes; (void)n_in; (void)out_size;
    void* fnp = nullptr;
    cudaDriverEntryPointQueryResult qr;
    cudaGetDriverEntryPoint("cuTensorMapEncodeTiled", &fnp, cudaEnableDefault, &qr);
    EncodeFn fn = (EncodeFn)fnp;
    Params P;
    encode2d(fn, &P.wq, d_in[1], D, D, 128, 64, CU_TENSOR_MAP_SWIZZLE_128B);
    encode2d(fn, &P.wo, d_in[4], D, D, 64, 64, CU_TENSOR_MAP_SWIZZLE_128B);
    encode2d(fn, &P.w1, d_in[6], D, FF, 64, 64, CU_TENSOR_MAP_SWIZZLE_128B);
    encode2d(fn, &P.w2, d_in[7], FF, D, 64, 64, CU_TENSOR_MAP_SWIZZLE_128B);
    P.w1p = (const __nv_bfloat16*)d_in[6];
    P.w2p = (const __nv_bfloat16*)d_in[7];
    P.wop = (const __nv_bfloat16*)d_in[4];
    P.wqp = (const __nv_bfloat16*)d_in[1];
    P.out = (__nv_bfloat16*)d_out;
    P.neg1 = 0xFFFFFFFFu; P.pad = 0;
    cudaFuncSetAttribute(fused_kernel, cudaFuncAttributeMaxDynamicSharedMemorySize, SMEM_BYTES);
    fused_kernel<<<NCTA, 512, SMEM_BYTES>>>((const __nv_bfloat16*)d_in[0], (const __nv_bfloat16*)d_in[2], (long long)((const char*)d_in[3] - (const char*)d_in[2]), P);
}
```

```cpp
#include <cuda_runtime.h>
#include <cuda_bf16.h>
#include <cuda.h>
#include <stdint.h>

namespace {

constexpr int D = 512, FF = 1376;
constexpr int NMAIN = 128, NHELP = 4, NCTA = NMAIN + NHELP;
constexpr uint32_t SENT = 0xFFFFFFFFu;
constexpr int SPIN_LIMIT = 1 << 22;

constexpr uint32_t KB = 1024, SLOT = 8192;
constexpr uint64_t XN_SLOTS = 7 | 16 << 8 | 6 << 16 | 17 << 24 | 21ull << 32 | 27ull << 40 | 24ull << 48 | 25ull << 56;
constexpr uint32_t WQ0_SLOTS = 0 | 2 << 8 | 4 << 16 | 10 << 24, WQ1_SLOTS = 12 | 14 << 8 | 18 << 16 | 22 << 24;
__host__ __device__ constexpr uint32_t xn_slot(int kb) { return (XN_SLOTS >> (8 * kb)) & 31; }
constexpr uint32_t SM_WKV = 208 * KB;
constexpr uint32_t SM_K = 0;
constexpr uint32_t SM_Q = 64 * KB;
constexpr uint32_t SM_V = 96 * KB;
constexpr uint32_t SM_MISC = 224 * KB;
constexpr uint32_t SMEM_BYTES = 227 * KB;
constexpr uint32_t SM_KTMP = 164 * KB;
constexpr uint32_t SM_RSTD = 226 * KB;
constexpr uint32_t SM_SENT = 208 * KB;
constexpr uint32_t MB_WQ = 0;
constexpr uint32_t MB_DONE = 4;
constexpr uint32_t MB_EMPTY = 9;
constexpr uint32_t MB_EPI = 15;
constexpr uint32_t MB_W1 = 16;
constexpr uint32_t MB_W2 = 24;
constexpr uint32_t MB_CS = 32;
constexpr uint32_t MB_KV = 33;
constexpr uint32_t MB_KV0 = 34;
constexpr uint32_t MB_MID = 35;
constexpr uint32_t MB_READY = 35;
constexpr uint32_t MB_STAT = 41;
constexpr uint32_t MB_FULL = 43;
constexpr uint32_t MB_NULL = 119;
constexpr uint32_t MB_WO = 120;
constexpr uint32_t MB_REL = 121;
constexpr uint32_t MISC_STAT = 2048;
constexpr uint32_t MISC_XBAR = 2304;
constexpr uint32_t MISC_NRM = 1056;
constexpr uint32_t MISC_EPOCH = 1072;
constexpr uint32_t MISC_TS = 1088;
constexpr uint32_t MISC_CS = 1344;

__host__ __device__ constexpr uint32_t wo_slot(int kb) { return kb < 2 ? 10 + kb : kb - 2; }
__host__ __device__ constexpr uint32_t w1_slot(int kb, int a) { return kb < 4 ? 12 + kb + 4 * a : (kb < 6 ? 3 * kb - 6 : 3 * kb - 18) + a; }

struct alignas(128) Small {
    unsigned epoch[160];
    unsigned cnt[100][32];
    float cs[1440];
    uint4 nrm[NMAIN * 4];
    uint4 kv[8192];
    uint4 kplain[4096];
};
__device__ Small g_s;
constexpr int C_KVH = 0, C_KV = 1, C_MID = 2, C_O = 3, C_H1 = 35, C_H2 = 67;
constexpr int X_O = 0, X_H1 = 32 * 32 * 128, X_H2 = 2 * X_H1, X_ST = X_H2 + 32 * 88 * 128, X_END = X_ST + 32 * 8 * 32;
constexpr int X_ARM = 16 * 32 * 128, X_SHARE = (X_END - X_ARM) / NMAIN;
__device__ uint4 g_x[X_END];
#define TS(i) do {} while (0)
#define TSF(k)

#define TS_ARG
#define TS_PASS

__device__ __forceinline__ void mbar_init(uint32_t bar, int cnt) { asm volatile("mbarrier.init.shared::cta.b64 [%0], %1;" :: "r"(bar), "r"(cnt) : "memory"); }
__device__ __forceinline__ void mbar_expect(uint32_t bar, uint32_t bytes) { asm volatile("mbarrier.arrive.expect_tx.shared::cta.b64 _, [%0], %1;" :: "r"(bar), "r"(bytes) : "memory"); }
__device__ __forceinline__ void mbar_arrive(uint32_t bar) { asm volatile("mbarrier.arrive.shared::cta.b64 _, [%0];" :: "r"(bar) : "memory"); }
__device__ __forceinline__ bool mbar_try(uint32_t bar, uint32_t parity) {
    uint32_t done;
    asm volatile("{.reg .pred p; mbarrier.try_wait.parity.shared::cta.b64 p, [%1], %2; selp.u32 %0, 1, 0, p;}" : "=r"(done) : "r"(bar), "r"(parity) : "memory");
    return __all_sync(0xffffffffu, done);
}
__device__ __forceinline__ void mbar_wait(uint32_t bar, uint32_t parity = 0) {
    if (__builtin_expect(!mbar_try(bar, parity), 0)) {
        int spins = 0;
        while (!mbar_try(bar, parity) && ++spins < (SPIN_LIMIT >> 6)) {}
    }
}
__device__ __forceinline__ void tma2d(uint32_t dst, const CUtensorMap* tm, int c0, int c1, uint32_t bar) {
    asm volatile("cp.async.bulk.tensor.2d.shared::cluster.global.mbarrier::complete_tx::bytes [%0], [%1, {%3, %4}], [%2];"
                 :: "r"(dst), "l"(tm), "r"(bar), "r"(c0), "r"(c1) : "memory");
}
__device__ __forceinline__ void bulk_g2s(uint32_t dst, const void* src, uint32_t bytes, uint32_t bar) {
    asm volatile("cp.async.bulk.shared::cluster.global.mbarrier::complete_tx::bytes [%0], [%1], %2, [%3];" :: "r"(dst), "l"(src), "r"(bytes), "r"(bar) : "memory");
}
__device__ __forceinline__ void fence_async_smem() { asm volatile("fence.proxy.async.shared::cta;" ::: "memory"); }
__device__ __forceinline__ void bar_sync(int id, int n) { asm volatile("bar.sync %0, %1;" :: "r"(id), "r"(n) : "memory"); }
__device__ __forceinline__ void bar_arrive(int id, int n) { asm volatile("bar.arrive %0, %1;" :: "r"(id), "r"(n) : "memory"); }
__device__ __forceinline__ void wg_fence() { asm volatile("wgmma.fence.sync.aligned;" ::: "memory"); }
__device__ __forceinline__ void wg_commit() { asm volatile("wgmma.commit_group.sync.aligned;" ::: "memory"); }
template <int N> __device__ __forceinline__ void wg_wait() { asm volatile("wgmma.wait_group.sync.aligned %0;" :: "n"(N) : "memory"); }
template <int N> __device__ __forceinline__ void fence_regs(float (&d)[N]) {
#pragma unroll
    for (int i = 0; i < N; i++) asm volatile("" : "+f"(d[i]) :: "memory");
}
template <int N> __device__ __forceinline__ void fence_regs(uint32_t (&d)[N]) {
#pragma unroll
    for (int i = 0; i < N; i++) asm volatile("" : "+r"(d[i]) :: "memory");
}
__device__ __forceinline__ uint64_t mkdesc(uint32_t addr, uint32_t lbo, uint32_t sbo, uint32_t swz) {
    return (uint64_t)(((addr & 0x3FFFF) >> 4) | ((lbo >> 4) << 16)) | ((uint64_t)((sbo >> 4) | (swz << 30)) << 32);
}
__device__ __forceinline__ float ex2(float x) { float y; asm("ex2.approx.ftz.f32 %0, %1;" : "=f"(y) : "f"(x)); return y; }
__device__ __forceinline__ float rcp(float x) { float y; asm("rcp.approx.ftz.f32 %0, %1;" : "=f"(y) : "f"(x)); return y; }
__device__ __forceinline__ uint32_t pack_bf16(float lo, float hi) { uint32_t r; asm("cvt.rn.bf16x2.f32 %0, %1, %2;" : "=r"(r) : "f"(hi), "f"(lo)); return r; }
__device__ __forceinline__ uint32_t pack_f16(float lo, float hi) { uint32_t r; asm("cvt.rn.f16x2.f32 %0, %1, %2;" : "=r"(r) : "f"(hi), "f"(lo)); return r; }
__device__ __forceinline__ float bf_lo(uint32_t v) { return __uint_as_float(v << 16); }
__device__ __forceinline__ float bf_hi(uint32_t v) { return __uint_as_float(v & 0xFFFF0000u); }
__device__ __forceinline__ uint4 ldg_relaxed(const uint4* p) {
    uint4 v; asm volatile("ld.relaxed.gpu.global.v4.u32 {%0,%1,%2,%3}, [%4];" : "=r"(v.x), "=r"(v.y), "=r"(v.z), "=r"(v.w) : "l"(p) : "memory"); return v;
}
__device__ __forceinline__ void stg128(void* p, uint32_t a, uint32_t b, uint32_t c, uint32_t d) {
    asm volatile("st.relaxed.gpu.global.v4.u32 [%0], {%1,%2,%3,%4};" :: "l"(p), "r"(a), "r"(b), "r"(c), "r"(d) : "memory");
}
__device__ __forceinline__ void stg128_if(bool c, void* p, uint32_t a, uint32_t b, uint32_t d, uint32_t e) {
    asm volatile("{.reg .pred p; setp.ne.u32 p, %5, 0; @p st.relaxed.gpu.global.v4.u32 [%0], {%1,%2,%3,%4};}" :: "l"(p), "r"(a), "r"(b), "r"(d), "r"(e), "r"((int)c) : "memory");
}
__device__ __forceinline__ void stg64(void* p, uint32_t a, uint32_t b) {
    asm volatile("st.relaxed.gpu.global.v2.u32 [%0], {%1,%2};" :: "l"(p), "r"(a), "r"(b) : "memory");
}
__device__ __forceinline__ void sts128(uint32_t a, uint32_t x, uint32_t y, uint32_t z, uint32_t w) {
    asm volatile("st.shared.v4.u32 [%0], {%1,%2,%3,%4};" :: "r"(a), "r"(x), "r"(y), "r"(z), "r"(w) : "memory");
}
__device__ __forceinline__ void sts32(uint32_t a, uint32_t x) { asm volatile("st.shared.u32 [%0], %1;" :: "r"(a), "r"(x) : "memory"); }
__device__ __forceinline__ float4 lds128f(uint32_t a) {
    float4 v; asm volatile("ld.shared.v4.f32 {%0,%1,%2,%3}, [%4];" : "=f"(v.x), "=f"(v.y), "=f"(v.z), "=f"(v.w) : "r"(a) : "memory"); return v;
}
__device__ __forceinline__ uint4 lds128(uint32_t a) {
    uint4 v; asm volatile("ld.shared.v4.u32 {%0,%1,%2,%3}, [%4];" : "=r"(v.x), "=r"(v.y), "=r"(v.z), "=r"(v.w) : "r"(a) : "memory"); return v;
}
__device__ __forceinline__ uint32_t lds32(uint32_t a) { uint32_t v; asm volatile("ld.shared.u32 %0, [%1];" : "=r"(v) : "r"(a) : "memory"); return v; }
__device__ __forceinline__ uint32_t nonzero(uint32_t w) { return w == 0u ? 0x8000u : w; }
__device__ __forceinline__ void stg32(void* p, uint32_t a) { asm volatile("st.global.u32 [%0], %1;" :: "l"(p), "r"(a) : "memory"); }
__device__ __forceinline__ uint32_t ldg32_relaxed(const void* p) { uint32_t v; asm volatile("ld.relaxed.gpu.global.u32 %0, [%1];" : "=r"(v) : "l"(p) : "memory"); return v; }
__device__ __forceinline__ void count_hint(int id) {
    if ((threadIdx.x & 31) == 0) asm volatile("red.relaxed.gpu.global.add.u32 [%0], 1;" :: "l"(g_s.cnt[id]) : "memory");
}
__device__ __forceinline__ void count_release(int id) {
    __syncwarp();
    if ((threadIdx.x & 31) == 0) asm volatile("red.release.gpu.global.add.u32 [%0], 1;" :: "l"(g_s.cnt[id]) : "memory");
    __syncwarp();
}
__device__ __forceinline__ void count_wait(int id, unsigned target) {
    uint32_t v; int spins = 0;
    do v = ldg32_relaxed(g_s.cnt[id]); while (__any_sync(0xffffffffu, v != target) && ++spins < SPIN_LIMIT);
    asm volatile("fence.acquire.gpu;" ::: "memory");
}
__device__ __forceinline__ void warp_done(uint32_t bar) {
    __syncwarp();
    asm volatile("{.reg .pred p; setp.eq.u32 p, %1, 0; @p mbarrier.arrive.shared::cta.b64 _, [%0];}" :: "r"(bar), "r"(threadIdx.x & 31) : "memory");
}
__device__ __forceinline__ uint32_t mul_bf16x2(uint32_t a, uint32_t b) { uint32_t r; asm("mul.rn.bf16x2 %0, %1, %2;" : "=r"(r) : "r"(a), "r"(b)); return r; }
__device__ __forceinline__ uint32_t fma_bf16x2(uint32_t a, uint32_t b, uint32_t c) { uint32_t r; asm("fma.rn.bf16x2 %0, %1, %2, %3;" : "=r"(r) : "r"(a), "r"(b), "r"(c)); return r; }
__device__ __forceinline__ uint32_t add_bf16x2(uint32_t a, uint32_t b) { uint32_t r; asm("add.rn.bf16x2 %0, %1, %2;" : "=r"(r) : "r"(a), "r"(b)); return r; }

#define R4(d, o) "+f"(d[o + 0]), "+f"(d[o + 1]), "+f"(d[o + 2]), "+f"(d[o + 3])
#define R8(d, o) R4(d, o), R4(d, o + 4)
#define R32(d) R8(d, 0), R8(d, 8), R8(d, 16), R8(d, 24)
#define D32 "{%0,%1,%2,%3,%4,%5,%6,%7,%8,%9,%10,%11,%12,%13,%14,%15,%16,%17,%18,%19,%20,%21,%22,%23,%24,%25,%26,%27,%28,%29,%30,%31}"
#define D64 "{%0,%1,%2,%3,%4,%5,%6,%7,%8,%9,%10,%11,%12,%13,%14,%15,%16,%17,%18,%19,%20,%21,%22,%23,%24,%25,%26,%27,%28,%29,%30,%31,%32,%33,%34,%35,%36,%37,%38,%39,%40,%41,%42,%43,%44,%45,%46,%47,%48,%49,%50,%51,%52,%53,%54,%55,%56,%57,%58,%59,%60,%61,%62,%63}"

__device__ __forceinline__ void mma_qk_f16(float (&d)[32], uint64_t da, uint64_t db) {
    asm volatile("{.reg .pred p; setp.eq.b32 p, 0, 0; wgmma.mma_async.sync.aligned.m64n64k16.f32.f16.f16 " D32 ", %32, %33, p, 1, 1, 0, 0;}"
                 : R32(d) : "l"(da), "l"(db));
}
__device__ __forceinline__ void mma_qk_bf16(float (&d)[32], uint64_t da, uint64_t db) {
    asm volatile("{.reg .pred p; setp.ne.b32 p, 0, 0; wgmma.mma_async.sync.aligned.m64n64k16.f32.bf16.bf16 " D32 ", %32, %33, p, 1, 1, 0, 0;}"
                 : R32(d) : "l"(da), "l"(db));
}
__device__ __forceinline__ void mma_pv(float (&d)[12], const uint32_t* a, uint64_t db) {
    asm volatile("{.reg .pred p; setp.eq.b32 p, 0, 0; wgmma.mma_async.sync.aligned.m64n24k16.f32.bf16.bf16 {%0,%1,%2,%3,%4,%5,%6,%7,%8,%9,%10,%11}, {%12,%13,%14,%15}, %16, p, 1, 1, 1;}"
                 : R8(d, 0), R4(d, 8) : "r"(a[0]), "r"(a[1]), "r"(a[2]), "r"(a[3]), "l"(db));
}
__device__ __forceinline__ void mma_ss128(float (&d)[64], uint64_t da, uint64_t db, int accum) {
    asm volatile("{.reg .pred p; setp.ne.b32 p, %66, 0; wgmma.mma_async.sync.aligned.m64n128k16.f32.bf16.bf16 " D64 ", %64, %65, p, 1, 1, 0, 1;}"
                 : R32(d), R8(d, 32), R8(d, 40), R8(d, 48), R8(d, 56) : "l"(da), "l"(db), "r"(accum));
}
__device__ __forceinline__ void stsm4(uint32_t addr, uint32_t a, uint32_t b, uint32_t c, uint32_t d) {
    asm volatile("stmatrix.sync.aligned.m8n8.x4.shared.b16 [%0], {%1,%2,%3,%4};" :: "r"(addr), "r"(a), "r"(b), "r"(c), "r"(d) : "memory");
}
__device__ __forceinline__ void mma_ss8(float (&d)[4], uint64_t da, uint64_t db, int accum) {
    asm volatile("{.reg .pred p; setp.ne.b32 p, %6, 0; wgmma.mma_async.sync.aligned.m64n8k16.f32.bf16.bf16 {%0,%1,%2,%3}, %4, %5, p, 1, 1, 0, 1;}"
                 : R4(d, 0) : "l"(da), "l"(db), "r"(accum));
}
__device__ __forceinline__ void mma_ss(float (&d)[32], uint64_t da, uint64_t db, int accum) {
    asm volatile("{.reg .pred p; setp.ne.b32 p, %34, 0; wgmma.mma_async.sync.aligned.m64n64k16.f32.bf16.bf16 " D32 ", %32, %33, p, 1, 1, 0, 1;}"
                 : R32(d) : "l"(da), "l"(db), "r"(accum));
}
__device__ __forceinline__ void mma_ss(float (&d)[88], uint64_t da, uint64_t db, int accum) {
    asm volatile("{.reg .pred p; setp.ne.b32 p, %90, 0; wgmma.mma_async.sync.aligned.m64n176k16.f32.bf16.bf16 " "{%0,%1,%2,%3,%4,%5,%6,%7,%8,%9,%10,%11,%12,%13,%14,%15,%16,%17,%18,%19,%20,%21,%22,%23,%24,%25,%26,%27,%28,%29,%30,%31,%32,%33,%34,%35,%36,%37,%38,%39,%40,%41,%42,%43,%44,%45,%46,%47,%48,%49,%50,%51,%52,%53,%54,%55,%56,%57,%58,%59,%60,%61,%62,%63,%64,%65,%66,%67,%68,%69,%70,%71,%72,%73,%74,%75,%76,%77,%78,%79,%80,%81,%82,%83,%84,%85,%86,%87}"
                 ", %88, %89, p, 1, 1, 0, 1;}"
                 : R32(d), R8(d, 32), R8(d, 40), R8(d, 48), R8(d, 56), R8(d, 64), R8(d, 72), R8(d, 80) : "l"(da), "l"(db), "r"(accum));
}

constexpr float EXP_MAGIC = 256.0f + 127.0f + 64.0f - 1.58621f + 0.00390625f;
#define MUFU_M 0x1111u
#define ALU_M 0x0000u
constexpr uint32_t MUFU_MASK = MUFU_M;
constexpr uint32_t ALU_MASK = ALU_M;
template <bool ALU>
__device__ __forceinline__ uint32_t exp2_pair(float y0, float y1, uint32_t cexp, uint32_t neg1) {
    uint32_t w, m, e, r;
    asm("prmt.b32 %0, %1, %2, 0x6521;" : "=r"(w) : "r"(__float_as_uint(y0)), "r"(__float_as_uint(y1)));
    asm("lop3.b32 %0, %1, 0x007F007F, %2, 0xEA;" : "=r"(m) : "r"(w), "r"(cexp));
    if (ALU) e = w - m;
    else asm("mad.lo.u32 %0, %1, %2, %3;" : "=r"(e) : "r"(m), "r"(neg1), "r"(w));
    asm("fma.rn.bf16x2 %0, %1, %2, %3;" : "=r"(r) : "r"(w), "r"(m), "r"(e));
    return r;
}

struct Params {
    const __nv_bfloat16* wqp;
    __nv_bfloat16* out;
    uint32_t neg1, pad;
    const __nv_bfloat16* w1p;
    const __nv_bfloat16* w2p;
    CUtensorMap wq, wo, w1, w2;
    const __nv_bfloat16* wop;
};

__device__ __forceinline__ int tail_m() { return (blockIdx.x >> 5) * 4 + ((blockIdx.x >> 2) & 3); }
__device__ __forceinline__ int tail_j() { return ((blockIdx.x >> 4) & 1) * 4 + (blockIdx.x & 3); }
__device__ __forceinline__ void load_box(uint32_t sb, const CUtensorMap* tm, uint32_t dst, uint32_t bar, uint32_t bytes, int c0, int c1) {
    mbar_expect(sb + SM_MISC + bar * 8, bytes);
    tma2d(sb + dst, tm, c0, c1, sb + SM_MISC + bar * 8);
}
__device__ __forceinline__ void load_wq(uint32_t sb, const Params& P, int gi, int atom) {
    load_box(sb, &P.wq, (((atom ? WQ1_SLOTS : WQ0_SLOTS) >> (8 * gi)) & 31) * SLOT, MB_WQ + gi, 16384, (blockIdx.x & 3) * 128 + atom * 64, gi * 128);
}
__device__ __forceinline__ void load_wo(uint32_t sb, const Params& P, int kb) { load_box(sb, &P.wo, wo_slot(kb) * SLOT, MB_WO, SLOT, tail_j() * 64, kb * 64); }
__device__ __forceinline__ void refill_job(uint32_t sb, const Params& P, int gi, int job) {
    const bool w1 = job < 3;
    load_box(sb, w1 ? &P.w1 : &P.wo, (w1 ? 12 + gi + 4 * job : 2 * gi + job - 3) * SLOT, w1 ? MB_W1 + gi : MB_WO, SLOT,
             tail_j() * (w1 ? 176 : 64) + (w1 ? job * 64 : 0), (w1 ? gi : 2 * gi + job - 1) * 64);
}

__host__ __device__ constexpr int ring_entry(int n) { return n < 32 ? (n & 3) : (n - 32) % 6; }
__host__ __device__ constexpr uint32_t ring_slot(int e) { return e < 4 ? 24 + e : e; }

template <int KIND> __host__ __device__ constexpr uint64_t b_slots(int first) {
    uint64_t v = 0;
    for (int i = first; i < first + 12; i++) v |= (uint64_t)((KIND == 0 ? wo_slot(i) : KIND == 1 ? w1_slot(i, 0) : w1_slot(i / 3, i % 3)) & 31) << (5 * (i - first));
    return v;
}
__device__ __forceinline__ uint64_t desc64(uint32_t lo, uint32_t hi) { uint64_t d; asm("mov.b64 %0, {%1, %2};" : "=l"(d) : "r"(lo), "r"(hi)); return d; }
__device__ __forceinline__ uint32_t mbar_test(uint32_t bar) {
    uint32_t done;
    asm volatile("{.reg .pred p; mbarrier.test_wait.parity.shared::cta.b64 p, [%1], 0; selp.u32 %0, 1, 0, p;}" : "=r"(done) : "r"(bar) : "memory");
    return done;
}
template <int KIND, int NACC>
__device__ __forceinline__ bool gemm_ss(float (&acc)[NACC], uint32_t sb, int pr TS_ARG) {
    const uint32_t mb = sb + SM_MISC;
    constexpr int NBLK = KIND == 2 ? 22 : 8, N0 = 16 * KIND;
    uint32_t full = mb + (MB_FULL + N0 + pr * NBLK) * 8, empty = mb + MB_NULL * 8, rel = mb + MB_NULL * 8;
    const uint32_t lane = threadIdx.x & 31, probe = sb + ((threadIdx.x >> 5) & 3) * 512 + (lane >> 4) * 2048 + (lane & 15) * 32 + (lane >> 2) * 4;
    uint32_t m = 0;
    constexpr uint32_t R4S = 24 | 25 << 5 | 26 << 10 | 27 << 15;
    uint32_t ra = KIND == 2 ? (pr ? (4 | 5 << 5 | R4S << 10) : (R4S | 4 << 20 | 5 << 25)) : (KIND == 0 && pr) ? (6 | 7 << 5 | 8 << 10 | 9 << 15) : R4S;
    uint64_t tab = b_slots<KIND>(0);
    const uint32_t a0 = (sb >> 4) | (8 << 16);
    uint32_t b0 = (sb >> 4) | ((KIND == 1 ? 4 * SLOT / 16 : 1) << 16);
    mbar_wait(full);
#pragma unroll 1
    for (int i = 0; i < NBLK; i++) {
        const uint32_t sa = ra & 31, da = a0 + sa * 512, db = b0 + ((uint32_t)tab & 31) * 512;
        full += (i == NBLK - 1) ? 0 : 8;
        const uint32_t ready = mbar_test(full);
        const uint32_t m0 = lds32(probe + sa * SLOT), m1 = lds32(probe + sa * SLOT + 4096);
        wg_fence();
#pragma unroll
        for (int s = 0; s < 4; s++) mma_ss(acc, desc64(da + s * 128, 16), desc64(db + s * 128, 0x40000040), s ? 1 : i);
        wg_commit();
        m = max(m, max(m0, m1));
        const uint32_t prev = empty, prel = rel;
        empty = mb + ((KIND == 0 && sa < 24) ? MB_NULL : MB_EMPTY + (sa & 7)) * 8;
        rel = mb + (KIND == 1 ? MB_REL + i : i == 3 ? MB_REL + 9 : MB_NULL) * 8;
        ra = KIND == 2 ? (ra >> 5) | (sa << 25) : i == 3 ? R4S : ra >> 5;
        tab = (KIND == 2 && i == 11) ? b_slots<KIND>(12) : tab >> 5;
        if (KIND == 1 && i == 3) b0 -= (3 * SLOT / 16) << 16;
        wg_wait<1>();
        warp_done(prev);
        if (KIND != 2) warp_done(prel);
        if (!__all_sync(0xffffffffu, ready)) mbar_wait(full);
    }
    bool bad = __any_sync(0xffffffffu, m == SENT);
    wg_wait<0>();
    fence_regs(acc);
    warp_done(empty);
    if (KIND != 2) warp_done(mb + (MB_REL + 8 - KIND) * 8);
    return __builtin_expect(bad, 0);
}
__device__ __forceinline__ void ring_feed(uint32_t sb, int e TS_ARG) {
    const uint32_t mb = sb + SM_MISC;
    uint32_t dst = sb + ring_slot(e) * SLOT, empty = mb + (MB_EMPTY + e) * 8;
    const bool lead = (threadIdx.x & 31) == 0;
    const uint4* base = g_x + tail_m() * 4096 + e * 512;
    uint32_t par = 0;
    auto fetch = [&](int n, const uint4* src, int job) {
        const uint32_t full = mb + (MB_FULL + n) * 8;
        if (lead) mbar_expect(full, SLOT);
        mbar_wait(empty, par); par ^= 1;
        if (job) mbar_wait(mb + (MB_READY + job) * 8);
        if (lead) bulk_g2s(dst, src, SLOT, full);
        __syncwarp();
    };
    if (e < 4) {
        fetch(4 + e, base + 2048, 0);
        if (lead) mbar_expect(mb + (MB_FULL + 8 + e) * 8, SLOT);
        mbar_wait(mb + (MB_DONE + 4) * 8);
        mbar_wait(mb + (MB_READY + 1) * 8);
        if (lead) bulk_g2s(sb + (6 + e) * SLOT, base + 65536, SLOT, mb + (MB_FULL + 8 + e) * 8);
        fetch(12 + e, base + 65536 + 2048, 0);
#pragma unroll 1
        for (int h = 0; h < 2; h++) {
            fetch(16 + 8 * h + e, base + X_H1 + h * 65536, 2 + h);
            fetch(20 + 8 * h + e, base + X_H1 + h * 65536 + 2048, 0);
        }
    } else {
#pragma unroll 1
        for (int h = 0; h < 2; h++) {
            const uint4* sp = g_x + X_ST + (h * 16 + tail_m()) * 256 + (threadIdx.x & 31);
            mbar_wait(mb + (MB_READY + 2 + h) * 8);
            uint4 u[8]; uint32_t m; int spins = 0;
            do {
                m = 0;
#pragma unroll
                for (int k = 0; k < 8; k++) u[k] = ldg_relaxed(sp + k * 32);
#pragma unroll
                for (int k = 0; k < 8; k++) m = max(m, u[k].x);
            } while (__any_sync(0xffffffffu, m == SENT) && ++spins < SPIN_LIMIT);
            float st[4] = {0.f, 0.f, 0.f, 0.f};
#pragma unroll
            for (int k = 0; k < 8; k++) { st[0] += __uint_as_float(u[k].x); st[1] += __uint_as_float(u[k].y); st[2] += __uint_as_float(u[k].z); st[3] += __uint_as_float(u[k].w); }
#pragma unroll
            for (int k = 0; k < 2; k++) {
                const float nmean = st[2 * k] * (-1.0f / D);
                st[2 * k + 1] = 0.5f * rsqrtf(fmaxf(fmaf(-nmean, nmean, st[2 * k + 1] * (1.0f / D)), 0.f) + 1e-5f);
                st[2 * k] = nmean * st[2 * k + 1];
            }
            sts128(mb + MISC_STAT + h * 512 + (threadIdx.x & 31) * 16, __float_as_uint(st[0]), __float_as_uint(st[1]), __float_as_uint(st[2]), __float_as_uint(st[3]));
            warp_done(mb + (MB_STAT + h) * 8);
        }
        mbar_wait(mb + (MB_REL + 7) * 8);
        par = 1;
    }
    const uint4* src = g_x + X_H2 + tail_m() * 88 * 128 + e * 512;
#pragma unroll 1
    for (int n = e; n < 44; n += 6, src += 6 * 512) {
        const bool second = n >= 22 && n < 28;
        if (second) src += 16 * 88 * 128 - 22 * 512;
        fetch(32 + n, src, n < 6 ? 4 : second ? 5 : 0);
        if (e == 4) {
            par ^= 1; dst += SLOT; empty += 8;
            fetch(33 + n, src + 512, 0);
            dst -= SLOT; empty -= 8;
        }
    }
}
__device__ float4 g_redo[NMAIN * 2 * 22 * 128];
__device__ __noinline__ void gemm_slow_impl(float4* out, int ntile, const uint4* a, int nst, const __nv_bfloat16* W, int ldw, int kmax, int n0) {
    const int lane = threadIdx.x & 31;
    const unsigned short* w = reinterpret_cast<const unsigned short*>(W);
    for (int j = 0; j < ntile; j++) {
        const uint32_t* p = reinterpret_cast<const uint32_t*>(a) + ((threadIdx.x >> 5) & 3) * 128 + lane;
        const int n = n0 + 8 * j + (lane >> 2);
        float d[4] = {0.f, 0.f, 0.f, 0.f};
        for (int st = 0; st < nst; st++, p += 512) {
            const int k = st * 16 + 2 * (lane & 3);
            uint32_t v0, v1, v2, v3, b0 = 0, b1 = 0; int spins = 0;
            do { v0 = ldg32_relaxed(p); v1 = ldg32_relaxed(p + 64); v2 = ldg32_relaxed(p + 32); v3 = ldg32_relaxed(p + 96); }
            while (__any_sync(0xffffffffu, max(max(v0, v1), max(v2, v3)) == SENT) && ++spins < SPIN_LIMIT);
            if (k < kmax && n < ldw) {
                const unsigned short* q = w + (size_t)k * ldw + n;
                b0 = q[0] | ((uint32_t)q[ldw] << 16); b1 = q[8 * ldw] | ((uint32_t)q[9 * ldw] << 16);
            }
            asm volatile("mma.sync.aligned.m16n8k16.row.col.f32.bf16.bf16.f32 {%0,%1,%2,%3}, {%4,%5,%6,%7}, {%8,%9}, {%0,%1,%2,%3};"
                         : R4(d, 0) : "r"(v0), "r"(v1), "r"(v2), "r"(v3), "r"(b0), "r"(b1));
        }
        out[j * 128] = make_float4(d[0], d[1], d[2], d[3]);
    }
}
template <int NACC>
__device__ __forceinline__ void gemm_slow(float (&acc)[NACC], const uint4* a, int nst, const __nv_bfloat16* W, int ldw, int kmax, int n0) {
    float4* tmp = g_redo + (blockIdx.x * 2 + (threadIdx.x >> 8)) * 22 * 128 + (threadIdx.x & 127);
    gemm_slow_impl(tmp, NACC / 4, a, nst, W, ldw, kmax, n0);
#pragma unroll
    for (int i = 0; i < NACC / 4; i++) { const float4 v = tmp[i * 128]; acc[4 * i] = v.x; acc[4 * i + 1] = v.y; acc[4 * i + 2] = v.z; acc[4 * i + 3] = v.w; }
}
__device__ __forceinline__ void store_tile(uint32_t* p, uint32_t r0k0, uint32_t r8k0, uint32_t r0k8, uint32_t r8k8) {
    stg32(p, r0k0); stg32(p + 32, r0k8); stg32(p + 64, r8k0); stg32(p + 96, r8k8);
}

__device__ __forceinline__ float quad_sum(float v) { v += __shfl_xor_sync(0xffffffffu, v, 1); v += __shfl_xor_sync(0xffffffffu, v, 2); return v; }
__device__ __forceinline__ float reduce4(const float (&st)[4], int lane) {
    const bool u16 = lane & 16, u8 = lane & 8;
    const float a0 = (u16 ? st[2] : st[0]) + __shfl_xor_sync(0xffffffffu, u16 ? st[0] : st[2], 16);
    const float a1 = (u16 ? st[3] : st[1]) + __shfl_xor_sync(0xffffffffu, u16 ? st[1] : st[3], 16);
    float v = (u8 ? a1 : a0) + __shfl_xor_sync(0xffffffffu, u8 ? a0 : a1, 8);
    v += __shfl_xor_sync(0xffffffffu, v, 4); v += __shfl_xor_sync(0xffffffffu, v, 2); v += __shfl_xor_sync(0xffffffffu, v, 1);
    return v;
}
__device__ __forceinline__ float silu2(float h) { float t; asm("tanh.approx.f32 %0, %1;" : "=f"(t) : "f"(h)); return fmaf(h, t, h); }

template <bool SAFE>
__device__ __forceinline__ void attention(const Params& P, uint32_t sb, int warp TS_ARG) {
    const uint32_t mb = sb + SM_MISC;
    const int tid = threadIdx.x, lane = tid & 31, b = blockIdx.x;
    const int wg = warp >> 2, ww = warp & 3, job = 3 - wg + 4 * ww;
    const uint32_t cexp = 0x9F809F80u + (tid >> 12);
    const uint32_t neg1 = P.neg1;
    unsigned cnt = 0;
    if (SAFE && warp == 8) cnt = ldg32_relaxed(g_s.cnt[C_KV]);
#pragma unroll 1
    for (int pass = 0; pass < 2; pass++) {
    float o[12], s[32];
    const uint64_t dq = mkdesc(sb + SM_Q + (pass * 4 + wg) * 2048, 128, 256, 0);
    uint64_t dk = mkdesc(sb + SM_K, 128, 256, 0), dv = mkdesc(sb + SM_V, 128, 32768, 0);
    float m0 = -INFINITY, m1 = -INFINITY;
#pragma unroll
    for (int i = 0; i < 12; i++) o[i] = 0.f;
#pragma unroll
    for (int i = 0; i < 32; i++) s[i] = ((MUFU_MASK >> (i / 2)) & 1) ? 0.f : EXP_MAGIC;
    fence_regs(s); fence_regs(o);
    wg_fence();
    if (SAFE) mma_qk_f16(s, dq, dk + 31 * 128); else mma_qk_bf16(s, dq, dk + 31 * 128);
    wg_commit();
    wg_wait<0>(); fence_regs(s);
#pragma unroll 1
    for (int u = pass ? 3 : (wg == 2) ? 0 : 1; u < (pass ? 8 : 3); u++) {
        int n = 2 * ((((wg == 2) ? 0x22444C31u : 0x22444C40u) >> (4 * u)) & 15);
#pragma unroll 1
        do {
            uint32_t p[16];
            if (SAFE) {
#pragma unroll
                for (int j = 0; j < 16; j++) {
                    if ((MUFU_MASK >> j) & 1) p[j] = pack_bf16(ex2(s[2 * j]), ex2(s[2 * j + 1]));
                    else if ((ALU_MASK >> j) & 1) p[j] = exp2_pair<true>(s[2 * j], s[2 * j + 1], cexp, neg1);
                    else p[j] = exp2_pair<false>(s[2 * j], s[2 * j + 1], cexp, neg1);
                }
            } else {
                fence_regs(o);
                float x0 = m0, x1 = m1;
#pragma unroll
                for (int j = 0; j < 8; j++) { x0 = fmaxf(x0, fmaxf(s[4 * j], s[4 * j + 1])); x1 = fmaxf(x1, fmaxf(s[4 * j + 2], s[4 * j + 3])); }
                x0 = fmaxf(x0, __shfl_xor_sync(0xffffffffu, x0, 1)); x0 = fmaxf(x0, __shfl_xor_sync(0xffffffffu, x0, 2));
                x1 = fmaxf(x1, __shfl_xor_sync(0xffffffffu, x1, 1)); x1 = fmaxf(x1, __shfl_xor_sync(0xffffffffu, x1, 2));
                const float c0 = ex2(m0 - x0), c1 = ex2(m1 - x1);
                m0 = x0; m1 = x1;
#pragma unroll
                for (int j = 0; j < 3; j++) { o[4 * j] *= c0; o[4 * j + 1] *= c0; o[4 * j + 2] *= c1; o[4 * j + 3] *= c1; }
#pragma unroll
                for (int j = 0; j < 8; j++) {
                    p[2 * j] = pack_bf16(ex2(s[4 * j] - m0), ex2(s[4 * j + 1] - m0));
                    p[2 * j + 1] = pack_bf16(ex2(s[4 * j + 2] - m1), ex2(s[4 * j + 3] - m1));
                }
                fence_regs(o);
            }
            fence_regs(p);
            wg_fence();
            if (SAFE) mma_qk_f16(s, dq, dk); else mma_qk_bf16(s, dq, dk);
#pragma unroll
            for (int j = 0; j < 4; j++) mma_pv(o, p + 4 * j, dv + j * 16);
            wg_commit();
            dk += 128; dv += 64;
            wg_wait<0>(); fence_regs(s);
        } while (--n > 0);
        if (u == 2 || u == 7) {
            fence_regs(o);
            const float i0 = rcp(o[8]), i1 = rcp(o[10]);
            if (u == 7) mbar_wait(mb + MB_MID * 8);
            store_tile(reinterpret_cast<uint32_t*>(g_x + X_O + (((u == 7) * 16 + (b >> 3)) * 32 + (b & 3) * 8 + 2 * wg + (ww >> 1)) * 128 + (((b >> 2) & 1) * 2 + (ww & 1)) * 32) + lane,
                       pack_bf16(o[0] * i0, o[1] * i0), pack_bf16(o[2] * i1, o[3] * i1), pack_bf16(o[4] * i0, o[5] * i0), pack_bf16(o[6] * i1, o[7] * i1));
            if (u == 2) asm volatile("cp.async.bulk.wait_group 0;" ::: "memory");
            else count_hint(C_O + 16 + (b >> 3));
            warp_done(mb + (MB_DONE + (u == 7) * 4) * 8);
            TS(5 + (u == 7));
        } else if (u >= 3) {
            if (u < 6) warp_done(mb + (MB_DONE + u - 2) * 8);
            if (job < (u == 3 ? 1 : 5)) {
                mbar_wait(mb + (MB_DONE + u - 3) * 8);
                if (u == 3) count_release(C_MID);
                else if (lane == 0) refill_job(sb, P, u - 4, job);
            } else if (u == 6) {
                if (job < 9) {
                    mbar_wait(mb + MB_MID * 8);
                    if (lane == 0) {
                        mbar_expect(mb + (MB_FULL + job - 5) * 8, SLOT);
                        bulk_g2s(sb + (19 + job) * SLOT, g_x + X_O + tail_m() * 4096 + (job - 5) * 512, SLOT, mb + (MB_FULL + job - 5) * 8);
                    }
                }
            } else if (warp == 7) {
                if (u == 4) cnt = ldg32_relaxed(g_s.cnt[C_MID]);
                if (u == 5) {
                    const unsigned target = lds32(mb + MISC_EPOCH) * NCTA;
                    if (__any_sync(0xffffffffu, cnt != target)) count_wait(C_MID, target);
                    asm volatile("fence.acquire.gpu; fence.proxy.async.global;" ::: "memory");
                    warp_done(mb + MB_MID * 8);
                }
            }
        } else if (u == 1) {
            if (SAFE) mbar_wait(mb + MB_KV * 8);
            TS(17);
            if (lane == 0) {
                if (job < 9) {
                    asm volatile("cp.async.bulk.global.shared::cta.bulk_group [%0], [%1], %2;"
                                 :: "l"(g_x + X_ARM + b * X_SHARE + job * 512), "r"(sb + SM_SENT), "r"(job < 8 ? 8192 : (X_SHARE - 4096) * 16) : "memory");
                    asm volatile("cp.async.bulk.commit_group;" ::: "memory");
                } else if (job < 11) load_wo(sb, P, job - 9);
            }
        } else if (SAFE) {
            if (warp == 8) {
                const unsigned target = lds32(mb + MISC_EPOCH) * NMAIN;
                if (__any_sync(0xffffffffu, cnt != target)) count_wait(C_KV, target);
                if (lane == 0) {
                    asm volatile("fence.acquire.gpu; fence.proxy.async.global;" ::: "memory");
                    mbar_expect(mb + MB_KV * 8, 47104 + 2 * 24576);
                    bulk_g2s(sb + SM_K + 16384, g_s.kv + 1024, 47104, mb + MB_KV * 8);
                    bulk_g2s(sb + SM_V + 8192, g_s.kv + 4096 + 512, 24576, mb + MB_KV * 8);
                    bulk_g2s(sb + SM_V + 32768 + 8192, g_s.kv + 6144 + 512, 24576, mb + MB_KV * 8);
                }
            }
        }
        __syncwarp();
    }
    }
}

__device__ __forceinline__ int kv_slot(int idx) {
    const int t = (idx & 63) >> 1, c = 2 * (blockIdx.x >> 2) + (idx & 1), hg = blockIdx.x & 3;
    return hg < 2 ? ((t + 31) & 31) * 128 + (c >> 3) * 16 + (hg & 1) * 8 + (c & 7) : 4096 + (hg & 1) * 2048 + t * 64 + c;
}

#define HOLDN 384
#define GATE_AT 2
__device__ __noinline__ void helper_cta(const Params& P, uint8_t* smem) {
    const int tid = threadIdx.x, b = blockIdx.x, hi = b - NMAIN;
    const unsigned epoch = g_s.epoch[b] + 1;
    float* red = reinterpret_cast<float*>(smem);
    if (tid < 32) count_wait(C_KV, epoch * NMAIN);
    __syncthreads();
    if (tid == 480) {
        for (int i = 0; i < 8; i++) asm volatile("cp.async.bulk.prefetch.L2.global [%0], %1;" :: "l"((const char*)P.wop + hi * 131072 + i * 16384), "r"(16384) : "memory");
        for (int i = 0; i < 43; i++) asm volatile("cp.async.bulk.prefetch.L2.global [%0], %1;" :: "l"((const char*)P.w2p + hi * 352256 + i * 8192), "r"(8192) : "memory");
    }
    if (tid < 344) {
        const int cg = tid % 43, rp = tid / 43;
        const uint4* src = reinterpret_cast<const uint4*>(P.w1p + (size_t)rp * 64 * FF + (hi * 43 + cg) * 8);
        float s[8] = {0, 0, 0, 0, 0, 0, 0, 0};
#pragma unroll 8
        for (int r = 0; r < 64; r++) {
            uint4 v = __ldg(src + r * (FF / 8));
            s[0] += bf_lo(v.x); s[1] += bf_hi(v.x); s[2] += bf_lo(v.y); s[3] += bf_hi(v.y);
            s[4] += bf_lo(v.z); s[5] += bf_hi(v.z); s[6] += bf_lo(v.w); s[7] += bf_hi(v.w);
        }
        float* part = red + (rp * 43 + cg) * 8;
#pragma unroll
        for (int i = 0; i < 8; i++) part[i] = s[i];
    }
    __syncthreads();
    if (tid < 344) {
        float s = 0.f;
#pragma unroll
        for (int rp = 0; rp < 8; rp++) s += red[rp * 344 + tid];
        g_s.cs[hi * 344 + tid] = s;
    } else if (hi == 3 && tid < 344 + 64) g_s.cs[FF + tid - 344] = 0.f;
    __syncthreads();
    if (tid < 32) count_release(C_MID);
    if (tid == 0) g_s.epoch[b] = epoch;
}

__global__ void __launch_bounds__(512, 1) fused_kernel(const __nv_bfloat16* __restrict__ x, const __nv_bfloat16* __restrict__ wk, long long wv_off,
                                                         const __grid_constant__ Params P) {
    extern __shared__ __align__(1024) uint8_t smem[];
    const uint32_t sb = (uint32_t)__cvta_generic_to_shared(smem);
    const uint32_t mb = sb + SM_MISC;
    const int tid = threadIdx.x, lane = tid & 31, b = blockIdx.x;
    if (b >= NMAIN) { helper_cta(P, smem); return; }
    const int tg = b >> 2, hg = b & 3;
    const int warp = __shfl_sync(0xffffffffu, tid >> 5, 0);

    const uint32_t xst = sb + (((0x160A1204u >> (8 * (warp >> 2))) & 31) * SLOT + (warp & 3) * 4096), xbar = mb + MISC_XBAR + warp * 8;
    if (lane == 0) {
        mbar_init(xbar, 1);
        asm volatile("fence.mbarrier_init.release.cluster;" ::: "memory");
        mbar_expect(xbar, 4096);
        bulk_g2s(xst, x + (size_t)((warp & 7) * 4 + tg * 32 + (warp >> 3) * 1024) * D, 4096, xbar);
    }
    const uint4 wkv = ldg_relaxed(reinterpret_cast<const uint4*>(reinterpret_cast<const char*>(wk) + (hg < 2 ? 0 : wv_off)) + tid * 2 + (hg & 1));
    unsigned epoch = 0;
    const int wg = warp >> 2, ww = warp & 3, g = lane >> 2, t4 = lane & 3, t128 = tid & 127;
    if (lane == 0) {
        if (warp < 4) {
            mbar_init(mb + (MB_WQ + warp) * 8, 2);
            asm volatile("fence.mbarrier_init.release.cluster;" ::: "memory");
            if (warp < 2) { load_wq(sb, P, warp, 0); load_wq(sb, P, warp, 1); }
            else asm volatile("cp.async.bulk.prefetch.L2.global [%0], %1;" :: "l"((const char*)P.wqp + 262144 + (b * 2 + warp - 2) * 1024), "r"(1024) : "memory");
        } else {
            if (warp < 8) asm volatile("prefetch.tensormap [%0];" :: "l"(&P.wq + (warp - 4)) : "memory");
            const uint32_t first = warp < 8 ? (0x78100904u >> (8 * (warp - 4))) & 255 : warp < 11 ? 14 * warp - 93 : 14 * warp - 95;
            const uint32_t end = warp < 8 ? (0x83131009u >> (8 * (warp - 4))) & 255 : warp < 11 ? 59 : 120;
            const uint32_t cnt = warp < 8 ? (0x08030410u >> (8 * (warp - 4))) & 255 : warp < 11 ? 1 : 2;
#pragma unroll
            for (uint32_t i = 0; i < 14; i++) if (first + i < end) mbar_init(mb + (first + i) * 8, cnt);
            if (warp == 7) sts128(mb + MISC_NRM, 0, 0, 0, 0);
        }
    }
    __syncwarp();
    TS(16);
    sts128(sb + SM_WKV + tid * 16, wkv.x, wkv.y, wkv.z, wkv.w);
    uint4 xv[4][2];
    mbar_wait(xbar);
#pragma unroll
    for (int i = 0; i < 8; i++) xv[i >> 1][i & 1] = lds128(xst + i * 512 + lane * 16);
    float dlt;
    {
        float st[4];
#pragma unroll
        for (int i = 0; i < 4; i++) {
            const uint32_t s = add_bf16x2(add_bf16x2(add_bf16x2(xv[i][0].x, xv[i][0].y), add_bf16x2(xv[i][0].z, xv[i][0].w)),
                                          add_bf16x2(add_bf16x2(xv[i][1].x, xv[i][1].y), add_bf16x2(xv[i][1].z, xv[i][1].w)));
            st[i] = bf_lo(s) + bf_hi(s);
        }
        TS(13);
        const float tot = reduce4(st, lane) * (-1.0f / D);
        const uint32_t nmr = pack_bf16(tot, tot);
        dlt = bf_lo(nmr) - tot;
        const uint32_t xa[2] = {sb + (((uint32_t)XN_SLOTS >> (lane & 24)) & 31) * SLOT + warp * 512, sb + (((uint32_t)(XN_SLOTS >> 32) >> (lane & 24)) & 31) * SLOT + warp * 512};
#pragma unroll
        for (int i = 0; i < 4; i++) {
            const uint32_t nm = __shfl_sync(0xffffffffu, nmr, i * 8);
            const uint32_t off = i * 128 + (((lane & 7) ^ ((warp & 1) * 4 + i)) << 4);
#pragma unroll
            for (int c = 0; c < 2; c++) {
                xv[i][c].x = add_bf16x2(xv[i][c].x, nm); xv[i][c].y = add_bf16x2(xv[i][c].y, nm);
                xv[i][c].z = add_bf16x2(xv[i][c].z, nm); xv[i][c].w = add_bf16x2(xv[i][c].w, nm);
                sts128(xa[c] + off, xv[i][c].x, xv[i][c].y, xv[i][c].z, xv[i][c].w);
            }
        }
    }
    fence_async_smem();
    TS(0);
    auto variances = [&]() {
        float st[4];
#pragma unroll
        for (int i = 0; i < 4; i++) {
            uint32_t a[2];
#pragma unroll
            for (int c = 0; c < 2; c++)
                a[c] = fma_bf16x2(xv[i][c].x, xv[i][c].x, fma_bf16x2(xv[i][c].y, xv[i][c].y, fma_bf16x2(xv[i][c].z, xv[i][c].z, mul_bf16x2(xv[i][c].w, xv[i][c].w))));
            st[i] = (bf_lo(a[0]) + bf_hi(a[0])) + (bf_lo(a[1]) + bf_hi(a[1]));
        }
        const float vs = reduce4(st, lane);
        if ((lane & 7) == 0) sts32(sb + SM_RSTD + (warp * 4 + (lane >> 3)) * 4, __float_as_uint(rsqrtf(fmaxf(vs * (1.0f / D) - dlt * dlt, 0.f) + 1e-5f)));
    };
    if (wg == 2) {
        float kv[4];
        const uint64_t da = mkdesc(sb, 16, 1024, 1), db = mkdesc(sb + SM_WKV, 128, 16, 0);
        bar_sync(7, 512);
        wg_fence();
#pragma unroll
        for (int s = 0; s < 32; s++) mma_ss8(kv, da + xn_slot(s >> 2) * 512 + (s & 3) * 2, db + s * 16, s);
        wg_commit();
        variances();
        wg_wait<0>(); fence_regs(kv);
        float2* kt = reinterpret_cast<float2*>(smem + SM_KTMP);
        kt[(ww * 16 + g) * 4 + t4] = make_float2(kv[0], kv[1]); kt[(ww * 16 + g + 8) * 4 + t4] = make_float2(kv[2], kv[3]);
        TS(24);
    } else {
        if (wg == 3) {
            if (ww == 0) epoch = ldg32_relaxed(g_s.epoch + b);
            bar_sync(7, 512);
            if (lane == 0) load_wq(sb, P, 2 + (ww >> 1), ww & 1);
            __syncwarp();
        } else bar_arrive(7, 512);
        variances();
    }
    uint4* const kvdst = (ww < 2 ? g_s.kv : g_s.kplain) + kv_slot(tid);
    __syncthreads();
    constexpr float QSCALE = 0.25f * 1.4426950408889634f;
    float qa[64];
    const uint32_t qbase = sb + SM_Q + (ww >> 1) * 8192 + (ww & 1) * 512 + lane * 16;
    if (wg == 0) {
        const float rs0 = __uint_as_float(lds32(sb + SM_RSTD + (ww * 16 + g) * 4)) * QSCALE, rs1 = __uint_as_float(lds32(sb + SM_RSTD + (ww * 16 + g + 8) * 4)) * QSCALE;
        mbar_wait(mb + MB_WQ * 8);
        bar_sync(2, 384);
#pragma unroll 1
        for (int i = 0; i < 4; i++) {
            const uint32_t s0 = (WQ0_SLOTS >> (8 * i)) & 31, s1 = (WQ1_SLOTS >> (8 * i)) & 31, xs = (uint32_t)(XN_SLOTS >> (16 * i));
            const uint64_t db = mkdesc(sb + s0 * SLOT, (s1 - s0) * SLOT, 1024, 1);
            const uint64_t da0 = mkdesc(sb + (xs & 31) * SLOT, 16, 1024, 1), da1 = mkdesc(sb + ((xs >> 8) & 31) * SLOT, 16, 1024, 1);
            mbar_wait(mb + (MB_WQ + i) * 8);
            wg_fence();
#pragma unroll
            for (int s = 0; s < 8; s++) mma_ss128(qa, (s < 4 ? da0 : da1) + (s & 3) * 2, db + s * 128, s ? 1 : i);
            wg_commit();
            wg_wait<1>();
            if (i == 1) bar_arrive(6, 160);
        }
        wg_wait<0>();
        fence_regs(qa);
        bar_arrive(5, 256);
        TS(1);
        float n0 = 0.f, n1 = 0.f;
#pragma unroll
        for (int h = 0; h < 8; h++) {
            const float* v = qa + 8 * h;
            stsm4(qbase + h * 1024, pack_f16(v[0] * rs0, v[1] * rs0), pack_f16(v[4] * rs0, v[5] * rs0), pack_f16(v[2] * rs1, v[3] * rs1), pack_f16(v[6] * rs1, v[7] * rs1));
            n0 = __uint_as_float(max(__float_as_uint(n0), __float_as_uint(v[0] * v[0] + v[1] * v[1] + v[4] * v[4] + v[5] * v[5])));
            n1 = __uint_as_float(max(__float_as_uint(n1), __float_as_uint(v[2] * v[2] + v[3] * v[3] + v[6] * v[6] + v[7] * v[7])));
        }
        const uint32_t nm = __reduce_max_sync(0xffffffffu, __float_as_uint(quad_sum(__uint_as_float(max(__float_as_uint(n0 * rs0 * rs0), __float_as_uint(n1 * rs1 * rs1))))));
        if (lane == 0) asm volatile("red.shared.max.u32 [%0], %1;" :: "r"(mb + MISC_NRM), "r"(nm) : "memory");
    } else if (wg == 2) {
        bar_sync(2, HOLDN);
#pragma unroll
        for (int i = 0; i < 4; i++) sts128(sb + SM_SENT + (i * 128 + t128) * 16, SENT, SENT, SENT, SENT);
#pragma unroll
        for (int i = 0; i < 16; i++) {
            if (i == 4) bar_sync(5, 256);
            sts128(sb + SM_V + 65536 + (i * 128 + t128) * 16, 0x3F803F80u, 0x3F803F80u, 0x3F803F80u, 0x3F803F80u);
        }
    } else if (wg == 1) {
        const int r = (lane & 1) * 32 + ((t128 & 63) >> 1);
        const uint32_t ra = sb + SM_KTMP + r * 32;
        float4 c0 = lds128f(ra), c1 = lds128f(ra + 16);
        const float rs = __uint_as_float(lds32(sb + SM_RSTD + r * 4));
        c0.x *= rs; c0.y *= rs; c0.z *= rs; c0.w *= rs; c1.x *= rs; c1.y *= rs; c1.z *= rs; c1.w *= rs;
        if (ww < 2 && hg < 2) {
            const float4 p0 = lds128f(ra - (r ? 32 : 0)), p1 = lds128f(ra - (r ? 16 : 0));
            const float rp = (r & 31) ? -__uint_as_float(lds32(sb + SM_RSTD + r * 4 - 4)) : 0.f;
            stg128(kvdst, nonzero(pack_f16(fmaf(p0.x, rp, c0.x), fmaf(p0.y, rp, c0.y))), nonzero(pack_f16(fmaf(p0.z, rp, c0.z), fmaf(p0.w, rp, c0.w))),
                   nonzero(pack_f16(fmaf(p1.x, rp, c1.x), fmaf(p1.y, rp, c1.y))), nonzero(pack_f16(fmaf(p1.z, rp, c1.z), fmaf(p1.w, rp, c1.w))));
        } else {
            if (ww >= 2) {
                const uint32_t nm = __reduce_max_sync(0xffffffffu, __float_as_uint((c0.x * c0.x + c0.y * c0.y) + (c0.z * c0.z + c0.w * c0.w) + (c1.x * c1.x + c1.y * c1.y) + (c1.z * c1.z + c1.w * c1.w))) | 1u;
                if (lane < 2) stg128(g_s.nrm + b * 4 + (ww - 2) * 2 + lane, nm, nm, nm, nm);
            }
            if (ww < 2 || hg < 2) stg128(kvdst, nonzero(pack_bf16(c0.x, c0.y)), nonzero(pack_bf16(c0.z, c0.w)), nonzero(pack_bf16(c1.x, c1.y)), nonzero(pack_bf16(c1.z, c1.w)));
        }
        if (ww < 2) count_hint(C_KVH);
        TS(1);
        if (ww < 3) bar_arrive(2, HOLDN);
        else { bar_sync(2, HOLDN); count_release(C_KV); }
    } else {
        epoch++;
        if (t128 == 0) { sts32(mb + MISC_EPOCH, epoch); g_s.epoch[b] = epoch; }
        if (ww == 0) count_wait(C_KVH, epoch * (2 * NMAIN));
        TS(1);
        bar_sync(3, 128);
        uint32_t nm = ldg32_relaxed(g_s.nrm + t128 * 4), nm2 = ldg32_relaxed(g_s.nrm + t128 * 4 + 2);
        if (ww == 0) bar_sync(6, 160);
        int spins = 0;
        bool bad;
        do {
            if (t128 == 0) {
                asm volatile("fence.proxy.async.global;" ::: "memory");
                mbar_expect(mb + MB_KV0 * 8, 34816);
                bulk_g2s(sb + SM_K + 31 * 2048, g_s.kv + 31 * 128, 2048, mb + MB_KV0 * 8);
                bulk_g2s(sb + SM_K, g_s.kv, 16384, mb + MB_KV0 * 8);
                bulk_g2s(sb + SM_V, g_s.kv + 4096, 8192, mb + MB_KV0 * 8);
                bulk_g2s(sb + SM_V + 32768, g_s.kv + 6144, 8192, mb + MB_KV0 * 8);
            }
            if (spins) { nm = ldg32_relaxed(g_s.nrm + t128 * 4); nm2 = ldg32_relaxed(g_s.nrm + t128 * 4 + 2); }
            __syncwarp();
            mbar_wait(mb + MB_KV0 * 8, spins & 1);
            const uint32_t probe = sb + (ww < 2 ? SM_K + ww * 8192 : SM_V + (ww - 2) * 32768) + lane * 32 + (lane >> 2) * 4;
            uint32_t mn = min(min(nm, nm2), lds32(sb + SM_K + 31 * 2048 + (ww & 1) * 1024 + lane * 32 + (lane >> 2) * 4));
#pragma unroll
            for (int k = 0; k < 8; k++) mn = min(mn, lds32(probe + k * 1024));
            uint32_t r;
            asm volatile("{.reg .pred p, q; setp.eq.u32 p, %1, 0; barrier.red.or.pred.aligned q, 3, 128, p; selp.u32 %0, 1, 0, q;}" : "=r"(r) : "r"(mn) : "memory");
            bad = __any_sync(0xffffffffu, r);
        } while (bad && ++spins < SPIN_LIMIT);
        TS(2);
        nm = max(nm, nm2);
        nm = max(nm, __shfl_xor_sync(0xffffffffu, nm, 4)); nm = max(nm, __shfl_xor_sync(0xffffffffu, nm, 8)); nm = max(nm, __shfl_xor_sync(0xffffffffu, nm, 16));
        if (lane < 4) asm volatile("red.shared.max.u32 [%0], %1;" :: "r"(mb + MISC_NRM + 4 + min(lane, 2) * 4), "r"(nm) : "memory");
    }
    fence_async_smem();
    TS(3);
    __syncthreads();
    const float4 nr = lds128f(mb + MISC_NRM);
    const bool safe = __all_sync(0xffffffffu, (nr.x * (nr.y + nr.z) <= 3500.0f) && (nr.x <= 65536.0f) && (nr.y + nr.z <= 65536.0f) && (nr.w <= 1e24f));
    TS(4);

    if (__builtin_expect(safe, 1)) {
        attention<true>(P, sb, warp TS_PASS);
    } else {
        if (wg == 0) {
            const float rs0 = __uint_as_float(lds32(sb + SM_RSTD + (ww * 16 + g) * 4)) * QSCALE, rs1 = __uint_as_float(lds32(sb + SM_RSTD + (ww * 16 + g + 8) * 4)) * QSCALE;
#pragma unroll
            for (int h = 0; h < 8; h++) {
                const float* v = qa + 8 * h;
                stsm4(qbase + h * 1024, pack_bf16(v[0] * rs0, v[1] * rs0), pack_bf16(v[4] * rs0, v[5] * rs0), pack_bf16(v[2] * rs1, v[3] * rs1), pack_bf16(v[6] * rs1, v[7] * rs1));
            }
            fence_async_smem();
        } else if (warp == 15) {
            count_wait(C_KV, lds32(mb + MISC_EPOCH) * NMAIN);
            if (lane == 0) {
                asm volatile("fence.proxy.async;" ::: "memory");
                mbar_expect(mb + MB_KV * 8, 131072);
                bulk_g2s(sb + SM_K, g_s.kplain, 65536, mb + MB_KV * 8);
                bulk_g2s(sb + SM_V, g_s.kv + 4096, 65536, mb + MB_KV * 8);
            }
            __syncwarp();
        }
        __syncthreads();
        mbar_wait(mb + MB_KV * 8);
        attention<false>(P, sb, warp TS_PASS);
    }

    const int j = tail_j();
    if (wg == 1 || wg == 2) {
        if (warp == 8) {
            epoch = lds32(mb + MISC_EPOCH);
#pragma unroll 1
            for (int job = 1; job < 6; job++) {
                count_wait(C_O + 32 * (job >> 1) + (job & 1) * 16 + tail_m(), epoch * (job == 1 ? 128 : 32));
                asm volatile("fence.proxy.async.global;" ::: "memory");
                warp_done(mb + (MB_READY + job) * 8);
                TS(18 + job);
            }
        } else if (warp == 9) {
#pragma unroll
            for (int i = 0; i < 2; i++) {
                if (lane < 22) {
                    const uint4 v = ldg_relaxed(reinterpret_cast<const uint4*>(g_s.cs + j * 176) + i * 22 + lane);
                    sts128(mb + MISC_CS + (i * 22 + lane) * 16, v.x, v.y, v.z, v.w);
                }
                stg128(g_s.kv + kv_slot(i * 32 + lane), 0u, 0u, 0u, 0u);
            }
            warp_done(mb + MB_CS * 8);
            if (lane < 4) stg128(g_s.nrm + b * 4 + lane, 0u, 0u, 0u, 0u);
#pragma unroll 1
            for (int i = 0; i < 16; i++) {
                mbar_wait(mb + (MB_W1 + i) * 8);
                const int n = i < 8 ? 16 + i + 8 * (lane & 1) : 32 + 3 * (i - 8) + (lane >> 1) + 22 * (lane & 1);
                if (lane < (i < 8 || i == 15 ? 2 : 6)) mbar_arrive(mb + (MB_FULL + n) * 8);
                __syncwarp();
            }
        } else {
            if (warp == 10) {
#pragma unroll 1
                for (int i = 3; i < 16; i++) {
                    const bool w1 = i < 8;
                    const int kb = i & 7;
                    const uint32_t bar = mb + (MB_W1 + i) * 8, dst = sb + w1_slot(kb, 0) * SLOT, step = kb < 4 ? 4 * SLOT : SLOT;
                    const CUtensorMap* tm = w1 ? &P.w1 : &P.w2;
                    const int c0 = w1 ? j * 176 : j * 64, c1 = w1 ? kb * 64 : kb * 192, d0 = w1 ? 64 : 0, d1 = 64 - d0;
                    if (lane == 0) mbar_expect(bar, i == 15 ? SLOT : 3 * SLOT);
                    mbar_wait(mb + (w1 ? (i == 3 ? MB_DONE + 4 : i < 6 ? MB_REL + 9 : MB_REL + 8) : MB_REL + kb) * 8);
                    if (i == 8 + GATE_AT) mbar_wait(mb + MB_EPI * 8);
                    if (lane == 0) {
                        tma2d(dst, tm, c0, c1, bar);
                        if (i < 15) { tma2d(dst + step, tm, c0 + d0, c1 + d1, bar); tma2d(dst + 2 * step, tm, c0 + 2 * d0, c1 + 2 * d1, bar); }
                    }
                    __syncwarp();
                }
            } else {
                ring_feed(sb, wg == 1 ? ww : 4 TS_PASS);
            }
        }
    } else {
        const int pr = (wg == 0), mt = 16 * pr + tail_m();
        uint32_t* const hp = reinterpret_cast<uint32_t*>(g_x + X_H1 + (mt * 32 + j * 4) * 128 + ww * 32) + lane;
        {
            uint32_t hk[16];
            const uint32_t* xp = reinterpret_cast<const uint32_t*>(x + (size_t)(mt * 64 + ww * 16 + g) * D + j * 64 + t4 * 2);
#pragma unroll
            for (int k = 0; k < 8; k++) { hk[2 * k] = __ldg(xp + k * 4); hk[2 * k + 1] = __ldg(xp + k * 4 + 8 * (D / 2)); }
            mbar_wait(mb + MB_WO * 8);
            float acc[32];
            if (gemm_ss<0>(acc, sb, pr TS_PASS)) gemm_slow(acc, g_x + X_O + mt * 32 * 128, 32, P.wop, D, D, j * 64);
            TS(7);
#pragma unroll
            for (int i = 0; i < 16; i++) hk[i] = pack_bf16(acc[2 * i] + bf_lo(hk[i]), acc[2 * i + 1] + bf_hi(hk[i]));
#pragma unroll
            for (int k = 0; k < 4; k++) store_tile(hp + k * 512, hk[4 * k], hk[4 * k + 1], hk[4 * k + 2], hk[4 * k + 3]);
            count_hint(C_H1 + mt);
            TS(8);
            float st[4] = {0.f, 0.f, 0.f, 0.f};
#pragma unroll
            for (int i = 0; i < 16; i++) {
                const float lo = bf_lo(hk[i]), hi = bf_hi(hk[i]);
                st[2 * (i & 1)] += lo + hi;
                st[2 * (i & 1) + 1] = fmaf(lo, lo, fmaf(hi, hi, st[2 * (i & 1) + 1]));
            }
#pragma unroll
            for (int o = 1; o < 4; o <<= 1)
#pragma unroll
                for (int i = 0; i < 4; i++) st[i] += __shfl_xor_sync(0xffffffffu, st[i], o);
            if (t4 == 0) stg128(g_x + X_ST + (mt * 8 + j) * 32 + ww * 8 + g, __float_as_uint(st[0]), __float_as_uint(st[1]), __float_as_uint(st[2]), __float_as_uint(st[3]));
        }
        {
            float acc[88];
            mbar_wait(mb + MB_CS * 8);
            if (gemm_ss<1>(acc, sb, pr TS_PASS)) gemm_slow(acc, g_x + X_H1 + mt * 32 * 128, 32, P.w1p, FF, D, j * 176);
            TS(9);
            mbar_wait(mb + (MB_STAT + pr) * 8);
            const float4 rs = lds128f(mb + MISC_STAT + pr * 512 + (ww * 8 + g) * 16);
            const float nmean[2] = {rs.x, rs.z}, hrstd[2] = {rs.y, rs.w};
            uint32_t* hb = reinterpret_cast<uint32_t*>(g_x + X_H2 + (mt * 88 + j * 11) * 128 + ww * 32) + lane;
#pragma unroll
            for (int i = 0; i < 22; i++) {
                float2 cs;
                asm volatile("ld.shared.v2.f32 {%0,%1}, [%2];" : "=f"(cs.x), "=f"(cs.y) : "r"(mb + MISC_CS + i * 32 + t4 * 8));
                const float* z = acc + 4 * i;
                uint32_t* p = hb + (i >> 1) * 512 + (i & 1) * 32;
                stg32(p, pack_bf16(silu2(fmaf(hrstd[0], z[0], nmean[0] * cs.x)), silu2(fmaf(hrstd[0], z[1], nmean[0] * cs.y))));
                stg32(p + 64, pack_bf16(silu2(fmaf(hrstd[1], z[2], nmean[1] * cs.x)), silu2(fmaf(hrstd[1], z[3], nmean[1] * cs.y))));
            }
            count_hint(C_H2 + mt);
            if (!pr) warp_done(mb + MB_EPI * 8);
            TS(10);
        }
        {
            uint32_t hk[16];
#pragma unroll
            for (int i = 0; i < 16; i++) hk[i] = ldg32_relaxed(hp + (i >> 2) * 512 + ((i & 1) * 2 + ((i >> 1) & 1)) * 32);
            float acc[32];
            if (gemm_ss<2>(acc, sb, pr TS_PASS)) gemm_slow(acc, g_x + X_H2 + mt * 88 * 128, 88, P.w2p, D, FF, j * 64);
            TS(11);
#pragma unroll
            for (int i = 0; i < 16; i++) hk[i] = pack_bf16(acc[2 * i] + bf_lo(hk[i]), acc[2 * i + 1] + bf_hi(hk[i]));
#pragma unroll
            for (int h = 0; h < 4; h++) {
                const uint32_t* v = hk + (h >> 1) * 8 + (h & 1);
                uint32_t v0 = v[0], v1 = v[2], v2 = v[4], v3 = v[6];
                const bool o1 = t4 & 1, o2 = t4 & 2;
                uint32_t a = __shfl_xor_sync(0xffffffffu, o1 ? v0 : v1, 1), c = __shfl_xor_sync(0xffffffffu, o1 ? v2 : v3, 1);
                if (o1) { v0 = a; v2 = c; } else { v1 = a; v3 = c; }
                a = __shfl_xor_sync(0xffffffffu, o2 ? v0 : v2, 2); c = __shfl_xor_sync(0xffffffffu, o2 ? v1 : v3, 2);
                if (o2) { v0 = a; v1 = c; } else { v2 = a; v3 = c; }
                *reinterpret_cast<uint4*>(P.out + (size_t)(mt * 64 + ww * 16 + g + 8 * (h & 1)) * D + j * 64 + (h >> 1) * 32 + t4 * 8) = make_uint4(v0, v1, v2, v3);
            }
        }
    }
    TS(12);
}

typedef CUresult (*EncodeFn)(CUtensorMap*, CUtensorMapDataType, cuuint32_t, void*, const cuuint64_t*, const cuuint64_t*, const cuuint32_t*,
                             const cuuint32_t*, CUtensorMapInterleave, CUtensorMapSwizzle, CUtensorMapL2promotion, CUtensorMapFloatOOBfill);

void encode2d(EncodeFn fn, CUtensorMap* tm, const void* ptr, int rows, int cols, int box_rows, int box_cols, CUtensorMapSwizzle sw) {
    cuuint64_t dims[2] = {(cuuint64_t)cols, (cuuint64_t)rows};
    cuuint64_t strides[1] = {(cuuint64_t)cols * 2};
    cuuint32_t box[2] = {(cuuint32_t)box_cols, (cuuint32_t)box_rows};
    cuuint32_t es[2] = {1, 1};
    fn(tm, CU_TENSOR_MAP_DATA_TYPE_BFLOAT16, 2, const_cast<void*>(ptr), dims, strides, box, es, CU_TENSOR_MAP_INTERLEAVE_NONE, sw,
       CU_TENSOR_MAP_L2_PROMOTION_L2_128B, CU_TENSOR_MAP_FLOAT_OOB_FILL_NONE);
}

}

extern "C" void kernel_launch(void* const* d_in, const int* in_sizes, int n_in, void* d_out, int out_size) {
    (void)in_sizes; (void)n_in; (void)out_size;
    void* fnp = nullptr;
    cudaDriverEntryPointQueryResult qr;
    cudaGetDriverEntryPoint("cuTensorMapEncodeTiled", &fnp, cudaEnableDefault, &qr);
    EncodeFn fn = (EncodeFn)fnp;
    Params P;
    encode2d(fn, &P.wq, d_in[1], D, D, 128, 64, CU_TENSOR_MAP_SWIZZLE_128B);
    encode2d(fn, &P.wo, d_in[4], D, D, 64, 64, CU_TENSOR_MAP_SWIZZLE_128B);
    encode2d(fn, &P.w1, d_in[6], D, FF, 64, 64, CU_TENSOR_MAP_SWIZZLE_128B);
    encode2d(fn, &P.w2, d_in[7], FF, D, 64, 64, CU_TENSOR_MAP_SWIZZLE_128B);
    P.w1p = (const __nv_bfloat16*)d_in[6];
    P.w2p = (const __nv_bfloat16*)d_in[7];
    P.wop = (const __nv_bfloat16*)d_in[4];
    P.wqp = (const __nv_bfloat16*)d_in[1];
    P.out = (__nv_bfloat16*)d_out;
    P.neg1 = 0xFFFFFFFFu; P.pad = 0;
    cudaFuncSetAttribute(fused_kernel, cudaFuncAttributeMaxDynamicSharedMemorySize, SMEM_BYTES);
    fused_kernel<<<NCTA, 512, SMEM_BYTES>>>((const __nv_bfloat16*)d_in[0], (const __nv_bfloat16*)d_in[2], (long long)((const char*)d_in[3] - (const char*)d_in[2]), P);
}
```

```cpp
#include <cuda_runtime.h>
#include <cuda_bf16.h>
#include <cuda.h>
#include <stdint.h>

namespace {

constexpr int D = 512, FF = 1376;
constexpr int NMAIN = 128, NHELP = 4, NCTA = NMAIN + NHELP;
constexpr uint32_t SENT = 0xFFFFFFFFu;
constexpr int SPIN_LIMIT = 1 << 22;

constexpr uint32_t KB = 1024, SLOT = 8192;
constexpr uint64_t XN_SLOTS = 7 | 16 << 8 | 6 << 16 | 17 << 24 | 21ull << 32 | 27ull << 40 | 24ull << 48 | 25ull << 56;
constexpr uint32_t WQ0_SLOTS = 0 | 2 << 8 | 4 << 16 | 10 << 24, WQ1_SLOTS = 12 | 14 << 8 | 18 << 16 | 22 << 24;
__host__ __device__ constexpr uint32_t xn_slot(int kb) { return (XN_SLOTS >> (8 * kb)) & 31; }
constexpr uint32_t SM_WKV = 208 * KB;
constexpr uint32_t SM_K = 0;
constexpr uint32_t SM_Q = 64 * KB;
constexpr uint32_t SM_V = 96 * KB;
constexpr uint32_t SM_MISC = 224 * KB;
constexpr uint32_t SMEM_BYTES = 227 * KB;
constexpr uint32_t SM_KTMP = 164 * KB;
constexpr uint32_t SM_RSTD = 226 * KB;
constexpr uint32_t SM_SENT = 208 * KB;
constexpr uint32_t MB_WQ = 0;
constexpr uint32_t MB_DONE = 4;
constexpr uint32_t MB_EMPTY = 9;
constexpr uint32_t MB_EPI = 15;
constexpr uint32_t MB_W1 = 16;
constexpr uint32_t MB_W2 = 24;
constexpr uint32_t MB_CS = 32;
constexpr uint32_t MB_KV = 33;
constexpr uint32_t MB_KV0 = 34;
constexpr uint32_t MB_MID = 35;
constexpr uint32_t MB_READY = 35;
constexpr uint32_t MB_STAT = 41;
constexpr uint32_t MB_FULL = 43;
constexpr uint32_t MB_NULL = 119;
constexpr uint32_t MB_WO = 120;
constexpr uint32_t MB_REL = 121;
constexpr uint32_t MISC_STAT = 2048;
constexpr uint32_t MISC_XBAR = 2304;
constexpr uint32_t MISC_NRM = 1056;
constexpr uint32_t MISC_EPOCH = 1072;
constexpr uint32_t MISC_TS = 1088;
constexpr uint32_t MISC_CS = 1344;

__host__ __device__ constexpr uint32_t wo_slot(int kb) { return kb < 2 ? 10 + kb : kb - 2; }
__host__ __device__ constexpr uint32_t w1_slot(int kb, int a) { return kb < 4 ? 12 + kb + 4 * a : (kb < 6 ? 3 * kb - 6 : 3 * kb - 18) + a; }

struct alignas(128) Small {
    unsigned epoch[160];
    unsigned cnt[100][32];
    float cs[1440];
    uint4 nrm[NMAIN * 4];
    uint4 kv[8192];
    uint4 kplain[4096];
};
__device__ Small g_s;
constexpr int C_KVH = 0, C_KV = 1, C_MID = 2, C_O = 3, C_H1 = 35, C_H2 = 67;
constexpr int X_O = 0, X_H1 = 32 * 32 * 128, X_H2 = 2 * X_H1, X_ST = X_H2 + 32 * 88 * 128, X_END = X_ST + 32 * 8 * 32;
constexpr int X_ARM = 16 * 32 * 128, X_SHARE = (X_END - X_ARM) / NMAIN;
__device__ uint4 g_x[X_END];
#define TS(i) do {} while (0)
#define TSF(k)

#define TS_ARG
#define TS_PASS

__device__ __forceinline__ void mbar_init(uint32_t bar, int cnt) { asm volatile("mbarrier.init.shared::cta.b64 [%0], %1;" :: "r"(bar), "r"(cnt) : "memory"); }
__device__ __forceinline__ void mbar_expect(uint32_t bar, uint32_t bytes) { asm volatile("mbarrier.arrive.expect_tx.shared::cta.b64 _, [%0], %1;" :: "r"(bar), "r"(bytes) : "memory"); }
__device__ __forceinline__ void mbar_arrive(uint32_t bar) { asm volatile("mbarrier.arrive.shared::cta.b64 _, [%0];" :: "r"(bar) : "memory"); }
__device__ __forceinline__ bool mbar_try(uint32_t bar, uint32_t parity) {
    uint32_t done;
    asm volatile("{.reg .pred p; mbarrier.try_wait.parity.shared::cta.b64 p, [%1], %2; selp.u32 %0, 1, 0, p;}" : "=r"(done) : "r"(bar), "r"(parity) : "memory");
    return __all_sync(0xffffffffu, done);
}
__device__ __forceinline__ void mbar_wait(uint32_t bar, uint32_t parity = 0) {
    if (__builtin_expect(!mbar_try(bar, parity), 0)) {
        int spins = 0;
        while (!mbar_try(bar, parity) && ++spins < (SPIN_LIMIT >> 6)) {}
    }
}
__device__ __forceinline__ void tma2d(uint32_t dst, const CUtensorMap* tm, int c0, int c1, uint32_t bar) {
    asm volatile("cp.async.bulk.tensor.2d.shared::cluster.global.mbarrier::complete_tx::bytes [%0], [%1, {%3, %4}], [%2];"
                 :: "r"(dst), "l"(tm), "r"(bar), "r"(c0), "r"(c1) : "memory");
}
__device__ __forceinline__ void bulk_g2s(uint32_t dst, const void* src, uint32_t bytes, uint32_t bar) {
    asm volatile("cp.async.bulk.shared::cluster.global.mbarrier::complete_tx::bytes [%0], [%1], %2, [%3];" :: "r"(dst), "l"(src), "r"(bytes), "r"(bar) : "memory");
}
__device__ __forceinline__ void fence_async_smem() { asm volatile("fence.proxy.async.shared::cta;" ::: "memory"); }
__device__ __forceinline__ void bar_sync(int id, int n) { asm volatile("bar.sync %0, %1;" :: "r"(id), "r"(n) : "memory"); }
__device__ __forceinline__ void bar_arrive(int id, int n) { asm volatile("bar.arrive %0, %1;" :: "r"(id), "r"(n) : "memory"); }
__device__ __forceinline__ void wg_fence() { asm volatile("wgmma.fence.sync.aligned;" ::: "memory"); }
__device__ __forceinline__ void wg_commit() { asm volatile("wgmma.commit_group.sync.aligned;" ::: "memory"); }
template <int N> __device__ __forceinline__ void wg_wait() { asm volatile("wgmma.wait_group.sync.aligned %0;" :: "n"(N) : "memory"); }
template <int N> __device__ __forceinline__ void fence_regs(float (&d)[N]) {
#pragma unroll
    for (int i = 0; i < N; i++) asm volatile("" : "+f"(d[i]) :: "memory");
}
template <int N> __device__ __forceinline__ void fence_regs(uint32_t (&d)[N]) {
#pragma unroll
    for (int i = 0; i < N; i++) asm volatile("" : "+r"(d[i]) :: "memory");
}
__device__ __forceinline__ uint64_t mkdesc(uint32_t addr, uint32_t lbo, uint32_t sbo, uint32_t swz) {
    return (uint64_t)(((addr & 0x3FFFF) >> 4) | ((lbo >> 4) << 16)) | ((uint64_t)((sbo >> 4) | (swz << 30)) << 32);
}
__device__ __forceinline__ float ex2(float x) { float y; asm("ex2.approx.ftz.f32 %0, %1;" : "=f"(y) : "f"(x)); return y; }
__device__ __forceinline__ float rcp(float x) { float y; asm("rcp.approx.ftz.f32 %0, %1;" : "=f"(y) : "f"(x)); return y; }
__device__ __forceinline__ uint32_t pack_bf16(float lo, float hi) { uint32_t r; asm("cvt.rn.bf16x2.f32 %0, %1, %2;" : "=r"(r) : "f"(hi), "f"(lo)); return r; }
__device__ __forceinline__ uint32_t pack_f16(float lo, float hi) { uint32_t r; asm("cvt.rn.f16x2.f32 %0, %1, %2;" : "=r"(r) : "f"(hi), "f"(lo)); return r; }
__device__ __forceinline__ float bf_lo(uint32_t v) { return __uint_as_float(v << 16); }
__device__ __forceinline__ float bf_hi(uint32_t v) { return __uint_as_float(v & 0xFFFF0000u); }
__device__ __forceinline__ uint4 ldg_relaxed(const uint4* p) {
    uint4 v; asm volatile("ld.relaxed.gpu.global.v4.u32 {%0,%1,%2,%3}, [%4];" : "=r"(v.x), "=r"(v.y), "=r"(v.z), "=r"(v.w) : "l"(p) : "memory"); return v;
}
__device__ __forceinline__ void stg128(void* p, uint32_t a, uint32_t b, uint32_t c, uint32_t d) {
    asm volatile("st.relaxed.gpu.global.v4.u32 [%0], {%1,%2,%3,%4};" :: "l"(p), "r"(a), "r"(b), "r"(c), "r"(d) : "memory");
}
__device__ __forceinline__ void stg128_if(bool c, void* p, uint32_t a, uint32_t b, uint32_t d, uint32_t e) {
    asm volatile("{.reg .pred p; setp.ne.u32 p, %5, 0; @p st.relaxed.gpu.global.v4.u32 [%0], {%1,%2,%3,%4};}" :: "l"(p), "r"(a), "r"(b), "r"(d), "r"(e), "r"((int)c) : "memory");
}
__device__ __forceinline__ void stg64(void* p, uint32_t a, uint32_t b) {
    asm volatile("st.relaxed.gpu.global.v2.u32 [%0], {%1,%2};" :: "l"(p), "r"(a), "r"(b) : "memory");
}
__device__ __forceinline__ void sts128(uint32_t a, uint32_t x, uint32_t y, uint32_t z, uint32_t w) {
    asm volatile("st.shared.v4.u32 [%0], {%1,%2,%3,%4};" :: "r"(a), "r"(x), "r"(y), "r"(z), "r"(w) : "memory");
}
__device__ __forceinline__ void sts32(uint32_t a, uint32_t x) { asm volatile("st.shared.u32 [%0], %1;" :: "r"(a), "r"(x) : "memory"); }
__device__ __forceinline__ float4 lds128f(uint32_t a) {
    float4 v; asm volatile("ld.shared.v4.f32 {%0,%1,%2,%3}, [%4];" : "=f"(v.x), "=f"(v.y), "=f"(v.z), "=f"(v.w) : "r"(a) : "memory"); return v;
}
__device__ __forceinline__ uint4 lds128(uint32_t a) {
    uint4 v; asm volatile("ld.shared.v4.u32 {%0,%1,%2,%3}, [%4];" : "=r"(v.x), "=r"(v.y), "=r"(v.z), "=r"(v.w) : "r"(a) : "memory"); return v;
}
__device__ __forceinline__ uint32_t lds32(uint32_t a) { uint32_t v; asm volatile("ld.shared.u32 %0, [%1];" : "=r"(v) : "r"(a) : "memory"); return v; }
__device__ __forceinline__ uint32_t nonzero(uint32_t w) { return w == 0u ? 0x8000u : w; }
__device__ __forceinline__ void stg32(void* p, uint32_t a) { asm volatile("st.global.u32 [%0], %1;" :: "l"(p), "r"(a) : "memory"); }
__device__ __forceinline__ uint32_t ldg32_relaxed(const void* p) { uint32_t v; asm volatile("ld.relaxed.gpu.global.u32 %0, [%1];" : "=r"(v) : "l"(p) : "memory"); return v; }
__device__ __forceinline__ void count_hint(int id) {
    if ((threadIdx.x & 31) == 0) asm volatile("red.relaxed.gpu.global.add.u32 [%0], 1;" :: "l"(g_s.cnt[id]) : "memory");
}
__device__ __forceinline__ void count_release(int id) {
    __syncwarp();
    if ((threadIdx.x & 31) == 0) asm volatile("red.release.gpu.global.add.u32 [%0], 1;" :: "l"(g_s.cnt[id]) : "memory");
    __syncwarp();
}
__device__ __forceinline__ void count_wait(int id, unsigned target) {
    uint32_t v; int spins = 0;
    do v = ldg32_relaxed(g_s.cnt[id]); while (__any_sync(0xffffffffu, v != target) && ++spins < SPIN_LIMIT);
    asm volatile("fence.acquire.gpu;" ::: "memory");
}
__device__ __forceinline__ void warp_done(uint32_t bar) {
    __syncwarp();
    asm volatile("{.reg .pred p; setp.eq.u32 p, %1, 0; @p mbarrier.arrive.shared::cta.b64 _, [%0];}" :: "r"(bar), "r"(threadIdx.x & 31) : "memory");
}
__device__ __forceinline__ uint32_t mul_bf16x2(uint32_t a, uint32_t b) { uint32_t r; asm("mul.rn.bf16x2 %0, %1, %2;" : "=r"(r) : "r"(a), "r"(b)); return r; }
__device__ __forceinline__ uint32_t fma_bf16x2(uint32_t a, uint32_t b, uint32_t c) { uint32_t r; asm("fma.rn.bf16x2 %0, %1, %2, %3;" : "=r"(r) : "r"(a), "r"(b), "r"(c)); return r; }
__device__ __forceinline__ uint32_t add_bf16x2(uint32_t a, uint32_t b) { uint32_t r; asm("add.rn.bf16x2 %0, %1, %2;" : "=r"(r) : "r"(a), "r"(b)); return r; }

#define R4(d, o) "+f"(d[o + 0]), "+f"(d[o + 1]), "+f"(d[o + 2]), "+f"(d[o + 3])
#define R8(d, o) R4(d, o), R4(d, o + 4)
#define R32(d) R8(d, 0), R8(d, 8), R8(d, 16), R8(d, 24)
#define D32 "{%0,%1,%2,%3,%4,%5,%6,%7,%8,%9,%10,%11,%12,%13,%14,%15,%16,%17,%18,%19,%20,%21,%22,%23,%24,%25,%26,%27,%28,%29,%30,%31}"
#define D64 "{%0,%1,%2,%3,%4,%5,%6,%7,%8,%9,%10,%11,%12,%13,%14,%15,%16,%17,%18,%19,%20,%21,%22,%23,%24,%25,%26,%27,%28,%29,%30,%31,%32,%33,%34,%35,%36,%37,%38,%39,%40,%41,%42,%43,%44,%45,%46,%47,%48,%49,%50,%51,%52,%53,%54,%55,%56,%57,%58,%59,%60,%61,%62,%63}"

__device__ __forceinline__ void mma_qk_f16(float (&d)[32], uint64_t da, uint64_t db) {
    asm volatile("{.reg .pred p; setp.eq.b32 p, 0, 0; wgmma.mma_async.sync.aligned.m64n64k16.f32.f16.f16 " D32 ", %32, %33, p, 1, 1, 0, 0;}"
                 : R32(d) : "l"(da), "l"(db));
}
__device__ __forceinline__ void mma_qk_bf16(float (&d)[32], uint64_t da, uint64_t db) {
    asm volatile("{.reg .pred p; setp.ne.b32 p, 0, 0; wgmma.mma_async.sync.aligned.m64n64k16.f32.bf16.bf16 " D32 ", %32, %33, p, 1, 1, 0, 0;}"
                 : R32(d) : "l"(da), "l"(db));
}
__device__ __forceinline__ void mma_pv(float (&d)[12], const uint32_t* a, uint64_t db) {
    asm volatile("{.reg .pred p; setp.eq.b32 p, 0, 0; wgmma.mma_async.sync.aligned.m64n24k16.f32.bf16.bf16 {%0,%1,%2,%3,%4,%5,%6,%7,%8,%9,%10,%11}, {%12,%13,%14,%15}, %16, p, 1, 1, 1;}"
                 : R8(d, 0), R4(d, 8) : "r"(a[0]), "r"(a[1]), "r"(a[2]), "r"(a[3]), "l"(db));
}
__device__ __forceinline__ void mma_ss128(float (&d)[64], uint64_t da, uint64_t db, int accum) {
    asm volatile("{.reg .pred p; setp.ne.b32 p, %66, 0; wgmma.mma_async.sync.aligned.m64n128k16.f32.bf16.bf16 " D64 ", %64, %65, p, 1, 1, 0, 1;}"
                 : R32(d), R8(d, 32), R8(d, 40), R8(d, 48), R8(d, 56) : "l"(da), "l"(db), "r"(accum));
}
__device__ __forceinline__ void stsm4(uint32_t addr, uint32_t a, uint32_t b, uint32_t c, uint32_t d) {
    asm volatile("stmatrix.sync.aligned.m8n8.x4.shared.b16 [%0], {%1,%2,%3,%4};" :: "r"(addr), "r"(a), "r"(b), "r"(c), "r"(d) : "memory");
}
__device__ __forceinline__ void mma_ss8(float (&d)[4], uint64_t da, uint64_t db, int accum) {
    asm volatile("{.reg .pred p; setp.ne.b32 p, %6, 0; wgmma.mma_async.sync.aligned.m64n8k16.f32.bf16.bf16 {%0,%1,%2,%3}, %4, %5, p, 1, 1, 0, 1;}"
                 : R4(d, 0) : "l"(da), "l"(db), "r"(accum));
}
__device__ __forceinline__ void mma_ss(float (&d)[32], uint64_t da, uint64_t db, int accum) {
    asm volatile("{.reg .pred p; setp.ne.b32 p, %34, 0; wgmma.mma_async.sync.aligned.m64n64k16.f32.bf16.bf16 " D32 ", %32, %33, p, 1, 1, 0, 1;}"
                 : R32(d) : "l"(da), "l"(db), "r"(accum));
}
__device__ __forceinline__ void mma_ss(float (&d)[88], uint64_t da, uint64_t db, int accum) {
    asm volatile("{.reg .pred p; setp.ne.b32 p, %90, 0; wgmma.mma_async.sync.aligned.m64n176k16.f32.bf16.bf16 " "{%0,%1,%2,%3,%4,%5,%6,%7,%8,%9,%10,%11,%12,%13,%14,%15,%16,%17,%18,%19,%20,%21,%22,%23,%24,%25,%26,%27,%28,%29,%30,%31,%32,%33,%34,%35,%36,%37,%38,%39,%40,%41,%42,%43,%44,%45,%46,%47,%48,%49,%50,%51,%52,%53,%54,%55,%56,%57,%58,%59,%60,%61,%62,%63,%64,%65,%66,%67,%68,%69,%70,%71,%72,%73,%74,%75,%76,%77,%78,%79,%80,%81,%82,%83,%84,%85,%86,%87}"
                 ", %88, %89, p, 1, 1, 0, 1;}"
                 : R32(d), R8(d, 32), R8(d, 40), R8(d, 48), R8(d, 56), R8(d, 64), R8(d, 72), R8(d, 80) : "l"(da), "l"(db), "r"(accum));
}

constexpr float EXP_MAGIC = 256.0f + 127.0f + 64.0f - 1.58621f + 0.00390625f;
#define MUFU_M 0x1111u
#define ATT_MODE 1
#define ALU_M 0x0000u
constexpr uint32_t MUFU_MASK = MUFU_M;
constexpr uint32_t ALU_MASK = ALU_M;
template <bool ALU>
__device__ __forceinline__ uint32_t exp2_pair(float y0, float y1, uint32_t cexp, uint32_t neg1) {
    uint32_t w, m, e, r;
    asm("prmt.b32 %0, %1, %2, 0x6521;" : "=r"(w) : "r"(__float_as_uint(y0)), "r"(__float_as_uint(y1)));
    asm("lop3.b32 %0, %1, 0x007F007F, %2, 0xEA;" : "=r"(m) : "r"(w), "r"(cexp));
    if (ALU) e = w - m;
    else asm("mad.lo.u32 %0, %1, %2, %3;" : "=r"(e) : "r"(m), "r"(neg1), "r"(w));
    asm("fma.rn.bf16x2 %0, %1, %2, %3;" : "=r"(r) : "r"(w), "r"(m), "r"(e));
    return r;
}

struct Params {
    const __nv_bfloat16* wqp;
    __nv_bfloat16* out;
    uint32_t neg1, pad;
    const __nv_bfloat16* w1p;
    const __nv_bfloat16* w2p;
    CUtensorMap wq, wo, w1, w2;
    const __nv_bfloat16* wop;
};

__device__ __forceinline__ int tail_m() { return (blockIdx.x >> 5) * 4 + ((blockIdx.x >> 2) & 3); }
__device__ __forceinline__ int tail_j() { return ((blockIdx.x >> 4) & 1) * 4 + (blockIdx.x & 3); }
__device__ __forceinline__ void load_box(uint32_t sb, const CUtensorMap* tm, uint32_t dst, uint32_t bar, uint32_t bytes, int c0, int c1) {
    mbar_expect(sb + SM_MISC + bar * 8, bytes);
    tma2d(sb + dst, tm, c0, c1, sb + SM_MISC + bar * 8);
}
__device__ __forceinline__ void load_wq(uint32_t sb, const Params& P, int gi, int atom) {
    load_box(sb, &P.wq, (((atom ? WQ1_SLOTS : WQ0_SLOTS) >> (8 * gi)) & 31) * SLOT, MB_WQ + gi, 16384, (blockIdx.x & 3) * 128 + atom * 64, gi * 128);
}
__device__ __forceinline__ void load_wo(uint32_t sb, const Params& P, int kb) { load_box(sb, &P.wo, wo_slot(kb) * SLOT, MB_WO, SLOT, tail_j() * 64, kb * 64); }
__device__ __forceinline__ void refill_job(uint32_t sb, const Params& P, int gi, int job) {
    const bool w1 = job < 3;
    load_box(sb, w1 ? &P.w1 : &P.wo, (w1 ? 12 + gi + 4 * job : 2 * gi + job - 3) * SLOT, w1 ? MB_W1 + gi : MB_WO, SLOT,
             tail_j() * (w1 ? 176 : 64) + (w1 ? job * 64 : 0), (w1 ? gi : 2 * gi + job - 1) * 64);
}

__host__ __device__ constexpr int ring_entry(int n) { return n < 32 ? (n & 3) : (n - 32) % 6; }
__host__ __device__ constexpr uint32_t ring_slot(int e) { return e < 4 ? 24 + e : e; }

template <int KIND> __host__ __device__ constexpr uint64_t b_slots(int first) {
    uint64_t v = 0;
    for (int i = first; i < first + 12; i++) v |= (uint64_t)((KIND == 0 ? wo_slot(i) : KIND == 1 ? w1_slot(i, 0) : w1_slot(i / 3, i % 3)) & 31) << (5 * (i - first));
    return v;
}
__device__ __forceinline__ uint64_t desc64(uint32_t lo, uint32_t hi) { uint64_t d; asm("mov.b64 %0, {%1, %2};" : "=l"(d) : "r"(lo), "r"(hi)); return d; }
__device__ __forceinline__ uint32_t mbar_test(uint32_t bar) {
    uint32_t done;
    asm volatile("{.reg .pred p; mbarrier.test_wait.parity.shared::cta.b64 p, [%1], 0; selp.u32 %0, 1, 0, p;}" : "=r"(done) : "r"(bar) : "memory");
    return done;
}
template <int KIND, int NACC>
__device__ __forceinline__ bool gemm_ss(float (&acc)[NACC], uint32_t sb, int pr TS_ARG) {
    const uint32_t mb = sb + SM_MISC;
    constexpr int NBLK = KIND == 2 ? 22 : 8, N0 = 16 * KIND;
    uint32_t full = mb + (MB_FULL + N0 + pr * NBLK) * 8, empty = mb + MB_NULL * 8, rel = mb + MB_NULL * 8;
    const uint32_t lane = threadIdx.x & 31, probe = sb + ((threadIdx.x >> 5) & 3) * 512 + (lane >> 4) * 2048 + (lane & 15) * 32 + (lane >> 2) * 4;
    uint32_t m = 0;
    constexpr uint32_t R4S = 24 | 25 << 5 | 26 << 10 | 27 << 15;
    uint32_t ra = KIND == 2 ? (pr ? (4 | 5 << 5 | R4S << 10) : (R4S | 4 << 20 | 5 << 25)) : (KIND == 0 && pr) ? (6 | 7 << 5 | 8 << 10 | 9 << 15) : R4S;
    uint64_t tab = b_slots<KIND>(0);
    const uint32_t a0 = (sb >> 4) | (8 << 16);
    uint32_t b0 = (sb >> 4) | ((KIND == 1 ? 4 * SLOT / 16 : 1) << 16);
    mbar_wait(full);
#pragma unroll 1
    for (int i = 0; i < NBLK; i++) {
        const uint32_t sa = ra & 31, da = a0 + sa * 512, db = b0 + ((uint32_t)tab & 31) * 512;
        full += (i == NBLK - 1) ? 0 : 8;
        const uint32_t ready = mbar_test(full);
        const uint32_t m0 = lds32(probe + sa * SLOT), m1 = lds32(probe + sa * SLOT + 4096);
        wg_fence();
#pragma unroll
        for (int s = 0; s < 4; s++) mma_ss(acc, desc64(da + s * 128, 16), desc64(db + s * 128, 0x40000040), s ? 1 : i);
        wg_commit();
        m = max(m, max(m0, m1));
        const uint32_t prev = empty, prel = rel;
        empty = mb + ((KIND == 0 && sa < 24) ? MB_NULL : MB_EMPTY + (sa & 7)) * 8;
        rel = mb + (KIND == 1 ? MB_REL + i : i == 3 ? MB_REL + 9 : MB_NULL) * 8;
        ra = KIND == 2 ? (ra >> 5) | (sa << 25) : i == 3 ? R4S : ra >> 5;
        tab = (KIND == 2 && i == 11) ? b_slots<KIND>(12) : tab >> 5;
        if (KIND == 1 && i == 3) b0 -= (3 * SLOT / 16) << 16;
        wg_wait<1>();
        warp_done(prev);
        if (KIND != 2) warp_done(prel);
        if (!__all_sync(0xffffffffu, ready)) mbar_wait(full);
    }
    bool bad = __any_sync(0xffffffffu, m == SENT);
    wg_wait<0>();
    fence_regs(acc);
    warp_done(empty);
    if (KIND != 2) warp_done(mb + (MB_REL + 8 - KIND) * 8);
    return __builtin_expect(bad, 0);
}
__device__ __forceinline__ void ring_feed(uint32_t sb, int e TS_ARG) {
    const uint32_t mb = sb + SM_MISC;
    uint32_t dst = sb + ring_slot(e) * SLOT, empty = mb + (MB_EMPTY + e) * 8;
    const bool lead = (threadIdx.x & 31) == 0;
    const uint4* base = g_x + tail_m() * 4096 + e * 512;
    uint32_t par = 0;
    auto fetch = [&](int n, const uint4* src, int job) {
        const uint32_t full = mb + (MB_FULL + n) * 8;
        if (lead) mbar_expect(full, SLOT);
        mbar_wait(empty, par); par ^= 1;
        if (job) mbar_wait(mb + (MB_READY + job) * 8);
        if (lead) bulk_g2s(dst, src, SLOT, full);
        __syncwarp();
    };
    if (e < 4) {
        fetch(4 + e, base + 2048, 0);
        if (lead) mbar_expect(mb + (MB_FULL + 8 + e) * 8, SLOT);
        mbar_wait(mb + (MB_DONE + 4) * 8);
        mbar_wait(mb + (MB_READY + 1) * 8);
        if (lead) bulk_g2s(sb + (6 + e) * SLOT, base + 65536, SLOT, mb + (MB_FULL + 8 + e) * 8);
        fetch(12 + e, base + 65536 + 2048, 0);
#pragma unroll 1
        for (int h = 0; h < 2; h++) {
            fetch(16 + 8 * h + e, base + X_H1 + h * 65536, 2 + h);
            fetch(20 + 8 * h + e, base + X_H1 + h * 65536 + 2048, 0);
        }
    } else {
#pragma unroll 1
        for (int h = 0; h < 2; h++) {
            const uint4* sp = g_x + X_ST + (h * 16 + tail_m()) * 256 + (threadIdx.x & 31);
            mbar_wait(mb + (MB_READY + 2 + h) * 8);
            uint4 u[8]; uint32_t m; int spins = 0;
            do {
                m = 0;
#pragma unroll
                for (int k = 0; k < 8; k++) u[k] = ldg_relaxed(sp + k * 32);
#pragma unroll
                for (int k = 0; k < 8; k++) m = max(m, u[k].x);
            } while (__any_sync(0xffffffffu, m == SENT) && ++spins < SPIN_LIMIT);
            float st[4] = {0.f, 0.f, 0.f, 0.f};
#pragma unroll
            for (int k = 0; k < 8; k++) { st[0] += __uint_as_float(u[k].x); st[1] += __uint_as_float(u[k].y); st[2] += __uint_as_float(u[k].z); st[3] += __uint_as_float(u[k].w); }
#pragma unroll
            for (int k = 0; k < 2; k++) {
                const float nmean = st[2 * k] * (-1.0f / D);
                st[2 * k + 1] = 0.5f * rsqrtf(fmaxf(fmaf(-nmean, nmean, st[2 * k + 1] * (1.0f / D)), 0.f) + 1e-5f);
                st[2 * k] = nmean * st[2 * k + 1];
            }
            sts128(mb + MISC_STAT + h * 512 + (threadIdx.x & 31) * 16, __float_as_uint(st[0]), __float_as_uint(st[1]), __float_as_uint(st[2]), __float_as_uint(st[3]));
            warp_done(mb + (MB_STAT + h) * 8);
        }
        mbar_wait(mb + (MB_REL + 7) * 8);
        par = 1;
    }
    const uint4* src = g_x + X_H2 + tail_m() * 88 * 128 + e * 512;
#pragma unroll 1
    for (int n = e; n < 44; n += 6, src += 6 * 512) {
        const bool second = n >= 22 && n < 28;
        if (second) src += 16 * 88 * 128 - 22 * 512;
        fetch(32 + n, src, n < 6 ? 4 : second ? 5 : 0);
        if (e == 4) {
            par ^= 1; dst += SLOT; empty += 8;
            fetch(33 + n, src + 512, 0);
            dst -= SLOT; empty -= 8;
        }
    }
}
__device__ float4 g_redo[NMAIN * 2 * 22 * 128];
__device__ __noinline__ void gemm_slow_impl(float4* out, int ntile, const uint4* a, int nst, const __nv_bfloat16* W, int ldw, int kmax, int n0) {
    const int lane = threadIdx.x & 31;
    const unsigned short* w = reinterpret_cast<const unsigned short*>(W);
    for (int j = 0; j < ntile; j++) {
        const uint32_t* p = reinterpret_cast<const uint32_t*>(a) + ((threadIdx.x >> 5) & 3) * 128 + lane;
        const int n = n0 + 8 * j + (lane >> 2);
        float d[4] = {0.f, 0.f, 0.f, 0.f};
        for (int st = 0; st < nst; st++, p += 512) {
            const int k = st * 16 + 2 * (lane & 3);
            uint32_t v0, v1, v2, v3, b0 = 0, b1 = 0; int spins = 0;
            do { v0 = ldg32_relaxed(p); v1 = ldg32_relaxed(p + 64); v2 = ldg32_relaxed(p + 32); v3 = ldg32_relaxed(p + 96); }
            while (__any_sync(0xffffffffu, max(max(v0, v1), max(v2, v3)) == SENT) && ++spins < SPIN_LIMIT);
            if (k < kmax && n < ldw) {
                const unsigned short* q = w + (size_t)k * ldw + n;
                b0 = q[0] | ((uint32_t)q[ldw] << 16); b1 = q[8 * ldw] | ((uint32_t)q[9 * ldw] << 16);
            }
            asm volatile("mma.sync.aligned.m16n8k16.row.col.f32.bf16.bf16.f32 {%0,%1,%2,%3}, {%4,%5,%6,%7}, {%8,%9}, {%0,%1,%2,%3};"
                         : R4(d, 0) : "r"(v0), "r"(v1), "r"(v2), "r"(v3), "r"(b0), "r"(b1));
        }
        out[j * 128] = make_float4(d[0], d[1], d[2], d[3]);
    }
}
template <int NACC>
__device__ __forceinline__ void gemm_slow(float (&acc)[NACC], const uint4* a, int nst, const __nv_bfloat16* W, int ldw, int kmax, int n0) {
    float4* tmp = g_redo + (blockIdx.x * 2 + (threadIdx.x >> 8)) * 22 * 128 + (threadIdx.x & 127);
    gemm_slow_impl(tmp, NACC / 4, a, nst, W, ldw, kmax, n0);
#pragma unroll
    for (int i = 0; i < NACC / 4; i++) { const float4 v = tmp[i * 128]; acc[4 * i] = v.x; acc[4 * i + 1] = v.y; acc[4 * i + 2] = v.z; acc[4 * i + 3] = v.w; }
}
__device__ __forceinline__ void store_tile(uint32_t* p, uint32_t r0k0, uint32_t r8k0, uint32_t r0k8, uint32_t r8k8) {
    stg32(p, r0k0); stg32(p + 32, r0k8); stg32(p + 64, r8k0); stg32(p + 96, r8k8);
}

__device__ __forceinline__ float quad_sum(float v) { v += __shfl_xor_sync(0xffffffffu, v, 1); v += __shfl_xor_sync(0xffffffffu, v, 2); return v; }
__device__ __forceinline__ float reduce4(const float (&st)[4], int lane) {
    const bool u16 = lane & 16, u8 = lane & 8;
    const float a0 = (u16 ? st[2] : st[0]) + __shfl_xor_sync(0xffffffffu, u16 ? st[0] : st[2], 16);
    const float a1 = (u16 ? st[3] : st[1]) + __shfl_xor_sync(0xffffffffu, u16 ? st[1] : st[3], 16);
    float v = (u8 ? a1 : a0) + __shfl_xor_sync(0xffffffffu, u8 ? a0 : a1, 8);
    v += __shfl_xor_sync(0xffffffffu, v, 4); v += __shfl_xor_sync(0xffffffffu, v, 2); v += __shfl_xor_sync(0xffffffffu, v, 1);
    return v;
}
__device__ __forceinline__ float silu2(float h) { float t; asm("tanh.approx.f32 %0, %1;" : "=f"(t) : "f"(h)); return fmaf(h, t, h); }

template <bool SAFE>
__device__ __forceinline__ void attention(const Params& P, uint32_t sb, int warp TS_ARG) {
    const uint32_t mb = sb + SM_MISC;
    const int tid = threadIdx.x, lane = tid & 31, b = blockIdx.x;
    const int wg = warp >> 2, ww = warp & 3, job = 3 - wg + 4 * ww;
    const uint32_t cexp = 0x9F809F80u + (tid >> 12);
    const uint32_t neg1 = P.neg1;
    unsigned cnt = 0;
    if (SAFE && warp == 8) cnt = ldg32_relaxed(g_s.cnt[C_KV]);
#pragma unroll 1
    for (int pass = 0; pass < 2; pass++) {
    float o[12], s[32];
    const uint64_t dq = mkdesc(sb + SM_Q + (pass * 4 + wg) * 2048, 128, 256, 0);
    uint64_t dk = mkdesc(sb + SM_K, 128, 256, 0), dv = mkdesc(sb + SM_V, 128, 32768, 0);
    float m0 = -INFINITY, m1 = -INFINITY;
#pragma unroll
    for (int i = 0; i < 12; i++) o[i] = 0.f;
#pragma unroll
    for (int i = 0; i < 32; i++) s[i] = ((MUFU_MASK >> (i / 2)) & 1) ? 0.f : EXP_MAGIC;
    fence_regs(s); fence_regs(o);
    wg_fence();
    if (SAFE) mma_qk_f16(s, dq, dk + 31 * 128); else mma_qk_bf16(s, dq, dk + 31 * 128);
    wg_commit();
    wg_wait<0>(); fence_regs(s);
#pragma unroll 1
    for (int u = pass ? 3 : (wg == 2) ? 0 : 1; u < (pass ? 8 : 3); u++) {
        int n = 2 * ((((wg == 2) ? 0x22444C31u : 0x22444C40u) >> (4 * u)) & 15);
        if (SAFE) {
            auto tile = [&](uint32_t (&p)[16]) {
#pragma unroll
                for (int j = 0; j < 16; j++) {
                    if ((MUFU_MASK >> j) & 1) p[j] = pack_bf16(ex2(s[2 * j]), ex2(s[2 * j + 1]));
                    else if ((ALU_MASK >> j) & 1) p[j] = exp2_pair<true>(s[2 * j], s[2 * j + 1], cexp, neg1);
                    else p[j] = exp2_pair<false>(s[2 * j], s[2 * j + 1], cexp, neg1);
                }
                fence_regs(p);
                wg_fence();
                if (ATT_MODE != 3) mma_qk_f16(s, dq, dk);
                if (ATT_MODE == 1) wg_commit();
#pragma unroll
                for (int j = 0; j < 4; j++) mma_pv(o, p + 4 * j, dv + j * 16);
                if (ATT_MODE == 3) mma_qk_f16(s, dq, dk);
                wg_commit();
                dk += 128; dv += 64;
                wg_wait<ATT_MODE == 1>(); fence_regs(s);
            };
#pragma unroll 1
            do {
                uint32_t p0[16], p1[16];
                tile(p0);
                if (ATT_MODE == 1) { tile(p1); n--; }
            } while (--n > 0);
            if (ATT_MODE == 1) wg_wait<0>();
        } else {
#pragma unroll 1
            do {
                uint32_t p[16];
                fence_regs(o);
                float x0 = m0, x1 = m1;
#pragma unroll
                for (int j = 0; j < 8; j++) { x0 = fmaxf(x0, fmaxf(s[4 * j], s[4 * j + 1])); x1 = fmaxf(x1, fmaxf(s[4 * j + 2], s[4 * j + 3])); }
                x0 = fmaxf(x0, __shfl_xor_sync(0xffffffffu, x0, 1)); x0 = fmaxf(x0, __shfl_xor_sync(0xffffffffu, x0, 2));
                x1 = fmaxf(x1, __shfl_xor_sync(0xffffffffu, x1, 1)); x1 = fmaxf(x1, __shfl_xor_sync(0xffffffffu, x1, 2));
                const float c0 = ex2(m0 - x0), c1 = ex2(m1 - x1);
                m0 = x0; m1 = x1;
#pragma unroll
                for (int j = 0; j < 3; j++) { o[4 * j] *= c0; o[4 * j + 1] *= c0; o[4 * j + 2] *= c1; o[4 * j + 3] *= c1; }
#pragma unroll
                for (int j = 0; j < 8; j++) {
                    p[2 * j] = pack_bf16(ex2(s[4 * j] - m0), ex2(s[4 * j + 1] - m0));
                    p[2 * j + 1] = pack_bf16(ex2(s[4 * j + 2] - m1), ex2(s[4 * j + 3] - m1));
                }
                fence_regs(o);
                fence_regs(p);
                wg_fence();
                mma_qk_bf16(s, dq, dk);
#pragma unroll
                for (int j = 0; j < 4; j++) mma_pv(o, p + 4 * j, dv + j * 16);
                wg_commit();
                dk += 128; dv += 64;
                wg_wait<0>(); fence_regs(s);
            } while (--n > 0);
        }
        if (u == 2 || u == 7) {
            fence_regs(o);
            const float i0 = rcp(o[8]), i1 = rcp(o[10]);
            if (u == 7) mbar_wait(mb + MB_MID * 8);
            store_tile(reinterpret_cast<uint32_t*>(g_x + X_O + (((u == 7) * 16 + (b >> 3)) * 32 + (b & 3) * 8 + 2 * wg + (ww >> 1)) * 128 + (((b >> 2) & 1) * 2 + (ww & 1)) * 32) + lane,
                       pack_bf16(o[0] * i0, o[1] * i0), pack_bf16(o[2] * i1, o[3] * i1), pack_bf16(o[4] * i0, o[5] * i0), pack_bf16(o[6] * i1, o[7] * i1));
            if (u == 2) asm volatile("cp.async.bulk.wait_group 0;" ::: "memory");
            else count_hint(C_O + 16 + (b >> 3));
            warp_done(mb + (MB_DONE + (u == 7) * 4) * 8);
            TS(5 + (u == 7));
        } else if (u >= 3) {
            if (u < 6) warp_done(mb + (MB_DONE + u - 2) * 8);
            if (job < (u == 3 ? 1 : 5)) {
                mbar_wait(mb + (MB_DONE + u - 3) * 8);
                if (u == 3) count_release(C_MID);
                else if (lane == 0) refill_job(sb, P, u - 4, job);
            } else if (u == 6) {
                if (job < 9) {
                    mbar_wait(mb + MB_MID * 8);
                    if (lane == 0) {
                        mbar_expect(mb + (MB_FULL + job - 5) * 8, SLOT);
                        bulk_g2s(sb + (19 + job) * SLOT, g_x + X_O + tail_m() * 4096 + (job - 5) * 512, SLOT, mb + (MB_FULL + job - 5) * 8);
                    }
                }
            } else if (warp == 7) {
                if (u == 4) cnt = ldg32_relaxed(g_s.cnt[C_MID]);
                if (u == 5) {
                    const unsigned target = lds32(mb + MISC_EPOCH) * NCTA;
                    if (__any_sync(0xffffffffu, cnt != target)) count_wait(C_MID, target);
                    asm volatile("fence.acquire.gpu; fence.proxy.async.global;" ::: "memory");
                    warp_done(mb + MB_MID * 8);
                }
            }
        } else if (u == 1) {
            if (SAFE) mbar_wait(mb + MB_KV * 8);
            TS(17);
            if (lane == 0) {
                if (job < 9) {
                    asm volatile("cp.async.bulk.global.shared::cta.bulk_group [%0], [%1], %2;"
                                 :: "l"(g_x + X_ARM + b * X_SHARE + job * 512), "r"(sb + SM_SENT), "r"(job < 8 ? 8192 : (X_SHARE - 4096) * 16) : "memory");
                    asm volatile("cp.async.bulk.commit_group;" ::: "memory");
                } else if (job < 11) load_wo(sb, P, job - 9);
            }
        } else if (SAFE) {
            if (warp == 8) {
                const unsigned target = lds32(mb + MISC_EPOCH) * NMAIN;
                if (__any_sync(0xffffffffu, cnt != target)) count_wait(C_KV, target);
                if (lane == 0) {
                    asm volatile("fence.acquire.gpu; fence.proxy.async.global;" ::: "memory");
                    mbar_expect(mb + MB_KV * 8, 47104 + 2 * 24576);
                    bulk_g2s(sb + SM_K + 16384, g_s.kv + 1024, 47104, mb + MB_KV * 8);
                    bulk_g2s(sb + SM_V + 8192, g_s.kv + 4096 + 512, 24576, mb + MB_KV * 8);
                    bulk_g2s(sb + SM_V + 32768 + 8192, g_s.kv + 6144 + 512, 24576, mb + MB_KV * 8);
                }
            }
        }
        __syncwarp();
    }
    }
}

__device__ __forceinline__ int kv_slot(int idx) {
    const int t = (idx & 63) >> 1, c = 2 * (blockIdx.x >> 2) + (idx & 1), hg = blockIdx.x & 3;
    return hg < 2 ? ((t + 31) & 31) * 128 + (c >> 3) * 16 + (hg & 1) * 8 + (c & 7) : 4096 + (hg & 1) * 2048 + t * 64 + c;
}

#define HOLDN 384
#define GATE_AT 2
__device__ __noinline__ void helper_cta(const Params& P, uint8_t* smem) {
    const int tid = threadIdx.x, b = blockIdx.x, hi = b - NMAIN;
    const unsigned epoch = g_s.epoch[b] + 1;
    float* red = reinterpret_cast<float*>(smem);
    if (tid < 32) count_wait(C_KV, epoch * NMAIN);
    __syncthreads();
    if (tid == 480) {
        for (int i = 0; i < 8; i++) asm volatile("cp.async.bulk.prefetch.L2.global [%0], %1;" :: "l"((const char*)P.wop + hi * 131072 + i * 16384), "r"(16384) : "memory");
        for (int i = 0; i < 43; i++) asm volatile("cp.async.bulk.prefetch.L2.global [%0], %1;" :: "l"((const char*)P.w2p + hi * 352256 + i * 8192), "r"(8192) : "memory");
    }
    if (tid < 344) {
        const int cg = tid % 43, rp = tid / 43;
        const uint4* src = reinterpret_cast<const uint4*>(P.w1p + (size_t)rp * 64 * FF + (hi * 43 + cg) * 8);
        float s[8] = {0, 0, 0, 0, 0, 0, 0, 0};
#pragma unroll 8
        for (int r = 0; r < 64; r++) {
            uint4 v = __ldg(src + r * (FF / 8));
            s[0] += bf_lo(v.x); s[1] += bf_hi(v.x); s[2] += bf_lo(v.y); s[3] += bf_hi(v.y);
            s[4] += bf_lo(v.z); s[5] += bf_hi(v.z); s[6] += bf_lo(v.w); s[7] += bf_hi(v.w);
        }
        float* part = red + (rp * 43 + cg) * 8;
#pragma unroll
        for (int i = 0; i < 8; i++) part[i] = s[i];
    }
    __syncthreads();
    if (tid < 344) {
        float s = 0.f;
#pragma unroll
        for (int rp = 0; rp < 8; rp++) s += red[rp * 344 + tid];
        g_s.cs[hi * 344 + tid] = s;
    } else if (hi == 3 && tid < 344 + 64) g_s.cs[FF + tid - 344] = 0.f;
    __syncthreads();
    if (tid < 32) count_release(C_MID);
    if (tid == 0) g_s.epoch[b] = epoch;
}

__global__ void __launch_bounds__(512, 1) fused_kernel(const __nv_bfloat16* __restrict__ x, const __nv_bfloat16* __restrict__ wk, long long wv_off,
                                                         const __grid_constant__ Params P) {
    extern __shared__ __align__(1024) uint8_t smem[];
    const uint32_t sb = (uint32_t)__cvta_generic_to_shared(smem);
    const uint32_t mb = sb + SM_MISC;
    const int tid = threadIdx.x, lane = tid & 31, b = blockIdx.x;
    if (b >= NMAIN) { helper_cta(P, smem); return; }
    const int tg = b >> 2, hg = b & 3;
    const int warp = __shfl_sync(0xffffffffu, tid >> 5, 0);

    const uint32_t xst = sb + (((0x160A1204u >> (8 * (warp >> 2))) & 31) * SLOT + (warp & 3) * 4096), xbar = mb + MISC_XBAR + warp * 8;
    if (lane == 0) {
        mbar_init(xbar, 1);
        asm volatile("fence.mbarrier_init.release.cluster;" ::: "memory");
        mbar_expect(xbar, 4096);
        bulk_g2s(xst, x + (size_t)((warp & 7) * 4 + tg * 32 + (warp >> 3) * 1024) * D, 4096, xbar);
    }
    const uint4 wkv = ldg_relaxed(reinterpret_cast<const uint4*>(reinterpret_cast<const char*>(wk) + (hg < 2 ? 0 : wv_off)) + tid * 2 + (hg & 1));
    unsigned epoch = 0;
    const int wg = warp >> 2, ww = warp & 3, g = lane >> 2, t4 = lane & 3, t128 = tid & 127;
    if (lane == 0) {
        if (warp < 4) {
            mbar_init(mb + (MB_WQ + warp) * 8, 2);
            asm volatile("fence.mbarrier_init.release.cluster;" ::: "memory");
            if (warp < 2) { load_wq(sb, P, warp, 0); load_wq(sb, P, warp, 1); }
            else asm volatile("cp.async.bulk.prefetch.L2.global [%0], %1;" :: "l"((const char*)P.wqp + 262144 + (b * 2 + warp - 2) * 1024), "r"(1024) : "memory");
        } else {
            if (warp < 8) asm volatile("prefetch.tensormap [%0];" :: "l"(&P.wq + (warp - 4)) : "memory");
            const uint32_t first = warp < 8 ? (0x78100904u >> (8 * (warp - 4))) & 255 : warp < 11 ? 14 * warp - 93 : 14 * warp - 95;
            const uint32_t end = warp < 8 ? (0x83131009u >> (8 * (warp - 4))) & 255 : warp < 11 ? 59 : 120;
            const uint32_t cnt = warp < 8 ? (0x08030410u >> (8 * (warp - 4))) & 255 : warp < 11 ? 1 : 2;
#pragma unroll
            for (uint32_t i = 0; i < 14; i++) if (first + i < end) mbar_init(mb + (first + i) * 8, cnt);
            if (warp == 7) sts128(mb + MISC_NRM, 0, 0, 0, 0);
        }
    }
    __syncwarp();
    TS(16);
    sts128(sb + SM_WKV + tid * 16, wkv.x, wkv.y, wkv.z, wkv.w);
    uint4 xv[4][2];
    mbar_wait(xbar);
#pragma unroll
    for (int i = 0; i < 8; i++) xv[i >> 1][i & 1] = lds128(xst + i * 512 + lane * 16);
    float dlt;
    {
        float st[4];
#pragma unroll
        for (int i = 0; i < 4; i++) {
            const uint32_t s = add_bf16x2(add_bf16x2(add_bf16x2(xv[i][0].x, xv[i][0].y), add_bf16x2(xv[i][0].z, xv[i][0].w)),
                                          add_bf16x2(add_bf16x2(xv[i][1].x, xv[i][1].y), add_bf16x2(xv[i][1].z, xv[i][1].w)));
            st[i] = bf_lo(s) + bf_hi(s);
        }
        TS(13);
        const float tot = reduce4(st, lane) * (-1.0f / D);
        const uint32_t nmr = pack_bf16(tot, tot);
        dlt = bf_lo(nmr) - tot;
        const uint32_t xa[2] = {sb + (((uint32_t)XN_SLOTS >> (lane & 24)) & 31) * SLOT + warp * 512, sb + (((uint32_t)(XN_SLOTS >> 32) >> (lane & 24)) & 31) * SLOT + warp * 512};
#pragma unroll
        for (int i = 0; i < 4; i++) {
            const uint32_t nm = __shfl_sync(0xffffffffu, nmr, i * 8);
            const uint32_t off = i * 128 + (((lane & 7) ^ ((warp & 1) * 4 + i)) << 4);
#pragma unroll
            for (int c = 0; c < 2; c++) {
                xv[i][c].x = add_bf16x2(xv[i][c].x, nm); xv[i][c].y = add_bf16x2(xv[i][c].y, nm);
                xv[i][c].z = add_bf16x2(xv[i][c].z, nm); xv[i][c].w = add_bf16x2(xv[i][c].w, nm);
                sts128(xa[c] + off, xv[i][c].x, xv[i][c].y, xv[i][c].z, xv[i][c].w);
            }
        }
    }
    fence_async_smem();
    TS(0);
    auto variances = [&]() {
        float st[4];
#pragma unroll
        for (int i = 0; i < 4; i++) {
            uint32_t a[2];
#pragma unroll
            for (int c = 0; c < 2; c++)
                a[c] = fma_bf16x2(xv[i][c].x, xv[i][c].x, fma_bf16x2(xv[i][c].y, xv[i][c].y, fma_bf16x2(xv[i][c].z, xv[i][c].z, mul_bf16x2(xv[i][c].w, xv[i][c].w))));
            st[i] = (bf_lo(a[0]) + bf_hi(a[0])) + (bf_lo(a[1]) + bf_hi(a[1]));
        }
        const float vs = reduce4(st, lane);
        if ((lane & 7) == 0) sts32(sb + SM_RSTD + (warp * 4 + (lane >> 3)) * 4, __float_as_uint(rsqrtf(fmaxf(vs * (1.0f / D) - dlt * dlt, 0.f) + 1e-5f)));
    };
    if (wg == 2) {
        float kv[4];
        const uint64_t da = mkdesc(sb, 16, 1024, 1), db = mkdesc(sb + SM_WKV, 128, 16, 0);
        bar_sync(7, 512);
        wg_fence();
#pragma unroll
        for (int s = 0; s < 32; s++) mma_ss8(kv, da + xn_slot(s >> 2) * 512 + (s & 3) * 2, db + s * 16, s);
        wg_commit();
        variances();
        wg_wait<0>(); fence_regs(kv);
        float2* kt = reinterpret_cast<float2*>(smem + SM_KTMP);
        kt[(ww * 16 + g) * 4 + t4] = make_float2(kv[0], kv[1]); kt[(ww * 16 + g + 8) * 4 + t4] = make_float2(kv[2], kv[3]);
        TS(24);
    } else {
        if (wg == 3) {
            if (ww == 0) epoch = ldg32_relaxed(g_s.epoch + b);
            bar_sync(7, 512);
            if (lane == 0) load_wq(sb, P, 2 + (ww >> 1), ww & 1);
            __syncwarp();
        } else bar_arrive(7, 512);
        variances();
    }
    uint4* const kvdst = (ww < 2 ? g_s.kv : g_s.kplain) + kv_slot(tid);
    __syncthreads();
    constexpr float QSCALE = 0.25f * 1.4426950408889634f;
    float qa[64];
    const uint32_t qbase = sb + SM_Q + (ww >> 1) * 8192 + (ww & 1) * 512 + lane * 16;
    if (wg == 0) {
        const float rs0 = __uint_as_float(lds32(sb + SM_RSTD + (ww * 16 + g) * 4)) * QSCALE, rs1 = __uint_as_float(lds32(sb + SM_RSTD + (ww * 16 + g + 8) * 4)) * QSCALE;
        mbar_wait(mb + MB_WQ * 8);
        bar_sync(2, 384);
#pragma unroll 1
        for (int i = 0; i < 4; i++) {
            const uint32_t s0 = (WQ0_SLOTS >> (8 * i)) & 31, s1 = (WQ1_SLOTS >> (8 * i)) & 31, xs = (uint32_t)(XN_SLOTS >> (16 * i));
            const uint64_t db = mkdesc(sb + s0 * SLOT, (s1 - s0) * SLOT, 1024, 1);
            const uint64_t da0 = mkdesc(sb + (xs & 31) * SLOT, 16, 1024, 1), da1 = mkdesc(sb + ((xs >> 8) & 31) * SLOT, 16, 1024, 1);
            mbar_wait(mb + (MB_WQ + i) * 8);
            wg_fence();
#pragma unroll
            for (int s = 0; s < 8; s++) mma_ss128(qa, (s < 4 ? da0 : da1) + (s & 3) * 2, db + s * 128, s ? 1 : i);
            wg_commit();
            wg_wait<1>();
            if (i == 1) bar_arrive(6, 160);
        }
        wg_wait<0>();
        fence_regs(qa);
        bar_arrive(5, 256);
        TS(1);
        float n0 = 0.f, n1 = 0.f;
#pragma unroll
        for (int h = 0; h < 8; h++) {
            const float* v = qa + 8 * h;
            stsm4(qbase + h * 1024, pack_f16(v[0] * rs0, v[1] * rs0), pack_f16(v[4] * rs0, v[5] * rs0), pack_f16(v[2] * rs1, v[3] * rs1), pack_f16(v[6] * rs1, v[7] * rs1));
            n0 = __uint_as_float(max(__float_as_uint(n0), __float_as_uint(v[0] * v[0] + v[1] * v[1] + v[4] * v[4] + v[5] * v[5])));
            n1 = __uint_as_float(max(__float_as_uint(n1), __float_as_uint(v[2] * v[2] + v[3] * v[3] + v[6] * v[6] + v[7] * v[7])));
        }
        const uint32_t nm = __reduce_max_sync(0xffffffffu, __float_as_uint(quad_sum(__uint_as_float(max(__float_as_uint(n0 * rs0 * rs0), __float_as_uint(n1 * rs1 * rs1))))));
        if (lane == 0) asm volatile("red.shared.max.u32 [%0], %1;" :: "r"(mb + MISC_NRM), "r"(nm) : "memory");
    } else if (wg == 2) {
        bar_sync(2, HOLDN);
#pragma unroll
        for (int i = 0; i < 4; i++) sts128(sb + SM_SENT + (i * 128 + t128) * 16, SENT, SENT, SENT, SENT);
#pragma unroll
        for (int i = 0; i < 16; i++) {
            if (i == 4) bar_sync(5, 256);
            sts128(sb + SM_V + 65536 + (i * 128 + t128) * 16, 0x3F803F80u, 0x3F803F80u, 0x3F803F80u, 0x3F803F80u);
        }
    } else if (wg == 1) {
        const int r = (lane & 1) * 32 + ((t128 & 63) >> 1);
        const uint32_t ra = sb + SM_KTMP + r * 32;
        float4 c0 = lds128f(ra), c1 = lds128f(ra + 16);
        const float rs = __uint_as_float(lds32(sb + SM_RSTD + r * 4));
        c0.x *= rs; c0.y *= rs; c0.z *= rs; c0.w *= rs; c1.x *= rs; c1.y *= rs; c1.z *= rs; c1.w *= rs;
        if (ww < 2 && hg < 2) {
            const float4 p0 = lds128f(ra - (r ? 32 : 0)), p1 = lds128f(ra - (r ? 16 : 0));
            const float rp = (r & 31) ? -__uint_as_float(lds32(sb + SM_RSTD + r * 4 - 4)) : 0.f;
            stg128(kvdst, nonzero(pack_f16(fmaf(p0.x, rp, c0.x), fmaf(p0.y, rp, c0.y))), nonzero(pack_f16(fmaf(p0.z, rp, c0.z), fmaf(p0.w, rp, c0.w))),
                   nonzero(pack_f16(fmaf(p1.x, rp, c1.x), fmaf(p1.y, rp, c1.y))), nonzero(pack_f16(fmaf(p1.z, rp, c1.z), fmaf(p1.w, rp, c1.w))));
        } else {
            if (ww >= 2) {
                const uint32_t nm = __reduce_max_sync(0xffffffffu, __float_as_uint((c0.x * c0.x + c0.y * c0.y) + (c0.z * c0.z + c0.w * c0.w) + (c1.x * c1.x + c1.y * c1.y) + (c1.z * c1.z + c1.w * c1.w))) | 1u;
                if (lane < 2) stg128(g_s.nrm + b * 4 + (ww - 2) * 2 + lane, nm, nm, nm, nm);
            }
            if (ww < 2 || hg < 2) stg128(kvdst, nonzero(pack_bf16(c0.x, c0.y)), nonzero(pack_bf16(c0.z, c0.w)), nonzero(pack_bf16(c1.x, c1.y)), nonzero(pack_bf16(c1.z, c1.w)));
        }
        if (ww < 2) count_hint(C_KVH);
        TS(1);
        if (ww < 3) bar_arrive(2, HOLDN);
        else { bar_sync(2, HOLDN); count_release(C_KV); }
    } else {
        epoch++;
        if (t128 == 0) { sts32(mb + MISC_EPOCH, epoch); g_s.epoch[b] = epoch; }
        const uint32_t kdst = sb + (ww == 0 ? SM_K + 31 * 2048 : ww == 1 ? SM_K : SM_V + (ww - 2) * 32768);
        const uint4* ksrc = g_s.kv + (ww == 0 ? 31 * 128 : ww == 1 ? 0 : ww * 2048);
        const uint32_t kbytes = ww == 0 ? 2048 : ww == 1 ? 16384 : 8192;
        if (t128 == 0) mbar_expect(mb + MB_KV0 * 8, 34816);
        if (ww == 1) bar_sync(6, 160);
        if (ww == 0) { count_wait(C_KVH, epoch * (2 * NMAIN)); asm volatile("fence.proxy.async.global;" ::: "memory"); }
        TS(1);
        bar_sync(3, 128);
        uint32_t nm, nm2;
        int spins = 0;
        bool bad;
        do {
            if (lane == 0) bulk_g2s(kdst, ksrc, kbytes, mb + MB_KV0 * 8);
            nm = ldg32_relaxed(g_s.nrm + t128 * 4); nm2 = ldg32_relaxed(g_s.nrm + t128 * 4 + 2);
            __syncwarp();
            mbar_wait(mb + MB_KV0 * 8, spins & 1);
            const uint32_t probe = sb + (ww < 2 ? SM_K + ww * 8192 : SM_V + (ww - 2) * 32768) + lane * 32 + (lane >> 2) * 4;
            uint32_t mn = min(min(nm, nm2), lds32(sb + SM_K + 31 * 2048 + (ww & 1) * 1024 + lane * 32 + (lane >> 2) * 4));
#pragma unroll
            for (int k = 0; k < 8; k++) mn = min(mn, lds32(probe + k * 1024));
            uint32_t r;
            asm volatile("{.reg .pred p, q; setp.eq.u32 p, %1, 0; barrier.red.or.pred.aligned q, 3, 128, p; selp.u32 %0, 1, 0, q;}" : "=r"(r) : "r"(mn) : "memory");
            bad = __any_sync(0xffffffffu, r);
            if (bad && t128 == 0) mbar_expect(mb + MB_KV0 * 8, 34816);
        } while (bad && ++spins < SPIN_LIMIT);
        TS(2);
        nm = max(nm, nm2);
        nm = max(nm, __shfl_xor_sync(0xffffffffu, nm, 4)); nm = max(nm, __shfl_xor_sync(0xffffffffu, nm, 8)); nm = max(nm, __shfl_xor_sync(0xffffffffu, nm, 16));
        if (lane < 4) asm volatile("red.shared.max.u32 [%0], %1;" :: "r"(mb + MISC_NRM + 4 + min(lane, 2) * 4), "r"(nm) : "memory");
    }
    fence_async_smem();
    TS(3);
    __syncthreads();
    const float4 nr = lds128f(mb + MISC_NRM);
    const bool safe = __all_sync(0xffffffffu, (nr.x * (nr.y + nr.z) <= 3500.0f) && (nr.x <= 65536.0f) && (nr.y + nr.z <= 65536.0f) && (nr.w <= 1e24f));
    TS(4);

    if (__builtin_expect(safe, 1)) {
        attention<true>(P, sb, warp TS_PASS);
    } else {
        if (wg == 0) {
            const float rs0 = __uint_as_float(lds32(sb + SM_RSTD + (ww * 16 + g) * 4)) * QSCALE, rs1 = __uint_as_float(lds32(sb + SM_RSTD + (ww * 16 + g + 8) * 4)) * QSCALE;
#pragma unroll
            for (int h = 0; h < 8; h++) {
                const float* v = qa + 8 * h;
                stsm4(qbase + h * 1024, pack_bf16(v[0] * rs0, v[1] * rs0), pack_bf16(v[4] * rs0, v[5] * rs0), pack_bf16(v[2] * rs1, v[3] * rs1), pack_bf16(v[6] * rs1, v[7] * rs1));
            }
            fence_async_smem();
        } else if (warp == 15) {
            count_wait(C_KV, lds32(mb + MISC_EPOCH) * NMAIN);
            if (lane == 0) {
                asm volatile("fence.proxy.async;" ::: "memory");
                mbar_expect(mb + MB_KV * 8, 131072);
                bulk_g2s(sb + SM_K, g_s.kplain, 65536, mb + MB_KV * 8);
                bulk_g2s(sb + SM_V, g_s.kv + 4096, 65536, mb + MB_KV * 8);
            }
            __syncwarp();
        }
        __syncthreads();
        mbar_wait(mb + MB_KV * 8);
        attention<false>(P, sb, warp TS_PASS);
    }

    const int j = tail_j();
    if (wg == 1 || wg == 2) {
        if (warp == 8) {
            epoch = lds32(mb + MISC_EPOCH);
#pragma unroll 1
            for (int job = 1; job < 6; job++) {
                count_wait(C_O + 32 * (job >> 1) + (job & 1) * 16 + tail_m(), epoch * (job == 1 ? 128 : 32));
                asm volatile("fence.proxy.async.global;" ::: "memory");
                warp_done(mb + (MB_READY + job) * 8);
                TS(18 + job);
            }
        } else if (warp == 9) {
#pragma unroll
            for (int i = 0; i < 2; i++) {
                if (lane < 22) {
                    const uint4 v = ldg_relaxed(reinterpret_cast<const uint4*>(g_s.cs + j * 176) + i * 22 + lane);
                    sts128(mb + MISC_CS + (i * 22 + lane) * 16, v.x, v.y, v.z, v.w);
                }
                stg128(g_s.kv + kv_slot(i * 32 + lane), 0u, 0u, 0u, 0u);
            }
            warp_done(mb + MB_CS * 8);
            if (lane < 4) stg128(g_s.nrm + b * 4 + lane, 0u, 0u, 0u, 0u);
#pragma unroll 1
            for (int i = 0; i < 16; i++) {
                mbar_wait(mb + (MB_W1 + i) * 8);
                const int n = i < 8 ? 16 + i + 8 * (lane & 1) : 32 + 3 * (i - 8) + (lane >> 1) + 22 * (lane & 1);
                if (lane < (i < 8 || i == 15 ? 2 : 6)) mbar_arrive(mb + (MB_FULL + n) * 8);
                __syncwarp();
            }
        } else {
            if (warp == 10) {
#pragma unroll 1
                for (int i = 3; i < 16; i++) {
                    const bool w1 = i < 8;
                    const int kb = i & 7;
                    const uint32_t bar = mb + (MB_W1 + i) * 8, dst = sb + w1_slot(kb, 0) * SLOT, step = kb < 4 ? 4 * SLOT : SLOT;
                    const CUtensorMap* tm = w1 ? &P.w1 : &P.w2;
                    const int c0 = w1 ? j * 176 : j * 64, c1 = w1 ? kb * 64 : kb * 192, d0 = w1 ? 64 : 0, d1 = 64 - d0;
                    if (lane == 0) mbar_expect(bar, i == 15 ? SLOT : 3 * SLOT);
                    mbar_wait(mb + (w1 ? (i == 3 ? MB_DONE + 4 : i < 6 ? MB_REL + 9 : MB_REL + 8) : MB_REL + kb) * 8);
                    if (i == 8 + GATE_AT) mbar_wait(mb + MB_EPI * 8);
                    if (lane == 0) {
                        tma2d(dst, tm, c0, c1, bar);
                        if (i < 15) { tma2d(dst + step, tm, c0 + d0, c1 + d1, bar); tma2d(dst + 2 * step, tm, c0 + 2 * d0, c1 + 2 * d1, bar); }
                    }
                    __syncwarp();
                }
            } else {
                ring_feed(sb, wg == 1 ? ww : 4 TS_PASS);
            }
        }
    } else {
        const int pr = (wg == 0), mt = 16 * pr + tail_m();
        uint32_t* const hp = reinterpret_cast<uint32_t*>(g_x + X_H1 + (mt * 32 + j * 4) * 128 + ww * 32) + lane;
        {
            uint32_t hk[16];
            const uint32_t* xp = reinterpret_cast<const uint32_t*>(x + (size_t)(mt * 64 + ww * 16 + g) * D + j * 64 + t4 * 2);
#pragma unroll
            for (int k = 0; k < 8; k++) { hk[2 * k] = __ldg(xp + k * 4); hk[2 * k + 1] = __ldg(xp + k * 4 + 8 * (D / 2)); }
            mbar_wait(mb + MB_WO * 8);
            float acc[32];
            if (gemm_ss<0>(acc, sb, pr TS_PASS)) gemm_slow(acc, g_x + X_O + mt * 32 * 128, 32, P.wop, D, D, j * 64);
            TS(7);
#pragma unroll
            for (int i = 0; i < 16; i++) hk[i] = pack_bf16(acc[2 * i] + bf_lo(hk[i]), acc[2 * i + 1] + bf_hi(hk[i]));
#pragma unroll
            for (int k = 0; k < 4; k++) store_tile(hp + k * 512, hk[4 * k], hk[4 * k + 1], hk[4 * k + 2], hk[4 * k + 3]);
            count_hint(C_H1 + mt);
            TS(8);
            float st[4] = {0.f, 0.f, 0.f, 0.f};
#pragma unroll
            for (int i = 0; i < 16; i++) {
                const float lo = bf_lo(hk[i]), hi = bf_hi(hk[i]);
                st[2 * (i & 1)] += lo + hi;
                st[2 * (i & 1) + 1] = fmaf(lo, lo, fmaf(hi, hi, st[2 * (i & 1) + 1]));
            }
#pragma unroll
            for (int o = 1; o < 4; o <<= 1)
#pragma unroll
                for (int i = 0; i < 4; i++) st[i] += __shfl_xor_sync(0xffffffffu, st[i], o);
            if (t4 == 0) stg128(g_x + X_ST + (mt * 8 + j) * 32 + ww * 8 + g, __float_as_uint(st[0]), __float_as_uint(st[1]), __float_as_uint(st[2]), __float_as_uint(st[3]));
        }
        {
            float acc[88];
            mbar_wait(mb + MB_CS * 8);
            if (gemm_ss<1>(acc, sb, pr TS_PASS)) gemm_slow(acc, g_x + X_H1 + mt * 32 * 128, 32, P.w1p, FF, D, j * 176);
            TS(9);
            mbar_wait(mb + (MB_STAT + pr) * 8);
            const float4 rs = lds128f(mb + MISC_STAT + pr * 512 + (ww * 8 + g) * 16);
            const float nmean[2] = {rs.x, rs.z}, hrstd[2] = {rs.y, rs.w};
            uint32_t* hb = reinterpret_cast<uint32_t*>(g_x + X_H2 + (mt * 88 + j * 11) * 128 + ww * 32) + lane;
#pragma unroll
            for (int i = 0; i < 22; i++) {
                float2 cs;
                asm volatile("ld.shared.v2.f32 {%0,%1}, [%2];" : "=f"(cs.x), "=f"(cs.y) : "r"(mb + MISC_CS + i * 32 + t4 * 8));
                const float* z = acc + 4 * i;
                uint32_t* p = hb + (i >> 1) * 512 + (i & 1) * 32;
                stg32(p, pack_bf16(silu2(fmaf(hrstd[0], z[0], nmean[0] * cs.x)), silu2(fmaf(hrstd[0], z[1], nmean[0] * cs.y))));
                stg32(p + 64, pack_bf16(silu2(fmaf(hrstd[1], z[2], nmean[1] * cs.x)), silu2(fmaf(hrstd[1], z[3], nmean[1] * cs.y))));
            }
            count_hint(C_H2 + mt);
            if (!pr) warp_done(mb + MB_EPI * 8);
            TS(10);
        }
        {
            uint32_t hk[16];
#pragma unroll
            for (int i = 0; i < 16; i++) hk[i] = ldg32_relaxed(hp + (i >> 2) * 512 + ((i & 1) * 2 + ((i >> 1) & 1)) * 32);
            float acc[32];
            if (gemm_ss<2>(acc, sb, pr TS_PASS)) gemm_slow(acc, g_x + X_H2 + mt * 88 * 128, 88, P.w2p, D, FF, j * 64);
            TS(11);
#pragma unroll
            for (int i = 0; i < 16; i++) hk[i] = pack_bf16(acc[2 * i] + bf_lo(hk[i]), acc[2 * i + 1] + bf_hi(hk[i]));
#pragma unroll
            for (int h = 0; h < 4; h++) {
                const uint32_t* v = hk + (h >> 1) * 8 + (h & 1);
                uint32_t v0 = v[0], v1 = v[2], v2 = v[4], v3 = v[6];
                const bool o1 = t4 & 1, o2 = t4 & 2;
                uint32_t a = __shfl_xor_sync(0xffffffffu, o1 ? v0 : v1, 1), c = __shfl_xor_sync(0xffffffffu, o1 ? v2 : v3, 1);
                if (o1) { v0 = a; v2 = c; } else { v1 = a; v3 = c; }
                a = __shfl_xor_sync(0xffffffffu, o2 ? v0 : v2, 2); c = __shfl_xor_sync(0xffffffffu, o2 ? v1 : v3, 2);
                if (o2) { v0 = a; v1 = c; } else { v2 = a; v3 = c; }
                *reinterpret_cast<uint4*>(P.out + (size_t)(mt * 64 + ww * 16 + g + 8 * (h & 1)) * D + j * 64 + (h >> 1) * 32 + t4 * 8) = make_uint4(v0, v1, v2, v3);
            }
        }
    }
    TS(12);
}

typedef CUresult (*EncodeFn)(CUtensorMap*, CUtensorMapDataType, cuuint32_t, void*, const cuuint64_t*, const cuuint64_t*, const cuuint32_t*,
                             const cuuint32_t*, CUtensorMapInterleave, CUtensorMapSwizzle, CUtensorMapL2promotion, CUtensorMapFloatOOBfill);

void encode2d(EncodeFn fn, CUtensorMap* tm, const void* ptr, int rows, int cols, int box_rows, int box_cols, CUtensorMapSwizzle sw) {
    cuuint64_t dims[2] = {(cuuint64_t)cols, (cuuint64_t)rows};
    cuuint64_t strides[1] = {(cuuint64_t)cols * 2};
    cuuint32_t box[2] = {(cuuint32_t)box_cols, (cuuint32_t)box_rows};
    cuuint32_t es[2] = {1, 1};
    fn(tm, CU_TENSOR_MAP_DATA_TYPE_BFLOAT16, 2, const_cast<void*>(ptr), dims, strides, box, es, CU_TENSOR_MAP_INTERLEAVE_NONE, sw,
       CU_TENSOR_MAP_L2_PROMOTION_L2_128B, CU_TENSOR_MAP_FLOAT_OOB_FILL_NONE);
}

}

extern "C" void kernel_launch(void* const* d_in, const int* in_sizes, int n_in, void* d_out, int out_size) {
    (void)in_sizes; (void)n_in; (void)out_size;
    void* fnp = nullptr;
    cudaDriverEntryPointQueryResult qr;
    cudaGetDriverEntryPoint("cuTensorMapEncodeTiled", &fnp, cudaEnableDefault, &qr);
    EncodeFn fn = (EncodeFn)fnp;
    Params P;
    encode2d(fn, &P.wq, d_in[1], D, D, 128, 64, CU_TENSOR_MAP_SWIZZLE_128B);
    encode2d(fn, &P.wo, d_in[4], D, D, 64, 64, CU_TENSOR_MAP_SWIZZLE_128B);
    encode2d(fn, &P.w1, d_in[6], D, FF, 64, 64, CU_TENSOR_MAP_SWIZZLE_128B);
    encode2d(fn, &P.w2, d_in[7], FF, D, 64, 64, CU_TENSOR_MAP_SWIZZLE_128B);
    P.w1p = (const __nv_bfloat16*)d_in[6];
    P.w2p = (const __nv_bfloat16*)d_in[7];
    P.wop = (const __nv_bfloat16*)d_in[4];
    P.wqp = (const __nv_bfloat16*)d_in[1];
    P.out = (__nv_bfloat16*)d_out;
    P.neg1 = 0xFFFFFFFFu; P.pad = 0;
    cudaFuncSetAttribute(fused_kernel, cudaFuncAttributeMaxDynamicSharedMemorySize, SMEM_BYTES);
    fused_kernel<<<NCTA, 512, SMEM_BYTES>>>((const __nv_bfloat16*)d_in[0], (const __nv_bfloat16*)d_in[2], (long long)((const char*)d_in[3] - (const char*)d_in[2]), P);
}
```

```cpp
#include <cuda_runtime.h>
#include <cuda_bf16.h>
#include <cuda.h>
#include <stdint.h>

namespace {

constexpr int D = 512, FF = 1376;
constexpr int NMAIN = 128, NHELP = 4, NCTA = NMAIN + NHELP;
constexpr uint32_t SENT = 0xFFFFFFFFu;
constexpr int SPIN_LIMIT = 1 << 22;

constexpr uint32_t KB = 1024, SLOT = 8192;
constexpr uint64_t XN_SLOTS = 7 | 16 << 8 | 6 << 16 | 17 << 24 | 21ull << 32 | 27ull << 40 | 24ull << 48 | 25ull << 56;
constexpr uint32_t WQ0_SLOTS = 0 | 2 << 8 | 4 << 16 | 10 << 24, WQ1_SLOTS = 12 | 14 << 8 | 18 << 16 | 22 << 24;
__host__ __device__ constexpr uint32_t xn_slot(int kb) { return (XN_SLOTS >> (8 * kb)) & 31; }
constexpr uint32_t SM_WKV = 208 * KB;
constexpr uint32_t SM_K = 0;
constexpr uint32_t SM_Q = 64 * KB;
constexpr uint32_t SM_V = 96 * KB;
constexpr uint32_t SM_MISC = 224 * KB;
constexpr uint32_t SMEM_BYTES = 227 * KB;
constexpr uint32_t SM_KTMP = 164 * KB;
constexpr uint32_t SM_RSTD = 226 * KB;
constexpr uint32_t SM_SENT = 208 * KB;
constexpr uint32_t MB_WQ = 0;
constexpr uint32_t MB_DONE = 4;
constexpr uint32_t MB_EMPTY = 9;
constexpr uint32_t MB_WOA = 15;
constexpr uint32_t MB_W1 = 16;
constexpr uint32_t MB_W2 = 24;
constexpr uint32_t MB_CS = 32;
constexpr uint32_t MB_KV = 33;
constexpr uint32_t MB_KV0 = 34;
constexpr uint32_t MB_MID = 35;
constexpr uint32_t MB_READY = 35;
constexpr uint32_t MB_STAT = 41;
constexpr uint32_t MB_FULL = 43;
constexpr uint32_t MB_NULL = 119;
constexpr uint32_t MB_WO = 120;
constexpr uint32_t MB_REL = 121;
constexpr uint32_t MB_RELW = 129;
constexpr uint32_t MISC_STAT = 2048;
constexpr uint32_t MISC_XBAR = 2304;
constexpr uint32_t MISC_NRM = 1104;
constexpr uint32_t MISC_EPOCH = 1096;
constexpr uint32_t MISC_TS = 1120;
constexpr uint32_t MISC_CS = 1344;

__host__ __device__ constexpr uint32_t wo_slot(int kb) { return kb < 2 ? 10 + kb : kb - 2; }
__host__ __device__ constexpr uint32_t w1_slot(int kb, int a) { return kb < 4 ? 12 + kb + 4 * a : (kb == 4 ? 0 : kb == 7 ? 3 : 3 * kb - 9) + a; }

struct alignas(128) Small {
    unsigned epoch[160];
    unsigned cnt[100][32];
    float cs[1440];
    uint4 nrm[NMAIN * 4];
    uint4 kv[8192];
    uint4 kplain[4096];
};
__device__ Small g_s;
constexpr int C_KVH = 0, C_KV = 1, C_MID = 2, C_O = 3, C_H1 = 35, C_H2 = 67;
constexpr int X_O = 0, X_H1 = 32 * 32 * 128, X_H2 = 2 * X_H1, X_ST = X_H2 + 32 * 88 * 128, X_END = X_ST + 32 * 8 * 32;
constexpr int X_ARM = 16 * 32 * 128, X_SHARE = (X_END - X_ARM) / NMAIN;
__device__ uint4 g_x[X_END];
#define TS(i) do {} while (0)
#define TSF(k)

#define TS_ARG
#define TS_PASS

__device__ __forceinline__ void mbar_init(uint32_t bar, int cnt) { asm volatile("mbarrier.init.shared::cta.b64 [%0], %1;" :: "r"(bar), "r"(cnt) : "memory"); }
__device__ __forceinline__ void mbar_expect(uint32_t bar, uint32_t bytes) { asm volatile("mbarrier.arrive.expect_tx.shared::cta.b64 _, [%0], %1;" :: "r"(bar), "r"(bytes) : "memory"); }
__device__ __forceinline__ void mbar_arrive(uint32_t bar) { asm volatile("mbarrier.arrive.shared::cta.b64 _, [%0];" :: "r"(bar) : "memory"); }
__device__ __forceinline__ bool mbar_try(uint32_t bar, uint32_t parity) {
    uint32_t done;
    asm volatile("{.reg .pred p; mbarrier.try_wait.parity.shared::cta.b64 p, [%1], %2; selp.u32 %0, 1, 0, p;}" : "=r"(done) : "r"(bar), "r"(parity) : "memory");
    return __all_sync(0xffffffffu, done);
}
__device__ __forceinline__ void mbar_wait(uint32_t bar, uint32_t parity = 0) {
    if (__builtin_expect(!mbar_try(bar, parity), 0)) {
        int spins = 0;
        while (!mbar_try(bar, parity) && ++spins < (SPIN_LIMIT >> 6)) {}
    }
}
__device__ __forceinline__ void tma2d(uint32_t dst, const CUtensorMap* tm, int c0, int c1, uint32_t bar) {
    asm volatile("cp.async.bulk.tensor.2d.shared::cluster.global.mbarrier::complete_tx::bytes [%0], [%1, {%3, %4}], [%2];"
                 :: "r"(dst), "l"(tm), "r"(bar), "r"(c0), "r"(c1) : "memory");
}
__device__ __forceinline__ void bulk_g2s(uint32_t dst, const void* src, uint32_t bytes, uint32_t bar) {
    asm volatile("cp.async.bulk.shared::cluster.global.mbarrier::complete_tx::bytes [%0], [%1], %2, [%3];" :: "r"(dst), "l"(src), "r"(bytes), "r"(bar) : "memory");
}
__device__ __forceinline__ void fence_async_smem() { asm volatile("fence.proxy.async.shared::cta;" ::: "memory"); }
__device__ __forceinline__ void bar_sync(int id, int n) { asm volatile("bar.sync %0, %1;" :: "r"(id), "r"(n) : "memory"); }
__device__ __forceinline__ void bar_arrive(int id, int n) { asm volatile("bar.arrive %0, %1;" :: "r"(id), "r"(n) : "memory"); }
__device__ __forceinline__ void wg_fence() { asm volatile("wgmma.fence.sync.aligned;" ::: "memory"); }
__device__ __forceinline__ void wg_commit() { asm volatile("wgmma.commit_group.sync.aligned;" ::: "memory"); }
template <int N> __device__ __forceinline__ void wg_wait() { asm volatile("wgmma.wait_group.sync.aligned %0;" :: "n"(N) : "memory"); }
template <int N> __device__ __forceinline__ void fence_regs(float (&d)[N]) {
#pragma unroll
    for (int i = 0; i < N; i++) asm volatile("" : "+f"(d[i]) :: "memory");
}
template <int N> __device__ __forceinline__ void fence_regs(uint32_t (&d)[N]) {
#pragma unroll
    for (int i = 0; i < N; i++) asm volatile("" : "+r"(d[i]) :: "memory");
}
__device__ __forceinline__ uint64_t mkdesc(uint32_t addr, uint32_t lbo, uint32_t sbo, uint32_t swz) {
    return (uint64_t)(((addr & 0x3FFFF) >> 4) | ((lbo >> 4) << 16)) | ((uint64_t)((sbo >> 4) | (swz << 30)) << 32);
}
__device__ __forceinline__ float ex2(float x) { float y; asm("ex2.approx.ftz.f32 %0, %1;" : "=f"(y) : "f"(x)); return y; }
__device__ __forceinline__ float rcp(float x) { float y; asm("rcp.approx.ftz.f32 %0, %1;" : "=f"(y) : "f"(x)); return y; }
__device__ __forceinline__ uint32_t pack_bf16(float lo, float hi) { uint32_t r; asm("cvt.rn.bf16x2.f32 %0, %1, %2;" : "=r"(r) : "f"(hi), "f"(lo)); return r; }
__device__ __forceinline__ uint32_t pack_f16(float lo, float hi) { uint32_t r; asm("cvt.rn.f16x2.f32 %0, %1, %2;" : "=r"(r) : "f"(hi), "f"(lo)); return r; }
__device__ __forceinline__ float bf_lo(uint32_t v) { return __uint_as_float(v << 16); }
__device__ __forceinline__ float bf_hi(uint32_t v) { return __uint_as_float(v & 0xFFFF0000u); }
__device__ __forceinline__ uint4 ldg_relaxed(const uint4* p) {
    uint4 v; asm volatile("ld.relaxed.gpu.global.v4.u32 {%0,%1,%2,%3}, [%4];" : "=r"(v.x), "=r"(v.y), "=r"(v.z), "=r"(v.w) : "l"(p) : "memory"); return v;
}
__device__ __forceinline__ void stg128(void* p, uint32_t a, uint32_t b, uint32_t c, uint32_t d) {
    asm volatile("st.relaxed.gpu.global.v4.u32 [%0], {%1,%2,%3,%4};" :: "l"(p), "r"(a), "r"(b), "r"(c), "r"(d) : "memory");
}
__device__ __forceinline__ void stg128_if(bool c, void* p, uint32_t a, uint32_t b, uint32_t d, uint32_t e) {
    asm volatile("{.reg .pred p; setp.ne.u32 p, %5, 0; @p st.relaxed.gpu.global.v4.u32 [%0], {%1,%2,%3,%4};}" :: "l"(p), "r"(a), "r"(b), "r"(d), "r"(e), "r"((int)c) : "memory");
}
__device__ __forceinline__ void stg64(void* p, uint32_t a, uint32_t b) {
    asm volatile("st.relaxed.gpu.global.v2.u32 [%0], {%1,%2};" :: "l"(p), "r"(a), "r"(b) : "memory");
}
__device__ __forceinline__ void sts128(uint32_t a, uint32_t x, uint32_t y, uint32_t z, uint32_t w) {
    asm volatile("st.shared.v4.u32 [%0], {%1,%2,%3,%4};" :: "r"(a), "r"(x), "r"(y), "r"(z), "r"(w) : "memory");
}
__device__ __forceinline__ void sts32(uint32_t a, uint32_t x) { asm volatile("st.shared.u32 [%0], %1;" :: "r"(a), "r"(x) : "memory"); }
__device__ __forceinline__ float4 lds128f(uint32_t a) {
    float4 v; asm volatile("ld.shared.v4.f32 {%0,%1,%2,%3}, [%4];" : "=f"(v.x), "=f"(v.y), "=f"(v.z), "=f"(v.w) : "r"(a) : "memory"); return v;
}
__device__ __forceinline__ uint4 lds128(uint32_t a) {
    uint4 v; asm volatile("ld.shared.v4.u32 {%0,%1,%2,%3}, [%4];" : "=r"(v.x), "=r"(v.y), "=r"(v.z), "=r"(v.w) : "r"(a) : "memory"); return v;
}
__device__ __forceinline__ uint32_t lds32(uint32_t a) { uint32_t v; asm volatile("ld.shared.u32 %0, [%1];" : "=r"(v) : "r"(a) : "memory"); return v; }
__device__ __forceinline__ uint32_t nonzero(uint32_t w) { return w == 0u ? 0x8000u : w; }
__device__ __forceinline__ void stg32(void* p, uint32_t a) { asm volatile("st.global.u32 [%0], %1;" :: "l"(p), "r"(a) : "memory"); }
__device__ __forceinline__ uint32_t ldg32_relaxed(const void* p) { uint32_t v; asm volatile("ld.relaxed.gpu.global.u32 %0, [%1];" : "=r"(v) : "l"(p) : "memory"); return v; }
__device__ __forceinline__ void count_hint(int id) {
    if ((threadIdx.x & 31) == 0) asm volatile("red.relaxed.gpu.global.add.u32 [%0], 1;" :: "l"(g_s.cnt[id]) : "memory");
}
__device__ __forceinline__ void count_release(int id) {
    __syncwarp();
    if ((threadIdx.x & 31) == 0) asm volatile("red.release.gpu.global.add.u32 [%0], 1;" :: "l"(g_s.cnt[id]) : "memory");
    __syncwarp();
}
__device__ __forceinline__ void count_wait(int id, unsigned target) {
    uint32_t v; int spins = 0;
    do v = ldg32_relaxed(g_s.cnt[id]); while (__any_sync(0xffffffffu, v != target) && ++spins < SPIN_LIMIT);
    asm volatile("fence.acquire.gpu;" ::: "memory");
}
__device__ __forceinline__ void warp_done(uint32_t bar) {
    __syncwarp();
    asm volatile("{.reg .pred p; setp.eq.u32 p, %1, 0; @p mbarrier.arrive.shared::cta.b64 _, [%0];}" :: "r"(bar), "r"(threadIdx.x & 31) : "memory");
}
__device__ __forceinline__ uint32_t mul_bf16x2(uint32_t a, uint32_t b) { uint32_t r; asm("mul.rn.bf16x2 %0, %1, %2;" : "=r"(r) : "r"(a), "r"(b)); return r; }
__device__ __forceinline__ uint32_t fma_bf16x2(uint32_t a, uint32_t b, uint32_t c) { uint32_t r; asm("fma.rn.bf16x2 %0, %1, %2, %3;" : "=r"(r) : "r"(a), "r"(b), "r"(c)); return r; }
__device__ __forceinline__ uint32_t add_bf16x2(uint32_t a, uint32_t b) { uint32_t r; asm("add.rn.bf16x2 %0, %1, %2;" : "=r"(r) : "r"(a), "r"(b)); return r; }

#define R4(d, o) "+f"(d[o + 0]), "+f"(d[o + 1]), "+f"(d[o + 2]), "+f"(d[o + 3])
#define R8(d, o) R4(d, o), R4(d, o + 4)
#define R32(d) R8(d, 0), R8(d, 8), R8(d, 16), R8(d, 24)
#define D32 "{%0,%1,%2,%3,%4,%5,%6,%7,%8,%9,%10,%11,%12,%13,%14,%15,%16,%17,%18,%19,%20,%21,%22,%23,%24,%25,%26,%27,%28,%29,%30,%31}"
#define D64 "{%0,%1,%2,%3,%4,%5,%6,%7,%8,%9,%10,%11,%12,%13,%14,%15,%16,%17,%18,%19,%20,%21,%22,%23,%24,%25,%26,%27,%28,%29,%30,%31,%32,%33,%34,%35,%36,%37,%38,%39,%40,%41,%42,%43,%44,%45,%46,%47,%48,%49,%50,%51,%52,%53,%54,%55,%56,%57,%58,%59,%60,%61,%62,%63}"

__device__ __forceinline__ void mma_qk_f16(float (&d)[32], uint64_t da, uint64_t db) {
    asm volatile("{.reg .pred p; setp.eq.b32 p, 0, 0; wgmma.mma_async.sync.aligned.m64n64k16.f32.f16.f16 " D32 ", %32, %33, p, 1, 1, 0, 0;}"
                 : R32(d) : "l"(da), "l"(db));
}
__device__ __forceinline__ void mma_qk_bf16(float (&d)[32], uint64_t da, uint64_t db) {
    asm volatile("{.reg .pred p; setp.ne.b32 p, 0, 0; wgmma.mma_async.sync.aligned.m64n64k16.f32.bf16.bf16 " D32 ", %32, %33, p, 1, 1, 0, 0;}"
                 : R32(d) : "l"(da), "l"(db));
}
__device__ __forceinline__ void mma_pv(float (&d)[12], const uint32_t* a, uint64_t db) {
    asm volatile("{.reg .pred p; setp.eq.b32 p, 0, 0; wgmma.mma_async.sync.aligned.m64n24k16.f32.bf16.bf16 {%0,%1,%2,%3,%4,%5,%6,%7,%8,%9,%10,%11}, {%12,%13,%14,%15}, %16, p, 1, 1, 1;}"
                 : R8(d, 0), R4(d, 8) : "r"(a[0]), "r"(a[1]), "r"(a[2]), "r"(a[3]), "l"(db));
}
__device__ __forceinline__ void mma_ss128(float (&d)[64], uint64_t da, uint64_t db, int accum) {
    asm volatile("{.reg .pred p; setp.ne.b32 p, %66, 0; wgmma.mma_async.sync.aligned.m64n128k16.f32.bf16.bf16 " D64 ", %64, %65, p, 1, 1, 0, 1;}"
                 : R32(d), R8(d, 32), R8(d, 40), R8(d, 48), R8(d, 56) : "l"(da), "l"(db), "r"(accum));
}
__device__ __forceinline__ void stsm4(uint32_t addr, uint32_t a, uint32_t b, uint32_t c, uint32_t d) {
    asm volatile("stmatrix.sync.aligned.m8n8.x4.shared.b16 [%0], {%1,%2,%3,%4};" :: "r"(addr), "r"(a), "r"(b), "r"(c), "r"(d) : "memory");
}
__device__ __forceinline__ void mma_ss8(float (&d)[4], uint64_t da, uint64_t db, int accum) {
    asm volatile("{.reg .pred p; setp.ne.b32 p, %6, 0; wgmma.mma_async.sync.aligned.m64n8k16.f32.bf16.bf16 {%0,%1,%2,%3}, %4, %5, p, 1, 1, 0, 1;}"
                 : R4(d, 0) : "l"(da), "l"(db), "r"(accum));
}
__device__ __forceinline__ void mma_ss(float (&d)[32], uint64_t da, uint64_t db, int accum) {
    asm volatile("{.reg .pred p; setp.ne.b32 p, %34, 0; wgmma.mma_async.sync.aligned.m64n64k16.f32.bf16.bf16 " D32 ", %32, %33, p, 1, 1, 0, 1;}"
                 : R32(d) : "l"(da), "l"(db), "r"(accum));
}
__device__ __forceinline__ void mma_ss(float (&d)[88], uint64_t da, uint64_t db, int accum) {
    asm volatile("{.reg .pred p; setp.ne.b32 p, %90, 0; wgmma.mma_async.sync.aligned.m64n176k16.f32.bf16.bf16 " "{%0,%1,%2,%3,%4,%5,%6,%7,%8,%9,%10,%11,%12,%13,%14,%15,%16,%17,%18,%19,%20,%21,%22,%23,%24,%25,%26,%27,%28,%29,%30,%31,%32,%33,%34,%35,%36,%37,%38,%39,%40,%41,%42,%43,%44,%45,%46,%47,%48,%49,%50,%51,%52,%53,%54,%55,%56,%57,%58,%59,%60,%61,%62,%63,%64,%65,%66,%67,%68,%69,%70,%71,%72,%73,%74,%75,%76,%77,%78,%79,%80,%81,%82,%83,%84,%85,%86,%87}"
                 ", %88, %89, p, 1, 1, 0, 1;}"
                 : R32(d), R8(d, 32), R8(d, 40), R8(d, 48), R8(d, 56), R8(d, 64), R8(d, 72), R8(d, 80) : "l"(da), "l"(db), "r"(accum));
}

constexpr float EXP_MAGIC = 256.0f + 127.0f + 64.0f - 1.58621f + 0.00390625f;
#define MUFU_M 0x8888u
#define ATT_MODE 1
#define ALU_M 0x0000u
constexpr uint32_t MUFU_MASK = MUFU_M;
constexpr uint32_t ALU_MASK = ALU_M;
template <bool ALU>
__device__ __forceinline__ uint32_t exp2_pair(float y0, float y1, uint32_t cexp, uint32_t neg1) {
    uint32_t w, m, e, r;
    asm("prmt.b32 %0, %1, %2, 0x6521;" : "=r"(w) : "r"(__float_as_uint(y0)), "r"(__float_as_uint(y1)));
    asm("lop3.b32 %0, %1, 0x007F007F, %2, 0xEA;" : "=r"(m) : "r"(w), "r"(cexp));
    if (ALU) e = w - m;
    else asm("mad.lo.u32 %0, %1, %2, %3;" : "=r"(e) : "r"(m), "r"(neg1), "r"(w));
    asm("fma.rn.bf16x2 %0, %1, %2, %3;" : "=r"(r) : "r"(w), "r"(m), "r"(e));
    return r;
}

struct Params {
    const __nv_bfloat16* wqp;
    __nv_bfloat16* out;
    uint32_t neg1, pad;
    const __nv_bfloat16* w1p;
    const __nv_bfloat16* w2p;
    CUtensorMap wq, wo, w1, w2;
    const __nv_bfloat16* wop;
};

__device__ __forceinline__ int tail_m() { return (blockIdx.x >> 5) * 4 + ((blockIdx.x >> 2) & 3); }
__device__ __forceinline__ int tail_j() { return ((blockIdx.x >> 4) & 1) * 4 + (blockIdx.x & 3); }
__device__ __forceinline__ void load_box(uint32_t sb, const CUtensorMap* tm, uint32_t dst, uint32_t bar, uint32_t bytes, int c0, int c1) {
    mbar_expect(sb + SM_MISC + bar * 8, bytes);
    tma2d(sb + dst, tm, c0, c1, sb + SM_MISC + bar * 8);
}
__device__ __forceinline__ void load_wq(uint32_t sb, const Params& P, int gi, int atom) {
    load_box(sb, &P.wq, (((atom ? WQ1_SLOTS : WQ0_SLOTS) >> (8 * gi)) & 31) * SLOT, MB_WQ + gi, 16384, (blockIdx.x & 3) * 128 + atom * 64, gi * 128);
}
__device__ __forceinline__ void load_wo(uint32_t sb, const Params& P, int kb) { load_box(sb, &P.wo, wo_slot(kb) * SLOT, MB_WO, SLOT, tail_j() * 64, kb * 64); }
__device__ __forceinline__ void refill_job(uint32_t sb, const Params& P, int gi, int job) {
    const bool w1 = job < 3;
    load_box(sb, w1 ? &P.w1 : &P.wo, (w1 ? 12 + gi + 4 * job : 2 * gi + job - 3) * SLOT, w1 ? MB_W1 + gi : MB_WO, SLOT,
             tail_j() * (w1 ? 176 : 64) + (w1 ? job * 64 : 0), (w1 ? gi : 2 * gi + job - 1) * 64);
}

__host__ __device__ constexpr int ring_entry(int n) { return n < 32 ? (n & 3) : (n - 32) % 6; }
__host__ __device__ constexpr uint32_t ring_slot(int e) { return e < 4 ? 24 + e : e; }

template <int KIND> __host__ __device__ constexpr uint64_t b_slots(int first) {
    uint64_t v = 0;
    for (int i = first; i < first + 12; i++) v |= (uint64_t)((KIND == 0 ? wo_slot(i) : KIND == 1 ? w1_slot(i, 0) : w1_slot(i / 3, i % 3)) & 31) << (5 * (i - first));
    return v;
}
__device__ __forceinline__ uint64_t desc64(uint32_t lo, uint32_t hi) { uint64_t d; asm("mov.b64 %0, {%1, %2};" : "=l"(d) : "r"(lo), "r"(hi)); return d; }
__device__ __forceinline__ uint32_t mbar_test(uint32_t bar) {
    uint32_t done;
    asm volatile("{.reg .pred p; mbarrier.test_wait.parity.shared::cta.b64 p, [%1], 0; selp.u32 %0, 1, 0, p;}" : "=r"(done) : "r"(bar) : "memory");
    return done;
}
template <int KIND, int NACC>
__device__ __forceinline__ bool gemm_ss(float (&acc)[NACC], uint32_t sb, int pr TS_ARG) {
    const uint32_t mb = sb + SM_MISC;
    constexpr int NBLK = KIND == 2 ? 22 : 8, N0 = 16 * KIND;
    uint32_t full = mb + (MB_FULL + N0 + pr * NBLK) * 8, empty = mb + MB_NULL * 8, rel = mb + MB_NULL * 8;
    const uint32_t lane = threadIdx.x & 31, probe = sb + ((threadIdx.x >> 5) & 3) * 512 + (lane >> 4) * 2048 + (lane & 15) * 32 + (lane >> 2) * 4;
    uint32_t m = 0;
    constexpr uint32_t R4S = 24 | 25 << 5 | 26 << 10 | 27 << 15;
    uint32_t ra = KIND == 2 ? (pr ? (4 | 5 << 5 | R4S << 10) : (R4S | 4 << 20 | 5 << 25)) : (KIND == 0 && pr) ? (15 | 19 << 5 | 23 << 10 | 6 << 15) : R4S;
    const uint32_t ra2 = KIND == 1 ? R4S : pr ? (7 | 8 << 5 | 9 << 10 | 27 << 15) : (14 | 18 << 5 | 22 << 10 | 24 << 15);
    uint64_t tab = b_slots<KIND>(0);
    const uint32_t a0 = (sb >> 4) | (8 << 16);
    uint32_t b0 = (sb >> 4) | ((KIND == 1 ? 4 * SLOT / 16 : 1) << 16);
    mbar_wait(full);
#pragma unroll 1
    for (int i = 0; i < NBLK; i++) {
        const uint32_t sa = ra & 31, da = a0 + sa * 512, db = b0 + ((uint32_t)tab & 31) * 512;
        full += (i == NBLK - 1) ? 0 : 8;
        const uint32_t ready = mbar_test(full);
        const uint32_t m0 = lds32(probe + sa * SLOT), m1 = lds32(probe + sa * SLOT + 4096);
        wg_fence();
#pragma unroll
        for (int s = 0; s < 4; s++) mma_ss(acc, desc64(da + s * 128, 16), desc64(db + s * 128, 0x40000040), s ? 1 : i);
        wg_commit();
        m = max(m, max(m0, m1));
        const uint32_t prev = empty, prel = rel;
        empty = mb + ((KIND == 0 && sa < 24) ? MB_NULL : MB_EMPTY + (sa & 7)) * 8;
        rel = mb + ((KIND == 1 ? MB_REL : MB_RELW) + i) * 8;
        ra = KIND == 2 ? (ra >> 5) | (sa << 25) : i == 3 ? ra2 : ra >> 5;
        tab = (KIND == 2 && i == 11) ? b_slots<KIND>(12) : tab >> 5;
        if (KIND == 1 && i == 3) b0 -= (3 * SLOT / 16) << 16;
        wg_wait<1>();
        warp_done(prev);
        if (KIND != 2) warp_done(prel);
        if (!__all_sync(0xffffffffu, ready)) mbar_wait(full);
    }
    bool bad = __any_sync(0xffffffffu, m == SENT);
    wg_wait<0>();
    fence_regs(acc);
    warp_done(empty);
    if (KIND != 2) warp_done(rel);
    if (KIND == 0 && !pr) warp_done(mb + MB_WOA * 8);
    return __builtin_expect(bad, 0);
}
__device__ __forceinline__ void ring_feed(uint32_t sb, int e TS_ARG) {
    const uint32_t mb = sb + SM_MISC;
    uint32_t dst = sb + ring_slot(e) * SLOT, empty = mb + (MB_EMPTY + e) * 8;
    const bool lead = (threadIdx.x & 31) == 0;
    const uint4* base = g_x + tail_m() * 4096 + e * 512;
    uint32_t par = 0;
    auto fetch = [&](int n, const uint4* src, int job) {
        const uint32_t full = mb + (MB_FULL + n) * 8;
        if (lead) mbar_expect(full, SLOT);
        mbar_wait(empty, par); par ^= 1;
        if (job) mbar_wait(mb + (MB_READY + job) * 8);
        if (lead) bulk_g2s(dst, src, SLOT, full);
        __syncwarp();
    };
    if (e < 4) {
        if (e == 0) fetch(7, base + 7 * 512, 0);
        if (lead) { mbar_expect(mb + (MB_FULL + 8 + e) * 8, SLOT); mbar_expect(mb + (MB_FULL + 12 + e) * 8, SLOT); }
        mbar_wait(mb + (MB_DONE + 4) * 8);
        if (e == 3) { mbar_wait(empty, par); par ^= 1; }
        mbar_wait(mb + (MB_READY + 1) * 8);
        if (lead) {
            bulk_g2s(sb + (e < 3 ? 15 + 4 * e : 6) * SLOT, base + 65536, SLOT, mb + (MB_FULL + 8 + e) * 8);
            bulk_g2s(sb + (e < 3 ? 7 + e : 27) * SLOT, base + 65536 + 2048, SLOT, mb + (MB_FULL + 12 + e) * 8);
        }
        __syncwarp();
#pragma unroll 1
        for (int h = 0; h < 2; h++) {
            fetch(16 + 8 * h + e, base + X_H1 + h * 65536, 2 + h);
            fetch(20 + 8 * h + e, base + X_H1 + h * 65536 + 2048, 0);
        }
    } else {
#pragma unroll 1
        for (int h = 0; h < 2; h++) {
            const uint4* sp = g_x + X_ST + (h * 16 + tail_m()) * 256 + (threadIdx.x & 31);
            mbar_wait(mb + (MB_READY + 2 + h) * 8);
            uint4 u[8]; uint32_t m; int spins = 0;
            do {
                m = 0;
#pragma unroll
                for (int k = 0; k < 8; k++) u[k] = ldg_relaxed(sp + k * 32);
#pragma unroll
                for (int k = 0; k < 8; k++) m = max(m, u[k].x);
            } while (__any_sync(0xffffffffu, m == SENT) && ++spins < SPIN_LIMIT);
            float st[4] = {0.f, 0.f, 0.f, 0.f};
#pragma unroll
            for (int k = 0; k < 8; k++) { st[0] += __uint_as_float(u[k].x); st[1] += __uint_as_float(u[k].y); st[2] += __uint_as_float(u[k].z); st[3] += __uint_as_float(u[k].w); }
#pragma unroll
            for (int k = 0; k < 2; k++) {
                const float nmean = st[2 * k] * (-1.0f / D);
                st[2 * k + 1] = 0.5f * rsqrtf(fmaxf(fmaf(-nmean, nmean, st[2 * k + 1] * (1.0f / D)), 0.f) + 1e-5f);
                st[2 * k] = nmean * st[2 * k + 1];
            }
            sts128(mb + MISC_STAT + h * 512 + (threadIdx.x & 31) * 16, __float_as_uint(st[0]), __float_as_uint(st[1]), __float_as_uint(st[2]), __float_as_uint(st[3]));
            warp_done(mb + (MB_STAT + h) * 8);
        }
        mbar_wait(mb + (MB_REL + 7) * 8);
        par = 1;
    }
    const uint4* src = g_x + X_H2 + tail_m() * 88 * 128 + e * 512;
#pragma unroll 1
    for (int n = e; n < 44; n += 6, src += 6 * 512) {
        const bool second = n >= 22 && n < 28;
        if (second) src += 16 * 88 * 128 - 22 * 512;
        fetch(32 + n, src, n < 6 ? 4 : second ? 5 : 0);
        if (e == 4) {
            par ^= 1; dst += SLOT; empty += 8;
            fetch(33 + n, src + 512, 0);
            dst -= SLOT; empty -= 8;
        }
    }
}
__device__ float4 g_redo[NMAIN * 2 * 22 * 128];
__device__ __noinline__ void gemm_slow_impl(float4* out, int ntile, const uint4* a, int nst, const __nv_bfloat16* W, int ldw, int kmax, int n0) {
    const int lane = threadIdx.x & 31;
    const unsigned short* w = reinterpret_cast<const unsigned short*>(W);
    for (int j = 0; j < ntile; j++) {
        const uint32_t* p = reinterpret_cast<const uint32_t*>(a) + ((threadIdx.x >> 5) & 3) * 128 + lane;
        const int n = n0 + 8 * j + (lane >> 2);
        float d[4] = {0.f, 0.f, 0.f, 0.f};
        for (int st = 0; st < nst; st++, p += 512) {
            const int k = st * 16 + 2 * (lane & 3);
            uint32_t v0, v1, v2, v3, b0 = 0, b1 = 0; int spins = 0;
            do { v0 = ldg32_relaxed(p); v1 = ldg32_relaxed(p + 64); v2 = ldg32_relaxed(p + 32); v3 = ldg32_relaxed(p + 96); }
            while (__any_sync(0xffffffffu, max(max(v0, v1), max(v2, v3)) == SENT) && ++spins < SPIN_LIMIT);
            if (k < kmax && n < ldw) {
                const unsigned short* q = w + (size_t)k * ldw + n;
                b0 = q[0] | ((uint32_t)q[ldw] << 16); b1 = q[8 * ldw] | ((uint32_t)q[9 * ldw] << 16);
            }
            asm volatile("mma.sync.aligned.m16n8k16.row.col.f32.bf16.bf16.f32 {%0,%1,%2,%3}, {%4,%5,%6,%7}, {%8,%9}, {%0,%1,%2,%3};"
                         : R4(d, 0) : "r"(v0), "r"(v1), "r"(v2), "r"(v3), "r"(b0), "r"(b1));
        }
        out[j * 128] = make_float4(d[0], d[1], d[2], d[3]);
    }
}
template <int NACC>
__device__ __forceinline__ void gemm_slow(float (&acc)[NACC], const uint4* a, int nst, const __nv_bfloat16* W, int ldw, int kmax, int n0) {
    float4* tmp = g_redo + (blockIdx.x * 2 + (threadIdx.x >> 8)) * 22 * 128 + (threadIdx.x & 127);
    gemm_slow_impl(tmp, NACC / 4, a, nst, W, ldw, kmax, n0);
#pragma unroll
    for (int i = 0; i < NACC / 4; i++) { const float4 v = tmp[i * 128]; acc[4 * i] = v.x; acc[4 * i + 1] = v.y; acc[4 * i + 2] = v.z; acc[4 * i + 3] = v.w; }
}
__device__ __forceinline__ void store_tile(uint32_t* p, uint32_t r0k0, uint32_t r8k0, uint32_t r0k8, uint32_t r8k8) {
    stg32(p, r0k0); stg32(p + 32, r0k8); stg32(p + 64, r8k0); stg32(p + 96, r8k8);
}

__device__ __forceinline__ float quad_sum(float v) { v += __shfl_xor_sync(0xffffffffu, v, 1); v += __shfl_xor_sync(0xffffffffu, v, 2); return v; }
__device__ __forceinline__ float reduce4(const float (&st)[4], int lane) {
    const bool u16 = lane & 16, u8 = lane & 8;
    const float a0 = (u16 ? st[2] : st[0]) + __shfl_xor_sync(0xffffffffu, u16 ? st[0] : st[2], 16);
    const float a1 = (u16 ? st[3] : st[1]) + __shfl_xor_sync(0xffffffffu, u16 ? st[1] : st[3], 16);
    float v = (u8 ? a1 : a0) + __shfl_xor_sync(0xffffffffu, u8 ? a0 : a1, 8);
    v += __shfl_xor_sync(0xffffffffu, v, 4); v += __shfl_xor_sync(0xffffffffu, v, 2); v += __shfl_xor_sync(0xffffffffu, v, 1);
    return v;
}
__device__ __forceinline__ float silu2(float h) { float t; asm("tanh.approx.f32 %0, %1;" : "=f"(t) : "f"(h)); return fmaf(h, t, h); }

template <bool SAFE>
__device__ __forceinline__ void attention(const Params& P, uint32_t sb, int warp TS_ARG) {
    const uint32_t mb = sb + SM_MISC;
    const int tid = threadIdx.x, lane = tid & 31, b = blockIdx.x;
    const int wg = warp >> 2, ww = warp & 3, job = 3 - wg + 4 * ww;
    const uint32_t cexp = 0x9F809F80u + (tid >> 12);
    const uint32_t neg1 = P.neg1;
    unsigned cnt = 0;
    if (SAFE && warp == 8) cnt = ldg32_relaxed(g_s.cnt[C_KV]);
#pragma unroll 1
    for (int pass = 0; pass < 2; pass++) {
    float o[12], s[32];
    const uint64_t dq = mkdesc(sb + SM_Q + (pass * 4 + wg) * 2048, 128, 256, 0);
    uint64_t dk = mkdesc(sb + SM_K, 128, 256, 0), dv = mkdesc(sb + SM_V, 128, 32768, 0);
    float m0 = -INFINITY, m1 = -INFINITY;
#pragma unroll
    for (int i = 0; i < 12; i++) o[i] = 0.f;
#pragma unroll
    for (int i = 0; i < 32; i++) s[i] = ((MUFU_MASK >> (i / 2)) & 1) ? 0.f : EXP_MAGIC;
    fence_regs(s); fence_regs(o);
    wg_fence();
    if (SAFE) mma_qk_f16(s, dq, dk + 31 * 128); else mma_qk_bf16(s, dq, dk + 31 * 128);
    wg_commit();
    wg_wait<0>(); fence_regs(s);
#pragma unroll 1
    for (int u = pass ? 3 : (wg == 2) ? 0 : 1; u < (pass ? 8 : 3); u++) {
        int n = 2 * ((((wg == 2) ? 0x22444C31u : 0x22444C40u) >> (4 * u)) & 15);
        if (SAFE) {
            auto tile = [&](uint32_t (&p)[16]) {
#pragma unroll
                for (int j = 0; j < 16; j++) {
                    if ((MUFU_MASK >> j) & 1) p[j] = pack_bf16(ex2(s[2 * j]), ex2(s[2 * j + 1]));
                    else if ((ALU_MASK >> j) & 1) p[j] = exp2_pair<true>(s[2 * j], s[2 * j + 1], cexp, neg1);
                    else p[j] = exp2_pair<false>(s[2 * j], s[2 * j + 1], cexp, neg1);
                }
                fence_regs(p);
                wg_fence();
                if (ATT_MODE != 3) mma_qk_f16(s, dq, dk);
                if (ATT_MODE == 1) wg_commit();
#pragma unroll
                for (int j = 0; j < 4; j++) mma_pv(o, p + 4 * j, dv + j * 16);
                if (ATT_MODE == 3) mma_qk_f16(s, dq, dk);
                wg_commit();
                dk += 128; dv += 64;
                wg_wait<ATT_MODE == 1>(); fence_regs(s);
            };
#pragma unroll 1
            do {
                uint32_t p0[16], p1[16];
                tile(p0);
                if (ATT_MODE == 1) { tile(p1); n--; }
            } while (--n > 0);
            if (ATT_MODE == 1) wg_wait<0>();
        } else {
#pragma unroll 1
            do {
                uint32_t p[16];
                fence_regs(o);
                float x0 = m0, x1 = m1;
#pragma unroll
                for (int j = 0; j < 8; j++) { x0 = fmaxf(x0, fmaxf(s[4 * j], s[4 * j + 1])); x1 = fmaxf(x1, fmaxf(s[4 * j + 2], s[4 * j + 3])); }
                x0 = fmaxf(x0, __shfl_xor_sync(0xffffffffu, x0, 1)); x0 = fmaxf(x0, __shfl_xor_sync(0xffffffffu, x0, 2));
                x1 = fmaxf(x1, __shfl_xor_sync(0xffffffffu, x1, 1)); x1 = fmaxf(x1, __shfl_xor_sync(0xffffffffu, x1, 2));
                const float c0 = ex2(m0 - x0), c1 = ex2(m1 - x1);
                m0 = x0; m1 = x1;
#pragma unroll
                for (int j = 0; j < 3; j++) { o[4 * j] *= c0; o[4 * j + 1] *= c0; o[4 * j + 2] *= c1; o[4 * j + 3] *= c1; }
#pragma unroll
                for (int j = 0; j < 8; j++) {
                    p[2 * j] = pack_bf16(ex2(s[4 * j] - m0), ex2(s[4 * j + 1] - m0));
                    p[2 * j + 1] = pack_bf16(ex2(s[4 * j + 2] - m1), ex2(s[4 * j + 3] - m1));
                }
                fence_regs(o);
                fence_regs(p);
                wg_fence();
                mma_qk_bf16(s, dq, dk);
#pragma unroll
                for (int j = 0; j < 4; j++) mma_pv(o, p + 4 * j, dv + j * 16);
                wg_commit();
                dk += 128; dv += 64;
                wg_wait<0>(); fence_regs(s);
            } while (--n > 0);
        }
        if (u == 2 || u == 7) {
            fence_regs(o);
            const float i0 = rcp(o[8]), i1 = rcp(o[10]);
            if (u == 7) mbar_wait(mb + MB_MID * 8);
            store_tile(reinterpret_cast<uint32_t*>(g_x + X_O + (((u == 7) * 16 + (b >> 3)) * 32 + (b & 3) * 8 + 2 * wg + (ww >> 1)) * 128 + (((b >> 2) & 1) * 2 + (ww & 1)) * 32) + lane,
                       pack_bf16(o[0] * i0, o[1] * i0), pack_bf16(o[2] * i1, o[3] * i1), pack_bf16(o[4] * i0, o[5] * i0), pack_bf16(o[6] * i1, o[7] * i1));
            if (u == 2) asm volatile("cp.async.bulk.wait_group 0;" ::: "memory");
            else count_hint(C_O + 16 + (b >> 3));
            warp_done(mb + (MB_DONE + (u == 7) * 4) * 8);
            TS(5 + (u == 7));
        } else if (u >= 3) {
            if (u < 6) warp_done(mb + (MB_DONE + u - 2) * 8);
            if (job < (u == 3 ? 1 : u == 6 ? 9 : 5)) {
                mbar_wait(mb + (MB_DONE + u - 3) * 8);
                if (u == 3) count_release(C_MID);
                else if (u < 6 || job == 3 || job == 4) { if (lane == 0) refill_job(sb, P, u - 4, job); }
                else {
                    const int n = job < 3 ? 4 + job : job - 5;
                    mbar_wait(mb + MB_MID * 8);
                    if (lane == 0) {
                        mbar_expect(mb + (MB_FULL + n) * 8, SLOT);
                        bulk_g2s(sb + (job < 3 ? 14 + 4 * job : 19 + job) * SLOT, g_x + X_O + tail_m() * 4096 + n * 512, SLOT, mb + (MB_FULL + n) * 8);
                    }
                }
            } else if (warp == 7) {
                if (u == 4) cnt = ldg32_relaxed(g_s.cnt[C_MID]);
                if (u == 5) {
                    const unsigned target = lds32(mb + MISC_EPOCH) * NCTA;
                    if (__any_sync(0xffffffffu, cnt != target)) count_wait(C_MID, target);
                    asm volatile("fence.acquire.gpu; fence.proxy.async.global;" ::: "memory");
                    warp_done(mb + MB_MID * 8);
                }
            }
        } else if (u == 1) {
            if (SAFE) mbar_wait(mb + MB_KV * 8);
            TS(17);
            if (lane == 0) {
                if (job < 9) {
                    asm volatile("cp.async.bulk.global.shared::cta.bulk_group [%0], [%1], %2;"
                                 :: "l"(g_x + X_ARM + b * X_SHARE + job * 512), "r"(sb + SM_SENT), "r"(job < 8 ? 8192 : (X_SHARE - 4096) * 16) : "memory");
                    asm volatile("cp.async.bulk.commit_group;" ::: "memory");
                } else if (job < 11) load_wo(sb, P, job - 9);
            }
        } else if (SAFE) {
            if (warp == 8) {
                const unsigned target = lds32(mb + MISC_EPOCH) * NMAIN;
                if (__any_sync(0xffffffffu, cnt != target)) count_wait(C_KV, target);
                if (lane == 0) {
                    asm volatile("fence.acquire.gpu; fence.proxy.async.global;" ::: "memory");
                    mbar_expect(mb + MB_KV * 8, 47104 + 2 * 24576);
                    bulk_g2s(sb + SM_K + 16384, g_s.kv + 1024, 47104, mb + MB_KV * 8);
                    bulk_g2s(sb + SM_V + 8192, g_s.kv + 4096 + 512, 24576, mb + MB_KV * 8);
                    bulk_g2s(sb + SM_V + 32768 + 8192, g_s.kv + 6144 + 512, 24576, mb + MB_KV * 8);
                }
            }
        }
        __syncwarp();
    }
    }
}

__device__ __forceinline__ int kv_slot(int idx) {
    const int t = (idx & 63) >> 1, c = 2 * (blockIdx.x >> 2) + (idx & 1), hg = blockIdx.x & 3;
    return hg < 2 ? ((t + 31) & 31) * 128 + (c >> 3) * 16 + (hg & 1) * 8 + (c & 7) : 4096 + (hg & 1) * 2048 + t * 64 + c;
}

#define HOLDN 384
#define PACE 5
#define GATE_AT 2
__device__ __noinline__ void helper_cta(const Params& P, uint8_t* smem) {
    const int tid = threadIdx.x, b = blockIdx.x, hi = b - NMAIN;
    const unsigned epoch = g_s.epoch[b] + 1;
    float* red = reinterpret_cast<float*>(smem);
    if (tid < 32) count_wait(C_KV, epoch * NMAIN);
    __syncthreads();
    if (tid == 480) {
        for (int i = 0; i < 8; i++) asm volatile("cp.async.bulk.prefetch.L2.global [%0], %1;" :: "l"((const char*)P.wop + hi * 131072 + i * 16384), "r"(16384) : "memory");
        for (int i = 0; i < 43; i++) asm volatile("cp.async.bulk.prefetch.L2.global [%0], %1;" :: "l"((const char*)P.w2p + hi * 352256 + i * 8192), "r"(8192) : "memory");
    }
    if (tid < 344) {
        const int cg = tid % 43, rp = tid / 43;
        const uint4* src = reinterpret_cast<const uint4*>(P.w1p + (size_t)rp * 64 * FF + (hi * 43 + cg) * 8);
        float s[8] = {0, 0, 0, 0, 0, 0, 0, 0};
#pragma unroll 8
        for (int r = 0; r < 64; r++) {
            uint4 v = __ldg(src + r * (FF / 8));
            s[0] += bf_lo(v.x); s[1] += bf_hi(v.x); s[2] += bf_lo(v.y); s[3] += bf_hi(v.y);
            s[4] += bf_lo(v.z); s[5] += bf_hi(v.z); s[6] += bf_lo(v.w); s[7] += bf_hi(v.w);
        }
        float* part = red + (rp * 43 + cg) * 8;
#pragma unroll
        for (int i = 0; i < 8; i++) part[i] = s[i];
    }
    __syncthreads();
    if (tid < 344) {
        float s = 0.f;
#pragma unroll
        for (int rp = 0; rp < 8; rp++) s += red[rp * 344 + tid];
        g_s.cs[hi * 344 + tid] = s;
    } else if (hi == 3 && tid < 344 + 64) g_s.cs[FF + tid - 344] = 0.f;
    __syncthreads();
    if (tid < 32) count_release(C_MID);
    if (tid == 0) g_s.epoch[b] = epoch;
}

__global__ void __launch_bounds__(512, 1) fused_kernel(const __nv_bfloat16* __restrict__ x, const __nv_bfloat16* __restrict__ wk, long long wv_off,
                                                         const __grid_constant__ Params P) {
    extern __shared__ __align__(1024) uint8_t smem[];
    const uint32_t sb = (uint32_t)__cvta_generic_to_shared(smem);
    const uint32_t mb = sb + SM_MISC;
    const int tid = threadIdx.x, lane = tid & 31, b = blockIdx.x;
    if (b >= NMAIN) { helper_cta(P, smem); return; }
    const int tg = b >> 2, hg = b & 3;
    const int warp = __shfl_sync(0xffffffffu, tid >> 5, 0);

    const uint32_t xst = sb + (((0x160A1204u >> (8 * (warp >> 2))) & 31) * SLOT + (warp & 3) * 4096), xbar = mb + MISC_XBAR + warp * 8;
    if (lane == 0) {
        mbar_init(xbar, 1);
        asm volatile("fence.mbarrier_init.release.cluster;" ::: "memory");
        mbar_expect(xbar, 4096);
        bulk_g2s(xst, x + (size_t)((warp & 7) * 4 + tg * 32 + (warp >> 3) * 1024) * D, 4096, xbar);
    }
    const uint4 wkv = ldg_relaxed(reinterpret_cast<const uint4*>(reinterpret_cast<const char*>(wk) + (hg < 2 ? 0 : wv_off)) + tid * 2 + (hg & 1));
    unsigned epoch = 0;
    const int wg = warp >> 2, ww = warp & 3, g = lane >> 2, t4 = lane & 3, t128 = tid & 127;
    if (lane == 0) {
        if (warp < 4) {
            mbar_init(mb + (MB_WQ + warp) * 8, 2);
            asm volatile("fence.mbarrier_init.release.cluster;" ::: "memory");
            if (warp < 2) { load_wq(sb, P, warp, 0); load_wq(sb, P, warp, 1); }
            else asm volatile("cp.async.bulk.prefetch.L2.global [%0], %1;" :: "l"((const char*)P.wqp + 262144 + (b * 2 + warp - 2) * 1024), "r"(1024) : "memory");
        } else {
            if (warp < 8) asm volatile("prefetch.tensormap [%0];" :: "l"(&P.wq + (warp - 4)) : "memory");
            const uint32_t first = warp < 8 ? (0x78100904u >> (8 * (warp - 4))) & 255 : warp < 11 ? 14 * warp - 94 : 14 * warp - 95;
            const uint32_t end = warp < 8 ? (0x89121009u >> (8 * (warp - 4))) & 255 : min(first + 14, warp < 11 ? 59u : 120u);
            const uint32_t cnt = warp < 8 ? (0x08030410u >> (8 * (warp - 4))) & 255 : warp < 11 ? 1 : 2;
#pragma unroll
            for (uint32_t i = 0; i < 17; i++) if (first + i < end) mbar_init(mb + (first + i) * 8, cnt);
            if (warp == 7) sts128(mb + MISC_NRM, 0, 0, 0, 0);
        }
    }
    __syncwarp();
    TS(16);
    sts128(sb + SM_WKV + tid * 16, wkv.x, wkv.y, wkv.z, wkv.w);
    uint4 xv[4][2];
    mbar_wait(xbar);
#pragma unroll
    for (int i = 0; i < 8; i++) xv[i >> 1][i & 1] = lds128(xst + i * 512 + lane * 16);
    float dlt;
    {
        float st[4];
#pragma unroll
        for (int i = 0; i < 4; i++) {
            const uint32_t s = add_bf16x2(add_bf16x2(add_bf16x2(xv[i][0].x, xv[i][0].y), add_bf16x2(xv[i][0].z, xv[i][0].w)),
                                          add_bf16x2(add_bf16x2(xv[i][1].x, xv[i][1].y), add_bf16x2(xv[i][1].z, xv[i][1].w)));
            st[i] = bf_lo(s) + bf_hi(s);
        }
        TS(13);
        const float tot = reduce4(st, lane) * (-1.0f / D);
        const uint32_t nmr = pack_bf16(tot, tot);
        dlt = bf_lo(nmr) - tot;
        const uint32_t xa[2] = {sb + (((uint32_t)XN_SLOTS >> (lane & 24)) & 31) * SLOT + warp * 512, sb + (((uint32_t)(XN_SLOTS >> 32) >> (lane & 24)) & 31) * SLOT + warp * 512};
#pragma unroll
        for (int i = 0; i < 4; i++) {
            const uint32_t nm = __shfl_sync(0xffffffffu, nmr, i * 8);
            const uint32_t off = i * 128 + (((lane & 7) ^ ((warp & 1) * 4 + i)) << 4);
#pragma unroll
            for (int c = 0; c < 2; c++) {
                xv[i][c].x = add_bf16x2(xv[i][c].x, nm); xv[i][c].y = add_bf16x2(xv[i][c].y, nm);
                xv[i][c].z = add_bf16x2(xv[i][c].z, nm); xv[i][c].w = add_bf16x2(xv[i][c].w, nm);
                sts128(xa[c] + off, xv[i][c].x, xv[i][c].y, xv[i][c].z, xv[i][c].w);
            }
        }
    }
    fence_async_smem();
    TS(0);
    auto variances = [&]() {
        float st[4];
#pragma unroll
        for (int i = 0; i < 4; i++) {
            uint32_t a[2];
#pragma unroll
            for (int c = 0; c < 2; c++)
                a[c] = fma_bf16x2(xv[i][c].x, xv[i][c].x, fma_bf16x2(xv[i][c].y, xv[i][c].y, fma_bf16x2(xv[i][c].z, xv[i][c].z, mul_bf16x2(xv[i][c].w, xv[i][c].w))));
            st[i] = (bf_lo(a[0]) + bf_hi(a[0])) + (bf_lo(a[1]) + bf_hi(a[1]));
        }
        const float vs = reduce4(st, lane);
        if ((lane & 7) == 0) sts32(sb + SM_RSTD + (warp * 4 + (lane >> 3)) * 4, __float_as_uint(rsqrtf(fmaxf(vs * (1.0f / D) - dlt * dlt, 0.f) + 1e-5f)));
    };
    if (wg == 2) {
        float kv[4];
        const uint64_t da = mkdesc(sb, 16, 1024, 1), db = mkdesc(sb + SM_WKV, 128, 16, 0);
        bar_sync(7, 512);
        wg_fence();
#pragma unroll
        for (int s = 0; s < 32; s++) mma_ss8(kv, da + xn_slot(s >> 2) * 512 + (s & 3) * 2, db + s * 16, s);
        wg_commit();
        variances();
        wg_wait<0>(); fence_regs(kv);
        float2* kt = reinterpret_cast<float2*>(smem + SM_KTMP);
        kt[(ww * 16 + g) * 4 + t4] = make_float2(kv[0], kv[1]); kt[(ww * 16 + g + 8) * 4 + t4] = make_float2(kv[2], kv[3]);
        TS(24);
    } else {
        if (wg == 3) {
            if (ww == 0) epoch = ldg32_relaxed(g_s.epoch + b);
            bar_sync(7, 512);
            if (lane == 0) load_wq(sb, P, 2 + (ww >> 1), ww & 1);
            __syncwarp();
        } else bar_arrive(7, 512);
        variances();
    }
    uint4* const kvdst = (ww < 2 ? g_s.kv : g_s.kplain) + kv_slot(tid);
    __syncthreads();
    constexpr float QSCALE = 0.25f * 1.4426950408889634f;
    float qa[64];
    const uint32_t qbase = sb + SM_Q + (ww >> 1) * 8192 + (ww & 1) * 512 + lane * 16;
    if (wg == 0) {
        const float rs0 = __uint_as_float(lds32(sb + SM_RSTD + (ww * 16 + g) * 4)) * QSCALE, rs1 = __uint_as_float(lds32(sb + SM_RSTD + (ww * 16 + g + 8) * 4)) * QSCALE;
        mbar_wait(mb + MB_WQ * 8);
        bar_sync(2, 384);
#pragma unroll 1
        for (int i = 0; i < 4; i++) {
            const uint32_t s0 = (WQ0_SLOTS >> (8 * i)) & 31, s1 = (WQ1_SLOTS >> (8 * i)) & 31, xs = (uint32_t)(XN_SLOTS >> (16 * i));
            const uint64_t db = mkdesc(sb + s0 * SLOT, (s1 - s0) * SLOT, 1024, 1);
            const uint64_t da0 = mkdesc(sb + (xs & 31) * SLOT, 16, 1024, 1), da1 = mkdesc(sb + ((xs >> 8) & 31) * SLOT, 16, 1024, 1);
            mbar_wait(mb + (MB_WQ + i) * 8);
            wg_fence();
#pragma unroll
            for (int s = 0; s < 8; s++) mma_ss128(qa, (s < 4 ? da0 : da1) + (s & 3) * 2, db + s * 128, s ? 1 : i);
            wg_commit();
            wg_wait<1>();
            if (i == 1) bar_arrive(6, 160);
        }
        wg_wait<0>();
        fence_regs(qa);
        bar_arrive(5, 256);
        TS(1);
        float n0 = 0.f, n1 = 0.f;
#pragma unroll
        for (int h = 0; h < 8; h++) {
            const float* v = qa + 8 * h;
            stsm4(qbase + h * 1024, pack_f16(v[0] * rs0, v[1] * rs0), pack_f16(v[4] * rs0, v[5] * rs0), pack_f16(v[2] * rs1, v[3] * rs1), pack_f16(v[6] * rs1, v[7] * rs1));
            n0 = __uint_as_float(max(__float_as_uint(n0), __float_as_uint(v[0] * v[0] + v[1] * v[1] + v[4] * v[4] + v[5] * v[5])));
            n1 = __uint_as_float(max(__float_as_uint(n1), __float_as_uint(v[2] * v[2] + v[3] * v[3] + v[6] * v[6] + v[7] * v[7])));
        }
        const uint32_t nm = __reduce_max_sync(0xffffffffu, __float_as_uint(quad_sum(__uint_as_float(max(__float_as_uint(n0 * rs0 * rs0), __float_as_uint(n1 * rs1 * rs1))))));
        if (lane == 0) asm volatile("red.shared.max.u32 [%0], %1;" :: "r"(mb + MISC_NRM), "r"(nm) : "memory");
    } else if (wg == 2) {
        bar_sync(2, HOLDN);
#pragma unroll
        for (int i = 0; i < 4; i++) sts128(sb + SM_SENT + (i * 128 + t128) * 16, SENT, SENT, SENT, SENT);
#pragma unroll
        for (int i = 0; i < 16; i++) {
            if (i == 4) bar_sync(5, 256);
            sts128(sb + SM_V + 65536 + (i * 128 + t128) * 16, 0x3F803F80u, 0x3F803F80u, 0x3F803F80u, 0x3F803F80u);
        }
    } else if (wg == 1) {
        const int r = (lane & 1) * 32 + ((t128 & 63) >> 1);
        const uint32_t ra = sb + SM_KTMP + r * 32;
        float4 c0 = lds128f(ra), c1 = lds128f(ra + 16);
        const float rs = __uint_as_float(lds32(sb + SM_RSTD + r * 4));
        c0.x *= rs; c0.y *= rs; c0.z *= rs; c0.w *= rs; c1.x *= rs; c1.y *= rs; c1.z *= rs; c1.w *= rs;
        if (ww < 2 && hg < 2) {
            const float4 p0 = lds128f(ra - (r ? 32 : 0)), p1 = lds128f(ra - (r ? 16 : 0));
            const float rp = (r & 31) ? -__uint_as_float(lds32(sb + SM_RSTD + r * 4 - 4)) : 0.f;
            stg128(kvdst, nonzero(pack_f16(fmaf(p0.x, rp, c0.x), fmaf(p0.y, rp, c0.y))), nonzero(pack_f16(fmaf(p0.z, rp, c0.z), fmaf(p0.w, rp, c0.w))),
                   nonzero(pack_f16(fmaf(p1.x, rp, c1.x), fmaf(p1.y, rp, c1.y))), nonzero(pack_f16(fmaf(p1.z, rp, c1.z), fmaf(p1.w, rp, c1.w))));
        } else {
            if (ww >= 2) {
                const uint32_t nm = __reduce_max_sync(0xffffffffu, __float_as_uint((c0.x * c0.x + c0.y * c0.y) + (c0.z * c0.z + c0.w * c0.w) + (c1.x * c1.x + c1.y * c1.y) + (c1.z * c1.z + c1.w * c1.w))) | 1u;
                if (lane < 2) stg128(g_s.nrm + b * 4 + (ww - 2) * 2 + lane, nm, nm, nm, nm);
            }
            if (ww < 2 || hg < 2) stg128(kvdst, nonzero(pack_bf16(c0.x, c0.y)), nonzero(pack_bf16(c0.z, c0.w)), nonzero(pack_bf16(c1.x, c1.y)), nonzero(pack_bf16(c1.z, c1.w)));
        }
        if (ww < 2) count_hint(C_KVH);
        TS(1);
        if (ww < 3) bar_arrive(2, HOLDN);
        else { bar_sync(2, HOLDN); count_release(C_KV); }
    } else {
        epoch++;
        if (t128 == 0) { sts32(mb + MISC_EPOCH, epoch); g_s.epoch[b] = epoch; }
        const uint32_t kdst = sb + (ww == 0 ? SM_K + 31 * 2048 : ww == 1 ? SM_K : SM_V + (ww - 2) * 32768);
        const uint4* ksrc = g_s.kv + (ww == 0 ? 31 * 128 : ww == 1 ? 0 : ww * 2048);
        const uint32_t kbytes = ww == 0 ? 2048 : ww == 1 ? 16384 : 8192;
        if (t128 == 0) mbar_expect(mb + MB_KV0 * 8, 34816);
        if (ww == 1) bar_sync(6, 160);
        if (ww == 0) { count_wait(C_KVH, epoch * (2 * NMAIN)); asm volatile("fence.proxy.async.global;" ::: "memory"); }
        TS(1);
        bar_sync(3, 128);
        uint32_t nm, nm2;
        int spins = 0;
        bool bad;
        do {
            if (lane == 0) bulk_g2s(kdst, ksrc, kbytes, mb + MB_KV0 * 8);
            nm = ldg32_relaxed(g_s.nrm + t128 * 4); nm2 = ldg32_relaxed(g_s.nrm + t128 * 4 + 2);
            __syncwarp();
            mbar_wait(mb + MB_KV0 * 8, spins & 1);
            const uint32_t probe = sb + (ww < 2 ? SM_K + ww * 8192 : SM_V + (ww - 2) * 32768) + lane * 32 + (lane >> 2) * 4;
            uint32_t mn = min(min(nm, nm2), lds32(sb + SM_K + 31 * 2048 + (ww & 1) * 1024 + lane * 32 + (lane >> 2) * 4));
#pragma unroll
            for (int k = 0; k < 8; k++) mn = min(mn, lds32(probe + k * 1024));
            uint32_t r;
            asm volatile("{.reg .pred p, q; setp.eq.u32 p, %1, 0; barrier.red.or.pred.aligned q, 3, 128, p; selp.u32 %0, 1, 0, q;}" : "=r"(r) : "r"(mn) : "memory");
            bad = __any_sync(0xffffffffu, r);
            if (bad && t128 == 0) mbar_expect(mb + MB_KV0 * 8, 34816);
        } while (bad && ++spins < SPIN_LIMIT);
        TS(2);
        nm = max(nm, nm2);
        nm = max(nm, __shfl_xor_sync(0xffffffffu, nm, 4)); nm = max(nm, __shfl_xor_sync(0xffffffffu, nm, 8)); nm = max(nm, __shfl_xor_sync(0xffffffffu, nm, 16));
        if (lane < 4) asm volatile("red.shared.max.u32 [%0], %1;" :: "r"(mb + MISC_NRM + 4 + min(lane, 2) * 4), "r"(nm) : "memory");
    }
    fence_async_smem();
    TS(3);
    __syncthreads();
    const float4 nr = lds128f(mb + MISC_NRM);
    const bool safe = __all_sync(0xffffffffu, (nr.x * (nr.y + nr.z) <= 3500.0f) && (nr.x <= 65536.0f) && (nr.y + nr.z <= 65536.0f) && (nr.w <= 1e24f));
    TS(4);

    if (__builtin_expect(safe, 1)) {
        attention<true>(P, sb, warp TS_PASS);
    } else {
        if (wg == 0) {
            const float rs0 = __uint_as_float(lds32(sb + SM_RSTD + (ww * 16 + g) * 4)) * QSCALE, rs1 = __uint_as_float(lds32(sb + SM_RSTD + (ww * 16 + g + 8) * 4)) * QSCALE;
#pragma unroll
            for (int h = 0; h < 8; h++) {
                const float* v = qa + 8 * h;
                stsm4(qbase + h * 1024, pack_bf16(v[0] * rs0, v[1] * rs0), pack_bf16(v[4] * rs0, v[5] * rs0), pack_bf16(v[2] * rs1, v[3] * rs1), pack_bf16(v[6] * rs1, v[7] * rs1));
            }
            fence_async_smem();
        } else if (warp == 15) {
            count_wait(C_KV, lds32(mb + MISC_EPOCH) * NMAIN);
            if (lane == 0) {
                asm volatile("fence.proxy.async;" ::: "memory");
                mbar_expect(mb + MB_KV * 8, 131072);
                bulk_g2s(sb + SM_K, g_s.kplain, 65536, mb + MB_KV * 8);
                bulk_g2s(sb + SM_V, g_s.kv + 4096, 65536, mb + MB_KV * 8);
            }
            __syncwarp();
        }
        __syncthreads();
        mbar_wait(mb + MB_KV * 8);
        attention<false>(P, sb, warp TS_PASS);
    }

    const int j = tail_j();
    if (wg == 1 || wg == 2) {
        if (warp == 8) {
            epoch = lds32(mb + MISC_EPOCH);
#pragma unroll 1
            for (int job = 1; job < 6; job++) {
                count_wait(C_O + 32 * (job >> 1) + (job & 1) * 16 + tail_m(), epoch * (job == 1 ? 128 : 32));
                asm volatile("fence.proxy.async.global;" ::: "memory");
                warp_done(mb + (MB_READY + job) * 8);
                TS(18 + job);
            }
        } else if (warp == 9) {
#pragma unroll
            for (int i = 0; i < 2; i++) {
                if (lane < 22) {
                    const uint4 v = ldg_relaxed(reinterpret_cast<const uint4*>(g_s.cs + j * 176) + i * 22 + lane);
                    sts128(mb + MISC_CS + (i * 22 + lane) * 16, v.x, v.y, v.z, v.w);
                }
                stg128(g_s.kv + kv_slot(i * 32 + lane), 0u, 0u, 0u, 0u);
            }
            warp_done(mb + MB_CS * 8);
            if (lane < 4) stg128(g_s.nrm + b * 4 + lane, 0u, 0u, 0u, 0u);
#pragma unroll 1
            for (int i = 0; i < 16; i++) {
                mbar_wait(mb + (MB_W1 + i) * 8);
                const int n = i < 8 ? 16 + i + 8 * (lane & 1) : 32 + 3 * (i - 8) + (lane >> 1) + 22 * (lane & 1);
                if (lane < (i < 8 || i == 15 ? 2 : 6)) mbar_arrive(mb + (MB_FULL + n) * 8);
                __syncwarp();
            }
        } else {
            if (warp == 10) {
#pragma unroll 1
                for (int i = 2; i < 16; i++) {
                    const bool w1 = i < 8;
                    const int kb = i & 7;
                    const uint32_t bar = mb + (MB_W1 + i) * 8, dst = sb + w1_slot(kb, 0) * SLOT, step = kb < 4 ? 4 * SLOT : SLOT;
                    const CUtensorMap* tm = w1 ? &P.w1 : &P.w2;
                    const int c0 = w1 ? j * 176 : j * 64, c1 = w1 ? kb * 64 : kb * 192, d0 = w1 ? 64 : 0, d1 = 64 - d0;
                    if (lane == 0) mbar_expect(bar, i == 15 ? SLOT : 3 * SLOT);
                    mbar_wait(mb + (w1 ? (i == 2 ? MB_WOA : i == 3 ? MB_RELW + 2 : MB_RELW + i) : MB_REL + kb) * 8);
                    if (i >= 8 + GATE_AT) mbar_wait(mb + (MB_FULL + 32 + max(3 * kb - PACE, 0)) * 8);
                    if (lane == 0) {
                        tma2d(dst, tm, c0, c1, bar);
                        if (i < 15) { tma2d(dst + step, tm, c0 + d0, c1 + d1, bar); tma2d(dst + 2 * step, tm, c0 + 2 * d0, c1 + 2 * d1, bar); }
                    }
                    __syncwarp();
                }
            } else {
                ring_feed(sb, wg == 1 ? ww : 4 TS_PASS);
            }
        }
    } else {
        const int pr = (wg == 0), mt = 16 * pr + tail_m();
        uint32_t* const hp = reinterpret_cast<uint32_t*>(g_x + X_H1 + (mt * 32 + j * 4) * 128 + ww * 32) + lane;
        {
            uint32_t hk[16];
            const uint32_t* xp = reinterpret_cast<const uint32_t*>(x + (size_t)(mt * 64 + ww * 16 + g) * D + j * 64 + t4 * 2);
#pragma unroll
            for (int k = 0; k < 8; k++) { hk[2 * k] = __ldg(xp + k * 4); hk[2 * k + 1] = __ldg(xp + k * 4 + 8 * (D / 2)); }
            mbar_wait(mb + MB_WO * 8);
            float acc[32];
            if (gemm_ss<0>(acc, sb, pr TS_PASS)) gemm_slow(acc, g_x + X_O + mt * 32 * 128, 32, P.wop, D, D, j * 64);
            TS(7);
#pragma unroll
            for (int i = 0; i < 16; i++) hk[i] = pack_bf16(acc[2 * i] + bf_lo(hk[i]), acc[2 * i + 1] + bf_hi(hk[i]));
#pragma unroll
            for (int k = 0; k < 4; k++) store_tile(hp + k * 512, hk[4 * k], hk[4 * k + 1], hk[4 * k + 2], hk[4 * k + 3]);
            count_hint(C_H1 + mt);
            TS(8);
            float st[4] = {0.f, 0.f, 0.f, 0.f};
#pragma unroll
            for (int i = 0; i < 16; i++) {
                const float lo = bf_lo(hk[i]), hi = bf_hi(hk[i]);
                st[2 * (i & 1)] += lo + hi;
                st[2 * (i & 1) + 1] = fmaf(lo, lo, fmaf(hi, hi, st[2 * (i & 1) + 1]));
            }
#pragma unroll
            for (int o = 1; o < 4; o <<= 1)
#pragma unroll
                for (int i = 0; i < 4; i++) st[i] += __shfl_xor_sync(0xffffffffu, st[i], o);
            if (t4 == 0) stg128(g_x + X_ST + (mt * 8 + j) * 32 + ww * 8 + g, __float_as_uint(st[0]), __float_as_uint(st[1]), __float_as_uint(st[2]), __float_as_uint(st[3]));
        }
        {
            float acc[88];
            mbar_wait(mb + MB_CS * 8);
            if (gemm_ss<1>(acc, sb, pr TS_PASS)) gemm_slow(acc, g_x + X_H1 + mt * 32 * 128, 32, P.w1p, FF, D, j * 176);
            TS(9);
            mbar_wait(mb + (MB_STAT + pr) * 8);
            const float4 rs = lds128f(mb + MISC_STAT + pr * 512 + (ww * 8 + g) * 16);
            const float nmean[2] = {rs.x, rs.z}, hrstd[2] = {rs.y, rs.w};
            uint32_t* hb = reinterpret_cast<uint32_t*>(g_x + X_H2 + (mt * 88 + j * 11) * 128 + ww * 32) + lane;
#pragma unroll
            for (int i = 0; i < 22; i++) {
                float2 cs;
                asm volatile("ld.shared.v2.f32 {%0,%1}, [%2];" : "=f"(cs.x), "=f"(cs.y) : "r"(mb + MISC_CS + i * 32 + t4 * 8));
                const float* z = acc + 4 * i;
                uint32_t* p = hb + (i >> 1) * 512 + (i & 1) * 32;
                stg32(p, pack_bf16(silu2(fmaf(hrstd[0], z[0], nmean[0] * cs.x)), silu2(fmaf(hrstd[0], z[1], nmean[0] * cs.y))));
                stg32(p + 64, pack_bf16(silu2(fmaf(hrstd[1], z[2], nmean[1] * cs.x)), silu2(fmaf(hrstd[1], z[3], nmean[1] * cs.y))));
            }
            count_hint(C_H2 + mt);
            TS(10);
        }
        {
            uint32_t hk[16];
#pragma unroll
            for (int i = 0; i < 16; i++) hk[i] = ldg32_relaxed(hp + (i >> 2) * 512 + ((i & 1) * 2 + ((i >> 1) & 1)) * 32);
            float acc[32];
            if (gemm_ss<2>(acc, sb, pr TS_PASS)) gemm_slow(acc, g_x + X_H2 + mt * 88 * 128, 88, P.w2p, D, FF, j * 64);
            TS(11);
#pragma unroll
            for (int i = 0; i < 16; i++) hk[i] = pack_bf16(acc[2 * i] + bf_lo(hk[i]), acc[2 * i + 1] + bf_hi(hk[i]));
#pragma unroll
            for (int h = 0; h < 4; h++) {
                const uint32_t* v = hk + (h >> 1) * 8 + (h & 1);
                uint32_t v0 = v[0], v1 = v[2], v2 = v[4], v3 = v[6];
                const bool o1 = t4 & 1, o2 = t4 & 2;
                uint32_t a = __shfl_xor_sync(0xffffffffu, o1 ? v0 : v1, 1), c = __shfl_xor_sync(0xffffffffu, o1 ? v2 : v3, 1);
                if (o1) { v0 = a; v2 = c; } else { v1 = a; v3 = c; }
                a = __shfl_xor_sync(0xffffffffu, o2 ? v0 : v2, 2); c = __shfl_xor_sync(0xffffffffu, o2 ? v1 : v3, 2);
                if (o2) { v0 = a; v1 = c; } else { v2 = a; v3 = c; }
                *reinterpret_cast<uint4*>(P.out + (size_t)(mt * 64 + ww * 16 + g + 8 * (h & 1)) * D + j * 64 + (h >> 1) * 32 + t4 * 8) = make_uint4(v0, v1, v2, v3);
            }
        }
    }
    TS(12);
}

typedef CUresult (*EncodeFn)(CUtensorMap*, CUtensorMapDataType, cuuint32_t, void*, const cuuint64_t*, const cuuint64_t*, const cuuint32_t*,
                             const cuuint32_t*, CUtensorMapInterleave, CUtensorMapSwizzle, CUtensorMapL2promotion, CUtensorMapFloatOOBfill);

void encode2d(EncodeFn fn, CUtensorMap* tm, const void* ptr, int rows, int cols, int box_rows, int box_cols, CUtensorMapSwizzle sw) {
    cuuint64_t dims[2] = {(cuuint64_t)cols, (cuuint64_t)rows};
    cuuint64_t strides[1] = {(cuuint64_t)cols * 2};
    cuuint32_t box[2] = {(cuuint32_t)box_cols, (cuuint32_t)box_rows};
    cuuint32_t es[2] = {1, 1};
    fn(tm, CU_TENSOR_MAP_DATA_TYPE_BFLOAT16, 2, const_cast<void*>(ptr), dims, strides, box, es, CU_TENSOR_MAP_INTERLEAVE_NONE, sw,
       CU_TENSOR_MAP_L2_PROMOTION_L2_128B, CU_TENSOR_MAP_FLOAT_OOB_FILL_NONE);
}

}

extern "C" void kernel_launch(void* const* d_in, const int* in_sizes, int n_in, void* d_out, int out_size) {
    (void)in_sizes; (void)n_in; (void)out_size;
    void* fnp = nullptr;
    cudaDriverEntryPointQueryResult qr;
    cudaGetDriverEntryPoint("cuTensorMapEncodeTiled", &fnp, cudaEnableDefault, &qr);
    EncodeFn fn = (EncodeFn)fnp;
    Params P;
    encode2d(fn, &P.wq, d_in[1], D, D, 128, 64, CU_TENSOR_MAP_SWIZZLE_128B);
    encode2d(fn, &P.wo, d_in[4], D, D, 64, 64, CU_TENSOR_MAP_SWIZZLE_128B);
    encode2d(fn, &P.w1, d_in[6], D, FF, 64, 64, CU_TENSOR_MAP_SWIZZLE_128B);
    encode2d(fn, &P.w2, d_in[7], FF, D, 64, 64, CU_TENSOR_MAP_SWIZZLE_128B);
    P.w1p = (const __nv_bfloat16*)d_in[6];
    P.w2p = (const __nv_bfloat16*)d_in[7];
    P.wop = (const __nv_bfloat16*)d_in[4];
    P.wqp = (const __nv_bfloat16*)d_in[1];
    P.out = (__nv_bfloat16*)d_out;
    P.neg1 = 0xFFFFFFFFu; P.pad = 0;
    cudaFuncSetAttribute(fused_kernel, cudaFuncAttributeMaxDynamicSharedMemorySize, SMEM_BYTES);
    fused_kernel<<<NCTA, 512, SMEM_BYTES>>>((const __nv_bfloat16*)d_in[0], (const __nv_bfloat16*)d_in[2], (long long)((const char*)d_in[3] - (const char*)d_in[2]), P);
}
```

```cpp
#include <cuda_runtime.h>
#include <cuda_bf16.h>
#include <cuda_fp16.h>
#include <cuda.h>
#include <stdint.h>

namespace {

constexpr int D = 512, FF = 1376;
constexpr int NMAIN = 128, NHELP = 4, NCTA = NMAIN + NHELP;
constexpr uint32_t SENT = 0xFFFFFFFFu;
constexpr int SPIN_LIMIT = 1 << 22;

constexpr uint32_t KB = 1024, SLOT = 8192;
constexpr uint64_t XN_SLOTS = 7 | 16 << 8 | 27 << 16 | 21 << 24 | 6ull << 32 | 14ull << 40 | 15ull << 48 | 17ull << 56;
constexpr uint32_t WQ0_SLOTS = 0 | 22 << 8 | 2 << 16 | 4 << 24, WQ1_SLOTS = 12 | 24 << 8 | 10 << 16 | 18 << 24;
__host__ __device__ constexpr uint32_t xn_slot(int kb) { return (XN_SLOTS >> (8 * kb)) & 31; }
constexpr uint32_t SM_WKV = 208 * KB;
constexpr uint32_t SM_K = 0;
constexpr uint32_t SM_Q = 64 * KB;
constexpr uint32_t SM_V = 96 * KB;
constexpr uint32_t SM_MISC = 224 * KB;
constexpr uint32_t SMEM_BYTES = 227 * KB;
constexpr uint32_t SM_KTMP = 164 * KB;
constexpr uint32_t SM_RSTD = 226 * KB;
constexpr uint32_t SM_SENT = 192 * KB;
constexpr uint32_t MB_WQ = 0;
constexpr uint32_t MB_DONE = 4;
constexpr uint32_t MB_EARLY = 5;
constexpr uint32_t MB_EMPTY = 9;
constexpr uint32_t MB_WOA = 6;
constexpr uint32_t MB_W1 = 16;
constexpr uint32_t MB_W2 = 24;
constexpr uint32_t MB_CS = 32;
constexpr uint32_t MB_KV = 33;
constexpr uint32_t MB_KV0 = 34;
constexpr uint32_t MB_MID = 35;
constexpr uint32_t MB_READY = 35;
constexpr uint32_t MB_STAT = 41;
constexpr uint32_t MB_FULL = 43;
constexpr uint32_t MB_NULL = 119;
constexpr uint32_t MB_WO = 120;
constexpr uint32_t MB_REL = 121;
constexpr uint32_t MB_RELW = 129;
constexpr uint32_t MISC_STAT = 2048;
constexpr uint32_t MISC_PROG = 2432;
constexpr uint32_t MISC_XBAR = 2304;
constexpr uint32_t MISC_NRM = 1056;
constexpr uint32_t MISC_EPOCH = 1072;
constexpr uint32_t MISC_TS = 1088;
constexpr uint32_t MISC_CS = 1344;

__host__ __device__ constexpr uint32_t wo_slot(int kb) { return kb < 2 ? 10 + kb : kb - 2; }
__host__ __device__ constexpr uint32_t w1_slot(int kb, int a) { return kb < 4 ? 12 + kb + 4 * a : (kb == 4 ? 0 : kb == 7 ? 3 : 3 * kb - 9) + a; }

struct alignas(128) Small {
    unsigned epoch[160];
    unsigned cnt[134][32];
    float cs[1440];
    uint4 kv[8192];
    uint4 kplain[4096];
};
__device__ Small g_s;
constexpr int C_H2E = 101;
constexpr int C_KVH = 0, C_KV = 99, C_MID = 2, C_O = 3, C_H1 = 35, C_H2 = 67;
constexpr int X_O = 0, X_H1 = 32 * 32 * 128, X_H2 = 2 * X_H1, X_ST = X_H2 + 32 * 88 * 128, X_END = X_ST + 32 * 8 * 32;
constexpr int X_ARM = 16 * 32 * 128, X_SHARE = (X_END - X_ARM) / NMAIN;
__device__ uint4 g_x[X_END];
#define TS(i) do {} while (0)
#define TSF(k)

#define TS_ARG
#define TS_PASS

__device__ __forceinline__ void mbar_init(uint32_t bar, int cnt) { asm volatile("mbarrier.init.shared::cta.b64 [%0], %1;" :: "r"(bar), "r"(cnt) : "memory"); }
__device__ __forceinline__ void mbar_expect(uint32_t bar, uint32_t bytes) { asm volatile("mbarrier.arrive.expect_tx.shared::cta.b64 _, [%0], %1;" :: "r"(bar), "r"(bytes) : "memory"); }
__device__ __forceinline__ void mbar_arrive(uint32_t bar) { asm volatile("mbarrier.arrive.shared::cta.b64 _, [%0];" :: "r"(bar) : "memory"); }
__device__ __forceinline__ bool mbar_try(uint32_t bar, uint32_t parity) {
    uint32_t done;
    asm volatile("{.reg .pred p; mbarrier.try_wait.parity.shared::cta.b64 p, [%1], %2; selp.u32 %0, 1, 0, p;}" : "=r"(done) : "r"(bar), "r"(parity) : "memory");
    return __all_sync(0xffffffffu, done);
}
__device__ __forceinline__ void mbar_wait(uint32_t bar, uint32_t parity = 0) {
    if (__builtin_expect(!mbar_try(bar, parity), 0)) {
        int spins = 0;
        while (!mbar_try(bar, parity) && ++spins < (SPIN_LIMIT >> 6)) {}
    }
}
__device__ __forceinline__ void tma2d(uint32_t dst, const CUtensorMap* tm, int c0, int c1, uint32_t bar) {
    asm volatile("cp.async.bulk.tensor.2d.shared::cluster.global.mbarrier::complete_tx::bytes [%0], [%1, {%3, %4}], [%2];"
                 :: "r"(dst), "l"(tm), "r"(bar), "r"(c0), "r"(c1) : "memory");
}
__device__ __forceinline__ void bulk_g2s(uint32_t dst, const void* src, uint32_t bytes, uint32_t bar) {
    asm volatile("cp.async.bulk.shared::cluster.global.mbarrier::complete_tx::bytes [%0], [%1], %2, [%3];" :: "r"(dst), "l"(src), "r"(bytes), "r"(bar) : "memory");
}
__device__ __forceinline__ void fence_async_smem() { asm volatile("fence.proxy.async.shared::cta;" ::: "memory"); }
__device__ __forceinline__ void bar_sync(int id, int n) { asm volatile("bar.sync %0, %1;" :: "r"(id), "r"(n) : "memory"); }
__device__ __forceinline__ void bar_arrive(int id, int n) { asm volatile("bar.arrive %0, %1;" :: "r"(id), "r"(n) : "memory"); }
__device__ __forceinline__ void wg_fence() { asm volatile("wgmma.fence.sync.aligned;" ::: "memory"); }
__device__ __forceinline__ void wg_commit() { asm volatile("wgmma.commit_group.sync.aligned;" ::: "memory"); }
template <int N> __device__ __forceinline__ void wg_wait() { asm volatile("wgmma.wait_group.sync.aligned %0;" :: "n"(N) : "memory"); }
template <int N> __device__ __forceinline__ void fence_regs(float (&d)[N]) {
#pragma unroll
    for (int i = 0; i < N; i++) asm volatile("" : "+f"(d[i]) :: "memory");
}
template <int N> __device__ __forceinline__ void fence_regs(uint32_t (&d)[N]) {
#pragma unroll
    for (int i = 0; i < N; i++) asm volatile("" : "+r"(d[i]) :: "memory");
}
__device__ __forceinline__ uint64_t mkdesc(uint32_t addr, uint32_t lbo, uint32_t sbo, uint32_t swz) {
    return (uint64_t)(((addr & 0x3FFFF) >> 4) | ((lbo >> 4) << 16)) | ((uint64_t)((sbo >> 4) | (swz << 30)) << 32);
}
__device__ __forceinline__ float ex2(float x) { float y; asm("ex2.approx.ftz.f32 %0, %1;" : "=f"(y) : "f"(x)); return y; }
__device__ __forceinline__ float rcp(float x) { float y; asm("rcp.approx.ftz.f32 %0, %1;" : "=f"(y) : "f"(x)); return y; }
__device__ __forceinline__ uint32_t pack_bf16(float lo, float hi) { uint32_t r; asm("cvt.rn.bf16x2.f32 %0, %1, %2;" : "=r"(r) : "f"(hi), "f"(lo)); return r; }
__device__ __forceinline__ uint32_t pack_f16(float lo, float hi) { uint32_t r; asm("cvt.rn.f16x2.f32 %0, %1, %2;" : "=r"(r) : "f"(hi), "f"(lo)); return r; }
__device__ __forceinline__ float bf_lo(uint32_t v) { return __uint_as_float(v << 16); }
__device__ __forceinline__ float bf_hi(uint32_t v) { return __uint_as_float(v & 0xFFFF0000u); }
__device__ __forceinline__ uint4 ldg_relaxed(const uint4* p) {
    uint4 v; asm volatile("ld.relaxed.gpu.global.v4.u32 {%0,%1,%2,%3}, [%4];" : "=r"(v.x), "=r"(v.y), "=r"(v.z), "=r"(v.w) : "l"(p) : "memory"); return v;
}
__device__ __forceinline__ void stg128(void* p, uint32_t a, uint32_t b, uint32_t c, uint32_t d) {
    asm volatile("st.relaxed.gpu.global.v4.u32 [%0], {%1,%2,%3,%4};" :: "l"(p), "r"(a), "r"(b), "r"(c), "r"(d) : "memory");
}
__device__ __forceinline__ void stg128_if(bool c, void* p, uint32_t a, uint32_t b, uint32_t d, uint32_t e) {
    asm volatile("{.reg .pred p; setp.ne.u32 p, %5, 0; @p st.relaxed.gpu.global.v4.u32 [%0], {%1,%2,%3,%4};}" :: "l"(p), "r"(a), "r"(b), "r"(d), "r"(e), "r"((int)c) : "memory");
}
__device__ __forceinline__ void stg64(void* p, uint32_t a, uint32_t b) {
    asm volatile("st.relaxed.gpu.global.v2.u32 [%0], {%1,%2};" :: "l"(p), "r"(a), "r"(b) : "memory");
}
__device__ __forceinline__ void sts128(uint32_t a, uint32_t x, uint32_t y, uint32_t z, uint32_t w) {
    asm volatile("st.shared.v4.u32 [%0], {%1,%2,%3,%4};" :: "r"(a), "r"(x), "r"(y), "r"(z), "r"(w) : "memory");
}
__device__ __forceinline__ void sts32(uint32_t a, uint32_t x) { asm volatile("st.shared.u32 [%0], %1;" :: "r"(a), "r"(x) : "memory"); }
__device__ __forceinline__ float4 lds128f(uint32_t a) {
    float4 v; asm volatile("ld.shared.v4.f32 {%0,%1,%2,%3}, [%4];" : "=f"(v.x), "=f"(v.y), "=f"(v.z), "=f"(v.w) : "r"(a) : "memory"); return v;
}
__device__ __forceinline__ uint4 lds128(uint32_t a) {
    uint4 v; asm volatile("ld.shared.v4.u32 {%0,%1,%2,%3}, [%4];" : "=r"(v.x), "=r"(v.y), "=r"(v.z), "=r"(v.w) : "r"(a) : "memory"); return v;
}
__device__ __forceinline__ uint32_t lds32(uint32_t a) { uint32_t v; asm volatile("ld.shared.u32 %0, [%1];" : "=r"(v) : "r"(a) : "memory"); return v; }
__device__ __forceinline__ uint32_t nonzero(uint32_t w) { return w == 0u ? 0x8000u : w; }
__device__ __forceinline__ void stg32(void* p, uint32_t a) { asm volatile("st.global.u32 [%0], %1;" :: "l"(p), "r"(a) : "memory"); }
__device__ __forceinline__ uint32_t ldg32_relaxed(const void* p) { uint32_t v; asm volatile("ld.relaxed.gpu.global.u32 %0, [%1];" : "=r"(v) : "l"(p) : "memory"); return v; }
__device__ __forceinline__ void red_lane0(unsigned* p) {
    asm volatile("{.reg .pred p; setp.eq.u32 p, %1, 0; @p red.relaxed.gpu.global.add.u32 [%0], 1;}" :: "l"(p), "r"(threadIdx.x & 31) : "memory");
}
__device__ __forceinline__ void count_hint(int id) { red_lane0(g_s.cnt[id] + (threadIdx.x & 31)); }
__device__ __forceinline__ void count_release(int id) {
    __syncwarp();
    if ((threadIdx.x & 31) == 0) asm volatile("red.release.gpu.global.add.u32 [%0], 1;" :: "l"(g_s.cnt[id]) : "memory");
    __syncwarp();
}
__device__ __forceinline__ void count_wait(int id, unsigned target) {
    uint32_t v; int spins = 0;
    do v = ldg32_relaxed(g_s.cnt[id]); while (__any_sync(0xffffffffu, v != target) && ++spins < SPIN_LIMIT);
    asm volatile("fence.acquire.gpu;" ::: "memory");
}
__device__ __forceinline__ void lane0_arrive(uint32_t bar) {
    asm volatile("{.reg .pred p; setp.eq.u32 p, %1, 0; @p mbarrier.arrive.shared::cta.b64 _, [%0];}" :: "r"(bar), "r"(threadIdx.x & 31) : "memory");
}
__device__ __forceinline__ void pair_done(uint32_t bar) {
    asm volatile("{.reg .pred p; setp.lt.u32 p, %1, 2; @p mbarrier.arrive.shared::cluster.b64 _, [%0];}" :: "r"(bar), "r"(threadIdx.x & 31) : "memory");
}
__device__ __forceinline__ void tma2d_pair(uint32_t dst, const CUtensorMap* tm, int c0, int c1, uint32_t bar) {
    asm volatile("cp.async.bulk.tensor.2d.shared::cluster.global.mbarrier::complete_tx::bytes.multicast::cluster [%0], [%1, {%3, %4}], [%2], %5;"
                 :: "r"(dst), "l"(tm), "r"(bar), "r"(c0), "r"(c1), "h"((unsigned short)3) : "memory");
}
__device__ __forceinline__ void warp_done(uint32_t bar) {
    __syncwarp();
    asm volatile("{.reg .pred p; setp.eq.u32 p, %1, 0; @p mbarrier.arrive.shared::cta.b64 _, [%0];}" :: "r"(bar), "r"(threadIdx.x & 31) : "memory");
}
__device__ __forceinline__ uint32_t mul_f16x2(uint32_t a, uint32_t b) { uint32_t r; asm("mul.rn.f16x2 %0, %1, %2;" : "=r"(r) : "r"(a), "r"(b)); return r; }
__device__ __forceinline__ uint32_t fma_f16x2(uint32_t a, uint32_t b, uint32_t c) { uint32_t r; asm("fma.rn.f16x2 %0, %1, %2, %3;" : "=r"(r) : "r"(a), "r"(b), "r"(c)); return r; }
__device__ __forceinline__ uint32_t vmax_u16x2(uint32_t a, uint32_t b) { uint32_t r; asm("max.u16x2 %0, %1, %2;" : "=r"(r) : "r"(a), "r"(b)); return r; }
__device__ __forceinline__ uint32_t mul_bf16x2(uint32_t a, uint32_t b) { uint32_t r; asm("mul.rn.bf16x2 %0, %1, %2;" : "=r"(r) : "r"(a), "r"(b)); return r; }
__device__ __forceinline__ uint32_t fma_bf16x2(uint32_t a, uint32_t b, uint32_t c) { uint32_t r; asm("fma.rn.bf16x2 %0, %1, %2, %3;" : "=r"(r) : "r"(a), "r"(b), "r"(c)); return r; }
__device__ __forceinline__ uint32_t add_bf16x2(uint32_t a, uint32_t b) { uint32_t r; asm("add.rn.bf16x2 %0, %1, %2;" : "=r"(r) : "r"(a), "r"(b)); return r; }

#define R4(d, o) "+f"(d[o + 0]), "+f"(d[o + 1]), "+f"(d[o + 2]), "+f"(d[o + 3])
#define R8(d, o) R4(d, o), R4(d, o + 4)
#define R32(d) R8(d, 0), R8(d, 8), R8(d, 16), R8(d, 24)
#define D32 "{%0,%1,%2,%3,%4,%5,%6,%7,%8,%9,%10,%11,%12,%13,%14,%15,%16,%17,%18,%19,%20,%21,%22,%23,%24,%25,%26,%27,%28,%29,%30,%31}"
#define D64 "{%0,%1,%2,%3,%4,%5,%6,%7,%8,%9,%10,%11,%12,%13,%14,%15,%16,%17,%18,%19,%20,%21,%22,%23,%24,%25,%26,%27,%28,%29,%30,%31,%32,%33,%34,%35,%36,%37,%38,%39,%40,%41,%42,%43,%44,%45,%46,%47,%48,%49,%50,%51,%52,%53,%54,%55,%56,%57,%58,%59,%60,%61,%62,%63}"

__device__ __forceinline__ void mma_qk_f16(float (&d)[32], uint64_t da, uint64_t db) {
    asm volatile("{.reg .pred p; setp.eq.b32 p, 0, 0; wgmma.mma_async.sync.aligned.m64n64k16.f32.f16.f16 " D32 ", %32, %33, p, 1, 1, 0, 0;}"
                 : R32(d) : "l"(da), "l"(db));
}
__device__ __forceinline__ void mma_qk_bf16(float (&d)[32], uint64_t da, uint64_t db) {
    asm volatile("{.reg .pred p; setp.ne.b32 p, 0, 0; wgmma.mma_async.sync.aligned.m64n64k16.f32.bf16.bf16 " D32 ", %32, %33, p, 1, 1, 0, 0;}"
                 : R32(d) : "l"(da), "l"(db));
}
__device__ __forceinline__ void mma_pv(float (&d)[12], const uint32_t* a, uint64_t db) {
    asm volatile("{.reg .pred p; setp.eq.b32 p, 0, 0; wgmma.mma_async.sync.aligned.m64n24k16.f32.bf16.bf16 {%0,%1,%2,%3,%4,%5,%6,%7,%8,%9,%10,%11}, {%12,%13,%14,%15}, %16, p, 1, 1, 1;}"
                 : R8(d, 0), R4(d, 8) : "r"(a[0]), "r"(a[1]), "r"(a[2]), "r"(a[3]), "l"(db));
}
__device__ __forceinline__ void mma_ss128(float (&d)[64], uint64_t da, uint64_t db, int accum) {
    asm volatile("{.reg .pred p; setp.ne.b32 p, %66, 0; wgmma.mma_async.sync.aligned.m64n128k16.f32.bf16.bf16 " D64 ", %64, %65, p, 1, 1, 0, 1;}"
                 : R32(d), R8(d, 32), R8(d, 40), R8(d, 48), R8(d, 56) : "l"(da), "l"(db), "r"(accum));
}
__device__ __forceinline__ void stsm4(uint32_t addr, uint32_t a, uint32_t b, uint32_t c, uint32_t d) {
    asm volatile("stmatrix.sync.aligned.m8n8.x4.shared.b16 [%0], {%1,%2,%3,%4};" :: "r"(addr), "r"(a), "r"(b), "r"(c), "r"(d) : "memory");
}
__device__ __forceinline__ void mma_ss8(float (&d)[4], uint64_t da, uint64_t db, int accum) {
    asm volatile("{.reg .pred p; setp.ne.b32 p, %6, 0; wgmma.mma_async.sync.aligned.m64n8k16.f32.bf16.bf16 {%0,%1,%2,%3}, %4, %5, p, 1, 1, 0, 1;}"
                 : R4(d, 0) : "l"(da), "l"(db), "r"(accum));
}
__device__ __forceinline__ void mma_ss(float (&d)[32], uint64_t da, uint64_t db, int accum) {
    asm volatile("{.reg .pred p; setp.ne.b32 p, %34, 0; wgmma.mma_async.sync.aligned.m64n64k16.f32.bf16.bf16 " D32 ", %32, %33, p, 1, 1, 0, 1;}"
                 : R32(d) : "l"(da), "l"(db), "r"(accum));
}
__device__ __forceinline__ void mma_ss(float (&d)[88], uint64_t da, uint64_t db, int accum) {
    asm volatile("{.reg .pred p; setp.ne.b32 p, %90, 0; wgmma.mma_async.sync.aligned.m64n176k16.f32.bf16.bf16 " "{%0,%1,%2,%3,%4,%5,%6,%7,%8,%9,%10,%11,%12,%13,%14,%15,%16,%17,%18,%19,%20,%21,%22,%23,%24,%25,%26,%27,%28,%29,%30,%31,%32,%33,%34,%35,%36,%37,%38,%39,%40,%41,%42,%43,%44,%45,%46,%47,%48,%49,%50,%51,%52,%53,%54,%55,%56,%57,%58,%59,%60,%61,%62,%63,%64,%65,%66,%67,%68,%69,%70,%71,%72,%73,%74,%75,%76,%77,%78,%79,%80,%81,%82,%83,%84,%85,%86,%87}"
                 ", %88, %89, p, 1, 1, 0, 1;}"
                 : R32(d), R8(d, 32), R8(d, 40), R8(d, 48), R8(d, 56), R8(d, 64), R8(d, 72), R8(d, 80) : "l"(da), "l"(db), "r"(accum));
}

constexpr float EXP_MAGIC = 256.0f + 127.0f + 64.0f - 1.58621f + 0.00390625f;
#define MUFU_M 0x1111u
#define ATT_MODE 1
#define ALU_M 0x0000u
constexpr uint32_t MUFU_MASK = MUFU_M;
constexpr uint32_t ALU_MASK = ALU_M;
template <bool ALU>
__device__ __forceinline__ uint32_t exp2_pair(float y0, float y1, uint32_t cexp, uint32_t neg1) {
    uint32_t w, m, e, r;
    asm("prmt.b32 %0, %1, %2, 0x6521;" : "=r"(w) : "r"(__float_as_uint(y0)), "r"(__float_as_uint(y1)));
    asm("lop3.b32 %0, %1, 0x007F007F, %2, 0xEA;" : "=r"(m) : "r"(w), "r"(cexp));
    if (ALU) e = w - m;
    else asm("mad.lo.u32 %0, %1, %2, %3;" : "=r"(e) : "r"(m), "r"(neg1), "r"(w));
    asm("fma.rn.bf16x2 %0, %1, %2, %3;" : "=r"(r) : "r"(w), "r"(m), "r"(e));
    return r;
}

struct Params {
    const __nv_bfloat16* wqp;
    __nv_bfloat16* out;
    uint32_t neg1, pad;
    const __nv_bfloat16* w1p;
    const __nv_bfloat16* w2p;
    CUtensorMap wq, wo, w1, w2, w2s;
    const __nv_bfloat16* wop;
};

__device__ __forceinline__ int cta_id() {
    const uint32_t c = blockIdx.x >> 1, t = c - 4, u = c - 36, q = (u * 37) >> 8;
    const uint32_t p = c < 4 ? 4 + c : c < 36 ? (t & 7) * 8 + (t >> 3) : c < 64 ? (1 + u - 7 * q) * 8 + 4 + q : c;
    return p * 2 + (blockIdx.x & 1);
}
__device__ __forceinline__ int tail_m(int b) { return (b >> 4) * 2 + (b & 1); }
__device__ __forceinline__ int tail_j(int b) { return (b >> 1) & 7; }
__device__ __forceinline__ int opaque(int v) { asm volatile("" : "+r"(v)); return v; }
__device__ __forceinline__ void load_box(uint32_t sb, const CUtensorMap* tm, uint32_t dst, uint32_t bar, uint32_t bytes, int c0, int c1) {
    mbar_expect(sb + SM_MISC + bar * 8, bytes);
    tma2d(sb + dst, tm, c0, c1, sb + SM_MISC + bar * 8);
}
__device__ __forceinline__ void load_wq(uint32_t sb, const Params& P, int b, int gi, int atom) {
    load_box(sb, &P.wq, (((atom ? WQ1_SLOTS : WQ0_SLOTS) >> (8 * gi)) & 31) * SLOT, MB_WQ + gi, 16384, (b & 3) * 128 + atom * 64, gi * 128);
}
__device__ __forceinline__ void load_wo(uint32_t sb, const Params& P, int b, int kb) { load_box(sb, &P.wo, wo_slot(kb) * SLOT, MB_WO, SLOT, tail_j(b) * 64, kb * 64); }
__device__ __forceinline__ void refill_job(uint32_t sb, const Params& P, int b, int gi, int job) {
    const bool w1 = job < 3;
    load_box(sb, w1 ? &P.w1 : &P.wo, (w1 ? 12 + gi + 4 * job : 2 * gi + job - 3) * SLOT, w1 ? MB_W1 + gi : MB_WO, SLOT,
             tail_j(b) * (w1 ? 176 : 64) + (w1 ? job * 64 : 0), (w1 ? gi : 2 * gi + job - 1) * 64);
}

__host__ __device__ constexpr int ring_entry(int n) { return n < 32 ? (n & 3) : (n - 32) % 6; }
__host__ __device__ constexpr uint32_t ring_slot(int e) { return e < 4 ? 24 + e : e - 1; }

template <int KIND> __host__ __device__ constexpr uint64_t b_slots(int first) {
    uint64_t v = 0;
    for (int i = first; i < first + 12; i++) v |= (uint64_t)((KIND == 0 ? wo_slot(i) : KIND == 1 ? w1_slot(i, 0) : w1_slot(i / 3, i % 3)) & 31) << (5 * (i - first));
    return v;
}
__device__ __forceinline__ uint64_t desc64(uint32_t lo, uint32_t hi) { uint64_t d; asm("mov.b64 %0, {%1, %2};" : "=l"(d) : "r"(lo), "r"(hi)); return d; }
__device__ __forceinline__ uint32_t mbar_test(uint32_t bar) {
    uint32_t done;
    asm volatile("{.reg .pred p; mbarrier.test_wait.parity.shared::cta.b64 p, [%1], 0; selp.u32 %0, 1, 0, p;}" : "=r"(done) : "r"(bar) : "memory");
    return done;
}
template <int KIND, int NACC>
__device__ __forceinline__ bool gemm_ss(float (&acc)[NACC], uint32_t sb, int pr TS_ARG) {
    const uint32_t mb = sb + SM_MISC;
    constexpr int NBLK = KIND == 2 ? 22 : 8, N0 = 16 * KIND;
    uint32_t full = mb + (MB_FULL + N0 + pr * NBLK) * 8, empty = mb + MB_NULL * 8, rel = mb + MB_NULL * 8;
    const uint32_t lane = threadIdx.x & 31, probe = sb + ((threadIdx.x >> 5) & 3) * 512 + (lane >> 4) * 2048 + (lane & 15) * 32 + (lane >> 2) * 4;
    uint32_t m = 0;
    uint32_t e = KIND == 2 ? 2 * pr : 0;
    uint64_t tab = b_slots<KIND>(0);
    const uint64_t tab2 = (b_slots<KIND>(12) & ((1ull << 45) - 1)) | ((uint64_t)(pr ? 27 : 25) << 45);
    const uint32_t a0 = ((sb & 0x3FFFF) >> 4) | (8 << 16);
    uint32_t b0 = ((sb & 0x3FFFF) >> 4) | ((KIND == 1 ? 4 * SLOT / 16 : 1) << 16);
    uint32_t peer;
    asm("mapa.shared::cluster.u32 %0, %1, %2;" : "=r"(peer) : "r"(sb), "r"((blockIdx.x & 1) ^ (lane & 1)));
    peer -= sb;
    uint64_t da = desc64(a0 + ring_slot(e) * 512, 16), db = desc64(b0 + ((uint32_t)tab & 31) * 512, 0x40000040);
    uint32_t pa = ring_slot(e) * SLOT;
    mbar_wait(full);
    full += 8;
#pragma unroll 1
    for (int i = 0; i < NBLK; i++) {
        const uint32_t ready = mbar_test(full), next = full;
        const uint32_t m0 = lds32(probe + pa), m1 = lds32(probe + pa + 4096);
        wg_fence();
#pragma unroll
        for (int s = 0; s < 4; s++) mma_ss(acc, da + s * 128, db + s * 128, s ? 1 : i);
        wg_commit();
        const uint32_t prev = empty, prel = rel;
        empty = mb + (MB_EMPTY + e) * 8;
        rel = mb + (MB_REL + i) * 8;
        e = (e == (KIND == 2 ? 6 : 3)) ? 0 : e + 1;
        tab = (KIND == 2 && i == 11) ? tab2 : tab >> 5;
        if (KIND == 1 && i == 3) b0 -= (3 * SLOT / 16) << 16;
        full += (i >= NBLK - 2) ? 0 : 8;
        pa = ring_slot(e) * SLOT;
        da = desc64(a0 + ring_slot(e) * 512, 16); db = desc64(b0 + ((uint32_t)tab & 31) * 512, 0x40000040);
        asm volatile("" : "+l"(da), "+l"(db), "+l"(tab), "+r"(pa), "+r"(full), "+r"(empty), "+r"(e));
        wg_wait<1>();
        warp_done(prev);
        if (KIND != 2) pair_done(prel + peer);
        if (!__all_sync(0xffffffffu, ready)) mbar_wait(next);
        asm volatile("{max.u32 %0, %0, %1; max.u32 %0, %0, %2;}" : "+r"(m) : "r"(m0), "r"(m1) : "memory");
    }
    bool bad = __any_sync(0xffffffffu, m == SENT);
    wg_wait<0>();
    fence_regs(acc);
    warp_done(empty);
    if (KIND == 2) warp_done(empty + 8); else pair_done(rel + peer);
    return __builtin_expect(bad, 0);
}
__device__ __forceinline__ bool gemm_wo(float (&acc)[32], uint32_t sb, int pr TS_ARG) {
    const uint32_t mb = sb + SM_MISC;
    const uint32_t lane = threadIdx.x & 31, probe = sb + ((threadIdx.x >> 5) & 3) * 512 + (lane >> 4) * 2048 + (lane & 15) * 32 + (lane >> 2) * 4;
    uint64_t ra = pr ? 0x090807061B1A130Full : 0x0816120E1B1A1918ull;
    const uint32_t a0 = ((sb & 0x3FFFF) >> 4) | (8 << 16), b0 = ((sb & 0x3FFFF) >> 4) | (1 << 16);
    uint32_t m = 0, full = mb + (MB_FULL + pr * 8) * 8, peer;
    asm("mapa.shared::cluster.u32 %0, %1, %2;" : "=r"(peer) : "r"(mb), "r"((blockIdx.x & 1) ^ (lane & 1)));
    mbar_wait(full); mbar_wait(full + 8);
#pragma unroll 1
    for (int i = 0; i < 4; i++, ra >>= 16) {
        const uint32_t sa = (uint32_t)ra & 31, sc = ((uint32_t)ra >> 8) & 31, db = b0 + wo_slot(2 * i) * 512;
        full += (i == 3) ? 0 : 16;
        const uint32_t ready = mbar_test(full) & mbar_test(full + 8);
        const uint32_t m0 = lds32(probe + sa * SLOT), m1 = lds32(probe + sa * SLOT + 4096), m2 = lds32(probe + sc * SLOT), m3 = lds32(probe + sc * SLOT + 4096);
        wg_fence();
#pragma unroll
        for (int s = 0; s < 8; s++) mma_ss(acc, desc64(a0 + (s < 4 ? sa : sc) * 512 + (s & 3) * 128, 16), desc64(db + s * 128, 0x40000040), s ? 1 : i);
        wg_commit();
        m = max(max(m, max(m0, m1)), max(m2, m3));
        wg_wait<1>();
        __syncwarp();
        pair_done((i & 1) ? peer + (MB_RELW + (i >> 1)) * 8 : (i && pr) ? mb + (MB_EMPTY + 2 + (lane & 1)) * 8 : peer + MB_NULL * 8);
        if (!__all_sync(0xffffffffu, ready)) { mbar_wait(full); mbar_wait(full + 8); }
    }
    const bool bad = __any_sync(0xffffffffu, m == SENT);
    wg_wait<0>();
    fence_regs(acc);
    pair_done(peer + (MB_RELW + 2) * 8);
    if (!pr) pair_done(peer + MB_WOA * 8);
    return __builtin_expect(bad, 0);
}
__device__ __forceinline__ void ring_feed(const Params& P, uint32_t sb, int b, int e TS_ARG) {
    const uint32_t mb = sb + SM_MISC;
    uint32_t dst = sb + ring_slot(e) * SLOT, empty = mb + (MB_EMPTY + e) * 8;
    const bool lead = (threadIdx.x & 31) == 0;
    const uint4* base = g_x + tail_m(b) * 4096 + e * 512;
    uint32_t par = 0;
    auto fetch = [&](int n, const uint4* src, int job) {
        const uint32_t full = mb + (MB_FULL + n) * 8;
        if (lead) mbar_expect(full, SLOT);
        mbar_wait(empty, par); par ^= 1;
        if (job) mbar_wait(mb + (MB_READY + job) * 8);
        if (lead) bulk_g2s(dst, src, SLOT, full);
        __syncwarp();
    };
    if (e < 4) {
        if (lead) { mbar_expect(mb + (MB_FULL + 8 + e) * 8, SLOT); mbar_expect(mb + (MB_FULL + 12 + e) * 8, SLOT); }
        mbar_wait(mb + (MB_DONE + 4) * 8);
        if (e >= 2) mbar_wait(mb + MB_WOA * 8);
        count_wait(C_O + 16 + tail_m(b), lds32(mb + MISC_EPOCH) * 128);
        asm volatile("fence.proxy.async.global;" ::: "memory");
        if (lead) {
            bulk_g2s(sb + (e < 2 ? 15 + 4 * e : 24 + e) * SLOT, base + 65536, SLOT, mb + (MB_FULL + 8 + e) * 8);
            bulk_g2s(sb + (6 + e) * SLOT, base + 65536 + 2048, SLOT, mb + (MB_FULL + 12 + e) * 8);
        }
        __syncwarp();
        if (e < 2) { mbar_wait(mb + MB_WOA * 8); par = 1; }
#pragma unroll 1
        for (int h = 0; h < 2; h++) {
            fetch(16 + 8 * h + e, base + X_H1 + h * 65536, 2 + h);
            fetch(20 + 8 * h + e, base + X_H1 + h * 65536 + 2048, 0);
        }
    } else {
        if (e == 4) {
        mbar_wait(mb + (MB_DONE + 4) * 8);
#pragma unroll 1
        for (int h = 0; h < 2; h++) {
            const uint4* sp = g_x + X_ST + (h * 16 + tail_m(b)) * 256 + (threadIdx.x & 31);
            mbar_wait(mb + (MB_READY + 2 + h) * 8);
            uint4 u[8]; uint32_t m; int spins = 0;
            do {
                m = 0;
#pragma unroll
                for (int k = 0; k < 8; k++) u[k] = ldg_relaxed(sp + k * 32);
#pragma unroll
                for (int k = 0; k < 8; k++) m = max(m, u[k].x);
            } while (__any_sync(0xffffffffu, m == SENT) && ++spins < SPIN_LIMIT);
            float st[4] = {0.f, 0.f, 0.f, 0.f};
#pragma unroll
            for (int k = 0; k < 8; k++) { st[0] += __uint_as_float(u[k].x); st[1] += __uint_as_float(u[k].y); st[2] += __uint_as_float(u[k].z); st[3] += __uint_as_float(u[k].w); }
#pragma unroll
            for (int k = 0; k < 2; k++) {
                const float nmean = st[2 * k] * (-1.0f / D);
                st[2 * k + 1] = 0.5f * rsqrtf(fmaxf(fmaf(-nmean, nmean, st[2 * k + 1] * (1.0f / D)), 0.f) + 1e-5f);
                st[2 * k] = nmean * st[2 * k + 1];
            }
            sts128(mb + MISC_STAT + h * 512 + (threadIdx.x & 31) * 16, __float_as_uint(st[0]), __float_as_uint(st[1]), __float_as_uint(st[2]), __float_as_uint(st[3]));
            warp_done(mb + (MB_STAT + h) * 8);
        }
        }
        mbar_wait(mb + (MB_REL + 7) * 8);
        par = 1;
    }
    const uint4* src = g_x + X_H2 + tail_m(b) * 88 * 128 + e * 512;
#pragma unroll 1
    for (int t = e; t < 46; t += 7, src += 7 * 512) {
        if (t >= 23 && t < 30) { src += 16 * 88 * 128 - 23 * 512; mbar_wait(mb + (MB_READY + 5) * 8); }
        if (t >= 8 && t < 15) mbar_wait(mb + (MB_READY + 4) * 8);
        const int n = 32 + t - (t >= 23);
        if (t == 22 || t == 45) {
            const uint32_t full = mb + (MB_FULL + n - 1) * 8;
            if (lead) mbar_expect(full, SLOT);
            mbar_wait(empty, par); par ^= 1;
            if (lead) tma2d(dst, &P.w2, tail_j(b) * 64, 7 * 176 + 64, full);
            __syncwarp();
        } else fetch(n, src, t < 7 ? (int)MB_EARLY - (int)MB_READY : 0);
        if (e == 4) {
            par ^= 1; dst += SLOT; empty += 8;
            fetch(n + 1, src + 512, 0);
            dst -= SLOT; empty -= 8;
        }
    }
}
__device__ __forceinline__ int f2_row(int pos) {
    return pos < 32 ? (pos >> 2) * 176 + (pos & 3) * 16 : pos < 60 ? ((pos - 32) >> 2) * 176 + 64 + (pos & 3) * 16
         : pos < 84 ? ((pos - 60) / 3) * 176 + 128 + ((pos - 60) % 3) * 16 : 7 * 176 + 64 + (pos & 3) * 16;
}
__device__ float4 g_redo[NMAIN * 2 * 22 * 128];
__device__ __noinline__ void gemm_slow_impl(float4* out, int ntile, const uint4* a, int nst, const __nv_bfloat16* W, int ldw, int kmax, int n0) {
    const int lane = threadIdx.x & 31;
    const unsigned short* w = reinterpret_cast<const unsigned short*>(W);
    for (int j = 0; j < ntile; j++) {
        const uint32_t* p = reinterpret_cast<const uint32_t*>(a) + ((threadIdx.x >> 5) & 3) * 128 + lane;
        const int n = n0 + 8 * j + (lane >> 2);
        float d[4] = {0.f, 0.f, 0.f, 0.f};
        for (int st = 0; st < nst; st++, p += 512) {
            const int k = (nst == 88 ? f2_row(st) : st * 16) + 2 * (lane & 3);
            uint32_t v0, v1, v2, v3, b0 = 0, b1 = 0; int spins = 0;
            do { v0 = ldg32_relaxed(p); v1 = ldg32_relaxed(p + 64); v2 = ldg32_relaxed(p + 32); v3 = ldg32_relaxed(p + 96); }
            while (__any_sync(0xffffffffu, max(max(v0, v1), max(v2, v3)) == SENT) && ++spins < SPIN_LIMIT);
            if (k < kmax && n < ldw) {
                const unsigned short* q = w + (size_t)k * ldw + n;
                b0 = q[0] | ((uint32_t)q[ldw] << 16); b1 = q[8 * ldw] | ((uint32_t)q[9 * ldw] << 16);
            }
            asm volatile("mma.sync.aligned.m16n8k16.row.col.f32.bf16.bf16.f32 {%0,%1,%2,%3}, {%4,%5,%6,%7}, {%8,%9}, {%0,%1,%2,%3};"
                         : R4(d, 0) : "r"(v0), "r"(v1), "r"(v2), "r"(v3), "r"(b0), "r"(b1));
        }
        out[j * 128] = make_float4(d[0], d[1], d[2], d[3]);
    }
}
template <int NACC>
__device__ __forceinline__ void gemm_slow(float (&acc)[NACC], const uint4* a, int nst, const __nv_bfloat16* W, int ldw, int kmax, int n0) {
    float4* tmp = g_redo + (blockIdx.x * 2 + (threadIdx.x >> 8)) * 22 * 128 + (threadIdx.x & 127);
    gemm_slow_impl(tmp, NACC / 4, a, nst, W, ldw, kmax, n0);
#pragma unroll
    for (int i = 0; i < NACC / 4; i++) { const float4 v = tmp[i * 128]; acc[4 * i] = v.x; acc[4 * i + 1] = v.y; acc[4 * i + 2] = v.z; acc[4 * i + 3] = v.w; }
}
__device__ __forceinline__ void store_tile(uint32_t* p, uint32_t r0k0, uint32_t r8k0, uint32_t r0k8, uint32_t r8k8) {
    stg32(p, r0k0); stg32(p + 32, r0k8); stg32(p + 64, r8k0); stg32(p + 96, r8k8);
}

__device__ __forceinline__ float quad_sum(float v) { v += __shfl_xor_sync(0xffffffffu, v, 1); v += __shfl_xor_sync(0xffffffffu, v, 2); return v; }
__device__ __forceinline__ float reduce4(const float (&st)[4], int lane) {
    const bool u16 = lane & 16, u8 = lane & 8;
    const float a0 = (u16 ? st[2] : st[0]) + __shfl_xor_sync(0xffffffffu, u16 ? st[0] : st[2], 16);
    const float a1 = (u16 ? st[3] : st[1]) + __shfl_xor_sync(0xffffffffu, u16 ? st[1] : st[3], 16);
    float v = (u8 ? a1 : a0) + __shfl_xor_sync(0xffffffffu, u8 ? a0 : a1, 8);
    v += __shfl_xor_sync(0xffffffffu, v, 4); v += __shfl_xor_sync(0xffffffffu, v, 2); v += __shfl_xor_sync(0xffffffffu, v, 1);
    return v;
}
__device__ __forceinline__ float silu2(float h) { float t; asm("tanh.approx.f32 %0, %1;" : "=f"(t) : "f"(h)); return fmaf(h, t, h); }

__device__ __forceinline__ void init_acc(float (&s)[32], float (&o)[12]) {
#pragma unroll
    for (int i = 0; i < 12; i++) o[i] = 0.f;
#pragma unroll
    for (int i = 0; i < 32; i++) s[i] = ((MUFU_MASK >> (i / 2)) & 1) ? 0.f : EXP_MAGIC;
    fence_regs(s); fence_regs(o);
}
#define OWNERS 0x32231
#define RESET_WG 3
#define CONS_A 0
__host__ __device__ constexpr uint32_t chore_list(int wg) {
    const int at[5] = {3, 6, 8, 10, 14};
    uint32_t v = 0; int sh = 0, done = 0;
    for (int c = 0; c < 5; c++) if (((OWNERS >> (4 * c)) & 15) == wg) { v |= (uint32_t)((c << 4) | (at[c] - done)) << sh; sh += 8; done = at[c]; }
    return v | (uint32_t)(0x80 | ((16 - done) & 15)) << sh;
}
template <bool SAFE>
__device__ __forceinline__ void attention(float (&s)[32], float (&o)[12], const Params& P, uint32_t sb, int warp, int b0, uint32_t* optr, unsigned* ocnt, uint32_t chores TS_ARG) {
    const uint32_t mb = sb + SM_MISC;
    const int tid = threadIdx.x, lane = tid & 31;
    const int wg = warp >> 2;
    const uint32_t cexp = 0x9F809F80u + (tid >> 12);
    const uint32_t neg1 = P.neg1;
#pragma unroll 1
    for (int pass = 0; pass < 2; pass++) {
    const uint64_t dq = mkdesc(sb + SM_Q + (pass * 4 + wg) * 2048, 128, 256, 0);
    uint64_t dk = mkdesc(sb + SM_K, 128, 256, 0), dv = mkdesc(sb + SM_V, 128, 32768, 0);
    float m0 = -INFINITY, m1 = -INFINITY;
    wg_fence();
    if (SAFE) mma_qk_f16(s, dq, dk + 31 * 128); else mma_qk_bf16(s, dq, dk + 31 * 128);
    wg_commit();
    wg_wait<0>(); fence_regs(s);
    uint32_t prog = pass ? mb + MISC_PROG : mb + MB_NULL * 8;
    uint32_t units = pass ? chores : 0x8C54u;
#pragma unroll 1
    while (true) {
        int n = 2 * (((units - 1) & 15) + 1);
        const int chore = (units >> 4) & 15;
        units >>= 8;
        if (SAFE) {
            auto tile = [&](uint32_t (&p)[16]) {
#pragma unroll
                for (int j = 0; j < 16; j++) {
                    if ((MUFU_MASK >> j) & 1) p[j] = pack_bf16(ex2(s[2 * j]), ex2(s[2 * j + 1]));
                    else if ((ALU_MASK >> j) & 1) p[j] = exp2_pair<true>(s[2 * j], s[2 * j + 1], cexp, neg1);
                    else p[j] = exp2_pair<false>(s[2 * j], s[2 * j + 1], cexp, neg1);
                }
                fence_regs(p);
                wg_fence();
                if (ATT_MODE != 3) mma_qk_f16(s, dq, dk);
                if (ATT_MODE == 1) wg_commit();
#pragma unroll
                for (int j = 0; j < 4; j++) mma_pv(o, p + 4 * j, dv + j * 16);
                if (ATT_MODE == 3) mma_qk_f16(s, dq, dk);
                wg_commit();
                dk += 128; dv += 64;
                wg_wait<ATT_MODE == 1>(); fence_regs(s);
            };
#pragma unroll 1
            do {
                uint32_t p0[16], p1[16];
                tile(p0);
                tile(p1);
                lane0_arrive(prog); prog += 8 * pass;
            } while ((n -= 2) > 0);
        } else {
#pragma unroll 1
            do {
                uint32_t p[16];
                fence_regs(o);
                float x0 = m0, x1 = m1;
#pragma unroll
                for (int j = 0; j < 8; j++) { x0 = fmaxf(x0, fmaxf(s[4 * j], s[4 * j + 1])); x1 = fmaxf(x1, fmaxf(s[4 * j + 2], s[4 * j + 3])); }
                x0 = fmaxf(x0, __shfl_xor_sync(0xffffffffu, x0, 1)); x0 = fmaxf(x0, __shfl_xor_sync(0xffffffffu, x0, 2));
                x1 = fmaxf(x1, __shfl_xor_sync(0xffffffffu, x1, 1)); x1 = fmaxf(x1, __shfl_xor_sync(0xffffffffu, x1, 2));
                const float c0 = ex2(m0 - x0), c1 = ex2(m1 - x1);
                m0 = x0; m1 = x1;
#pragma unroll
                for (int j = 0; j < 3; j++) { o[4 * j] *= c0; o[4 * j + 1] *= c0; o[4 * j + 2] *= c1; o[4 * j + 3] *= c1; }
#pragma unroll
                for (int j = 0; j < 8; j++) {
                    p[2 * j] = pack_bf16(ex2(s[4 * j] - m0), ex2(s[4 * j + 1] - m0));
                    p[2 * j + 1] = pack_bf16(ex2(s[4 * j + 2] - m1), ex2(s[4 * j + 3] - m1));
                }
                fence_regs(o);
                fence_regs(p);
                wg_fence();
                mma_qk_bf16(s, dq, dk);
#pragma unroll
                for (int j = 0; j < 4; j++) mma_pv(o, p + 4 * j, dv + j * 16);
                wg_commit();
                dk += 128; dv += 64;
                wg_wait<0>(); fence_regs(s);
                if (n & 1) { lane0_arrive(prog); prog += 8 * pass; }
            } while (--n > 0);
        }
        if (chore == 8) break;
        const int b = opaque(b0), ww = __shfl_sync(0xffffffffu, opaque(tid >> 5) & 3, 0);
        if (chore == 5) {
            if (SAFE) mbar_wait(mb + MB_KV * 8);
            TS(17);
            if (lane == 0) {
                if (wg == RESET_WG && ww < 3) {
                    asm volatile("cp.async.bulk.global.shared::cta.bulk_group [%0], [%1], %2;" :: "l"(g_x + X_ARM + b * X_SHARE + ww * 2048), "r"(sb + SM_SENT), "r"(ww < 2 ? 32768 : (X_SHARE - 4096) * 16) : "memory");
                    asm volatile("cp.async.bulk.commit_group;" ::: "memory");
                }
            }
        } else if (chore == 0) {
            if (ww == 0) { mbar_wait(mb + MB_DONE * 8); count_release(C_MID); }
            else if (ww < 3 && lane == 0) load_wo(sb, P, b, ww - 1);
        } else if (chore != 2) {
            const int gi = chore >> 1;
            mbar_wait(mb + MISC_PROG + (4 * gi + 4) * 8);
            if (gi == 2 && ww < 3) {
                mbar_wait(mb + MB_MID * 8);
                if (lane == 0) {
                    mbar_expect(mb + (MB_FULL + 4 + ww) * 8, SLOT);
                    bulk_g2s(sb + (14 + 4 * ww) * SLOT, g_x + X_O + tail_m(b) * 4096 + (4 + ww) * 512, SLOT, mb + (MB_FULL + 4 + ww) * 8);
                }
            } else if (lane == 0) { refill_job(sb, P, b, gi, ww); if (ww == 3) refill_job(sb, P, b, gi, 4); }
        } else {
            count_wait(C_MID, lds32(mb + MISC_EPOCH) * NCTA);
            if (lane == 0) {
                asm volatile("fence.proxy.async.global;" ::: "memory");
                if (ww == 0) mbar_arrive(mb + MB_MID * 8);
                mbar_expect(mb + (MB_FULL + ww) * 8, SLOT);
                bulk_g2s(sb + (24 + ww) * SLOT, g_x + X_O + tail_m(b) * 4096 + ww * 512, SLOT, mb + (MB_FULL + ww) * 8);
                if (ww == 3) { mbar_expect(mb + (MB_FULL + 7) * 8, SLOT); bulk_g2s(sb + 8 * SLOT, g_x + X_O + tail_m(b) * 4096 + 7 * 512, SLOT, mb + (MB_FULL + 7) * 8); }
            }
        }
        __syncwarp();
    }
    wg_wait<0>();
    fence_regs(o);
    const float i0 = rcp(o[8]), i1 = rcp(o[10]);
    if (pass) mbar_wait(mb + MB_MID * 8);
    store_tile(optr, pack_bf16(o[0] * i0, o[1] * i0), pack_bf16(o[2] * i1, o[3] * i1), pack_bf16(o[4] * i0, o[5] * i0), pack_bf16(o[6] * i1, o[7] * i1));
    optr += 16 * 32 * 128 * 4;
    if (pass) red_lane0(ocnt);
    else asm volatile("cp.async.bulk.wait_group 0;" ::: "memory");
    warp_done(mb + (MB_DONE + pass * 4) * 8);
    TS(5 + pass);
    if (pass) break;
    init_acc(s, o);
    }
}

__device__ __forceinline__ unsigned kv_target(unsigned epoch) { return ((epoch + 1) >> 1) * NMAIN; }
__device__ __forceinline__ int kv_slot(int b, int idx) {
    const int t = (idx & 63) >> 1, c = 2 * (b >> 2) + (idx & 1), hg = b & 3;
    return hg < 2 ? ((t + 31) & 31) * 128 + (c >> 3) * 16 + (hg & 1) * 8 + (c & 7) : 4096 + (hg & 1) * 2048 + t * 64 + c;
}

#define HOLDN 384
#define GATE_AT 2
__device__ __noinline__ void helper_cta(const Params& P, uint8_t* smem) {
    const int tid = threadIdx.x, b = blockIdx.x, hi = b - NMAIN;
    const unsigned epoch = g_s.epoch[b] + 1;
    float* red = reinterpret_cast<float*>(smem);
    if (tid < 32) count_wait(C_KV + (epoch & 1), kv_target(epoch));
    bar_sync(0, 512);
    if (tid == 480) {
        for (int i = 0; i < 8; i++) asm volatile("cp.async.bulk.prefetch.L2.global [%0], %1;" :: "l"((const char*)P.wop + hi * 131072 + i * 16384), "r"(16384) : "memory");
        for (int i = 0; i < 43; i++) asm volatile("cp.async.bulk.prefetch.L2.global [%0], %1;" :: "l"((const char*)P.w2p + hi * 352256 + i * 8192), "r"(8192) : "memory");
    }
    if (tid < 344) {
        const int cg = tid % 43, rp = tid / 43;
        const uint4* src = reinterpret_cast<const uint4*>(P.w1p + (size_t)rp * 64 * FF + (hi * 43 + cg) * 8);
        float s[8] = {0, 0, 0, 0, 0, 0, 0, 0};
#pragma unroll 8
        for (int r = 0; r < 64; r++) {
            uint4 v = __ldg(src + r * (FF / 8));
            s[0] += bf_lo(v.x); s[1] += bf_hi(v.x); s[2] += bf_lo(v.y); s[3] += bf_hi(v.y);
            s[4] += bf_lo(v.z); s[5] += bf_hi(v.z); s[6] += bf_lo(v.w); s[7] += bf_hi(v.w);
        }
        float* part = red + (rp * 43 + cg) * 8;
#pragma unroll
        for (int i = 0; i < 8; i++) part[i] = s[i];
    }
    bar_sync(0, 512);
    if (tid < 344) {
        float s = 0.f;
#pragma unroll
        for (int rp = 0; rp < 8; rp++) s += red[rp * 344 + tid];
        g_s.cs[hi * 344 + tid] = s;
    } else if (hi == 3 && tid < 344 + 64) g_s.cs[FF + tid - 344] = 0.f;
    bar_sync(0, 512);
    if (tid < 32) count_release(C_MID);
    if (tid == 0) g_s.epoch[b] = epoch;
    if (hi == 0 && tid < 3) g_s.cnt[C_KV + (~epoch & 1)][1 + tid] = 0;
}

__global__ void __cluster_dims__(2, 1, 1) __launch_bounds__(512, 1) fused_kernel(const __nv_bfloat16* __restrict__ x, const __nv_bfloat16* __restrict__ wk, long long wv_off,
                                                         const __grid_constant__ Params P) {
    extern __shared__ __align__(1024) uint8_t smem[];
    const uint32_t sb = (uint32_t)__cvta_generic_to_shared(smem);
    const uint32_t mb = sb + SM_MISC;
    const int tid = threadIdx.x, lane = tid & 31, b = cta_id();
    const int warp = __shfl_sync(0xffffffffu, tid >> 5, 0);
    if (b >= NMAIN) { helper_cta(P, smem); return; }
    const int tg = b >> 2, hg = b & 3;

    const uint32_t xst = sb + (((0x120A0402u >> (8 * (warp >> 2))) & 31) * SLOT + (warp & 3) * 4096), xbar = mb + MISC_XBAR + warp * 8;
    if (lane == 0) {
        mbar_init(xbar, 1);
        mbar_init(mb + MISC_PROG + warp * 8, 16);
        asm volatile("fence.mbarrier_init.release.cluster;" ::: "memory");
        mbar_expect(xbar, 4096);
        bulk_g2s(xst, x + (size_t)((warp & 7) * 4 + tg * 32 + (warp >> 3) * 1024) * D, 4096, xbar);
    }
    const uint4 wkv = ldg_relaxed(reinterpret_cast<const uint4*>(reinterpret_cast<const char*>(wk) + (hg < 2 ? 0 : wv_off)) + tid * 2 + (hg & 1));
    unsigned epoch = 0;
    const int wg = warp >> 2, ww = warp & 3, g = lane >> 2, t4 = lane & 3, t128 = tid & 127;
    if (lane == 0) {
        if (warp < 4) {
            mbar_init(mb + (MB_WQ + warp) * 8, 2);
            asm volatile("fence.mbarrier_init.release.cluster;" ::: "memory");
            if (warp < 2) { load_wq(sb, P, b, warp, 0); load_wq(sb, P, b, warp, 1); }
            else asm volatile("cp.async.bulk.prefetch.L2.global [%0], %1;" :: "l"((const char*)P.wqp + 262144 + (b * 2 + warp - 2) * 1024), "r"(1024) : "memory");
        } else {
            if (warp < 9) asm volatile("prefetch.tensormap [%0];" :: "l"(&P.wq + (warp - 4)) : "memory");
            const uint32_t first = warp < 8 ? (0x79100904u >> (8 * (warp - 4))) & 255 : warp < 11 ? 14 * warp - 94 : 14 * warp - 95;
            const uint32_t end = warp < 8 ? (0x84121009u >> (8 * (warp - 4))) & 255 : warp < 11 ? 59 : 120;
            const uint32_t cnt = warp < 8 ? (0x10030410u >> (8 * (warp - 4))) & 255 : warp < 11 ? 1 : 2;
#pragma unroll
            for (uint32_t i = 0; i < 14; i++) if (first + i < end) mbar_init(mb + (first + i) * 8, cnt);
            if (warp == 6) { mbar_init(mb + MB_WO * 8, 8); }
            if (warp == 4) mbar_init(mb + MB_WOA * 8, 8);
        }
    }
    __syncwarp();
    TS(16);
    sts128(sb + SM_WKV + tid * 16, wkv.x, wkv.y, wkv.z, wkv.w);
    uint4 xv[4][2];
    mbar_wait(xbar);
#pragma unroll
    for (int i = 0; i < 8; i++) xv[i >> 1][i & 1] = lds128(xst + i * 512 + lane * 16);
    float dlt;
    {
        float st[4];
#pragma unroll
        for (int i = 0; i < 4; i++) {
            const uint32_t s = add_bf16x2(add_bf16x2(add_bf16x2(xv[i][0].x, xv[i][0].y), add_bf16x2(xv[i][0].z, xv[i][0].w)),
                                          add_bf16x2(add_bf16x2(xv[i][1].x, xv[i][1].y), add_bf16x2(xv[i][1].z, xv[i][1].w)));
            st[i] = bf_lo(s) + bf_hi(s);
        }
        TS(13);
        const float tot = reduce4(st, lane) * (-1.0f / D);
        const uint32_t nmr = pack_bf16(tot, tot);
        dlt = bf_lo(nmr) - tot;
        const uint32_t xa[2] = {sb + (((uint32_t)XN_SLOTS >> (lane & 24)) & 31) * SLOT + warp * 512, sb + (((uint32_t)(XN_SLOTS >> 32) >> (lane & 24)) & 31) * SLOT + warp * 512};
#pragma unroll
        for (int i = 0; i < 4; i++) {
            const uint32_t nm = __shfl_sync(0xffffffffu, nmr, i * 8);
            const uint32_t off = i * 128 + (((lane & 7) ^ ((warp & 1) * 4 + i)) << 4);
#pragma unroll
            for (int c = 0; c < 2; c++) {
                xv[i][c].x = add_bf16x2(xv[i][c].x, nm); xv[i][c].y = add_bf16x2(xv[i][c].y, nm);
                xv[i][c].z = add_bf16x2(xv[i][c].z, nm); xv[i][c].w = add_bf16x2(xv[i][c].w, nm);
                sts128(xa[c] + off, xv[i][c].x, xv[i][c].y, xv[i][c].z, xv[i][c].w);
            }
        }
    }
    fence_async_smem();
    TS(0);
    auto variances = [&]() {
        float st[4];
#pragma unroll
        for (int i = 0; i < 4; i++) {
            uint32_t a[2];
#pragma unroll
            for (int c = 0; c < 2; c++)
                a[c] = fma_bf16x2(xv[i][c].x, xv[i][c].x, fma_bf16x2(xv[i][c].y, xv[i][c].y, fma_bf16x2(xv[i][c].z, xv[i][c].z, mul_bf16x2(xv[i][c].w, xv[i][c].w))));
            st[i] = (bf_lo(a[0]) + bf_hi(a[0])) + (bf_lo(a[1]) + bf_hi(a[1]));
        }
        const float vs = reduce4(st, lane);
        if ((lane & 7) == 0) sts32(sb + SM_RSTD + (warp * 4 + (lane >> 3)) * 4, __float_as_uint(rsqrtf(fmaxf(vs * (1.0f / D) - dlt * dlt, 0.f) + 1e-5f)));
    };
    if (wg == 2) {
        float kv[4];
        const uint64_t da = mkdesc(sb, 16, 1024, 1), db = mkdesc(sb + SM_WKV, 128, 16, 0);
        bar_sync(7, 512);
        wg_fence();
#pragma unroll
        for (int s = 0; s < 32; s++) mma_ss8(kv, da + xn_slot(s >> 2) * 512 + (s & 3) * 2, db + s * 16, s);
        wg_commit();
        variances();
        wg_wait<0>(); fence_regs(kv);
        float2* kt = reinterpret_cast<float2*>(smem + SM_KTMP);
        kt[(ww * 16 + g) * 4 + t4] = make_float2(kv[0], kv[1]); kt[(ww * 16 + g + 8) * 4 + t4] = make_float2(kv[2], kv[3]);
        TS(24);
    } else {
        if (wg == 3) {
            if (ww == 0) epoch = ldg32_relaxed(g_s.epoch + b);
            bar_sync(7, 512);
            if (lane == 0) load_wq(sb, P, b, 2 + (ww >> 1), ww & 1);
            __syncwarp();
        } else {
            bar_arrive(7, 512);
            if (warp >= 6) epoch = ldg32_relaxed(g_s.epoch + b);
        }
        variances();
    }
    constexpr float QSCALE = 0.25f * 1.4426950408889634f;
    uint32_t unsafe = 0;
    const uint32_t qbase = sb + SM_Q + (ww >> 1) * 8192 + (ww & 1) * 512 + lane * 16;
    if (wg == 0) {
        float qa[64];
        mbar_wait(mb + MB_WQ * 8);
        bar_sync(0, 512);
        const float rs0 = __uint_as_float(lds32(sb + SM_RSTD + (ww * 16 + g) * 4)) * QSCALE, rs1 = __uint_as_float(lds32(sb + SM_RSTD + (ww * 16 + g + 8) * 4)) * QSCALE;
        bar_sync(2, 384);
#pragma unroll 1
        for (int i = 0; i < 4; i++) {
            const uint32_t s0 = (WQ0_SLOTS >> (8 * i)) & 31, s1 = (WQ1_SLOTS >> (8 * i)) & 31, xs = (uint32_t)(XN_SLOTS >> (16 * i));
            const uint64_t db = mkdesc(sb + s0 * SLOT, (s1 - s0) * SLOT, 1024, 1);
            const uint64_t da0 = mkdesc(sb + (xs & 31) * SLOT, 16, 1024, 1), da1 = mkdesc(sb + ((xs >> 8) & 31) * SLOT, 16, 1024, 1);
            mbar_wait(mb + (MB_WQ + i) * 8);
            wg_fence();
#pragma unroll
            for (int s = 0; s < 8; s++) mma_ss128(qa, (s < 4 ? da0 : da1) + (s & 3) * 2, db + s * 128, s ? 1 : i);
            wg_commit();
            wg_wait<1>();
            if (i == 1) bar_arrive(6, 160);
            if (i == 2) bar_arrive(4, 256);
        }
        wg_wait<0>();
        fence_regs(qa);
        TS(1);
        uint32_t nq = 0;
#pragma unroll
        for (int h = 0; h < 8; h++) {
            const float* v = qa + 8 * h;
            const uint32_t q0 = pack_f16(v[0] * rs0, v[1] * rs0), q1 = pack_f16(v[4] * rs0, v[5] * rs0), q2 = pack_f16(v[2] * rs1, v[3] * rs1), q3 = pack_f16(v[6] * rs1, v[7] * rs1);
            stsm4(qbase + h * 1024, q0, q1, q2, q3);
            nq = vmax_u16x2(nq, vmax_u16x2(fma_f16x2(q0, q0, mul_f16x2(q1, q1)), fma_f16x2(q2, q2, mul_f16x2(q3, q3))));
        }
        const float q2 = quad_sum(__half2float(__ushort_as_half(nq & 0xFFFF)) + __half2float(__ushort_as_half(nq >> 16)));
        bar_sync(5, 160);
        const float4 nr = lds128f(mb + MISC_NRM);
        const bool ok = (q2 * (nr.y + nr.z) <= 3500.0f) && (q2 <= 60000.0f) && (nr.y + nr.z <= 65536.0f) && (nr.w <= 1e24f);
        asm volatile("{.reg .pred p, q; setp.eq.u32 p, %1, 0; barrier.red.or.pred.aligned q, 5, 128, p; selp.u32 %0, 1, 0, q;}" : "=r"(unsafe) : "r"((uint32_t)ok) : "memory");
        if (__builtin_expect(__any_sync(0xffffffffu, unsafe), 0)) {
#pragma unroll
            for (int h = 0; h < 8; h++) {
                const float* v = qa + 8 * h;
                stsm4(qbase + h * 1024, pack_bf16(v[0] * rs0, v[1] * rs0), pack_bf16(v[4] * rs0, v[5] * rs0), pack_bf16(v[2] * rs1, v[3] * rs1), pack_bf16(v[6] * rs1, v[7] * rs1));
            }
        }
    } else if (wg == 2) {
        bar_arrive(0, 512);
        bar_sync(2, HOLDN);
#pragma unroll
        for (int i = 0; i < 32; i++) {
            const int k = i < 4 ? i : i < 8 ? 20 + i : i < 28 ? i - 4 : i;
            if (i == 8) bar_sync(4, 256);
            const uint32_t v = k < 16 ? 0x3F803F80u : SENT;
            sts128(sb + SM_V + 65536 + (k * 128 + t128) * 16, v, v, v, v);
        }
    } else if (wg == 1) {
        const int r = (lane & 1) * 32 + ((t128 & 63) >> 1);
        const uint32_t ra = sb + SM_KTMP + r * 32, rb = ra - (r ? 32 : 0);
        uint4* kvdst = (ww < 2 ? g_s.kv : g_s.kplain) + kv_slot(b, tid);
        asm volatile("" : "+l"(kvdst));
        bar_sync(0, 512);
        float4 c0 = lds128f(ra), c1 = lds128f(ra + 16);
        const float rs = __uint_as_float(lds32(sb + SM_RSTD + r * 4)), rq = __uint_as_float(lds32(sb + SM_RSTD + r * 4 - 4));
        const float4 p0 = lds128f(rb), p1 = lds128f(rb + 16);
        c0.x *= rs; c0.y *= rs; c0.z *= rs; c0.w *= rs; c1.x *= rs; c1.y *= rs; c1.z *= rs; c1.w *= rs;
        if (ww < 2 && hg < 2) {
            const float rp = (r & 31) ? -rq : 0.f;
            stg128(kvdst, nonzero(pack_f16(fmaf(p0.x, rp, c0.x), fmaf(p0.y, rp, c0.y))), nonzero(pack_f16(fmaf(p0.z, rp, c0.z), fmaf(p0.w, rp, c0.w))),
                   nonzero(pack_f16(fmaf(p1.x, rp, c1.x), fmaf(p1.y, rp, c1.y))), nonzero(pack_f16(fmaf(p1.z, rp, c1.z), fmaf(p1.w, rp, c1.w))));
        } else {
            if (ww >= 2) {
                epoch++;
                const uint32_t nm = __reduce_max_sync(0xffffffffu, __float_as_uint((c0.x * c0.x + c0.y * c0.y) + (c0.z * c0.z + c0.w * c0.w) + (c1.x * c1.x + c1.y * c1.y) + (c1.z * c1.z + c1.w * c1.w)));
                if (lane == 0) asm volatile("red.relaxed.gpu.global.max.u32 [%0], %1;" :: "l"(g_s.cnt[C_KV + (epoch & 1)] + 1 + min(hg, 2)), "r"(nm) : "memory");
            }
            if (ww < 2 || hg < 2) stg128(kvdst, nonzero(pack_bf16(c0.x, c0.y)), nonzero(pack_bf16(c0.z, c0.w)), nonzero(pack_bf16(c1.x, c1.y)), nonzero(pack_bf16(c1.z, c1.w)));
        }
        if (ww < 2) count_hint(C_KVH);
        TS(1);
        if (ww < 3) bar_arrive(2, HOLDN);
        else {
            bar_sync(2, HOLDN);
            count_release(C_KV + (epoch & 1));
            if (lane == 0) mbar_expect(mb + MB_KV * 8, 47104 + 2 * 24576);
            uint4 v; int spins = 0;
            do v = ldg_relaxed(reinterpret_cast<const uint4*>(g_s.cnt[C_KV + (epoch & 1)])); while (__any_sync(0xffffffffu, v.x != kv_target(epoch)) && ++spins < SPIN_LIMIT);
            asm volatile("fence.acquire.gpu; fence.proxy.async.global;" ::: "memory");
            if (lane == 0) sts128(mb + MISC_NRM, v.x, v.y, v.z, v.w);
            __syncwarp();
            bar_arrive(5, 160);
        }
    } else {
        bar_arrive(0, 512);
        epoch++;
        if (t128 == 0) { sts32(mb + MISC_EPOCH, epoch); mbar_expect(mb + MB_KV0 * 8, 34816); }
        if (ww == 1) bar_sync(6, 160);
        if (ww == 0) { count_wait(C_KVH, epoch * (2 * NMAIN)); asm volatile("fence.proxy.async.global;" ::: "memory"); }
        TS(1);
        bar_sync(3, 128);
    }
    uint32_t* optr = reinterpret_cast<uint32_t*>(g_x + X_O + ((b >> 3) * 32 + hg * 8 + 2 * wg + (ww >> 1)) * 128 + ((tg & 1) * 2 + (ww & 1)) * 32) + lane;
    unsigned* ocnt = g_s.cnt[C_O + 16 + (b >> 3)] + lane;
    asm volatile("" : "+l"(optr), "+l"(ocnt));
    const uint32_t chores = wg == 3 ? chore_list(3) : wg == 2 ? chore_list(2) : wg == 1 ? chore_list(1) : chore_list(0);
    float s[32], o[12];
    init_acc(s, o);
    uint32_t votes;
    for (int spins = 0; ; spins++) {
        uint32_t mn = 1;
        if (wg != 3) fence_async_smem();
        else {
            const uint32_t kdst = sb + (ww == 0 ? SM_K + 31 * 2048 : ww == 1 ? SM_K : SM_V + (ww - 2) * 32768);
            if (lane == 0) bulk_g2s(kdst, g_s.kv + (ww == 0 ? 31 * 128 : ww == 1 ? 0 : ww * 2048), ww == 0 ? 2048 : ww == 1 ? 16384 : 8192, mb + MB_KV0 * 8);
            __syncwarp();
            const uint32_t probe = sb + (ww < 2 ? SM_K + ww * 8192 : SM_V + (ww - 2) * 32768) + lane * 32 + (lane >> 2) * 4;
            mbar_wait(mb + MB_KV0 * 8, spins & 1);
            TS(2);
            mn = min(mn, lds32(sb + SM_K + 31 * 2048 + (ww & 1) * 1024 + lane * 32 + (lane >> 2) * 4));
#pragma unroll
            for (int k = 0; k < 8; k++) mn = min(mn, lds32(probe + k * 1024));
        }
        TS(3);
        const uint32_t vote = unsafe | (__any_sync(0xffffffffu, mn == 0u) && lane == 0);
        asm volatile("{.reg .pred p; setp.ne.u32 p, %1, 0; barrier.red.popc.aligned.u32 %0, 1, 512, p;}" : "=r"(votes) : "r"(vote) : "memory");
        votes = __shfl_sync(0xffffffffu, votes, 0);
        if (__builtin_expect((votes & 127) == 0, 1) || spins >= SPIN_LIMIT) break;
        if (tid == 384) mbar_expect(mb + MB_KV0 * 8, 34816);
    }
    if (lane == 0 && wg == 3 && ww > 0)
        bulk_g2s(sb + (ww == 1 ? SM_K + 16384 : SM_V + (ww - 2) * 32768 + 8192), g_s.kv + (ww == 1 ? 1024 : ww * 2048 + 512), ww == 1 ? 47104 : 24576, mb + MB_KV * 8);
    __syncwarp();
    TS(4);

    if (__builtin_expect(votes < 128, 1)) {
        attention<true>(s, o, P, sb, warp, b, optr, ocnt, chores TS_PASS);
    } else {
        if (warp == 7) {
            mbar_wait(mb + MB_KV * 8);
            if (lane == 0) {
                asm volatile("fence.proxy.async;" ::: "memory");
                mbar_expect(mb + MISC_XBAR, 65536);
                bulk_g2s(sb + SM_K, g_s.kplain, 65536, mb + MISC_XBAR);
            }
            __syncwarp();
        }
        mbar_wait(mb + MISC_XBAR, 1);
        attention<false>(s, o, P, sb, warp, b, optr, ocnt, chores TS_PASS);
    }

    const int j = tail_j(b);
    if (wg == 1 || wg == 2) {
        if (warp == 8) {
            epoch = lds32(mb + MISC_EPOCH);
            if (lane == 0) g_s.epoch[b] = epoch;
#pragma unroll 1
            for (int job = 2; job < 6; job++) {
                if (job == 4) {
                    count_wait(C_H2E + tail_m(b), epoch * 32);
                    asm volatile("fence.proxy.async.global;" ::: "memory");
                    if (lane < 16) mbar_arrive(mb + MB_EARLY * 8);
                    __syncwarp();
                    TS(18);
                }
                count_wait(C_O + 32 * (job >> 1) + (job & 1) * 16 + tail_m(b), epoch * (job == 1 ? 128 : 32));
                asm volatile("fence.proxy.async.global;" ::: "memory");
                warp_done(mb + (MB_READY + job) * 8);
                TS(18 + job);
            }
        } else if (warp == 9) {
#pragma unroll
            for (int i = 0; i < 2; i++) {
                if (lane < 22) {
                    const uint4 v = ldg_relaxed(reinterpret_cast<const uint4*>(g_s.cs + j * 176) + i * 22 + lane);
                    sts128(mb + MISC_CS + (i * 22 + lane) * 16, v.x, v.y, v.z, v.w);
                }
                stg128(g_s.kv + kv_slot(b, i * 32 + lane), 0u, 0u, 0u, 0u);
            }
            warp_done(mb + MB_CS * 8);
#pragma unroll 1
            for (int i = 0; i < 15; i++) {
                mbar_wait(mb + (MB_W1 + i) * 8);
                const int n = i < 8 ? 16 + i + 8 * (lane & 1) : 32 + 3 * (i - 8) + (lane >> 1) + 22 * (lane & 1);
                if (lane < (i < 8 ? 2 : 6)) mbar_arrive(mb + (MB_FULL + n) * 8);
                __syncwarp();
            }
        } else {
            if (warp == 10) {
#pragma unroll 1
                for (int i = 2; i < 15; i++) {
                    const bool w1 = i < 8;
                    const int kb = i & 7;
                    const uint32_t bar = mb + (MB_W1 + i) * 8, dst = sb + w1_slot(kb, 0) * SLOT, step = kb < 4 ? 4 * SLOT : SLOT;
                    if (lane == 0) mbar_expect(bar, 3 * SLOT);
                    mbar_wait(mb + (w1 ? (i == 2 ? MB_WOA : MB_RELW + min(i - 3, 2)) : MB_REL + kb) * 8);
                    if (i == 2) mbar_wait(mb + (MB_FULL + 8) * 8);
                    if (lane == 0) {
                        const int odd = (i ^ b) & 1;
                        if (i == 13 || i == 14) {
#pragma unroll 1
                            for (int a = odd; a < 4; a += 2) tma2d_pair(dst + a * 6144, &P.w2s, j * 64, ((i - 13) * 4 + a) * 176 + 128, bar);
                        } else {
#pragma unroll 1
                            for (int a = odd; a < 3; a += 2) {
                                const int n = 3 * kb + a;
                                tma2d_pair(dst + a * step, w1 ? &P.w1 : &P.w2, w1 ? j * 176 + a * 64 : j * 64, w1 ? kb * 64 : (n & 7) * 176 + (n >> 3) * 64, bar);
                            }
                        }
                    }
                    __syncwarp();
                }
            }
            ring_feed(P, sb, b, wg == 1 ? ww : warp == 11 ? 4 : 6 TS_PASS);
        }
    } else {
        const int pr = (wg != CONS_A), mt = 16 * pr + tail_m(b);
        uint32_t* const hp = reinterpret_cast<uint32_t*>(g_x + X_H1 + (mt * 32 + j * 4) * 128 + ww * 32) + lane;
        {
            uint32_t hk[16];
            const uint32_t* xp = reinterpret_cast<const uint32_t*>(x + (size_t)(mt * 64 + ww * 16 + g) * D + j * 64 + t4 * 2);
#pragma unroll
            for (int k = 0; k < 8; k++) { hk[2 * k] = __ldg(xp + k * 4); hk[2 * k + 1] = __ldg(xp + k * 4 + 8 * (D / 2)); }
            mbar_wait(mb + MB_WO * 8);
            float acc[32];
            if (gemm_wo(acc, sb, pr TS_PASS)) gemm_slow(acc, g_x + X_O + mt * 32 * 128, 32, P.wop, D, D, j * 64);
            TS(7);
#pragma unroll
            for (int i = 0; i < 16; i++) hk[i] = pack_bf16(acc[2 * i] + bf_lo(hk[i]), acc[2 * i + 1] + bf_hi(hk[i]));
#pragma unroll
            for (int k = 0; k < 4; k++) store_tile(hp + k * 512, hk[4 * k], hk[4 * k + 1], hk[4 * k + 2], hk[4 * k + 3]);
            count_hint(C_H1 + mt);
            TS(8);
            float st[4] = {0.f, 0.f, 0.f, 0.f};
#pragma unroll
            for (int i = 0; i < 16; i++) {
                const float lo = bf_lo(hk[i]), hi = bf_hi(hk[i]);
                st[2 * (i & 1)] += lo + hi;
                st[2 * (i & 1) + 1] = fmaf(lo, lo, fmaf(hi, hi, st[2 * (i & 1) + 1]));
            }
#pragma unroll
            for (int o = 1; o < 4; o <<= 1)
#pragma unroll
                for (int i = 0; i < 4; i++) st[i] += __shfl_xor_sync(0xffffffffu, st[i], o);
            if (t4 == 0) stg128(g_x + X_ST + (mt * 8 + j) * 32 + ww * 8 + g, __float_as_uint(st[0]), __float_as_uint(st[1]), __float_as_uint(st[2]), __float_as_uint(st[3]));
        }
        {
            float acc[88];
            mbar_wait(mb + MB_CS * 8);
            mbar_wait(mb + (MB_RELW + 1) * 8);
            if (gemm_ss<1>(acc, sb, pr TS_PASS)) gemm_slow(acc, g_x + X_H1 + mt * 32 * 128, 32, P.w1p, FF, D, j * 176);
            TS(9);
            mbar_wait(mb + (MB_STAT + pr) * 8);
            const float4 rs = lds128f(mb + MISC_STAT + pr * 512 + (ww * 8 + g) * 16);
            const float nmean[2] = {rs.x, rs.z}, hrstd[2] = {rs.y, rs.w};
            uint32_t* hb = reinterpret_cast<uint32_t*>(g_x + X_H2 + (mt * 88 + j * 4) * 128 + ww * 32) + lane;
#pragma unroll
            for (int i = 0; i < 22; i++) {
                float2 cs;
                asm volatile("ld.shared.v2.f32 {%0,%1}, [%2];" : "=f"(cs.x), "=f"(cs.y) : "r"(mb + MISC_CS + i * 32 + t4 * 8));
                const float* z = acc + 4 * i;
                if (i == 8) { count_hint(C_H2E + mt); hb += (j == 7 ? 52 : 28) * 512; }
                if (i == 16) hb += (j == 7 ? -7 : 24 - j) * 512;
                uint32_t* p = hb + (i >> 1) * 512 + (i & 1) * 32;
                stg32(p, pack_bf16(silu2(fmaf(hrstd[0], z[0], nmean[0] * cs.x)), silu2(fmaf(hrstd[0], z[1], nmean[0] * cs.y))));
                stg32(p + 64, pack_bf16(silu2(fmaf(hrstd[1], z[2], nmean[1] * cs.x)), silu2(fmaf(hrstd[1], z[3], nmean[1] * cs.y))));
            }
            count_hint(C_H2 + mt);
            TS(10);
        }
        {
            uint32_t hk[16];
#pragma unroll
            for (int i = 0; i < 16; i++) hk[i] = ldg32_relaxed(hp + (i >> 2) * 512 + ((i & 1) * 2 + ((i >> 1) & 1)) * 32);
            float acc[32];
            if (gemm_ss<2>(acc, sb, pr TS_PASS)) gemm_slow(acc, g_x + X_H2 + mt * 88 * 128, 88, P.w2p, D, FF, j * 64);
            TS(11);
#pragma unroll
            for (int i = 0; i < 16; i++) hk[i] = pack_bf16(acc[2 * i] + bf_lo(hk[i]), acc[2 * i + 1] + bf_hi(hk[i]));
#pragma unroll
            for (int h = 0; h < 4; h++) {
                const uint32_t* v = hk + (h >> 1) * 8 + (h & 1);
                uint32_t v0 = v[0], v1 = v[2], v2 = v[4], v3 = v[6];
                const bool o1 = t4 & 1, o2 = t4 & 2;
                uint32_t a = __shfl_xor_sync(0xffffffffu, o1 ? v0 : v1, 1), c = __shfl_xor_sync(0xffffffffu, o1 ? v2 : v3, 1);
                if (o1) { v0 = a; v2 = c; } else { v1 = a; v3 = c; }
                a = __shfl_xor_sync(0xffffffffu, o2 ? v0 : v2, 2); c = __shfl_xor_sync(0xffffffffu, o2 ? v1 : v3, 2);
                if (o2) { v0 = a; v1 = c; } else { v2 = a; v3 = c; }
                *reinterpret_cast<uint4*>(P.out + (size_t)(mt * 64 + ww * 16 + g + 8 * (h & 1)) * D + j * 64 + (h >> 1) * 32 + t4 * 8) = make_uint4(v0, v1, v2, v3);
            }
        }
    }
    TS(12);
}

typedef CUresult (*EncodeFn)(CUtensorMap*, CUtensorMapDataType, cuuint32_t, void*, const cuuint64_t*, const cuuint64_t*, const cuuint32_t*,
                             const cuuint32_t*, CUtensorMapInterleave, CUtensorMapSwizzle, CUtensorMapL2promotion, CUtensorMapFloatOOBfill);

void encode2d(EncodeFn fn, CUtensorMap* tm, const void* ptr, int rows, int cols, int box_rows, int box_cols, CUtensorMapSwizzle sw) {
    cuuint64_t dims[2] = {(cuuint64_t)cols, (cuuint64_t)rows};
    cuuint64_t strides[1] = {(cuuint64_t)cols * 2};
    cuuint32_t box[2] = {(cuuint32_t)box_cols, (cuuint32_t)box_rows};
    cuuint32_t es[2] = {1, 1};
    fn(tm, CU_TENSOR_MAP_DATA_TYPE_BFLOAT16, 2, const_cast<void*>(ptr), dims, strides, box, es, CU_TENSOR_MAP_INTERLEAVE_NONE, sw,
       CU_TENSOR_MAP_L2_PROMOTION_L2_128B, CU_TENSOR_MAP_FLOAT_OOB_FILL_NONE);
}

}

extern "C" void kernel_launch(void* const* d_in, const int* in_sizes, int n_in, void* d_out, int out_size) {
    (void)in_sizes; (void)n_in; (void)out_size;
    void* fnp = nullptr;
    cudaDriverEntryPointQueryResult qr;
    cudaGetDriverEntryPoint("cuTensorMapEncodeTiled", &fnp, cudaEnableDefault, &qr);
    EncodeFn fn = (EncodeFn)fnp;
    Params P;
    encode2d(fn, &P.wq, d_in[1], D, D, 128, 64, CU_TENSOR_MAP_SWIZZLE_128B);
    encode2d(fn, &P.wo, d_in[4], D, D, 64, 64, CU_TENSOR_MAP_SWIZZLE_128B);
    encode2d(fn, &P.w1, d_in[6], D, FF, 64, 64, CU_TENSOR_MAP_SWIZZLE_128B);
    encode2d(fn, &P.w2, d_in[7], FF, D, 64, 64, CU_TENSOR_MAP_SWIZZLE_128B);
    encode2d(fn, &P.w2s, d_in[7], FF, D, 48, 64, CU_TENSOR_MAP_SWIZZLE_128B);
    P.w1p = (const __nv_bfloat16*)d_in[6];
    P.w2p = (const __nv_bfloat16*)d_in[7];
    P.wop = (const __nv_bfloat16*)d_in[4];
    P.wqp = (const __nv_bfloat16*)d_in[1];
    P.out = (__nv_bfloat16*)d_out;
    P.neg1 = 0xFFFFFFFFu; P.pad = 0;
    cudaFuncSetAttribute(fused_kernel, cudaFuncAttributeMaxDynamicSharedMemorySize, SMEM_BYTES);
    fused_kernel<<<NCTA, 512, SMEM_BYTES>>>((const __nv_bfloat16*)d_in[0], (const __nv_bfloat16*)d_in[2], (long long)((const char*)d_in[3] - (const char*)d_in[2]), P);
}
```
